```python
import torch

def _softmax(x, axis=-1):
    return torch.softmax(x, dim=axis)
def _gelu(x):
    return torch.nn.functional.gelu(x, approximate="tanh")
def _silu(x):
    return torch.nn.functional.silu(x)
def _sigmoid(x):
    return torch.sigmoid(x)
def _layernorm(x, axis=-1, eps=1e-5):
    m = x.mean(dim=axis, keepdim=True)
    v = x.var(dim=axis, keepdim=True, unbiased=False)
    return (x - m) / torch.sqrt(v + eps)
def _scatter_add(tgt, idx, src, axis=0):
    return tgt.clone().index_add_(axis, idx, src)
def _segment_sum(src, seg, n):
    out = torch.zeros((n,) + src.shape[1:], dtype=src.dtype)
    return out.index_add_(0, seg, src)
def _pad(x, pw):
    flat = tuple(v for pair in reversed(pw) for v in pair)
    return torch.nn.functional.pad(x, flat)

kernel_name = 'interleave_layers__ssm_conv_s4__sliding_local_dilated__prompt'

def setup_inputs():

    _w = (lambda a: (lambda t: t.to(torch.bfloat16) if t.is_floating_point() else t)(torch.as_tensor(a)))
    def _A_setup():
        B, L, D, N = 1, 2048, 512, 128
        A_re = -(lambda _x: torch.exp(torch.as_tensor(_x)))((lambda *s: torch.randn(*s, dtype=torch.bfloat16) * 1.6)(D, N))
        A_im = torch.pi * (lambda *s: torch.randn(*s, dtype=torch.bfloat16) * 0.1)(D, N)
        B_re = (lambda *s: torch.randn(*s, dtype=torch.bfloat16) * 0.1)(D, N)
        B_im = (lambda *s: torch.randn(*s, dtype=torch.bfloat16) * 0.1)(D, N)
        C_re = (lambda *s: torch.randn(*s, dtype=torch.bfloat16) * 0.1)(D, N)
        C_im = (lambda *s: torch.randn(*s, dtype=torch.bfloat16) * 0.1)(D, N)
        log_dt = (lambda *s: torch.randn(*s, dtype=torch.bfloat16) * 0.1)(D) * 0.5 - 4.0
        Dskip = (lambda *s: torch.randn(*s, dtype=torch.bfloat16) * 0.1)(D)
        return {
            "u": _w((lambda *s: torch.randn(*s, dtype=torch.bfloat16) * 0.05)(B, L, D)),
            "A_re": _w(A_re),
            "A_im": _w(A_im),
            "B_re": _w(B_re),
            "B_im": _w(B_im),
            "C_re": _w(C_re),
            "C_im": _w(C_im),
            "log_dt": _w(log_dt),
            "Dskip": _w(Dskip),
        }
    _A_in = _A_setup()

    def _B_setup():
        B, S, D = 1, 2048, 512
        return {
            "x": _w((lambda *s: torch.randn(*s, dtype=torch.bfloat16) * 0.05)(B, S, D)),
            "wqkv": _w((lambda *s: torch.randn(*s, dtype=torch.bfloat16) * 0.05)(D, 3 * D)),
            "wo": _w((lambda *s: torch.randn(*s, dtype=torch.bfloat16) * 0.05)(D, D)),
        }
    _B_in = _B_setup()

    return {
        "A_u": _A_in["u"],
        "A_A_re": _A_in["A_re"],
        "A_A_im": _A_in["A_im"],
        "A_B_re": _A_in["B_re"],
        "A_B_im": _A_in["B_im"],
        "A_C_re": _A_in["C_re"],
        "A_C_im": _A_in["C_im"],
        "A_log_dt": _A_in["log_dt"],
        "A_Dskip": _A_in["Dskip"],
        "B_x": _B_in["x"],
        "B_wqkv": _B_in["wqkv"],
        "B_wo": _B_in["wo"],
    }

def reference(A_u, A_A_re, A_A_im, A_B_re, A_B_im, A_C_re, A_C_im, A_log_dt, A_Dskip, B_x, B_wqkv, B_wo):
    def _A_ref(u, A_re, A_im, B_re, B_im, C_re, C_im, log_dt, Dskip):
        Bsz, L, D = u.shape
        dt = torch.exp(log_dt)[:, None]
        A = A_re + 1j * A_im
        Bc = B_re + 1j * B_im
        Cc = C_re + 1j * C_im
        logdA = dt * A
        dB = dt * Bc
        l = (lambda x, dt: x.to(dt))(torch.arange(L), A_re.dtype)
        P = torch.exp(logdA[:, :, None] * l[None, None, :])
        K = torch.einsum("dn,dnl,dn->dl", Cc, P, dB).real
        L2 = 2 * L
        Kp = _pad(K, ((0, 0), (0, L)))
        up = (lambda x, *d: x.permute(*d))(u, 0, 2, 1)
        up = _pad(up, ((0, 0), (0, 0), (0, L)))
        Kf = (lambda x, axes=(-2,-1): torch.fft.rfft2(x.float(), dim=axes))(Kp[:, None, :], axes=(-2, -1))
        Uf = (lambda x, axes=(-2,-1): torch.fft.rfft2(x.float(), dim=axes))(up[:, :, None, :], axes=(-2, -1))
        Yf = Uf * Kf[None, :, :, :]
        y = (lambda x, s, axes=(-2,-1): torch.fft.irfft2(x, s=s, dim=axes).to(torch.bfloat16))(Yf, (1, L2), axes=(-2, -1))[:, :, 0, :L]
        y = (lambda x, *d: x.permute(*d))(y, 0, 2, 1) + u * Dskip[None, None, :]
        return y

    def _B_ref(x, wqkv, wo):
        B, S, D = x.shape
        H = 32; Dh = D // H
        W, dil = 8, 2
        qkv = (lambda x, *d: x.permute(*d))((x @ wqkv).reshape(B, S, 3, H, Dh), 2, 0, 3, 1, 4)
        q, k, v = qkv[0], qkv[1], qkv[2]
        scale = Dh ** -0.5
        pos = torch.arange(S)
        off = torch.arange(W) * dil
        idx = pos[:, None] - off[None, :]
        mask = idx >= 0
        idx_c = torch.where(mask, idx, 0).reshape(-1)
        kg = k[:, :, idx_c, :].reshape(B, H, S, W, Dh)
        vg = v[:, :, idx_c, :].reshape(B, H, S, W, Dh)
        logits = torch.einsum("bhsd,bhswd->bhsw", q, kg) * scale
        logits = torch.where(mask[None, None, :, :], logits, -1e9)
        attn = _softmax(logits, axis=-1)
        o = torch.einsum("bhsw,bhswd->bhsd", attn, vg)
        return (lambda x, *d: x.permute(*d))(o, 0, 2, 1, 3).reshape(B, S, D) @ wo

    x = A_u
    x = x + _A_ref(_layernorm(x, axis=-1), A_A_re, A_A_im, A_B_re, A_B_im, A_C_re, A_C_im, A_log_dt, A_Dskip)
    x = x + _B_ref(_layernorm(x, axis=-1), B_wqkv, B_wo)
    x = x + _A_ref(_layernorm(x, axis=-1), A_A_re, A_A_im, A_B_re, A_B_im, A_C_re, A_C_im, A_log_dt, A_Dskip)
    x = x + _B_ref(_layernorm(x, axis=-1), B_wqkv, B_wo)
    return x
```

```cpp
#include <cuda_runtime.h>
#include <cuda_bf16.h>
#include <cuda.h>
#include <stdint.h>

#define DEV __device__ __forceinline__
#define RARE(x) __builtin_expect(!!(x), 0)

#define KWOP 30
#define KFR 3
#define KDR 0
constexpr int NTHR = 512;
constexpr int REG_MAIN = 192, REG_AUX = 96, REG_PROD = 32;
constexpr int NBARU = 416;
constexpr int SPIN_LIMIT = 1 << 22;

constexpr uint32_t SB = 1024;
__host__ __device__ constexpr uint32_t slot(int n) { return SB + n * 8192; }
__host__ __device__ constexpr int wslot(int k) { return k < 2 ? 3 * k : k < 4 ? 3 * k + 6 : k < 6 ? 21 - 3 * k : 3 * k - 18; }
constexpr uint32_t SM_A = slot(22), A_E = 0u - 32768;
constexpr uint32_t SM_O = slot(18), O_E = 0u - 147456;
constexpr uint32_t SM_WO = slot(10), SM_X = slot(8), SM_KV = slot(9);
constexpr uint32_t SM_NAN = slot(26) - 2048;
constexpr uint32_t SM_TAP  = slot(26);
constexpr int TAP_SZ = 3440;
constexpr uint32_t SM_STAT = SM_TAP + 4 * TAP_SZ;
constexpr uint32_t SM_CS   = SM_STAT + 1024;
constexpr uint32_t SM_MISC = SM_CS + 768;
constexpr uint32_t SM_BAR  = SM_MISC + 528;
constexpr int SM_TOTAL = SM_BAR + 304 - SB;
static_assert(SM_TOTAL <= 232448, "");
constexpr int R_SZ = 15360, R_U = 512, R_X5 = 4608, R_X3 = 7680, R_BO = 10752, R_BE = 12800;
constexpr int X_5 = 576, X_3 = 648, T_E = 2 * 720, T_O = 1600 + 2 * 721, T_C = 3390, T_K = 3424;
constexpr uint32_t B_RD = SM_BAR, B_ED = SM_BAR + 16, B_F = SM_BAR + 32, B_AT = SM_BAR + 56;
constexpr uint32_t B_AE = SM_BAR + 72, B_QE = SM_BAR + 88, B_ST = SM_BAR + 96, B_CS = SM_BAR + 112;
constexpr uint32_t B_WO = SM_BAR + 120, B_W6 = SM_BAR + 128, B_U = SM_BAR + 144, B_E = SM_BAR + 152, B_A = SM_BAR + 160, B_O = SM_BAR + 192,
                   B_Z = SM_BAR + 256, B_WF = SM_BAR + 272, B_W4 = SM_BAR + 280, B_N = SM_BAR + 288;
constexpr int NB_U = 1, NB_B = 2, NB_K = 8, NB_Y = 6, NB_WG = 8, NB_T = 10, NB_AUX = 12, NB_P0 = 13, NB_H = 15;

__device__ uint4    g_XG[2][128 * 1024];
__device__ uint4    g_XF[2][32 * 512 * 8];
__device__ uint4    g_O[32 * 8 * 512];
__device__ __align__(128) uint32_t g_OF[2][32 * 32];
__device__ uint4    g_H[2][33 * 8 * 256];
__device__ uint4    g_SR[2][8][512];
__device__ uint4    g_ST[2][32 * 128];
__device__ uint4    g_PS[128 * 64];
__device__ float4   g_CS[16 * 1536 / 4];
__device__ uint32_t g_C[4 * 32];
#define PROFD(slot, v) do {} while (0)
#define PROF(slot) do {} while (0)

DEV uint32_t s2u(const void* p) { return (uint32_t)__cvta_generic_to_shared(p); }
template <class T> DEV T opq(T x) { asm volatile("" : "+r"(x)); return x; }
DEV int lane_id() { int l; asm volatile("mov.u32 %0,%%laneid;" : "=r"(l)); return l; }
DEV uint32_t pack2(float lo, float hi) { uint32_t d; asm("cvt.rn.bf16x2.f32 %0,%1,%2;" : "=r"(d) : "f"(hi), "f"(lo)); return d; }
DEV float bflo(uint32_t v) { return __uint_as_float(v << 16); }
DEV float bfhi(uint32_t v) { return __uint_as_float(v & 0xFFFF0000u); }
DEV float bfr(float x) { return bflo(pack2(x, 0.f)); }
DEV uint32_t hadd2(uint32_t a, uint32_t b) { uint32_t d; asm("add.rn.bf16x2 %0,%1,%2;" : "=r"(d) : "r"(a), "r"(b)); return d; }
DEV uint32_t hsub2(uint32_t a, uint32_t b) { uint32_t d; asm("sub.rn.bf16x2 %0,%1,%2;" : "=r"(d) : "r"(a), "r"(b)); return d; }
DEV uint32_t hmul2(uint32_t a, uint32_t b) { uint32_t d; asm("mul.rn.bf16x2 %0,%1,%2;" : "=r"(d) : "r"(a), "r"(b)); return d; }
DEV uint32_t hfma2(uint32_t a, uint32_t b, uint32_t c) { uint32_t d; asm("fma.rn.bf16x2 %0,%1,%2,%3;" : "=r"(d) : "r"(a), "r"(b), "r"(c)); return d; }
DEV uint32_t hmax2(uint32_t a, uint32_t b) { uint32_t d; asm("max.bf16x2 %0,%1,%2;" : "=r"(d) : "r"(a), "r"(b)); return d; }
DEV uint32_t prmt(uint32_t a, uint32_t b, uint32_t s) { uint32_t d; asm("prmt.b32 %0,%1,%2,%3;" : "=r"(d) : "r"(a), "r"(b), "r"(s)); return d; }
DEV uint32_t nzmap(uint32_t v) { return v == 0u ? 0x80000000u : v; }
DEV float rcp(float x) { float y; asm("rcp.approx.ftz.f32 %0,%1;" : "=f"(y) : "f"(x)); return y; }
DEV float sqrt_(float x) { float y; asm("sqrt.approx.ftz.f32 %0,%1;" : "=f"(y) : "f"(x)); return y; }
DEV float ex2(float x) { float y; asm("ex2.approx.ftz.f32 %0,%1;" : "=f"(y) : "f"(x)); return y; }

DEV uint4 ldr4(const void* p) { uint4 v; asm volatile("ld.relaxed.gpu.global.v4.u32 {%0,%1,%2,%3},[%4];" : "=r"(v.x), "=r"(v.y), "=r"(v.z), "=r"(v.w) : "l"(p) : "memory"); return v; }
DEV void ldr4_if(uint4& v, const void* p, bool c) {
  asm volatile("{.reg .pred q; setp.ne.u32 q,%5,0; @q ld.relaxed.gpu.global.v4.u32 {%0,%1,%2,%3},[%4];}"
    : "+r"(v.x), "+r"(v.y), "+r"(v.z), "+r"(v.w) : "l"(p), "r"((uint32_t)c) : "memory");
}
DEV uint2 ldr2(const void* p) { uint2 v; asm volatile("ld.relaxed.gpu.global.v2.u32 {%0,%1},[%2];" : "=r"(v.x), "=r"(v.y) : "l"(p) : "memory"); return v; }
DEV void ldr2_if(uint2& v, const void* p, bool c) {
  asm volatile("{.reg .pred q; setp.ne.u32 q,%3,0; @q ld.relaxed.gpu.global.v2.u32 {%0,%1},[%2];}" : "+r"(v.x), "+r"(v.y) : "l"(p), "r"((uint32_t)c) : "memory");
}
DEV uint32_t ldr1(const void* p) { uint32_t v; asm volatile("ld.relaxed.gpu.global.u32 %0,[%1];" : "=r"(v) : "l"(p) : "memory"); return v; }
DEV float ldnan(const uint16_t* p) {
  uint32_t v = 0xFFFFu;
#pragma unroll 1
  for (int it = 0; it < SPIN_LIMIT && v == 0xFFFFu; ++it) asm volatile("ld.relaxed.gpu.global.u16 %0,[%1];" : "=r"(v) : "l"(p) : "memory");
  return __uint_as_float(v << 16);
}
DEV uint4 ldw4(const void* p) { uint4 v; asm volatile("ld.global.v4.u32 {%0,%1,%2,%3},[%4];" : "=r"(v.x), "=r"(v.y), "=r"(v.z), "=r"(v.w) : "l"(p) : "memory"); return v; }
DEV uint2 ldw2(const void* p) { uint2 v; asm volatile("ld.global.v2.u32 {%0,%1},[%2];" : "=r"(v.x), "=r"(v.y) : "l"(p) : "memory"); return v; }
DEV uint32_t ldw1(const void* p) { uint32_t v; asm volatile("ld.global.u32 %0,[%1];" : "=r"(v) : "l"(p) : "memory"); return v; }
DEV void str4(void* p, uint32_t a, uint32_t b, uint32_t c, uint32_t d) { asm volatile("st.relaxed.gpu.global.v4.u32 [%0],{%1,%2,%3,%4};" :: "l"(p), "r"(a), "r"(b), "r"(c), "r"(d) : "memory"); }
DEV void str2(void* p, uint32_t a, uint32_t b) { asm volatile("st.relaxed.gpu.global.v2.u32 [%0],{%1,%2};" :: "l"(p), "r"(a), "r"(b) : "memory"); }
DEV void str1(void* p, uint32_t a) { asm volatile("st.relaxed.gpu.global.u32 [%0],%1;" :: "l"(p), "r"(a) : "memory"); }
DEV void stw4(void* p, uint32_t a, uint32_t b, uint32_t c, uint32_t d) { asm volatile("st.global.v4.u32 [%0],{%1,%2,%3,%4};" :: "l"(p), "r"(a), "r"(b), "r"(c), "r"(d) : "memory"); }
DEV uint4 ldnc4(const void* p) { uint4 v; asm volatile("ld.global.nc.v4.u32 {%0,%1,%2,%3},[%4];" : "=r"(v.x), "=r"(v.y), "=r"(v.z), "=r"(v.w) : "l"(p)); return v; }
DEV uint2 ldnc2(const void* p) { uint2 v; asm volatile("ld.global.nc.v2.u32 {%0,%1},[%2];" : "=r"(v.x), "=r"(v.y) : "l"(p)); return v; }

DEV uint2 lds2(uint32_t a) { uint2 v; asm volatile("ld.shared.v2.u32 {%0,%1},[%2];" : "=r"(v.x), "=r"(v.y) : "r"(a)); return v; }
DEV float lds16f(uint32_t a) { uint32_t v; asm volatile("ld.shared.u16 %0,[%1];" : "=r"(v) : "r"(a)); return __uint_as_float(v << 16); }
DEV void sts2(uint32_t a, uint32_t x, uint32_t y) { asm volatile("st.shared.v2.u32 [%0],{%1,%2};" :: "r"(a), "r"(x), "r"(y) : "memory"); }
DEV uint32_t lds1(uint32_t a) { uint32_t v; asm volatile("ld.shared.u32 %0,[%1];" : "=r"(v) : "r"(a)); return v; }
DEV uint32_t lds1z(uint32_t a, bool c) {
  uint32_t v; asm volatile("{.reg .pred q; setp.ne.u32 q,%2,0; mov.u32 %0,0; @q ld.shared.u32 %0,[%1];}" : "=r"(v) : "r"(a), "r"((uint32_t)c)); return v;
}
DEV uint4 lds4z(uint32_t a, bool c) {
  uint4 v = make_uint4(0, 0, 0, 0);
  asm volatile("{.reg .pred q; setp.ne.u32 q,%5,0; @q ld.shared.v4.u32 {%0,%1,%2,%3},[%4];}" : "+r"(v.x), "+r"(v.y), "+r"(v.z), "+r"(v.w) : "r"(a), "r"((uint32_t)c));
  return v;
}
DEV float lds1f(uint32_t a) { float v; asm volatile("ld.shared.f32 %0,[%1];" : "=f"(v) : "r"(a)); return v; }
DEV float2 lds2f(uint32_t a) { float2 v; asm volatile("ld.shared.v2.f32 {%0,%1},[%2];" : "=f"(v.x), "=f"(v.y) : "r"(a)); return v; }
DEV float4 lds4f(uint32_t a) { float4 v; asm volatile("ld.shared.v4.f32 {%0,%1,%2,%3},[%4];" : "=f"(v.x), "=f"(v.y), "=f"(v.z), "=f"(v.w) : "r"(a)); return v; }
DEV uint4 lds4(uint32_t a) { uint4 v; asm volatile("ld.shared.v4.u32 {%0,%1,%2,%3},[%4];" : "=r"(v.x), "=r"(v.y), "=r"(v.z), "=r"(v.w) : "r"(a)); return v; }
DEV void sts1(uint32_t a, uint32_t v) { asm volatile("st.shared.u32 [%0],%1;" :: "r"(a), "r"(v) : "memory"); }
DEV void sts16(uint32_t a, uint32_t v) { asm volatile("{.reg .b16 h; cvt.u16.u32 h,%1; st.shared.u16 [%0],h;}" :: "r"(a), "r"(v) : "memory"); }
DEV void sts2f(uint32_t a, float x, float y) { asm volatile("st.shared.v2.f32 [%0],{%1,%2};" :: "r"(a), "f"(x), "f"(y) : "memory"); }
DEV void sts4f(uint32_t a, float x, float y, float z, float w) { asm volatile("st.shared.v4.f32 [%0],{%1,%2,%3,%4};" :: "r"(a), "f"(x), "f"(y), "f"(z), "f"(w) : "memory"); }
DEV void sts4(uint32_t a, uint32_t x, uint32_t y, uint32_t z, uint32_t w) { asm volatile("st.shared.v4.u32 [%0],{%1,%2,%3,%4};" :: "r"(a), "r"(x), "r"(y), "r"(z), "r"(w) : "memory"); }

DEV void ldsm4(uint32_t (&r)[4], uint32_t a) { asm volatile("ldmatrix.sync.aligned.m8n8.x4.shared.b16 {%0,%1,%2,%3},[%4];" : "=r"(r[0]), "=r"(r[1]), "=r"(r[2]), "=r"(r[3]) : "r"(a) : "memory"); }
DEV void ldsm4t(uint32_t (&r)[4], uint32_t a) { asm volatile("ldmatrix.sync.aligned.m8n8.x4.trans.shared.b16 {%0,%1,%2,%3},[%4];" : "=r"(r[0]), "=r"(r[1]), "=r"(r[2]), "=r"(r[3]) : "r"(a) : "memory"); }
DEV void ldsm2(uint32_t (&r)[2], uint32_t a) { asm volatile("ldmatrix.sync.aligned.m8n8.x2.shared.b16 {%0,%1},[%2];" : "=r"(r[0]), "=r"(r[1]) : "r"(a) : "memory"); }
DEV void stsm4(uint32_t a, uint32_t r0, uint32_t r1, uint32_t r2, uint32_t r3) { asm volatile("stmatrix.sync.aligned.m8n8.x4.shared.b16 [%0],{%1,%2,%3,%4};" :: "r"(a), "r"(r0), "r"(r1), "r"(r2), "r"(r3) : "memory"); }
DEV void stsm2(uint32_t a, uint32_t r0, uint32_t r1) { asm volatile("stmatrix.sync.aligned.m8n8.x2.shared.b16 [%0],{%1,%2};" :: "r"(a), "r"(r0), "r"(r1) : "memory"); }
DEV void stsm4t(uint32_t a, uint32_t r0, uint32_t r1, uint32_t r2, uint32_t r3) { asm volatile("stmatrix.sync.aligned.m8n8.x4.trans.shared.b16 [%0],{%1,%2,%3,%4};" :: "r"(a), "r"(r0), "r"(r1), "r"(r2), "r"(r3) : "memory"); }
DEV uint32_t movm(uint32_t a) { uint32_t d; asm volatile("movmatrix.sync.aligned.m8n8.trans.b16 %0,%1;" : "=r"(d) : "r"(a)); return d; }
DEV void mma16(float (&d)[4], uint32_t a0, uint32_t a1, uint32_t a2, uint32_t a3, uint32_t b0, uint32_t b1) {
  asm volatile("mma.sync.aligned.m16n8k16.row.col.f32.bf16.bf16.f32 {%0,%1,%2,%3},{%4,%5,%6,%7},{%8,%9},{%0,%1,%2,%3};"
    : "+f"(d[0]), "+f"(d[1]), "+f"(d[2]), "+f"(d[3]) : "r"(a0), "r"(a1), "r"(a2), "r"(a3), "r"(b0), "r"(b1));
}
DEV void mma16z(float (&d)[4], uint32_t a0, uint32_t a1, uint32_t a2, uint32_t a3, uint32_t b0, uint32_t b1) {
  asm volatile("mma.sync.aligned.m16n8k16.row.col.f32.bf16.bf16.f32 {%0,%1,%2,%3},{%4,%5,%6,%7},{%8,%9},{%10,%10,%10,%10};"
    : "=f"(d[0]), "=f"(d[1]), "=f"(d[2]), "=f"(d[3]) : "r"(a0), "r"(a1), "r"(a2), "r"(a3), "r"(b0), "r"(b1), "f"(0.f));
}
DEV void mma8(float (&d)[4], uint32_t a0, uint32_t a1, uint32_t b0) {
  asm volatile("mma.sync.aligned.m16n8k8.row.col.f32.bf16.bf16.f32 {%0,%1,%2,%3},{%4,%5},{%6},{%0,%1,%2,%3};"
    : "+f"(d[0]), "+f"(d[1]), "+f"(d[2]), "+f"(d[3]) : "r"(a0), "r"(a1), "r"(b0));
}

DEV void bar_sync(int id, int n) { asm volatile("bar.sync %0,%1;" :: "r"(id), "r"(n) : "memory"); }
DEV void bar_sync_if(int id, int n, int c) { asm volatile("{.reg .pred q; setp.ne.s32 q,%2,0; @q bar.sync %0,%1;}" :: "r"(id), "r"(n), "r"(c) : "memory"); }
DEV void bar_arrive_if(int id, int n, int c) { asm volatile("{.reg .pred q; setp.ne.s32 q,%2,0; @q bar.arrive %0,%1;}" :: "r"(id), "r"(n), "r"(c) : "memory"); }
DEV bool bar_any(int id, int n, bool c) {
  uint32_t r; asm volatile("{.reg .pred p,q; setp.ne.u32 q,%3,0; bar.red.or.pred p,%1,%2,q; selp.u32 %0,1,0,p;}" : "=r"(r) : "r"(id), "r"(n), "r"((uint32_t)c) : "memory");
  return __any_sync(0xffffffffu, r);
}
DEV void bar_arrive(int id, int n) { asm volatile("bar.arrive %0,%1;" :: "r"(id), "r"(n) : "memory"); }
DEV void fence_async_glob() { asm volatile("fence.proxy.async.global;" ::: "memory"); }
DEV void fence_async_smem() { asm volatile("fence.proxy.async.shared::cta;" ::: "memory"); }
DEV void mbar_init(uint32_t b, int n) { asm volatile("mbarrier.init.shared::cta.b64 [%0],%1;" :: "r"(b), "r"(n) : "memory"); }
DEV void mbar_arrive(uint32_t b) { asm volatile("mbarrier.arrive.shared::cta.b64 _,[%0];" :: "r"(b) : "memory"); }
DEV void mbar_expect(uint32_t b, int bytes) { asm volatile("mbarrier.arrive.expect_tx.shared::cta.b64 _,[%0],%1;" :: "r"(b), "r"(bytes) : "memory"); }
DEV void mbar_wait(uint32_t b, uint32_t ph) {
  asm volatile("{\n.reg .pred p,q;\n.reg .u32 n;\n"
               "mbarrier.try_wait.parity.shared::cta.b64 p,[%0],%1;\n@p bra D;\nmov.u32 n,0;\n"
               "W: mbarrier.try_wait.parity.shared::cta.b64 p,[%0],%1;\n@p bra D;\n"
               "add.u32 n,n,1;\nsetp.lt.u32 q,n,%2;\n@q bra W;\ntrap;\nD:\n}"
               :: "r"(b), "r"(ph), "n"(SPIN_LIMIT) : "memory");
}
DEV void spin_guard(int it) { asm volatile("{.reg .pred p; setp.gt.s32 p,%0,%1; @p trap;}" :: "r"(it), "n"(SPIN_LIMIT)); }
DEV void cnt_wait(int k, int lane) {
  for (int it = 0; !__all_sync(0xffffffffu, ldr1(g_C + k + (lane & 3) * 32) >= 32); ++it) spin_guard(it);
}
DEV void mbar_arrive1(uint32_t b) { asm volatile("{.reg .pred p; elect.sync _|p,0xffffffff; @p mbarrier.arrive.shared::cta.b64 _,[%0];}" :: "r"(b) : "memory"); }
DEV void mbar_arrive1_if(uint32_t b, int c) {
  asm volatile("{.reg .pred p,q; setp.ne.s32 q,%1,0; elect.sync _|p,0xffffffff; and.pred p,p,q; @p mbarrier.arrive.shared::cta.b64 _,[%0];}" :: "r"(b), "r"(c) : "memory");
}
DEV void mbar_expect1(uint32_t b, int bytes) { asm volatile("{.reg .pred p; elect.sync _|p,0xffffffff; @p mbarrier.arrive.expect_tx.shared::cta.b64 _,[%0],%1;}" :: "r"(b), "r"(bytes) : "memory"); }
DEV void cnt_add1(uint32_t* q) { asm volatile("{.reg .pred p; elect.sync _|p,0xffffffff; @p red.relaxed.gpu.global.add.u32 [%0],1;}" :: "l"(q) : "memory"); }
DEV void tma4(uint32_t dst, const CUtensorMap* m, int c0, int c1, int c2, int c3, uint32_t bar) {
  asm volatile("{.reg .pred p; elect.sync _|p,0xffffffff;\n"
    "@p cp.async.bulk.tensor.4d.shared::cluster.global.mbarrier::complete_tx::bytes [%0],[%1,{%2,%3,%4,%5}],[%6];}"
    :: "r"(dst), "l"(m), "r"(c0), "r"(c1), "r"(c2), "r"(c3), "r"(bar) : "memory");
}
DEV void tma3(uint32_t dst, const CUtensorMap* m, int c0, int c1, int c2, uint32_t bar) {
  asm volatile("{.reg .pred p; elect.sync _|p,0xffffffff;\n"
    "@p cp.async.bulk.tensor.3d.shared::cluster.global.mbarrier::complete_tx::bytes [%0],[%1,{%2,%3,%4}],[%5];}"
    :: "r"(dst), "l"(m), "r"(c0), "r"(c1), "r"(c2), "r"(bar) : "memory");
}
DEV void bulk(uint32_t dst, const void* src, int bytes, uint32_t bar) {
  asm volatile("{.reg .pred p; elect.sync _|p,0xffffffff;\n@p cp.async.bulk.shared::cluster.global.mbarrier::complete_tx::bytes [%0],[%1],%2,[%3];}" :: "r"(dst), "l"(src), "r"(bytes), "r"(bar) : "memory");
}

DEV void bulk_store(void* dst, uint32_t src, int bytes) {
  asm volatile("{.reg .pred p; elect.sync _|p,0xffffffff;\n@p cp.async.bulk.global.shared::cta.bulk_group [%0],[%1],%2;}" :: "l"(dst), "r"(src), "r"(bytes) : "memory");
}
DEV void tma2_store(const CUtensorMap* m, uint32_t src, int c0, int c1) {
  asm volatile("{.reg .pred p; elect.sync _|p,0xffffffff;\n@p cp.async.bulk.tensor.2d.global.shared::cta.bulk_group [%0,{%2,%3}],[%1];}" :: "l"(m), "r"(src), "r"(c0), "r"(c1) : "memory");
}
DEV void bulk_wait() { asm volatile("cp.async.bulk.commit_group;\ncp.async.bulk.wait_group 0;\nfence.proxy.async.global;" ::: "memory"); }

DEV uint64_t mkdesc(uint32_t addr, uint32_t lbo, uint32_t sbo, uint32_t swz) {
  return (uint64_t)((addr >> 4) | ((lbo >> 4) << 16)) | ((uint64_t)((sbo >> 4) | (swz << 30)) << 32);
}
DEV void wg_fence() { asm volatile("wgmma.fence.sync.aligned;" ::: "memory"); }
DEV void wg_commit() { asm volatile("wgmma.commit_group.sync.aligned;" ::: "memory"); }
template <int N> DEV void wg_wait() { asm volatile("wgmma.wait_group.sync.aligned %0;" :: "n"(N) : "memory"); }
template <int N> DEV void zero(float (&d)[N]) {
#pragma unroll
  for (int i = 0; i < N; ++i) d[i] = 0.f;
}
template <int N> DEV void zerov(float (&d)[N]) {
#pragma unroll
  for (int i = 0; i < N; ++i) asm volatile("mov.b32 %0,0;" : "=f"(d[i]));
}
template <int N> DEV void undef(float (&d)[N]) {
#pragma unroll
  for (int i = 0; i < N; ++i) asm volatile("" : "=f"(d[i]));
}
#define R4(d, o) "+f"(d[o]), "+f"(d[o + 1]), "+f"(d[o + 2]), "+f"(d[o + 3])
#define R8(d, o) R4(d, o), R4(d, o + 4)
#define R16(d, o) R8(d, o), R8(d, o + 8)
template <int ACC> DEV void wg_rs64k(float (&d)[32], const uint32_t (&a)[4], uint64_t db) {
  asm volatile("{.reg .pred p; setp.ne.s32 p,%37,0;\nwgmma.mma_async.sync.aligned.m64n64k16.f32.bf16.bf16 {%0,%1,%2,%3,%4,%5,%6,%7,%8,%9,%10,%11,%12,%13,%14,%15,%16,%17,%18,%19,%20,%21,%22,%23,%24,%25,%26,%27,%28,%29,%30,%31},{%32,%33,%34,%35},%36,p,1,1,0;}"
    : R16(d, 0), R16(d, 16) : "r"(a[0]), "r"(a[1]), "r"(a[2]), "r"(a[3]), "l"(db), "n"(ACC));
}
template <int ACC> DEV void wg_rs24t(float (&d)[12], const uint32_t (&a)[4], uint64_t db) {
  asm volatile("{.reg .pred p; setp.ne.s32 p,%17,0;\nwgmma.mma_async.sync.aligned.m64n24k16.f32.bf16.bf16 {%0,%1,%2,%3,%4,%5,%6,%7,%8,%9,%10,%11},{%12,%13,%14,%15},%16,p,1,1,1;}"
    : R8(d, 0), R4(d, 8) : "r"(a[0]), "r"(a[1]), "r"(a[2]), "r"(a[3]), "l"(db), "n"(ACC));
}
template <int ACC> DEV void wg_rs16t(float (&d)[8], const uint32_t (&a)[4], uint64_t db) {
  asm volatile("{.reg .pred p; setp.ne.s32 p,%13,0;\nwgmma.mma_async.sync.aligned.m64n16k16.f32.bf16.bf16 {%0,%1,%2,%3,%4,%5,%6,%7},{%8,%9,%10,%11},%12,p,1,1,1;}"
    : R8(d, 0) : "r"(a[0]), "r"(a[1]), "r"(a[2]), "r"(a[3]), "l"(db), "n"(ACC));
}
template <int ACC> DEV void wg_rs32t(float (&d)[16], const uint32_t (&a)[4], uint64_t db) {
  asm volatile("{.reg .pred p; setp.ne.s32 p,%21,0;\nwgmma.mma_async.sync.aligned.m64n32k16.f32.bf16.bf16 {%0,%1,%2,%3,%4,%5,%6,%7,%8,%9,%10,%11,%12,%13,%14,%15},{%16,%17,%18,%19},%20,p,1,1,1;}"
    : R16(d, 0) : "r"(a[0]), "r"(a[1]), "r"(a[2]), "r"(a[3]), "l"(db), "n"(ACC));
}
template <int ACC> DEV void wg_ss192(float (&d)[96], uint64_t da, uint64_t db) {
  asm volatile("{.reg .pred p; setp.ne.s32 p,%98,0;\nwgmma.mma_async.sync.aligned.m64n192k16.f32.bf16.bf16 {"
    "%0,%1,%2,%3,%4,%5,%6,%7,%8,%9,%10,%11,%12,%13,%14,%15,%16,%17,%18,%19,%20,%21,%22,%23,%24,%25,%26,%27,%28,%29,%30,%31,"
    "%32,%33,%34,%35,%36,%37,%38,%39,%40,%41,%42,%43,%44,%45,%46,%47,%48,%49,%50,%51,%52,%53,%54,%55,%56,%57,%58,%59,%60,%61,%62,%63,"
    "%64,%65,%66,%67,%68,%69,%70,%71,%72,%73,%74,%75,%76,%77,%78,%79,%80,%81,%82,%83,%84,%85,%86,%87,%88,%89,%90,%91,%92,%93,%94,%95},"
    "%96,%97,p,1,1,1,1;}"
    : R16(d, 0), R16(d, 16), R16(d, 32), R16(d, 48), R16(d, 64), R16(d, 80) : "l"(da), "l"(db), "n"(ACC));
}
template <int ACC> DEV void wg_ss64(float (&d)[32], uint64_t da, uint64_t db) {
  asm volatile("{.reg .pred p; setp.ne.s32 p,%34,0;\nwgmma.mma_async.sync.aligned.m64n64k16.f32.bf16.bf16 {%0,%1,%2,%3,%4,%5,%6,%7,%8,%9,%10,%11,%12,%13,%14,%15,%16,%17,%18,%19,%20,%21,%22,%23,%24,%25,%26,%27,%28,%29,%30,%31},%32,%33,p,1,1,0,1;}"
    : R8(d, 0), R8(d, 8), R8(d, 16), R8(d, 24) : "l"(da), "l"(db), "n"(ACC));
}

struct Params {
  const uint16_t *x0, *Are, *Aim, *Bre, *Bim, *Cre, *Cim, *logdt, *dskip, *wqkv, *wo;
  uint16_t* out;
  uint8_t role[144];
  int by_sm;
  uint32_t zero, spare;
};

DEV uint32_t ln_word(float mean, float var) {
  float v = bfr(var);
  float s = sqrt_(bfr(v + 1e-5f));
  return pack2(mean, s);
}

DEV int stat_group(int c) { return 16 * (c & 4) + 4 * (c >> 3) + (c & 3); }
DEV int xg_off(int G, int g) { return (G >> 6) * 1024 + (G & 63) * 8 + (g ^ (G & 2)); }
DEV int sr_off(int G, int g) { return (G >> 6) * 256 + (g & 2) * 64 + 2 * (G & 63) + ((g >> 2) & 1); }
DEV uint32_t region(int chl) { return SM_A + (chl >> 1) * A_E + (chl & 1) * R_SZ; }
template <int N> DEV float4 gram(const uint32_t (&w)[N][2], int g) {
  float s0[4], s1[4];
  const uint32_t one = 0x3F803F80u;
  mma16z(s0, w[0][0], one, w[1][0], one, w[0][0], w[1][0]); mma16z(s1, w[0][1], one, w[1][1], one, w[0][1], w[1][1]);
#pragma unroll
  for (int j = 2; j < N; j += 2) {
    mma16(s0, w[j][0], one, w[j + 1][0], one, w[j][0], w[j + 1][0]); mma16(s1, w[j][1], one, w[j + 1][1], one, w[j][1], w[j + 1][1]);
  }
  const bool od = g & 1;
  return make_float4(od ? s0[3] : s0[2], od ? s0[1] : s0[0], od ? s1[3] : s1[2], od ? s1[1] : s1[0]);
}
DEV uint32_t ln_sums(float s, float q) { const float m = s * (1.f / 512.f); return ln_word(m, fmaxf(q * (1.f / 512.f) - m * m, 0.f)); }
DEV void cmul(float& orr, float& oi, float ar, float ai, float br, float bi) {
  float r = ar * br - ai * bi, i = ar * bi + ai * br; orr = r; oi = i;
}
DEV void cexp_(float al, float bt, float s, float& er, float& ei) {
  float mag = ex2(al * s), ph = bt * s;
  ph -= rintf(ph);
  float ang = ph * 6.283185307179586f;
  er = mag * __cosf(ang); ei = mag * __sinf(ang);
}

DEV void kgen(const Params& P, int c, int wm, int lane) {
  const int chl = wm >> 1, mh = wm & 1, g = lane >> 2, t = lane & 3;
  const int ch = 256 * (chl >> 1) + 2 * c + (chl & 1);
  const int mo = ch * 64 + mh * 32 + lane;
  uint32_t vAr = __ldg((const uint32_t*)P.Are + mo), vAi = __ldg((const uint32_t*)P.Aim + mo);
  uint32_t vBr = __ldg((const uint32_t*)P.Bre + mo), vBi = __ldg((const uint32_t*)P.Bim + mo);
  uint32_t vCr = __ldg((const uint32_t*)P.Cre + mo), vCi = __ldg((const uint32_t*)P.Cim + mo);
  uint32_t vld = __ldg(P.logdt + ch), vds = __ldg(P.dskip + ch);
  {
    const uint32_t tz = SM_TAP + chl * TAP_SZ + (mh * 32 + lane) * 16;
#pragma unroll
    for (int k = 0; k < 3; ++k) sts4(tz + k * 1024, 0, 0, 0, 0);
    static_assert(TAP_SZ > 3072 && TAP_SZ <= 4096, "");
    if (mh * 32 + lane < TAP_SZ / 16 - 192) sts4(tz + 3072, 0, 0, 0, 0);
  }
  const float dt = bfr(__expf(bflo(vld)));
  const uint32_t tb = slot(wm);
  float acc[5][4];
#pragma unroll
  for (int i = 0; i < 5; ++i) { acc[i][0] = acc[i][1] = acc[i][2] = acc[i][3] = 0.f; }
  float k2048 = 0.f;
#pragma unroll 1
  for (int r = 0; r < 2; ++r) {
    const float are = r ? bfhi(vAr) : bflo(vAr), aim = r ? bfhi(vAi) : bflo(vAi);
    const float bre = r ? bfhi(vBr) : bflo(vBr), bim = r ? bfhi(vBi) : bflo(vBi);
    const float cre = r ? bfhi(vCr) : bflo(vCr), cim = r ? bfhi(vCi) : bflo(vCi);
    const float al = dt * are * 1.4426950408889634f, bt = dt * aim * 0.15915494309189535f;
    float wr, wi; cmul(wr, wi, cre, cim, dt * bre, dt * bim);
    if (r == 0) PROFD(2, __float_as_uint(wr + al + bt));
    float e1r, e1i, e8r, e8i, eLr, eLi;
    cexp_(al, bt, 1.f, e1r, e1i); cexp_(al, bt, 8.f, e8r, e8i); cexp_(al, bt, 128.f, eLr, eLi);
    const uint32_t tw = tb + lane * 4;
    float pr[8], pi[8];
    pr[1] = e1r; pi[1] = e1i;
#pragma unroll
    for (int k = 2; k < 8; ++k) cmul(pr[k], pi[k], pr[k - 1], pi[k - 1], e1r, e1i);
    float yr = 1.f, yi = 0.f, qr = wr, qi = wi;
#pragma unroll
    for (int a = 0; a < 16; ++a) {
      sts1(tw + a * 144, pack2(yr, -yi));
      if (a == 0) { yr = e8r; yi = e8i; } else if (a < 15) cmul(yr, yi, yr, yi, e8r, e8i);
      const int step = a < 2 ? 1 : a < 4 ? 2 : a < 8 ? 4 : 8;
      const int row0 = 16 + (a < 2 ? 8 * a : a < 4 ? 16 + 4 * (a - 2) : a < 8 ? 24 + 2 * (a - 4) : 32 + (a - 8));
      sts1(tw + row0 * 144, pack2(qr, qi));
#pragma unroll
      for (int k = step; k < 8; k += step) {
        float xr, xi; cmul(xr, xi, qr, qi, pr[k], pi[k]);
        sts1(tw + (row0 + k / step) * 144, pack2(xr, xi));
      }
      cmul(qr, qi, qr, qi, eLr, eLi);
    }
    k2048 += qr;
    __syncwarp();
    if (r == 0) PROF(3);
#pragma unroll
    for (int kp = 0; kp < 2; ++kp) {
      uint32_t a0[4], a1[4];
      const uint32_t aa = tb + ((lane & 7) + 8 * ((lane >> 3) & 1)) * 144 + (lane >> 4) * 16 + kp * 64;
      ldsm4(a0, aa); ldsm4(a1, aa + 32);
#pragma unroll
      for (int tl = 0; tl < 5; ++tl) {
        uint32_t b[4];
        ldsm4(b, tb + (16 + 8 * tl + (lane & 7)) * 144 + (lane >> 3) * 16 + kp * 64);
        mma16(acc[tl], a0[0], a0[1], a0[2], a0[3], b[0], b[1]);
        mma16(acc[tl], a1[0], a1[1], a1[2], a1[3], b[2], b[3]);
      }
    }
    __syncwarp();
  }
#pragma unroll
  for (int o = 16; o > 0; o >>= 1) k2048 += __shfl_xor_sync(0xffffffffu, k2048, o);
  if (mh == 0) {
    sts4f(tb + lane * 16, acc[2][0], acc[2][1], acc[2][2], acc[2][3]);
    sts4f(tb + 512 + lane * 16, acc[3][0], acc[3][1], acc[3][2], acc[3][3]);
  } else {
    sts4f(tb + lane * 16, acc[0][0], acc[0][1], acc[0][2], acc[0][3]);
    sts4f(tb + 512 + lane * 16, acc[1][0], acc[1][1], acc[1][2], acc[1][3]);
    sts4f(tb + 1024 + lane * 16, acc[4][0], acc[4][1], acc[4][2], acc[4][3]);
    if (lane == 0) sts1(tb + 1536, __float_as_uint(k2048));
  }
  PROF(4);
  bar_sync(NB_K + chl, 64);
  const uint32_t ob = slot(wm ^ 1), tp = SM_TAP + chl * TAP_SZ;
  if (mh == 0) {
#pragma unroll
    for (int tl = 0; tl < 2; ++tl) {
      float4 o = lds4f(ob + tl * 512 + lane * 16);
      if (tl == 0 && lane == 0) o.x += bflo(vds);
      uint32_t v0 = pack2(acc[tl][0] + o.x, acc[tl][1] + o.y), v1 = pack2(acc[tl][2] + o.z, acc[tl][3] + o.w);
      const int l = 128 * tl + 8 * g + 2 * t;
      sts16(tp + T_E + 2 * (0 - l), v0); sts16(tp + T_E + 2 * (-1 - l), v0 >> 16);
      sts16(tp + T_O + 2 * (0 - l), v0); sts16(tp + T_O + 2 * (-1 - l), v0 >> 16);
      sts16(tp + T_E + 2 * (-64 - l), v1); sts16(tp + T_E + 2 * (-65 - l), v1 >> 16);
      sts16(tp + T_O + 2 * (-64 - l), v1); sts16(tp + T_O + 2 * (-65 - l), v1 >> 16);
    }
    float4 o = lds4f(ob + 1024 + lane * 16);
    uint32_t v0 = pack2(acc[4][0] + o.x, acc[4][1] + o.y), v1 = pack2(acc[4][2] + o.z, acc[4][3] + o.w);
    const int x = 32 * t + g - 1;
    if (lane == 0) { sts16(tp + T_E - 2 * (X_5 + 63), v0); sts16(tp + T_O - 2 * (X_5 + 63), v0); sts1(tp + T_K, prmt(v0, v0, 0x1010)); }
    else sts16(tp + T_C - 2 * x, v0);
    sts16(tp + T_C - 2 * (x + 16), v0 >> 16);
    sts16(tp + T_C - 2 * (x + 8), v1);
    sts16(tp + T_C - 2 * (x + 24), v1 >> 16);
    if (lane == 0) sts16(tp + T_C - 2 * 127, pack2(k2048 + __uint_as_float(lds1(ob + 1536)), 0.f));
  } else {
    float4 o2 = lds4f(ob + lane * 16), o3 = lds4f(ob + 512 + lane * 16);
    uint32_t v0 = pack2(acc[2][0] + o2.x, acc[2][1] + o2.y), v1 = pack2(acc[2][2] + o2.z, acc[2][3] + o2.w);
    const int l0 = 256 + 128 * (t >> 1) + 4 * (t & 1) + 8 * g;
    if (lane != 0) { sts16(tp + T_E + 2 * (1 - l0), v0); sts16(tp + T_O + 2 * (1 - l0), v0); }
    sts16(tp + T_E + 2 * (0 - l0), v0); sts16(tp + T_O + 2 * (0 - l0), v0);
    sts16(tp + T_E + 2 * (-1 - l0), v0); sts16(tp + T_O + 2 * (-1 - l0), v0);
    sts16(tp + T_E + 2 * (-2 - l0), v0 >> 16); sts16(tp + T_O + 2 * (-2 - l0), v0 >> 16);
    sts16(tp + T_E + 2 * (-63 - l0), v1); sts16(tp + T_O + 2 * (-63 - l0), v1);
    sts16(tp + T_E + 2 * (-64 - l0), v1); sts16(tp + T_O + 2 * (-64 - l0), v1);
    sts16(tp + T_E + 2 * (-65 - l0), v1); sts16(tp + T_O + 2 * (-65 - l0), v1);
    sts16(tp + T_E + 2 * (-66 - l0), v1 >> 16); sts16(tp + T_O + 2 * (-66 - l0), v1 >> 16);
    uint32_t w0 = pack2(acc[3][0] + o3.x, acc[3][1] + o3.y), w1 = pack2(acc[3][2] + o3.z, acc[3][3] + o3.w);
    const int x = 16 * t + g;
    if (lane == 0) {
      const uint32_t k = prmt(w0, w0, 0x1010);
      sts1(tp + T_E - 2 * 514, k); sts1(tp + T_E - 2 * 512, k);
      sts16(tp + T_O - 2 * 514, k); sts1(tp + T_O - 2 * 513, k); sts16(tp + T_O - 2 * 511, k);
    } else { sts16(tp + T_E - 2 * (X_5 - 1 + x), w0); sts16(tp + T_O - 2 * (X_5 - 1 + x), w0); }
    sts16(tp + T_E - 2 * (X_3 + x), w0 >> 16); sts16(tp + T_O - 2 * (X_3 + x), w0 >> 16);
    sts16(tp + T_E - 2 * (X_5 + 7 + x), w1); sts16(tp + T_O - 2 * (X_5 + 7 + x), w1);
    sts16(tp + T_E - 2 * (X_3 + 8 + x), w1 >> 16); sts16(tp + T_O - 2 * (X_3 + 8 + x), w1 >> 16);
  }
}

DEV bool bad8(const uint4& v) { return min(v.x, v.z) == 0u; }
DEV uint32_t uchunk(uint32_t reg, int x) { return reg + R_U + (x ^ ((x >> 3) & 3)) * 16; }
DEV uint32_t& xword(uint4 (&x)[2], int e, int tp) { uint4& v = x[tp >> 1]; return tp & 1 ? (e ? v.w : v.z) : (e ? v.y : v.x); }

DEV void sload(int c, int j, int layer, uint4 (&s)[2][2]) {
  const uint4* st = &g_SR[layer][c >> 4][opq(j)];
  mbar_wait(B_U, layer);
  PROF(layer ? 25 : 10);
#pragma unroll
  for (int z = 0; z < 4; ++z) s[z >> 1][z & 1] = ldr4(st + z * 128);
}
DEV void uload(int c, int j, int layer, uint4 (&x)[2][2][2], uint4 (&s)[2][2]) {
  j = opq(j);
  const uint4* st = &g_SR[layer][c >> 4][j];
  const int o0 = 2 * j + ((j >> 2) & 1), o1 = o0 ^ 1;
#pragma unroll
  for (int z = 0; z < 4; ++z) { uint4& v = s[z >> 1][z & 1]; ldr4_if(v, st + z * 128, bad8(v)); }
  PROF(layer ? 26 : 11);
  mbar_wait(B_E, layer);
#pragma unroll
  for (int z = 0; z < 8; ++z) x[z >> 2][(z >> 1) & 1][z & 1] = lds4(SM_X + 16 * (z & 1 ? o1 : o0) + (z >> 1) * 4096);
  PROF(layer ? 27 : 14);
  for (int it = 0;; ++it) {
    uint32_t m = ~0u;
#pragma unroll
    for (int z = 0; z < 4; ++z) { const uint4& v = s[z >> 1][z & 1]; m = min(m, min(v.x, v.z)); }
#pragma unroll
    for (int z = 0; z < 8; ++z) { const uint4& v = x[z >> 2][(z >> 1) & 1][z & 1]; m = min(m, min(v.x, v.z)); }
    if (!RARE(m == 0)) break;
#pragma unroll
    for (int z = 0; z < 4; ++z) { uint4& v = s[z >> 1][z & 1]; ldr4_if(v, st + z * 128, bad8(v)); }
#pragma unroll
    for (int z = 0; z < 8; ++z) {
      uint4& v = x[z >> 2][(z >> 1) & 1][z & 1];
      ldr4_if(v, &g_XG[layer][c * 1024 + (opq(o0) ^ (z & 1)) + (z >> 1) * 256], bad8(v));
    }
    spin_guard(it);
  }
  PROF(4 + 12 * layer);
}
DEV void uprep(int j, int k, uint4 (&x)[2][2], uint4 (&s)[2], uint32_t (&u)[4][4]) {
  const uint32_t ua = uchunk(0, opq(j)) + k * 2048;
#pragma unroll
  for (int chl = 0; chl < 4; ++chl) {
#pragma unroll
    for (int tp = 0; tp < 4; ++tp) u[chl][tp] = hmul2(hsub2(xword(x[chl >> 1], chl & 1, tp), xword(s, 1, tp)), xword(s, 0, tp));
    sts4(ua + region(chl), u[chl][0], u[chl][1], u[chl][2], u[chl][3]);
  }
}

template <bool FULL> DEV void box_unit(uint32_t reg, int s, const uint32_t (&d)[4], uint32_t (&pv)[4]) {
  const uint2 a = lds2(uchunk(reg, s - 2) + 8);
  const uint4 b = lds4(uchunk(reg, s - 1));
  const uint32_t u[9] = {a.x, a.y, b.x, b.y, b.z, b.w, d[0], d[1], d[2]};
  uint32_t v[8], p[8];
#pragma unroll
  for (int j = 0; j < 8; ++j) { v[j] = prmt(u[j], u[j + 1], 0x5432); p[j] = hadd2(u[j], v[j]); }
  const uint32_t o = reg + s * 16;
  uint32_t x[4], y[4];
#pragma unroll
  for (int j = 0; j < 4; ++j) { x[j] = hadd2(hadd2(p[1 + j], p[2 + j]), u[3 + j]); y[j] = hadd2(v[3 + j], p[4 + j]); pv[j] = p[4 + j]; }
  sts4(o + R_X5, x[0], x[1], x[2], x[3]);
  sts4(o + R_X3, y[0], y[1], y[2], y[3]);
  if (FULL) {
#pragma unroll
    for (int j = 0; j < 4; ++j) { y[j] = hadd2(hadd2(v[j], v[3 + j]), x[j]); x[j] = hadd2(hadd2(u[j], u[4 + j]), y[j]); }
    const bool od = s & 1;
    sts4(o + R_BO, od ? y[0] : x[0], od ? y[1] : x[1], od ? y[2] : x[2], od ? y[3] : x[3]);
    sts4(o + R_BE + 16, od ? x[0] : y[0], od ? x[1] : y[1], od ? x[2] : y[2], od ? x[3] : y[3]);
  }
}
DEV void box_full(int j, int chl, uint32_t (&u)[4]) {
  const uint32_t d[4] = {u[0], u[1], u[2], u[3]};
  box_unit<true>(region(chl), j, d, u);
  fence_async_smem();
  bar_arrive(NB_B + chl, 288);
}
DEV void box_help(int chl, int lane) {
  const uint32_t reg = region(chl);
#pragma unroll 1
  for (int s = 128 + opq(lane); s < 192; s += 32) {
    const uint4 d = lds4(uchunk(reg, s));
    const uint32_t u[4] = {d.x, d.y, d.z, d.w};
    uint32_t v[4];
    box_unit<false>(reg, s, u, v);
  }
  fence_async_smem();
  bar_arrive(NB_B + chl, 288);
}

DEV uint4 hadd8(const uint4& a, const uint4& b) { return make_uint4(hadd2(a.x, b.x), hadd2(a.y, b.y), hadd2(a.z, b.z), hadd2(a.w, b.w)); }
DEV void conv_out(int c, int j, int chl, uint4 (&x)[2][2][2], const uint32_t (&v)[4], uint4* XF) {
  const int rho = chl >> 1, e = chl & 1;
  const uint32_t ua = uchunk(region(chl), j), fa = region(chl) + R_X5 + j * 16, ha = region(chl) + R_X3 + (j & 1) * 1088 + (j >> 1) * 16;
  const int m8 = ((j & 4) + ((j >> 1) & 1)) ^ ((2 * c + e) & 7);
  uint2* xo = (uint2*)XF + (((j >> 3) * 512 + 256 * rho + 2 * c + e) * 16 + (j & 1));
  bar_sync(NB_Y + e, 256);
  uint4 y[2], f[2], h[2];
#pragma unroll
  for (int k = 0; k < 2; ++k) {
    y[k] = lds4(ua + k * 2048);
    f[k] = lds4z(ua + k * 2048 + R_BO - R_U, k || j >= 36);
    h[k] = lds4z(fa + k * 2048 - 1024, k || j >= 64);
  }
  const uint32_t q = lds1(SM_TAP + chl * TAP_SZ + T_K);
  const uint4 r = lds4(ha);
  h[1] = hadd8(h[1], make_uint4(hfma2(q, v[0], r.x), hfma2(q, v[1], r.y), hfma2(q, v[2], r.z), hfma2(q, v[3], r.w)));
#pragma unroll
  for (int k = 0; k < 2; ++k) {
    const uint4 o = hadd8(hadd8(y[k], hadd8(f[k], h[k])), make_uint4(xword(x[k][rho], e, 0), xword(x[k][rho], e, 1), xword(x[k][rho], e, 2), xword(x[k][rho], e, 3)));
    str2(xo + k * 131072 + 2 * m8, prmt(o.x, o.y, 0x5410), prmt(o.z, o.w, 0x5410));
    str2(xo + k * 131072 + 2 * (m8 ^ 2), prmt(o.x, o.y, 0x7632), prmt(o.z, o.w, 0x7632));
  }
  if (e) { __syncwarp(); mbar_arrive1(B_RD + rho * 8); }
}

DEV uint32_t cpy(uint32_t v, uint32_t id) {
  uint32_t d; asm volatile("prmt.b32 %0,%1,%1,%2;" : "=r"(d) : "r"(v), "r"(id)); return d;
}
DEV void tapcp(uint32_t (&q)[4][4], uint32_t top, uint32_t id) {
#pragma unroll
  for (int kk = 0; kk < 4; ++kk) { q[kk][3] = cpy(q[kk][0], id); q[kk][2] = cpy(kk < 3 ? q[kk < 3 ? kk + 1 : 0][1] : top, id); }
}
template <int UP> DEV void tapldz(uint32_t (&q)[4][4], uint32_t a, int w) {
#pragma unroll
  for (int kk = 0; kk < 4; ++kk) { q[kk][1] = lds1z(a + 32 * kk, UP ? w < kk : w >= kk); q[kk][0] = lds1z(a + 32 * kk + 16, UP ? w <= kk : w >= kk); }
}

DEV void far_taps(uint32_t (&q)[5][4][4], uint32_t ga, uint32_t gc, int w, uint32_t id) {
  tapldz<0>(q[0], ga, w); tapldz<1>(q[1], ga - 128, w);
#pragma unroll
  for (int kk = 0; kk < 4; ++kk) {
    q[4][kk][0] = lds1z(gc + 32 * kk, w >= kk); q[4][kk][2] = lds1z(gc + 32 * kk + 16, w >= kk);
    q[4][kk][1] = lds1(gc + 32 * kk - 128); q[4][kk][3] = lds1(gc + 32 * kk - 112);
  }
  tapcp(q[0], 0, id); tapcp(q[1], q[0][0][1], id);
}

DEV void conv_round(int e, int rho, int w, int lane) {
  const int g = lane >> 2, t = lane & 3, chl = 2 * rho + e;
  const uint32_t reg = region(chl), tp = SM_TAP + chl * TAP_SZ;
  const uint32_t g0 = tp + ((g & 1) ? T_O : T_E) + 2 * (2 * t - g) - 16;
  uint32_t ga = g0 - 32 * (w & 1) - 576 * (w >> 1);
  const uint32_t id = opq(0x3210u), gc = tp + T_C - 2 + 4 * (t - g - 8 * w);
  float acc[32], f1[12], f2[8], f3[16];
  uint32_t q[5][4][4];
  {
    uint32_t qn[18][4];
    qn[0][2] = lds1(ga + 64);
#pragma unroll
    for (int n = 0; n < 18; ++n) {
      const bool nz = n < 15 || w < 2 || (n == 15 && w == 2);
      qn[n][0] = n < 15 ? lds1(ga + 48 - 32 * n) : lds1z(ga + 48 - 32 * n, nz);
      qn[n][1] = n < 15 ? lds1(ga + 32 - 32 * n) : lds1z(ga + 32 - 32 * n, nz);
    }
#pragma unroll
    for (int n = 0; n < 18; ++n) { qn[n][3] = cpy(qn[n][0], id); if (n) qn[n][2] = cpy(qn[n - 1][1], id); }
    far_taps(q, ga = g0 - 32 * w - 2 * X_5, gc, w, id);
    bar_sync_if(NB_U, NBARU, 1 - rho);
    PROF(43);
    bar_sync_if(NB_T + 1 - e, 256, chl);
    const uint64_t db = mkdesc(reg + R_U, 16, 512, 2) + 2;
    undef(acc);
    wg_fence();
#pragma unroll
    for (int n = 0; n < 18; ++n) {
      if (n) wg_rs64k<1>(acc, qn[n], db - 2 * n); else wg_rs64k<0>(acc, qn[0], db);
      if (n == 9) wg_commit();
    }
    wg_commit();
  }
  wg_wait<1>();
  tapldz<0>(q[2], ga - 2 * (X_3 - X_5), w); tapldz<1>(q[3], ga - 2 * (X_3 - X_5) - 128, w);
  tapcp(q[2], 0, id); tapcp(q[3], q[2][0][1], id);
  PROF(12);
  bar_sync(NB_B + chl, 288);
  const uint64_t db = mkdesc(reg + R_X5, 128, 1024, 0);
  undef(f1); undef(f2);
  wg_fence();
#pragma unroll
  for (int n = 0; n < 8; ++n) {
    const uint64_t d = db + (n >> 2) * ((R_X3 - R_X5) / 16) + 16 * (n & 3);
    if (n) wg_rs24t<1>(f1, q[2 * (n >> 2)][n & 3], d); else wg_rs24t<0>(f1, q[0][0], d);
    if (n) wg_rs16t<1>(f2, q[2 * (n >> 2) + 1][n & 3], d); else wg_rs16t<0>(f2, q[1][0], d);
  }
  wg_commit();
  wg_wait<1>();
  PROF(13);
  undef(f3);
  wg_fence();
#pragma unroll
  for (int n = 0; n < 4; ++n) {
    const uint64_t d = db + (R_BO - R_X5) / 16 + 16 * n;
    if (n) wg_rs32t<1>(f3, q[4][n], d); else wg_rs32t<0>(f3, q[4][0], d);
  }
  wg_commit();
  bar_arrive_if(NB_T + e, 256, chl - 3);
  wg_wait<0>();
  PROF(14);
  bar_sync(NB_WG + e, 128);
  {
    const int p = (lane + 9 * (w >> 1)) & 31;
    const uint32_t ya = reg + ((w >> 1) ? R_BO : R_U) + p * 64 + (((2 * (w & 1)) ^ ((p >> 1) & 3)) * 16);
    const uint32_t up = p < lane ? 2048 : 0;
#pragma unroll
    for (int z = 0; z < 4; ++z) {
      const float* a = acc + 16 * (z >> 1) + 2 * (z & 1);
      stsm4t((ya + (up ^ ((z >> 1) * 2048))) ^ ((z & 1) * 16), pack2(a[0], a[1]), pack2(a[4], a[5]), pack2(a[8], a[9]), pack2(a[12], a[13]));
    }
  }
  {
    const uint32_t fa = reg + R_X5 + (16 * w + (lane & 15)) * 16;
    stsm2(fa, pack2(f1[0], f1[1]), pack2(f1[2], f1[3]));
    stsm4(fa + 1024 + (lane >> 4) * 1024, pack2(f1[4] + f2[0], f1[5] + f2[1]), pack2(f1[6] + f2[2], f1[7] + f2[3]),
          pack2(f1[8] + f2[4], f1[9] + f2[5]), pack2(f1[10] + f2[6], f1[11] + f2[7]));
    stsm4(reg + R_X3 + (lane < 16 ? 1088 : 0) + (8 * w + (lane & 7) + 4 * (lane & 8)) * 16, pack2(f3[0], f3[1]), pack2(f3[2] + f3[4], f3[3] + f3[5]),
          pack2(f3[8], f3[9]), pack2(f3[10] + f3[12], f3[11] + f3[13]));
  }
  bar_arrive(NB_Y + e, 256);
}
constexpr uint32_t FILL = 0xFFFFFFFFu;
template <int N> DEV void fixo(uint4 (&A)[N], const uint4* p) {
#pragma unroll 1
  for (int it = 0; it < SPIN_LIMIT; ++it) {
    uint32_t m = A[0].x;
#pragma unroll
    for (int k = 1; k < N; ++k) m = max(m, A[k].x);
    if (__all_sync(0xffffffffu, m != FILL)) break;
#pragma unroll
    for (int k = 0; k < N; ++k) ldr4_if(A[k], p + k * 32, A[k].x == FILL);
  }
}
DEV bool rows_nan(float a, float b) {
  return __any_sync(0xffffffffu, a != a || b != b);
}
template <int N> DEV void slow_step(float (&acc)[N], float a0, float a1, const uint16_t* wr, uint32_t zero) {
#pragma unroll
  for (int j = 0; j < N / 4; ++j) {
    const uint32_t v = __ldg((const uint32_t*)(wr + (j >> 3) * 512 + 8 * (j & 7)));
    acc[4 * j] += a0 * bflo(v); acc[4 * j + 1] += a0 * bfhi(v); acc[4 * j + 2] += a1 * bflo(v); acc[4 * j + 3] += a1 * bfhi(v);
    if ((j & 3) == 3) wr += __float_as_uint(acc[4 * j]) & zero;
  }
}
DEV int res_off(int w, int lane) { return ((lane & 7) + 8 * (lane >> 4)) * 8 + ((2 * (w & 2) + (w & 1) + ((lane >> 2) & 2)) ^ (lane & 7)); }
DEV void res_load(uint32_t (&res)[8][2], uint32_t sa, int w, int lane) {
  const uint32_t a = sa + res_off(w, opq(lane)) * 16;
#pragma unroll
  for (int j = 0; j < 8; j += 2) {
    uint32_t r[4];
    ldsm4t(r, a + j * 1024);
    res[j][0] = r[0]; res[j][1] = r[1]; res[j + 1][0] = r[2]; res[j + 1][1] = r[3];
  }
}

DEV uint32_t after(uint32_t b, const uint32_t (&res)[8][2], uint32_t zero) {
  return b + ((res[0][0] ^ res[2][0] ^ res[4][0] ^ res[6][0]) & zero);
}

DEV void attn_phase(const Params& P, int c, int e, int w, int lane, int layer) {
  lane = opq(lane); c = opq(c);
  const int i = c >> 3, cg = c & 7, J = 16 * e + i, G = 4 * J + w;
  const int g = lane >> 2, t = lane & 3;
  float acc[96];
  uint32_t res[8][2];
  float2 cs[16];
  float4 st;
  const uint32_t csb = opq(SM_CS + 8 * t);
  {
    const uint32_t sa = SM_A + e * A_E, ba = B_A + 16 * e;
    const uint64_t da = mkdesc(sa, 8192, 1024, 1), db = mkdesc(SB, 8192, 1024, 1);
    undef(acc);
#pragma unroll
    for (int j = 0; j < 8; ++j) asm volatile("" : "=r"(res[j][0]), "=r"(res[j][1]));
    mbar_wait(B_WF, layer);
    mbar_wait(ba, 0);
    mbar_wait(B_RD + 8, layer);
    bar_sync_if(NB_T, 256, e);
    PROF(24);
#pragma unroll
    for (int j = 0; j < 4; ++j) {
      if (j == 1) { mbar_wait(ba + 8, 0); PROF(39); }
      wg_fence();
#pragma unroll
      for (int k = 0; k < 4; ++k) {
        if (j | k) wg_ss192<1>(acc, da + j * 512 + k * 128, db + wslot(j) * 512 + k * 128); else wg_ss192<0>(acc, da, db);
        if (j == 3 && k == 1) wg_commit();
      }
      wg_commit();
      if (j == 1 || j == 2) { wg_wait<1>(); mbar_arrive1_if(B_F + 8 * (j - 1), e); }
    }
    wg_wait<1>();
    bar_arrive(NB_T + e, 256);
    wg_wait<0>();
    if (cg < 4) res_load(res, sa + cg * 8192, w, lane);
    mbar_arrive1(after(B_AE + 8 * e, res, P.zero));
    PROF(25);
    mbar_wait(B_CS, 0);
#pragma unroll 1
    for (uint32_t late = P.zero;; late = 1) {
      if (late) {
        const uint16_t* xr = (const uint16_t*)g_XF[layer] + opq(J) * 32768;
        zero(acc);
#pragma unroll 1
        for (int k = 0; k < 512; ++k)
          slow_step(acc, ldnan(xr + k * 64 + ((2 * w) ^ (k & 7)) * 8 + g), ldnan(xr + k * 64 + ((2 * w + 1) ^ (k & 7)) * 8 + g),
                    P.wqkv + (k * 1536 + 64 * cg + 2 * t), P.zero);
        const uint32_t* q = (const uint32_t*)xr + ((64 * cg + g) * 32 + t);
        const int m8 = (2 * (w & 2) + (w & 1)) ^ g;
#pragma unroll 1
        for (int it = 0; it < SPIN_LIMIT; ++it) {
          uint32_t m = 0;
#pragma unroll
          for (int z = 0; z < 16; ++z) { const uint32_t x = ldr1(q + (z >> 1) * 256 + (m8 ^ (2 * (z & 1))) * 4); m = max(m, x); res[z >> 1][z & 1] = movm(x); }
          if (__all_sync(0xffffffffu, m != FILL)) break;
        }
#pragma unroll
        for (int z = 0; z < 16; ++z) cs[z] = lds2f(csb + 256 + z * 32);
      } else {
#pragma unroll
        for (int z = 0; z < 16; ++z) cs[z] = lds2f(csb + 256 + z * 32);
        mbar_wait(B_W4, layer);
        mbar_wait(ba, 1);
        bar_sync(NB_T + 1 - e, 256);
        PROF(26);
#pragma unroll
        for (int j = 4; j < 8; ++j) {
          if (j == 5) mbar_wait(ba + 8, 1);
          if (j >= 6) mbar_wait(B_W6 + 8 * (j - 6), layer);
          if (j > 4) PROF(31 + j);
          wg_fence();
#pragma unroll
          for (int k = 0; k < 4; ++k) {
            wg_ss192<1>(acc, da + (j & 3) * 512 + k * 128, db + wslot(j) * 512 + k * 128);
            if (j == 7 && k == 1) wg_commit();
          }
          wg_commit();
          if (j == 5) {
            if (cg >= 4) res_load(res, sa + (cg - 4) * 8192, w, lane);
            wg_wait<1>(); mbar_arrive1_if(B_F + 16, e); PROF(40);
          }
        }
      }
      uint32_t rs = hadd2(res[0][0], res[0][1]);
#pragma unroll
      for (int z = 2; z < 16; ++z) rs = hadd2(rs, res[z >> 1][z & 1]);
      const float rn = bflo(rs) + bfhi(rs);
      wg_wait<1>();
      bar_arrive_if(NB_T, 256, !(e | late));
      mbar_wait(B_ST + 8 * e, layer);
      st = lds4f(SM_STAT + ((4 * e + w) * 8 + g) * 16);
      PROF(34 + layer);
      wg_wait<0>();
      if (!rows_nan(acc[0] + rn, acc[2]) || late) break;
    }
  }
  mbar_arrive1(B_QE);
  PROF(8 + 12 * layer);
  uint32_t Q[4][4], K[4][2][2], V[4][2][2];
  {
#pragma unroll
    for (int z = 0; z < 8; ++z) {
      const float* a = acc + 32 + 4 * z; const float* b = acc + 64 + 4 * z;
      K[z >> 1][1][z & 1] = pack2((a[2] - st.z * cs[z].x) * st.w, (a[3] - st.z * cs[z].y) * st.w);
      V[z >> 1][1][z & 1] = movm(pack2((b[2] - st.z * cs[8 + z].x) * st.w, (b[3] - st.z * cs[8 + z].y) * st.w));
    }
    const uint32_t kv = SM_KV + (2 * e + (w & 1)) * 2048 + lane * 16;
    uint4* h = g_H[layer] + ((J * 8 + cg) * 256 + (w & 1) * 128 + lane);
    if (w >= 2) {
#pragma unroll
      for (int z = 0; z < 4; ++z) str4(h + 2048 + z * 32, K[z][1][0], K[z][1][1], V[z][1][0], V[z][1][1]);
    } else {
      mbar_wait(B_F + 16, layer);
#pragma unroll
      for (int z = 0; z < 4; ++z) sts4(kv + z * 512, K[z][1][0], K[z][1][1], V[z][1][0], V[z][1][1]);
      bar_arrive(NB_WG + e, 128);
    }
    PROF(42);
#pragma unroll
    for (int z = 0; z < 8; ++z) {
      const float* a = acc + 32 + 4 * z; const float* b = acc + 64 + 4 * z;
      K[z >> 1][0][z & 1] = pack2((a[0] - st.x * cs[z].x) * st.y, (a[1] - st.x * cs[z].y) * st.y);
      V[z >> 1][0][z & 1] = movm(pack2((b[0] - st.x * cs[8 + z].x) * st.y, (b[1] - st.x * cs[8 + z].y) * st.y));
    }
#pragma unroll
    for (int z = 0; z < 8; ++z) {
      const float2 cq = lds2f(csb + z * 32);
      const float* a = acc + 4 * z;
      Q[z >> 1][2 * (z & 1)] = pack2(a[0] - st.x * cq.x, a[1] - st.x * cq.y);
      Q[z >> 1][2 * (z & 1) + 1] = pack2(a[2] - st.z * cq.x, a[3] - st.z * cq.y);
    }
    PROF(27);
    uint4 hv[4];
    if (w >= 2) {
      bar_sync(NB_WG + e, 128);
#pragma unroll
      for (int z = 0; z < 4; ++z) hv[z] = lds4(kv + z * 512);
    } else {
#pragma unroll
      for (int z = 0; z < 4; ++z) { hv[z] = make_uint4(0, 0, 0, 0); ldr4_if(hv[z], h + z * 32, G >= 2); }
    }
    const bool p0 = 2 * t > g, p1 = 2 * t + 1 > g, first = G < 2;
    float s[4][4], mx[4][2];
#pragma unroll
    for (int z = 0; z < 4; ++z) {
      float S[4];
      mma16z(s[z], Q[z][0], Q[z][1], Q[z][2], Q[z][3], K[z][0][0], K[z][0][1]);
      mma16z(S, Q[z][0], Q[z][1], Q[z][2], Q[z][3], K[z][1][0], K[z][1][1]);
      s[z][2] = p0 ? s[z][2] : S[2]; s[z][3] = p1 ? s[z][3] : S[3];
    }
    const float sc0 = st.y * (0.25f * 1.4426950408889634f), sc1 = st.w * (0.25f * 1.4426950408889634f);
    uint32_t pw[4][2];
#pragma unroll
    for (int r = 1; r >= 0; --r) {
      if (r == 0) {
        fixo(hv, h);
        PROFD(41, hv[3].x);
#pragma unroll
        for (int z = 0; z < 4; ++z) {
          float S[4];
          mma16z(S, Q[z][0], Q[z][1], Q[z][2], Q[z][3], hv[z].x, hv[z].y);
          if (first) S[0] = S[1] = __uint_as_float(0xFF800000u);
          s[z][0] = p0 ? S[0] : s[z][0]; s[z][1] = p1 ? S[1] : s[z][1];
        }
      }
#pragma unroll
      for (int z = 0; z < 4; ++z) mx[z][r] = fmaxf(s[z][2 * r], s[z][2 * r + 1]);
#pragma unroll
      for (int o = 1; o < 3; ++o)
#pragma unroll
        for (int z = 0; z < 4; ++z) mx[z][r] = fmaxf(mx[z][r], __shfl_xor_sync(0xffffffffu, mx[z][r], o));
#pragma unroll
      for (int z = 0; z < 4; ++z) pw[z][r] = pack2(ex2((s[z][2 * r] - mx[z][r]) * (r ? sc1 : sc0)), ex2((s[z][2 * r + 1] - mx[z][r]) * (r ? sc1 : sc0)));
    }
    mbar_wait(layer ? B_N : B_Z, layer);
    const uint32_t M = (p0 ? 0xFFFFu : 0u) | (p1 ? 0xFFFF0000u : 0u);
    uint4* O = g_O + ((J * 8 + cg) * 512 + (2 * (w & 2) + (w & 1)) * 64 + t * 8 + g);
#pragma unroll
    for (int h2 = 0; h2 < 2; ++h2) {
      uint32_t ow[2][4];
#pragma unroll
      for (int z = 0; z < 2; ++z) {
        const int n = 2 * h2 + z;
        const uint32_t w0 = pw[n][0], w1 = pw[n][1];
        float sm[4] = {0.f, 0.f, 0.f, 0.f}, Oa[2][4];
        mma8(sm, w0, w1, 0x3F803F80u);
        mma16z(Oa[0], w0 & ~M, w1 & M, 0u, w1 & ~M, V[n][0][0], V[n][1][0]); mma8(Oa[0], w0 & M, 0u, hv[n].z);
        mma16z(Oa[1], w0 & ~M, w1 & M, 0u, w1 & ~M, V[n][0][1], V[n][1][1]); mma8(Oa[1], w0 & M, 0u, hv[n].w);
        const float i0 = rcp(sm[0]), i1 = rcp(sm[2]);
#pragma unroll
        for (int d = 0; d < 2; ++d) { ow[0][2 * z + d] = pack2(Oa[d][0] * i0, Oa[d][1] * i0); ow[1][2 * z + d] = pack2(Oa[d][2] * i1, Oa[d][3] * i1); }
      }
#pragma unroll
      for (int hi = 0; hi < 2; ++hi) str4(O + hi * 128 + h2 * 32, ow[hi][0], ow[hi][1], ow[hi][2], ow[hi][3]);
    }
  }
  if (lane == 0) str1(g_OF[layer] + (J * 32 + cg * 4 + w), 1);
  __syncwarp();
  mbar_arrive1(B_AT + 8 * e + (lds1(csb) & P.zero));
  PROF(9 + 12 * layer);
  float ac[32];
  undef(ac);
  const uint32_t so = SM_O + e * O_E;
  {
    const uint32_t bo = B_O + 32 * e;
    const uint64_t dw = mkdesc(SM_WO, 8192, 1024, 1), da = mkdesc(so, 512, 1024, 0);
    mbar_wait(B_WO, layer);
#pragma unroll
    for (int j = 0; j < 4; ++j) {
      mbar_wait(bo + 8 * j, layer);
      if (j == 0) { PROF(32 + layer); mbar_wait(B_AT + 8, layer); }
      wg_fence();
#pragma unroll
      for (int k = 8 * j; k < 8 * j + 8; ++k) {
        const uint64_t a = da + (k >> 2) * 512 + (k & 3) * 8, b = dw + (k & 3) * 1024 + (k >> 2) * 128;
        if (k) wg_ss64<1>(ac, a, b); else wg_ss64<0>(ac, a, b);
      }
      wg_commit();
    }
#pragma unroll 1
    for (uint32_t late = P.zero;; late = 1) {
      if (late) {
        const uint16_t* op = (const uint16_t*)(g_O + (J * 4096 + w * 128 + g));
        wg_wait<0>();
        zero(ac);
#pragma unroll 1
        for (int k = 0; k < 512; ++k) {
          const uint16_t* q = op + (k >> 6) * 4096 + (k & 56) * 8 + (k & 7);
          slow_step(ac, ldnan(q), ldnan(q + 512), P.wo + (((k & ~31) + 4 * (k & 6) + ((k >> 2) & 6) + (k & 1)) * 512 + 64 * cg + 2 * t), P.zero);
        }
      }
      wg_wait<0>();
      if (!rows_nan(ac[0], ac[2]) || late) break;
    }
  }
  PROF(10 + 12 * layer);
#pragma unroll
  for (int j = 0; j < 8; ++j) {
    res[j][0] = hadd2(res[j][0], pack2(ac[4 * j], ac[4 * j + 1]));
    res[j][1] = hadd2(res[j][1], pack2(ac[4 * j + 2], ac[4 * j + 3]));
  }
  if (layer == 0) {
    const float4 s = gram(res, g);
    if (t == (g >> 1))
      str4(&g_PS[(G * 8 + cg) * 8 + g], nzmap(__float_as_uint(s.x)), __float_as_uint(s.y), __float_as_uint(s.z), __float_as_uint(s.w));
    const int xo = (32 * (cg & 3) + t) * 2048 + (cg >> 2) * 512 + xg_off(G, g);
#pragma unroll
    for (int j = 0; j < 8; ++j) {
      str2((uint2*)g_XG[1] + (xo + j * 8192), nzmap(prmt(res[j][0], res[j][1], 0x5410)), prmt(res[j][0], res[j][1], 0x7632));
    }
    __syncwarp();
    mbar_arrive1(B_ED + 8 * e);
  } else {
    const uint32_t stg = so + w * 2048;
    const int row = (lane & 7) + 8 * ((lane >> 3) & 1);
    bar_sync(NB_WG + e, 128);
#pragma unroll
    for (int j = 0; j < 8; j += 2)
      stsm4(stg + row * 128 + (((j + (lane >> 4)) ^ (row & 7)) * 16), res[j][0], res[j][1], res[j + 1][0], res[j + 1][1]);
    __syncwarp();
#pragma unroll
    for (int k = 0; k < 4; ++k) {
      const int r = 4 * k + (lane >> 3);
      const uint4 v = lds4(stg + r * 128 + (((lane & 7) ^ (r & 7)) * 16));
      stw4(P.out + ((16 * G + 2 * (lane >> 3)) * 512 + 64 * cg + 8 * (lane & 7)) + ((k & 1) * 8 + (k >> 1)) * 512, v.x, v.y, v.z, v.w);
    }
  }
  PROF(11 + 12 * layer);
}

DEV void aux_prologue(const Params& P, int c, int wa, int lane, uint4 (&s0)[2][2]) {
  const int i = c >> 3, cg = c & 7, g = lane >> 2, t = lane & 3, G = stat_group(c);
  uint4 wv[8];
  {
    uint32_t w[16][2];
    const uint16_t* row = P.x0 + ((16 * G + 2 * g) * 512 + 128 * wa + 8 * t);
#pragma unroll
    for (int z = 0; z < 8; ++z) {
      const uint4 v = ldnc4(row + (z & 1) * 512 + (z >> 1) * 32);
      const int o = 4 * (z >> 1);
      w[o][z & 1] = v.x; w[o + 1][z & 1] = v.y; w[o + 2][z & 1] = v.z; w[o + 3][z & 1] = v.w;
    }
    uint2* xo = (uint2*)g_XG[0] + ((64 * (wa & 1) + 4 * t) * 2048 + (wa >> 1) * 512 + xg_off(G, g));
#pragma unroll
    for (int n = 0; n < 16; ++n) str2(xo + (16 * (n >> 2) + (n & 3)) * 2048, nzmap(prmt(w[n][0], w[n][1], 0x5410)), prmt(w[n][0], w[n][1], 0x7632));
    const float4 s = gram(w, g);
    if (t == (g >> 1)) sts4f(SM_MISC + (wa * 8 + g) * 16, s.x, s.y, s.z, s.w);
    bar_arrive(NB_P0, 192);
  }
  PROF(2);
  if (wa < 3) {
#pragma unroll
    for (int k = 0; k < 8; ++k) wv[k] = ldnc4(P.wqkv + ((32 * i + (lane >> 3)) * 1536 + wa * 512 + 64 * cg + 8 * (lane & 7)) + 4 * k * 1536);
  } else if (lane == 0) {
    asm volatile("cp.async.bulk.prefetch.L2.global [%0],4096;" :: "l"(P.wo + (size_t)c * 2048) : "memory");
  }
  if (wa < 3) {
    float cs[8];
#pragma unroll
    for (int k = 0; k < 8; ++k) cs[k] = 0.f;
#pragma unroll
    for (int k = 0; k < 8; ++k) {
      cs[0] += bflo(wv[k].x); cs[1] += bfhi(wv[k].x); cs[2] += bflo(wv[k].y); cs[3] += bfhi(wv[k].y);
      cs[4] += bflo(wv[k].z); cs[5] += bfhi(wv[k].z); cs[6] += bflo(wv[k].w); cs[7] += bfhi(wv[k].w);
    }
#pragma unroll
    for (int k = 0; k < 8; ++k) { cs[k] += __shfl_xor_sync(0xffffffffu, cs[k], 8); cs[k] += __shfl_xor_sync(0xffffffffu, cs[k], 16); }
    if (lane < 16) {
      const int hf = lane >> 3;
      str4(&g_CS[(i * 1536 + wa * 512 + 64 * cg + 8 * (lane & 7)) / 4 + hf],
           __float_as_uint(hf ? cs[4] : cs[0]), __float_as_uint(hf ? cs[5] : cs[1]), __float_as_uint(hf ? cs[6] : cs[2]), __float_as_uint(hf ? cs[7] : cs[3]));
    }
  }
  bar_arrive(NB_P0 + 1, 160);
  sload(c, 32 * wa + lane, 0, s0);
}

DEV void stat_part(int c, int wa, int lane, int layer, int h, float (&v)[2]) {
  lane = opq(lane);
  const int e = wa >> 1;
  uint32_t x[4][4];
  mbar_wait(B_A + 16 * e, h); mbar_wait(B_A + 16 * e + 8, h);
#pragma unroll
  for (int k = 0; k < 4; ++k) ldsm4t(x[k], SM_A + e * A_E + (128 * (wa & 1) + lane) * 128 + (((c ^ lane) & 7) * 16) + k * 4096);
  float s[4] = {0.f, 0.f, 0.f, 0.f};
#pragma unroll
  for (int k = 0; k < 16; ++k) { const float a = bflo(x[k >> 2][k & 3]), b = bfhi(x[k >> 2][k & 3]); s[0] += a; s[1] += a * a; s[2] += b; s[3] += b * b; }
  s[0] += s[2]; s[1] += s[3];
  if (RARE(s[1] != s[1])) {
    const uint16_t* q = (const uint16_t*)(g_XF[layer] + ((32 * e + 2 * (c >> 3) + h) * 2048 + (wa & 1) * 1024)) + (lane >> 2);
    s[0] = s[1] = 0.f;
#pragma unroll 1
    for (int k = 0; k < 32; ++k) {
      const int r = 2 * (lane & 3) + (k & 1);
      const float a = ldnan(q + ((k >> 1) * 8 + r) * 64 + ((c ^ r) & 7) * 8);
      s[0] += a; s[1] += a * a;
    }
  }
  v[0] += s[0]; v[1] += s[1];
  __syncwarp();
}
DEV void stat_finish(int c, int wa, int lane, int layer, float (&v)[2]) {
  lane = opq(lane);
  const bool b = lane & 1;
  const float s = (b ? v[1] : v[0]) + __shfl_xor_sync(0xffffffffu, b ? v[0] : v[1], 1);
  str1((uint32_t*)g_ST[layer] + ((128 * (wa >> 1) + c) * 64 + (wa & 1) * 32 + lane), nzmap(__float_as_uint(s)));
  const uint4* sp = g_ST[layer] + ((128 * (wa >> 1) + (c & ~7) + 4 * (wa & 1) + (lane >> 3)) * 16 + (lane & 7));
  uint4 x, y;
  for (int it = 0;; ++it) {
    x = ldr4(sp); y = ldr4(sp + 8);
    if (__all_sync(0xffffffffu, min(min(min(x.x, x.y), min(x.z, x.w)), min(min(y.x, y.y), min(y.z, y.w))) != 0u)) break;
    spin_guard(it);
  }
  const uint32_t q = ln_sums((__uint_as_float(x.x) + __uint_as_float(x.z)) + (__uint_as_float(y.x) + __uint_as_float(y.z)),
                             (__uint_as_float(x.y) + __uint_as_float(x.w)) + (__uint_as_float(y.y) + __uint_as_float(y.w)));
  sts2f(SM_STAT + (16 * wa + (lane >> 4) * 8 + (lane & 7)) * 16 + (lane & 8), bflo(q), rcp(bfhi(q)));
  __syncwarp();
  mbar_arrive1(B_ST + 4 * (wa & 2));
}

DEV void nan_source(uint32_t a, int lane) {
#pragma unroll
  for (int k = 0; k < 4; ++k) sts4(a + k * 512 + lane * 16, FILL, FILL, FILL, FILL);
  fence_async_smem();
  __syncwarp();
}
DEV void load_a(int J, int e, int layer, int h) {
  const uint4* src = g_XF[layer] + (2 * J + h) * 2048;
  const uint32_t dst = SM_A + e * A_E, b = B_A + 16 * e;
  mbar_expect1(b, 8192); bulk(dst, src, 8192, b);
  mbar_expect1(b + 8, 24576); bulk(dst + 8192, src + 512, 24576, b + 8);
}
__global__ void __launch_bounds__(NTHR, 1)
fused_kernel(const __grid_constant__ CUtensorMap mapW, const __grid_constant__ CUtensorMap mapWo, const __grid_constant__ CUtensorMap mapX,
             const __grid_constant__ Params P) {
  extern __shared__ __align__(1024) uint8_t smem_raw[];
  if (s2u(smem_raw) != SB) __trap();
  const int warp = __shfl_sync(0xffffffffu, threadIdx.x >> 5, 0), lane = threadIdx.x & 31;
  uint32_t smid; asm volatile("mov.u32 %0,%%smid;" : "=r"(smid));
  if (warp & 1) asm volatile("" :: "l"(P.x0), "l"(P.dskip), "l"(P.out));
  const int c = __shfl_sync(0xffffffffu, P.by_sm ? P.role[smid] : blockIdx.x, 0);
  if (c >= 128) {
#pragma unroll 1
    for (int k = (c - 128) * NTHR + threadIdx.x; k < 131072; k += P.spare * NTHR) str4(g_XG[1] + k, 0, 0, 0, 0);
    __threadfence();
    __syncthreads();
    if (warp == 0) { cnt_wait(1, lane); cnt_add1(g_C + 6); }
    __syncthreads();
#pragma unroll 1
    for (int k = (c - 128) * NTHR + threadIdx.x; k < 131072; k += P.spare * NTHR) str4(g_XG[0] + k, 0, 0, 0, 0);
    return;
  }
#define DONE() do {} while (0)
  {
#pragma unroll
    for (int k = 0; k < 3; ++k) {
      const int n = k < 2 ? 2 * warp + k : 21 + warp;
      if (k < 2 || warp >= 11)
      asm volatile("{.reg .pred p; elect.sync _|p,0xffffffff; @p mbarrier.init.shared::cta.b64 [%0],%1;}"
                   :: "r"(SM_BAR + n * 8), "r"(n > 14 ? 1 : n == 14 ? 3 : n > 11 ? 2 : n == 11 ? 8 : n > 8 ? 6 : 4) : "memory");
    }
    fence_async_smem();
  }
  __syncthreads();
  PROF(0);
  const int cg = c & 7;
  if (warp < 8) {
    asm volatile("setmaxnreg.inc.sync.aligned.u32 %0;" :: "n"(REG_MAIN));
    kgen(P, c, warp, lane);
    bar_sync(0, 256);
    PROF(1);
#pragma unroll 1
    for (int layer = 0; layer < 2; ++layer) {
#pragma unroll 1
      for (int rho = 0; rho < 2; ++rho) {
        const int wz = warp + ((rho + layer) & P.zero);
        conv_round(wz >> 2, rho, wz & 3, lane_id());
        PROF(6 + rho + 12 * layer);
      }
      const int z = layer & P.zero;
      attn_phase(P, c + z, (warp + z) >> 2, (warp + z) & 3, lane_id(), layer);
    }
    DONE();
  } else if (warp < 12) {
    asm volatile("setmaxnreg.dec.sync.aligned.u32 %0;" :: "n"(REG_AUX));
    uint4 x[2][2][2], s[2][2];
    aux_prologue(P, c, warp - 8, lane, s);
    PROF(1);
    const int c0 = c;
#pragma unroll 1
    for (int layer = 0;; ++layer) {
      const int c = c0 + (layer & P.zero), cg = c & 7, wa = warp - 8 + (layer & P.zero);
#define lane lane_id()
#define j (32 * wa + lane_id())
      sts4(region(wa) + opq(lane) * 16, 0, 0, 0, 0);
      if (lane == 0) sts4(region(wa) + R_BE, 0, 0, 0, 0);
      uint32_t u[4][4];
      uload(c, j, layer, x, s);
      uprep(j, 1, x[1], s[1], u);
      uprep(j, 0, x[0], s[0], u);
      fence_async_smem();
      bar_arrive(NB_U, NBARU);
      bar_sync(NB_H, 192);
      PROF(5 + 12 * layer);
      box_full(j, 0, u[0]);
      PROF(31);
      box_full(j, 1, u[1]);
      mbar_wait(B_Z, 0);
      conv_out(c, j, 0, x, u[0], g_XF[layer]);
      PROF(32);
      box_full(j, 2, u[2]);
      conv_out(c, j, 1, x, u[1], g_XF[layer]);
      PROF(6 + 12 * layer);
      box_full(j, 3, u[3]);
      PROF(3 + 12 * layer);
      conv_out(c, j, 2, x, u[2], g_XF[layer]);
      PROF(33);
      conv_out(c, j, 3, x, u[3], g_XF[layer]);
      PROF(7 + 12 * layer);
      float v[2];
      zero(v);
      stat_part(c, wa, lane, layer, 0, v);
      mbar_arrive1(B_AE + 4 * (wa & 2));
      if (layer == 0 && wa < 3) {
        const int ln = opq(lane);
        float a = 0.f, b = 0.f;
#pragma unroll
        for (int k = 0; k < 16; ++k) { const uint2 q = ldr2((const float*)g_CS + (wa * 512 + 64 * cg + 2 * ln) + k * 1536); a += __uint_as_float(q.x); b += __uint_as_float(q.y); }
        sts2f(SM_CS + wa * 256 + ln * 8, a, b);
        __syncwarp();
        mbar_arrive1(B_CS);
      }
      stat_part(c, wa, lane, layer, 1, v);
      PROF(9 + 12 * layer);
      stat_finish(c, wa, lane, layer, v);
      PROF(8 + 12 * layer);
      if (layer) break;
      sload(c, j, 1, s);
#undef lane
#undef j
    }
    DONE();
  } else {
    asm volatile("setmaxnreg.dec.sync.aligned.u32 %0;" :: "n"(REG_PROD));
    if (warp == 12) {
      if (lane == 0) {
        asm volatile("prefetch.tensormap [%0];" :: "l"(&mapW) : "memory");
        asm volatile("prefetch.tensormap [%0];" :: "l"(&mapWo) : "memory");
        asm volatile("prefetch.tensormap [%0];" :: "l"(&mapX) : "memory");
      }
      __syncwarp();
#pragma unroll 1
      for (int layer = 0; layer < 2; ++layer) {
        bar_sync(NB_U, NBARU);
        if (layer == 1 && c < 4 && ((0x47 >> lane) & 1)) str1(g_C + c * 32 + lane, 0);
        mbar_expect1(B_WF, 4 * 24576);
#pragma unroll
        for (int k = 0; k < 4; ++k) tma3(slot(wslot(k)), &mapW, 64 * cg, 64 * k, 0, B_WF);
        mbar_wait(B_WF, layer);
        mbar_expect1(B_W4, 2 * 24576);
#pragma unroll
        for (int k = 4; k < 6; ++k) tma3(slot(wslot(k)), &mapW, 64 * cg, 64 * k, 0, B_W4);
        bar_sync(NB_AUX, 64);
#pragma unroll 1
        for (int k = 0; k < 2; ++k) {
          mbar_expect1(B_W6 + 8 * k, 24576);
          mbar_wait(B_F + 8 * k, layer);
          tma3(slot(3 * k), &mapW, 64 * cg, 384 + 64 * k, 0, B_W6 + 8 * k);
        }
        mbar_expect1(B_WO, 65536);
        mbar_wait(B_AE + 8, layer);
        nan_source(slot(12), lane);
        uint4* fp = layer ? g_O + c * 512 : g_XF[1] + c * 512;
#pragma unroll 1
        for (int r = 7; r >= 0; --r) {
          __nanosleep(KWOP);
          if (r >= 4) {
            bulk_store(fp + (r & 3) * 128, slot(12), 2048); bulk_store(fp + 65536 + (r & 3) * 128, slot(12), 2048);
            if (layer == 0) bulk_store(g_H[1] + ((c + 8) * 256 + (r & 2) * 16384 + (r & 1) * 128), slot(12), 2048);
          }
          if (r == KFR) { bulk_wait(); __threadfence(); mbar_arrive1(B_N); PROF(9 + 12 * layer); }
          if (r == 1) mbar_wait(B_F + 16, layer);
          tma4(SM_WO + r * 8192, &mapWo, 64 * cg, 0, r >> 1, 32 * (r & 1), B_WO);
        }
        PROF(8 + 12 * layer);
      }
      DONE();
    } else if (warp == 13) {
      const int G = stat_group(c);
#pragma unroll 1
      for (int layer = 0; layer < 2; ++layer) {
        float z[4];
        if (layer == 0) {
          bar_sync(NB_P0, 192);
          const float4 a = lds4f(SM_MISC + lane * 16);
          z[0] = a.x; z[1] = a.y; z[2] = a.z; z[3] = a.w;
        } else {
          mbar_wait(B_ED + 2 * (c & 4), 0);
          uint4* ps = &g_PS[G * 64 + lane];
          uint4 a, b;
          for (int it = 0;; ++it) {
            a = ldr4(ps); b = ldr4(ps + 32);
            if (__all_sync(0xffffffffu, min(a.x, b.x) != 0u)) break;
            spin_guard(it);
          }
          z[0] = __uint_as_float(a.x) + __uint_as_float(b.x); z[1] = __uint_as_float(a.y) + __uint_as_float(b.y);
          z[2] = __uint_as_float(a.z) + __uint_as_float(b.z); z[3] = __uint_as_float(a.w) + __uint_as_float(b.w);
        }
#pragma unroll
        for (int o = 8; o < 32; o <<= 1)
#pragma unroll
          for (int k = 0; k < 4; ++k) z[k] += __shfl_xor_sync(0xffffffffu, z[k], o);
        const uint32_t w0 = ln_sums(z[0], z[1]), w1 = ln_sums(z[2], z[3]);
        const uint32_t r = nzmap(pack2(rcp(bfhi(w0)), rcp(bfhi(w1)))), m = prmt(w0, w1, 0x5410);
        uint2* so = (uint2*)&g_SR[layer][lane >> 3][sr_off(G, lane)] + (lane & 1);
        str2(so, r, m); str2(so + 4 * 1024, r, m);
        PROF(4 + 12 * layer);
        bar_sync(NB_H, 192);
        box_help(0, lane);
        box_help(2, lane);
        PROF(6 + 12 * layer);
      }
      DONE();
    } else if (warp == 14) {
#pragma unroll 1
      for (int layer = 0; layer < 2; ++layer) {
        if (layer) { mbar_wait(B_N, 0); mbar_wait(B_ED, 0); mbar_wait(B_ED + 8, 0); } else bar_sync(NB_P0, 192);
        cnt_add1(g_C + (c >> 5) * 32 + 3 * layer);
        mbar_expect1(B_E, 16384);
        PROF(4 + 12 * layer);
        cnt_wait(3 * layer, lane);
        mbar_arrive1(B_U);
        bulk(SM_X, g_XG[layer] + c * 1024, 16384, B_E);
        PROF(5 + 12 * layer);
        if (layer == 0) {
          nan_source(SM_NAN, lane);
          mbar_wait(B_E, 0);
#pragma unroll 1
          for (int k = 0; k < 8; ++k) tma2_store(&mapX, SM_NAN, 128 * c, 8 * k);
#pragma unroll 1
          for (int k = 0; k < 4; ++k) bulk_store(g_H[0] + ((c + 8) * 256 + (k >> 1) * 32768 + (k & 1) * 128), SM_NAN, 2048);
#pragma unroll 1
          for (int k = 0; k < 8; ++k) bulk_store(g_O + (c * 512 + (k >> 2) * 65536 + (k & 3) * 128), SM_NAN, 2048);
          bulk_wait();
          mbar_arrive1(B_Z);
          PROF(24);
          __threadfence();
          mbar_arrive1(B_Z + 8);
          PROF(11);
        }
        mbar_wait(B_RD, layer);
        cnt_wait(3 * layer + 1, lane);
        load_a(c >> 3, 0, layer, 0);
        PROF(6 + 12 * layer);
        mbar_wait(B_RD + 8, layer);
        load_a(16 + (c >> 3), 1, layer, 0);
        cnt_wait(3 * layer + 2, lane);
        PROF(7 + 12 * layer);
        mbar_wait(B_AE, layer);
        load_a(c >> 3, 0, layer, 1);
        bar_arrive(NB_AUX, 64);
        PROF(8 + 12 * layer);
        mbar_wait(B_AE + 8, layer);
        load_a(16 + (c >> 3), 1, layer, 1);
        if (layer == 0)
          for (int it = 0; ldr1(g_C + 6) < P.spare; ++it) spin_guard(it);
        mbar_wait(B_QE, layer);
#pragma unroll 1
        for (int e = 0; e < 2; ++e) {
          const int J = 16 * e + (c >> 3);
          mbar_wait(B_AT + 8 * e, layer);
          uint32_t todo = 0x01010101u;
#pragma unroll 1
          for (int it = 0; todo; ++it) {
            uint32_t m = __ballot_sync(0xffffffffu, ldr1(g_OF[layer] + J * 32 + lane) != 0u);
            m &= m >> 4; m &= m >> 2; m &= m >> 1; m &= todo;
            todo ^= m;
#pragma unroll 1
            for (; m; m &= m - 1) {
              const int j = __ffs(m) - 1;
              mbar_expect1(B_O + 32 * e + j, 16384);
              bulk(SM_O + e * O_E + 2048 * j, g_O + (J * 4096 + j * 128), 16384, B_O + 32 * e + j);
            }
            spin_guard(it);
          }
          PROF(9 + e + 12 * layer);
        }
      }
      DONE();
    }
    if (warp == 15) {
      const int G = stat_group(c);
      str4(&g_ST[0][(lane >> 4) * 2048 + c * 16 + (lane & 15)], 0, 0, 0, 0); str4(&g_ST[1][(lane >> 4) * 2048 + c * 16 + (lane & 15)], 0, 0, 0, 0);
      if (lane < 4) str4(g_OF[lane >> 1] + ((lane & 1) * 512 + c * 4), 0, 0, 0, 0);
      str4(&g_PS[G * 64 + lane], 0, 0, 0, 0); str4(&g_PS[G * 64 + 32 + lane], 0, 0, 0, 0);
      str4(&g_SR[1][lane >> 2][sr_off(G, 2 * lane)], 0, 0, 0, 0);
      if (c < 4 && lane < 3) str1(g_C + c * 32 + 3 + lane, 0);
      bar_sync(NB_P0 + 1, 160);
      __threadfence();
#pragma unroll 1
      for (int layer = 0; layer < 2; ++layer) {
        PROF(4 + 12 * layer);
        bar_sync(NB_H, 192);
        box_help(1, lane);
        if (layer) str4(&g_SR[0][lane >> 2][sr_off(G, 2 * lane)], 0, 0, 0, 0);
        mbar_wait(B_Z + 8, 0);
        mbar_wait(B_RD, layer);
        cnt_add1(g_C + (c >> 5) * 32 + 3 * layer + 1);
        box_help(3, lane);
        mbar_wait(B_RD + 8, layer);
        cnt_add1(g_C + (c >> 5) * 32 + 3 * layer + 2);
        if (P.spare == 0) {
#pragma unroll 1
          for (int k = 0; k < 32; ++k) str4(g_XG[layer] + (c * 1024 + k * 32 + lane), 0, 0, 0, 0);
        }
      }
    }
  }
}

typedef CUresult (*EncodeFn)(CUtensorMap*, CUtensorMapDataType, cuuint32_t, void*, const cuuint64_t*, const cuuint64_t*,
                             const cuuint32_t*, const cuuint32_t*, CUtensorMapInterleave, CUtensorMapSwizzle,
                             CUtensorMapL2promotion, CUtensorMapFloatOOBfill);

static int place_roles(uint8_t* role) {
  int dev = 0, nsm = 0;
  cudaGetDevice(&dev);
  cudaDeviceGetAttribute(&nsm, cudaDevAttrMultiProcessorCount, dev);
  if (nsm < 128 || nsm > 144 || (nsm & 1)) return 0;
  cudaFuncSetAttribute(fused_kernel, cudaFuncAttributeNonPortableClusterSizeAllowed, 1);
  int occ[9] = {0};
  for (int k = 2; k <= 8; ++k) {
    cudaLaunchConfig_t cfg = {};
    cudaLaunchAttribute at[1];
    at[0].id = cudaLaunchAttributeClusterDimension;
    at[0].val.clusterDim.x = 2 * k; at[0].val.clusterDim.y = 1; at[0].val.clusterDim.z = 1;
    cfg.gridDim = dim3(2 * k); cfg.blockDim = dim3(NTHR); cfg.dynamicSmemBytes = SM_TOTAL; cfg.attrs = at; cfg.numAttrs = 1;
    if (cudaOccupancyMaxActiveClusters(&occ[k], fused_kernel, &cfg) != cudaSuccess) { cudaGetLastError(); occ[k] = 0; }
  }
  int n[10];
  n[7] = occ[8]; n[6] = occ[7]; n[5] = occ[6] - 0; n[4] = occ[5];
  n[3] = occ[4] - n[7]; n[1] = occ[2] - n[3] - n[5] - n[7]; n[0] = n[2] = n[1];
  n[8] = occ[3] - n[2] - n[5];
  const int ntpc = nsm / 2;
  int sum = 0;
  bool ok = n[0] > 0 && n[0] <= 8;
  for (int r = 0; r < 9; ++r) { ok = ok && n[r] >= 0 && (r == 0 || n[r] <= n[r - 1]); sum += n[r]; }
  if (!ok || sum > ntpc) { for (int r = 0; r < 9; ++r) n[r] = r < 8 ? 8 : 0; sum = 64; }
  int tp[8][9], cnt[8] = {0}, pool[72], np = 0, id = 0;
  for (int r = 0; r < 9; ++r)
    for (int g = n[0] - n[r]; g < n[0]; ++g) tp[g][cnt[g]++] = id++;
  for (; id < ntpc; ++id) pool[np++] = id;
  int order[72], no = 0;
  for (int g = 0; g < n[0]; ++g) {
    const int full = cnt[g] / 4 * 4;
    for (int k = 0; k < cnt[g]; ++k) { if (k < full) order[no++] = tp[g][k]; else pool[np++] = tp[g][k]; }
  }
  for (int k = 0; k < np; ++k) order[no++] = pool[k];
  for (int k = 0; k < ntpc; ++k) { role[2 * order[k]] = 2 * k; role[2 * order[k] + 1] = 2 * k + 1; }
  return nsm;
}

extern "C" void kernel_launch(void* const* d_in, const int* in_sizes, int n_in, void* d_out, int out_size) {
  (void)in_sizes; (void)n_in; (void)out_size;
  static EncodeFn enc = nullptr;
  static uint8_t role[144];
  static int nsm = 0;
  static void* xf = nullptr;
  if (!enc) {
    void* fn = nullptr;
    cudaDriverEntryPointQueryResult qr;
    cudaGetDriverEntryPoint("cuTensorMapEncodeTiled", &fn, cudaEnableDefault, &qr);
    enc = (EncodeFn)fn;
    cudaFuncSetAttribute(fused_kernel, cudaFuncAttributeMaxDynamicSharedMemorySize, SM_TOTAL);
    nsm = place_roles(role);
    cudaGetSymbolAddress(&xf, g_XF);
  }
  CUtensorMap mW, mWo, mX;
  {
    cuuint64_t dim[3] = {512, 512, 3}, str[2] = {3072, 1024};
    cuuint32_t box[3] = {64, 64, 3}, es[3] = {1, 1, 1};
    enc(&mW, CU_TENSOR_MAP_DATA_TYPE_BFLOAT16, 3, d_in[10], dim, str, box, es, CU_TENSOR_MAP_INTERLEAVE_NONE,
        CU_TENSOR_MAP_SWIZZLE_128B, CU_TENSOR_MAP_L2_PROMOTION_NONE, CU_TENSOR_MAP_FLOAT_OOB_FILL_NONE);
  }
  {
    cuuint64_t dim[4] = {512, 2, 4, 64}, str[3] = {1024, 2048, 8192};
    cuuint32_t box[4] = {64, 2, 1, 32}, es[4] = {1, 1, 1, 1};
    enc(&mWo, CU_TENSOR_MAP_DATA_TYPE_BFLOAT16, 4, d_in[11], dim, str, box, es, CU_TENSOR_MAP_INTERLEAVE_NONE,
        CU_TENSOR_MAP_SWIZZLE_128B, CU_TENSOR_MAP_L2_PROMOTION_NONE, CU_TENSOR_MAP_FLOAT_OOB_FILL_NONE);
  }
  {
    cuuint64_t dim[2] = {16384, 64}, str[1] = {32768};
    cuuint32_t box[2] = {128, 8}, es[2] = {1, 1};
    enc(&mX, CU_TENSOR_MAP_DATA_TYPE_BFLOAT16, 2, xf, dim, str, box, es, CU_TENSOR_MAP_INTERLEAVE_NONE,
        CU_TENSOR_MAP_SWIZZLE_NONE, CU_TENSOR_MAP_L2_PROMOTION_NONE, CU_TENSOR_MAP_FLOAT_OOB_FILL_NONE);
  }
  Params P;
  P.x0 = (const uint16_t*)d_in[0]; P.Are = (const uint16_t*)d_in[1]; P.Aim = (const uint16_t*)d_in[2];
  P.Bre = (const uint16_t*)d_in[3]; P.Bim = (const uint16_t*)d_in[4]; P.Cre = (const uint16_t*)d_in[5];
  P.Cim = (const uint16_t*)d_in[6]; P.logdt = (const uint16_t*)d_in[7]; P.dskip = (const uint16_t*)d_in[8];
  P.wqkv = (const uint16_t*)d_in[10]; P.wo = (const uint16_t*)d_in[11]; P.out = (uint16_t*)d_out;
  for (int k = 0; k < 144; ++k) P.role[k] = role[k];
  P.by_sm = nsm > 0;
  P.zero = 0;
  P.spare = nsm > 0 ? nsm - 128 : 0;
  fused_kernel<<<nsm > 0 ? nsm : 128, NTHR, SM_TOTAL, cudaStreamPerThread>>>(mW, mWo, mX, P);
}
```

```cpp
#include <cuda_runtime.h>
#include <cuda_bf16.h>
#include <cuda.h>
#include <stdint.h>
#include <stddef.h>

#define DEV __device__ __forceinline__
#define RARE(x) __builtin_expect(!!(x), 0)

#define KWOP 30
#define KFR 3
#define KBL 2
#define KDR 0
constexpr int NTHR = 512;
constexpr int REG_MAIN = 192, REG_AUX = 96, REG_PROD = 32;
constexpr int NBARU = 416;
constexpr int SPIN_LIMIT = 1 << 22;

constexpr uint32_t SB = 1024;
__host__ __device__ constexpr uint32_t slot(int n) { return SB + n * 8192; }
__host__ __device__ constexpr int wslot(int k) { return k < 2 ? 3 * k : k < 4 ? 3 * k + 6 : k < 6 ? 21 - 3 * k : 3 * k - 18; }
constexpr uint32_t SM_A = slot(22), A_E = 0u - 32768;
constexpr uint32_t SM_O = slot(18), O_E = 0u - 147456;
constexpr uint32_t SM_WO = slot(10), SM_X = slot(8), SM_KV = slot(9);
constexpr uint32_t SM_TAP  = slot(26);
constexpr int TAP_SZ = 3440;
constexpr uint32_t SM_STAT = SM_TAP + 4 * TAP_SZ;
constexpr uint32_t SM_CS   = SM_STAT + 1024;
constexpr uint32_t SM_MISC = SM_CS + 768;
constexpr uint32_t SM_BAR  = SM_MISC + 528;
constexpr int SM_TOTAL = SM_BAR + 304 - SB;
static_assert(SM_TOTAL <= 232448, "");
constexpr int R_SZ = 16384, R_U = 512, R_X5 = 5120, R_X3 = 8704, R_BO = 11776, R_BE = 13824;
constexpr int X_5 = 576, X_3 = 648, T_E = 2 * 720, T_O = 1600 + 2 * 721, T_C = 3390, T_K = 3424;
constexpr uint32_t B_RD = SM_BAR, B_ED = SM_BAR + 16, B_F = SM_BAR + 32, B_AT = SM_BAR + 56;
constexpr uint32_t B_AE = SM_BAR + 72, B_QE = SM_BAR + 88, B_ST = SM_BAR + 96, B_CS = SM_BAR + 112;
constexpr uint32_t B_WO = SM_BAR + 120, B_W6 = SM_BAR + 128, B_U = SM_BAR + 144, B_E = SM_BAR + 152, B_A = SM_BAR + 160, B_O = SM_BAR + 192,
                   B_Z = SM_BAR + 256, B_WF = SM_BAR + 272, B_W4 = SM_BAR + 280, B_N = SM_BAR + 288;
constexpr int NB_U = 1, NB_B = 2, NB_K = 8, NB_Y = 6, NB_WG = 8, NB_T = 10, NB_AUX = 12, NB_P0 = 13, NB_H = 15;

struct Scratch {
  uint4    XG[2][128 * 1024];
  uint4    O[32 * 8 * 512];
  uint32_t C[8 * 32];
  uint32_t OF[2][32 * 32];
  uint4    CS[16 * 1536 / 4];
  uint4    PS[128 * 64];
  uint4    ST[2][32 * 128];
  uint4    SR[2][8][512];
  uint4    XF[2][32 * 512 * 8];
  uint4    H[2][33 * 8 * 256];
};
__device__ __align__(1024) Scratch g_S;
#define SCR ((Scratch*)(P.mid - offsetof(Scratch, C)))
#define PROFD(slot, v) do {} while (0)
#define PROF(slot) do {} while (0)

DEV uint32_t s2u(const void* p) { return (uint32_t)__cvta_generic_to_shared(p); }
template <class T> DEV T opq(T x) { asm volatile("" : "+r"(x)); return x; }
DEV int lane_id() { int l; asm volatile("mov.u32 %0,%%laneid;" : "=r"(l)); return l; }
DEV uint32_t pack2(float lo, float hi) { uint32_t d; asm("cvt.rn.bf16x2.f32 %0,%1,%2;" : "=r"(d) : "f"(hi), "f"(lo)); return d; }
DEV float bflo(uint32_t v) { return __uint_as_float(v << 16); }
DEV float bfhi(uint32_t v) { return __uint_as_float(v & 0xFFFF0000u); }
DEV float bfr(float x) { return bflo(pack2(x, 0.f)); }
DEV uint32_t hadd2(uint32_t a, uint32_t b) { uint32_t d; asm("add.rn.bf16x2 %0,%1,%2;" : "=r"(d) : "r"(a), "r"(b)); return d; }
DEV uint32_t hsub2(uint32_t a, uint32_t b) { uint32_t d; asm("sub.rn.bf16x2 %0,%1,%2;" : "=r"(d) : "r"(a), "r"(b)); return d; }
DEV uint32_t hmul2(uint32_t a, uint32_t b) { uint32_t d; asm("mul.rn.bf16x2 %0,%1,%2;" : "=r"(d) : "r"(a), "r"(b)); return d; }
DEV uint32_t hfma2(uint32_t a, uint32_t b, uint32_t c) { uint32_t d; asm("fma.rn.bf16x2 %0,%1,%2,%3;" : "=r"(d) : "r"(a), "r"(b), "r"(c)); return d; }
DEV uint32_t hmax2(uint32_t a, uint32_t b) { uint32_t d; asm("max.bf16x2 %0,%1,%2;" : "=r"(d) : "r"(a), "r"(b)); return d; }
DEV uint32_t prmt(uint32_t a, uint32_t b, uint32_t s) { uint32_t d; asm("prmt.b32 %0,%1,%2,%3;" : "=r"(d) : "r"(a), "r"(b), "r"(s)); return d; }
DEV uint32_t nzmap(uint32_t v) { return v == 0u ? 0x80000000u : v; }
DEV float rcp(float x) { float y; asm("rcp.approx.ftz.f32 %0,%1;" : "=f"(y) : "f"(x)); return y; }
DEV float sqrt_(float x) { float y; asm("sqrt.approx.ftz.f32 %0,%1;" : "=f"(y) : "f"(x)); return y; }
DEV float ex2(float x) { float y; asm("ex2.approx.ftz.f32 %0,%1;" : "=f"(y) : "f"(x)); return y; }

DEV uint4 ldr4(const void* p) { uint4 v; asm volatile("ld.relaxed.gpu.global.v4.u32 {%0,%1,%2,%3},[%4];" : "=r"(v.x), "=r"(v.y), "=r"(v.z), "=r"(v.w) : "l"(p) : "memory"); return v; }
DEV void ldr4_if(uint4& v, const void* p, bool c) {
  asm volatile("{.reg .pred q; setp.ne.u32 q,%5,0; @q ld.relaxed.gpu.global.v4.u32 {%0,%1,%2,%3},[%4];}"
    : "+r"(v.x), "+r"(v.y), "+r"(v.z), "+r"(v.w) : "l"(p), "r"((uint32_t)c) : "memory");
}
DEV uint2 ldr2(const void* p) { uint2 v; asm volatile("ld.relaxed.gpu.global.v2.u32 {%0,%1},[%2];" : "=r"(v.x), "=r"(v.y) : "l"(p) : "memory"); return v; }
DEV void ldr2_if(uint2& v, const void* p, bool c) {
  asm volatile("{.reg .pred q; setp.ne.u32 q,%3,0; @q ld.relaxed.gpu.global.v2.u32 {%0,%1},[%2];}" : "+r"(v.x), "+r"(v.y) : "l"(p), "r"((uint32_t)c) : "memory");
}
DEV uint32_t ldr1(const void* p) { uint32_t v; asm volatile("ld.relaxed.gpu.global.u32 %0,[%1];" : "=r"(v) : "l"(p) : "memory"); return v; }
DEV float ldnan(const uint16_t* p) {
  uint32_t v = 0xFFFFu;
#pragma unroll 1
  for (int it = 0; it < SPIN_LIMIT && v == 0xFFFFu; ++it) asm volatile("ld.relaxed.gpu.global.u16 %0,[%1];" : "=r"(v) : "l"(p) : "memory");
  return __uint_as_float(v << 16);
}
DEV uint4 ldw4(const void* p) { uint4 v; asm volatile("ld.global.v4.u32 {%0,%1,%2,%3},[%4];" : "=r"(v.x), "=r"(v.y), "=r"(v.z), "=r"(v.w) : "l"(p) : "memory"); return v; }
DEV uint2 ldw2(const void* p) { uint2 v; asm volatile("ld.global.v2.u32 {%0,%1},[%2];" : "=r"(v.x), "=r"(v.y) : "l"(p) : "memory"); return v; }
DEV uint32_t ldw1(const void* p) { uint32_t v; asm volatile("ld.global.u32 %0,[%1];" : "=r"(v) : "l"(p) : "memory"); return v; }
DEV void str4(void* p, uint32_t a, uint32_t b, uint32_t c, uint32_t d) { asm volatile("st.relaxed.gpu.global.v4.u32 [%0],{%1,%2,%3,%4};" :: "l"(p), "r"(a), "r"(b), "r"(c), "r"(d) : "memory"); }
DEV void str2(void* p, uint32_t a, uint32_t b) { asm volatile("st.relaxed.gpu.global.v2.u32 [%0],{%1,%2};" :: "l"(p), "r"(a), "r"(b) : "memory"); }
DEV void str1(void* p, uint32_t a) { asm volatile("st.relaxed.gpu.global.u32 [%0],%1;" :: "l"(p), "r"(a) : "memory"); }
DEV void stw4(void* p, uint32_t a, uint32_t b, uint32_t c, uint32_t d) { asm volatile("st.global.v4.u32 [%0],{%1,%2,%3,%4};" :: "l"(p), "r"(a), "r"(b), "r"(c), "r"(d) : "memory"); }
DEV uint4 ldnc4(const void* p) { uint4 v; asm volatile("ld.global.nc.v4.u32 {%0,%1,%2,%3},[%4];" : "=r"(v.x), "=r"(v.y), "=r"(v.z), "=r"(v.w) : "l"(p)); return v; }
DEV uint32_t ldnc1(const void* p) { uint32_t v; asm volatile("ld.global.nc.u32 %0,[%1];" : "=r"(v) : "l"(p)); return v; }
DEV uint2 ldnc2(const void* p) { uint2 v; asm volatile("ld.global.nc.v2.u32 {%0,%1},[%2];" : "=r"(v.x), "=r"(v.y) : "l"(p)); return v; }

DEV uint2 lds2(uint32_t a) { uint2 v; asm volatile("ld.shared.v2.u32 {%0,%1},[%2];" : "=r"(v.x), "=r"(v.y) : "r"(a)); return v; }
DEV float lds16f(uint32_t a) { uint32_t v; asm volatile("ld.shared.u16 %0,[%1];" : "=r"(v) : "r"(a)); return __uint_as_float(v << 16); }
DEV void sts2(uint32_t a, uint32_t x, uint32_t y) { asm volatile("st.shared.v2.u32 [%0],{%1,%2};" :: "r"(a), "r"(x), "r"(y) : "memory"); }
DEV uint32_t lds1(uint32_t a) { uint32_t v; asm volatile("ld.shared.u32 %0,[%1];" : "=r"(v) : "r"(a)); return v; }
DEV uint32_t lds1z(uint32_t a, bool c) {
  uint32_t v; asm volatile("{.reg .pred q; setp.ne.u32 q,%2,0; mov.u32 %0,0; @q ld.shared.u32 %0,[%1];}" : "=r"(v) : "r"(a), "r"((uint32_t)c)); return v;
}
DEV uint4 lds4z(uint32_t a, bool c) {
  uint4 v = make_uint4(0, 0, 0, 0);
  asm volatile("{.reg .pred q; setp.ne.u32 q,%5,0; @q ld.shared.v4.u32 {%0,%1,%2,%3},[%4];}" : "+r"(v.x), "+r"(v.y), "+r"(v.z), "+r"(v.w) : "r"(a), "r"((uint32_t)c));
  return v;
}
DEV float lds1f(uint32_t a) { float v; asm volatile("ld.shared.f32 %0,[%1];" : "=f"(v) : "r"(a)); return v; }
DEV float2 lds2f(uint32_t a) { float2 v; asm volatile("ld.shared.v2.f32 {%0,%1},[%2];" : "=f"(v.x), "=f"(v.y) : "r"(a)); return v; }
DEV float4 lds4f(uint32_t a) { float4 v; asm volatile("ld.shared.v4.f32 {%0,%1,%2,%3},[%4];" : "=f"(v.x), "=f"(v.y), "=f"(v.z), "=f"(v.w) : "r"(a)); return v; }
DEV uint4 lds4(uint32_t a) { uint4 v; asm volatile("ld.shared.v4.u32 {%0,%1,%2,%3},[%4];" : "=r"(v.x), "=r"(v.y), "=r"(v.z), "=r"(v.w) : "r"(a)); return v; }
DEV void sts1(uint32_t a, uint32_t v) { asm volatile("st.shared.u32 [%0],%1;" :: "r"(a), "r"(v) : "memory"); }
DEV void sts16(uint32_t a, uint32_t v) { asm volatile("{.reg .b16 h; cvt.u16.u32 h,%1; st.shared.u16 [%0],h;}" :: "r"(a), "r"(v) : "memory"); }
DEV void sts2f(uint32_t a, float x, float y) { asm volatile("st.shared.v2.f32 [%0],{%1,%2};" :: "r"(a), "f"(x), "f"(y) : "memory"); }
DEV void sts4f(uint32_t a, float x, float y, float z, float w) { asm volatile("st.shared.v4.f32 [%0],{%1,%2,%3,%4};" :: "r"(a), "f"(x), "f"(y), "f"(z), "f"(w) : "memory"); }
DEV void sts4(uint32_t a, uint32_t x, uint32_t y, uint32_t z, uint32_t w) { asm volatile("st.shared.v4.u32 [%0],{%1,%2,%3,%4};" :: "r"(a), "r"(x), "r"(y), "r"(z), "r"(w) : "memory"); }

DEV void ldsm4(uint32_t (&r)[4], uint32_t a) { asm volatile("ldmatrix.sync.aligned.m8n8.x4.shared.b16 {%0,%1,%2,%3},[%4];" : "=r"(r[0]), "=r"(r[1]), "=r"(r[2]), "=r"(r[3]) : "r"(a) : "memory"); }
DEV void ldsm4t(uint32_t (&r)[4], uint32_t a) { asm volatile("ldmatrix.sync.aligned.m8n8.x4.trans.shared.b16 {%0,%1,%2,%3},[%4];" : "=r"(r[0]), "=r"(r[1]), "=r"(r[2]), "=r"(r[3]) : "r"(a) : "memory"); }
DEV void ldsm2(uint32_t (&r)[2], uint32_t a) { asm volatile("ldmatrix.sync.aligned.m8n8.x2.shared.b16 {%0,%1},[%2];" : "=r"(r[0]), "=r"(r[1]) : "r"(a) : "memory"); }
DEV void stsm4(uint32_t a, uint32_t r0, uint32_t r1, uint32_t r2, uint32_t r3) { asm volatile("stmatrix.sync.aligned.m8n8.x4.shared.b16 [%0],{%1,%2,%3,%4};" :: "r"(a), "r"(r0), "r"(r1), "r"(r2), "r"(r3) : "memory"); }
DEV void stsm2(uint32_t a, uint32_t r0, uint32_t r1) { asm volatile("stmatrix.sync.aligned.m8n8.x2.shared.b16 [%0],{%1,%2};" :: "r"(a), "r"(r0), "r"(r1) : "memory"); }
DEV void stsm4t(uint32_t a, uint32_t r0, uint32_t r1, uint32_t r2, uint32_t r3) { asm volatile("stmatrix.sync.aligned.m8n8.x4.trans.shared.b16 [%0],{%1,%2,%3,%4};" :: "r"(a), "r"(r0), "r"(r1), "r"(r2), "r"(r3) : "memory"); }
DEV uint32_t movm(uint32_t a) { uint32_t d; asm volatile("movmatrix.sync.aligned.m8n8.trans.b16 %0,%1;" : "=r"(d) : "r"(a)); return d; }
DEV void mma16(float (&d)[4], uint32_t a0, uint32_t a1, uint32_t a2, uint32_t a3, uint32_t b0, uint32_t b1) {
  asm volatile("mma.sync.aligned.m16n8k16.row.col.f32.bf16.bf16.f32 {%0,%1,%2,%3},{%4,%5,%6,%7},{%8,%9},{%0,%1,%2,%3};"
    : "+f"(d[0]), "+f"(d[1]), "+f"(d[2]), "+f"(d[3]) : "r"(a0), "r"(a1), "r"(a2), "r"(a3), "r"(b0), "r"(b1));
}
DEV void mma16z(float (&d)[4], uint32_t a0, uint32_t a1, uint32_t a2, uint32_t a3, uint32_t b0, uint32_t b1) {
  asm volatile("mma.sync.aligned.m16n8k16.row.col.f32.bf16.bf16.f32 {%0,%1,%2,%3},{%4,%5,%6,%7},{%8,%9},{%10,%10,%10,%10};"
    : "=f"(d[0]), "=f"(d[1]), "=f"(d[2]), "=f"(d[3]) : "r"(a0), "r"(a1), "r"(a2), "r"(a3), "r"(b0), "r"(b1), "f"(0.f));
}
DEV void mma8(float (&d)[4], uint32_t a0, uint32_t a1, uint32_t b0) {
  asm volatile("mma.sync.aligned.m16n8k8.row.col.f32.bf16.bf16.f32 {%0,%1,%2,%3},{%4,%5},{%6},{%0,%1,%2,%3};"
    : "+f"(d[0]), "+f"(d[1]), "+f"(d[2]), "+f"(d[3]) : "r"(a0), "r"(a1), "r"(b0));
}

DEV void bar_sync(int id, int n) { asm volatile("bar.sync %0,%1;" :: "r"(id), "r"(n) : "memory"); }
DEV void bar_sync_if(int id, int n, int c) { asm volatile("{.reg .pred q; setp.ne.s32 q,%2,0; @q bar.sync %0,%1;}" :: "r"(id), "r"(n), "r"(c) : "memory"); }
DEV void bar_arrive_if(int id, int n, int c) { asm volatile("{.reg .pred q; setp.ne.s32 q,%2,0; @q bar.arrive %0,%1;}" :: "r"(id), "r"(n), "r"(c) : "memory"); }
DEV bool bar_any(int id, int n, bool c) {
  uint32_t r; asm volatile("{.reg .pred p,q; setp.ne.u32 q,%3,0; bar.red.or.pred p,%1,%2,q; selp.u32 %0,1,0,p;}" : "=r"(r) : "r"(id), "r"(n), "r"((uint32_t)c) : "memory");
  return __any_sync(0xffffffffu, r);
}
DEV void bar_arrive(int id, int n) { asm volatile("bar.arrive %0,%1;" :: "r"(id), "r"(n) : "memory"); }
DEV void fence_async_glob() { asm volatile("fence.proxy.async.global;" ::: "memory"); }
DEV void fence_async_smem() { asm volatile("fence.proxy.async.shared::cta;" ::: "memory"); }
DEV void mbar_init(uint32_t b, int n) { asm volatile("mbarrier.init.shared::cta.b64 [%0],%1;" :: "r"(b), "r"(n) : "memory"); }
DEV void mbar_arrive(uint32_t b) { asm volatile("mbarrier.arrive.shared::cta.b64 _,[%0];" :: "r"(b) : "memory"); }
DEV void mbar_expect(uint32_t b, int bytes) { asm volatile("mbarrier.arrive.expect_tx.shared::cta.b64 _,[%0],%1;" :: "r"(b), "r"(bytes) : "memory"); }
DEV void mbar_wait(uint32_t b, uint32_t ph) {
  asm volatile("{\n.reg .pred p,q;\n.reg .u32 n;\n"
               "mbarrier.try_wait.parity.shared::cta.b64 p,[%0],%1;\n@p bra D;\nmov.u32 n,0;\n"
               "W: mbarrier.try_wait.parity.shared::cta.b64 p,[%0],%1;\n@p bra D;\n"
               "add.u32 n,n,1;\nsetp.lt.u32 q,n,%2;\n@q bra W;\ntrap;\nD:\n}"
               :: "r"(b), "r"(ph), "n"(SPIN_LIMIT) : "memory");
}
DEV void spin_guard(int it) { asm volatile("{.reg .pred p; setp.gt.s32 p,%0,%1; @p trap;}" :: "r"(it), "n"(SPIN_LIMIT)); }
DEV void cnt_wait(const uint32_t* k, int lane) {
  for (int it = 0; !__all_sync(0xffffffffu, ldr1(k + (lane & 3) * 32) >= 32); ++it) spin_guard(it);
}
DEV void mbar_arrive1(uint32_t b) { asm volatile("{.reg .pred p; elect.sync _|p,0xffffffff; @p mbarrier.arrive.shared::cta.b64 _,[%0];}" :: "r"(b) : "memory"); }
DEV void mbar_arrive1_if(uint32_t b, int c) {
  asm volatile("{.reg .pred p,q; setp.ne.s32 q,%1,0; elect.sync _|p,0xffffffff; and.pred p,p,q; @p mbarrier.arrive.shared::cta.b64 _,[%0];}" :: "r"(b), "r"(c) : "memory");
}
DEV void mbar_expect1(uint32_t b, int bytes) { asm volatile("{.reg .pred p; elect.sync _|p,0xffffffff; @p mbarrier.arrive.expect_tx.shared::cta.b64 _,[%0],%1;}" :: "r"(b), "r"(bytes) : "memory"); }
DEV void cnt_add1(uint32_t* q) { asm volatile("{.reg .pred p; elect.sync _|p,0xffffffff; @p red.relaxed.gpu.global.add.u32 [%0],1;}" :: "l"(q) : "memory"); }
DEV void tma4(uint32_t dst, const CUtensorMap* m, int c0, int c1, int c2, int c3, uint32_t bar) {
  asm volatile("{.reg .pred p; elect.sync _|p,0xffffffff;\n"
    "@p cp.async.bulk.tensor.4d.shared::cluster.global.mbarrier::complete_tx::bytes [%0],[%1,{%2,%3,%4,%5}],[%6];}"
    :: "r"(dst), "l"(m), "r"(c0), "r"(c1), "r"(c2), "r"(c3), "r"(bar) : "memory");
}
DEV void tma3(uint32_t dst, const CUtensorMap* m, int c0, int c1, int c2, uint32_t bar) {
  asm volatile("{.reg .pred p; elect.sync _|p,0xffffffff;\n"
    "@p cp.async.bulk.tensor.3d.shared::cluster.global.mbarrier::complete_tx::bytes [%0],[%1,{%2,%3,%4}],[%5];}"
    :: "r"(dst), "l"(m), "r"(c0), "r"(c1), "r"(c2), "r"(bar) : "memory");
}
DEV void bulk(uint32_t dst, const void* src, int bytes, uint32_t bar) {
  asm volatile("{.reg .pred p; elect.sync _|p,0xffffffff;\n@p cp.async.bulk.shared::cluster.global.mbarrier::complete_tx::bytes [%0],[%1],%2,[%3];}" :: "r"(dst), "l"(src), "r"(bytes), "r"(bar) : "memory");
}

DEV void bulk_store(void* dst, uint32_t src, int bytes) {
  asm volatile("{.reg .pred p; elect.sync _|p,0xffffffff;\n@p cp.async.bulk.global.shared::cta.bulk_group [%0],[%1],%2;}" :: "l"(dst), "r"(src), "r"(bytes) : "memory");
}
DEV void tma2_store(const CUtensorMap* m, uint32_t src, int c0, int c1) {
  asm volatile("{.reg .pred p; elect.sync _|p,0xffffffff;\n@p cp.async.bulk.tensor.2d.global.shared::cta.bulk_group [%0,{%2,%3}],[%1];}" :: "l"(m), "r"(src), "r"(c0), "r"(c1) : "memory");
}
DEV void bulk_wait() { asm volatile("cp.async.bulk.commit_group;\ncp.async.bulk.wait_group 0;\nfence.proxy.async.global;" ::: "memory"); }

DEV uint64_t mkdesc(uint32_t addr, uint32_t lbo, uint32_t sbo, uint32_t swz) {
  return (uint64_t)((addr >> 4) | ((lbo >> 4) << 16)) | ((uint64_t)((sbo >> 4) | (swz << 30)) << 32);
}
DEV void wg_fence() { asm volatile("wgmma.fence.sync.aligned;" ::: "memory"); }
DEV void wg_commit() { asm volatile("wgmma.commit_group.sync.aligned;" ::: "memory"); }
template <int N> DEV void wg_wait() { asm volatile("wgmma.wait_group.sync.aligned %0;" :: "n"(N) : "memory"); }
template <int N> DEV void zero(float (&d)[N]) {
#pragma unroll
  for (int i = 0; i < N; ++i) d[i] = 0.f;
}
template <int N> DEV void zerov(float (&d)[N]) {
#pragma unroll
  for (int i = 0; i < N; ++i) asm volatile("mov.b32 %0,0;" : "=f"(d[i]));
}
template <int N> DEV void undef(float (&d)[N]) {
#pragma unroll
  for (int i = 0; i < N; ++i) asm volatile("" : "=f"(d[i]));
}
#define R4(d, o) "+f"(d[o]), "+f"(d[o + 1]), "+f"(d[o + 2]), "+f"(d[o + 3])
#define R8(d, o) R4(d, o), R4(d, o + 4)
#define R16(d, o) R8(d, o), R8(d, o + 8)
template <int ACC> DEV void wg_rs64k(float (&d)[32], const uint32_t (&a)[4], uint64_t db) {
  asm volatile("{.reg .pred p; setp.ne.s32 p,%37,0;\nwgmma.mma_async.sync.aligned.m64n64k16.f32.bf16.bf16 {%0,%1,%2,%3,%4,%5,%6,%7,%8,%9,%10,%11,%12,%13,%14,%15,%16,%17,%18,%19,%20,%21,%22,%23,%24,%25,%26,%27,%28,%29,%30,%31},{%32,%33,%34,%35},%36,p,1,1,0;}"
    : R16(d, 0), R16(d, 16) : "r"(a[0]), "r"(a[1]), "r"(a[2]), "r"(a[3]), "l"(db), "n"(ACC));
}
template <int ACC> DEV void wg_rs48t(float (&d)[24], const uint32_t (&a)[4], uint64_t db) {
  asm volatile("{.reg .pred p; setp.ne.s32 p,%29,0;\nwgmma.mma_async.sync.aligned.m64n48k16.f32.bf16.bf16 {%0,%1,%2,%3,%4,%5,%6,%7,%8,%9,%10,%11,%12,%13,%14,%15,%16,%17,%18,%19,%20,%21,%22,%23},{%24,%25,%26,%27},%28,p,1,1,1;}"
    : R16(d, 0), R8(d, 16) : "r"(a[0]), "r"(a[1]), "r"(a[2]), "r"(a[3]), "l"(db), "n"(ACC));
}
template <int ACC> DEV void wg_rs32t(float (&d)[16], const uint32_t (&a)[4], uint64_t db) {
  asm volatile("{.reg .pred p; setp.ne.s32 p,%21,0;\nwgmma.mma_async.sync.aligned.m64n32k16.f32.bf16.bf16 {%0,%1,%2,%3,%4,%5,%6,%7,%8,%9,%10,%11,%12,%13,%14,%15},{%16,%17,%18,%19},%20,p,1,1,1;}"
    : R16(d, 0) : "r"(a[0]), "r"(a[1]), "r"(a[2]), "r"(a[3]), "l"(db), "n"(ACC));
}
template <int ACC> DEV void wg_ss192(float (&d)[96], uint64_t da, uint64_t db) {
  asm volatile("{.reg .pred p; setp.ne.s32 p,%98,0;\nwgmma.mma_async.sync.aligned.m64n192k16.f32.bf16.bf16 {"
    "%0,%1,%2,%3,%4,%5,%6,%7,%8,%9,%10,%11,%12,%13,%14,%15,%16,%17,%18,%19,%20,%21,%22,%23,%24,%25,%26,%27,%28,%29,%30,%31,"
    "%32,%33,%34,%35,%36,%37,%38,%39,%40,%41,%42,%43,%44,%45,%46,%47,%48,%49,%50,%51,%52,%53,%54,%55,%56,%57,%58,%59,%60,%61,%62,%63,"
    "%64,%65,%66,%67,%68,%69,%70,%71,%72,%73,%74,%75,%76,%77,%78,%79,%80,%81,%82,%83,%84,%85,%86,%87,%88,%89,%90,%91,%92,%93,%94,%95},"
    "%96,%97,p,1,1,1,1;}"
    : R16(d, 0), R16(d, 16), R16(d, 32), R16(d, 48), R16(d, 64), R16(d, 80) : "l"(da), "l"(db), "n"(ACC));
}
template <int ACC> DEV void wg_ss64(float (&d)[32], uint64_t da, uint64_t db) {
  asm volatile("{.reg .pred p; setp.ne.s32 p,%34,0;\nwgmma.mma_async.sync.aligned.m64n64k16.f32.bf16.bf16 {%0,%1,%2,%3,%4,%5,%6,%7,%8,%9,%10,%11,%12,%13,%14,%15,%16,%17,%18,%19,%20,%21,%22,%23,%24,%25,%26,%27,%28,%29,%30,%31},%32,%33,p,1,1,0,1;}"
    : R8(d, 0), R8(d, 8), R8(d, 16), R8(d, 24) : "l"(da), "l"(db), "n"(ACC));
}

DEV uint32_t cpy(uint32_t v, uint32_t id) {
  uint32_t d; asm volatile("prmt.b32 %0,%1,%1,%2;" : "=r"(d) : "r"(v), "r"(id)); return d;
}
struct Params {
  uint32_t zero, spare;
  char* mid;
  const uint16_t *x0, *Are, *Aim, *Bre, *Bim, *Cre, *Cim, *logdt, *dskip, *wqkv, *wo;
  uint16_t* out;
  uint8_t role[144];
};

DEV uint32_t ln_word(float mean, float var) {
  float v = bfr(var);
  float s = sqrt_(bfr(v + 1e-5f));
  return pack2(mean, s);
}

DEV int stat_group(int c) { return 16 * (c & 4) + 4 * (c >> 3) + (c & 3); }
DEV int xg_off(int G, int g) { return (G >> 6) * 1024 + (G & 63) * 8 + (g ^ (G & 2)); }
DEV int sr_off(int G, int g) { return (G >> 6) * 256 + (g & 2) * 64 + 2 * (G & 63) + ((g >> 2) & 1); }
DEV uint32_t region(int chl) { return SM_A + (chl >> 1) * A_E + (chl & 1) * R_SZ; }
template <int N> DEV float4 gram(const uint32_t (&w)[N][2], int g) {
  float s0[4], s1[4];
  const uint32_t one = 0x3F803F80u;
  mma16z(s0, w[0][0], one, w[1][0], one, w[0][0], w[1][0]); mma16z(s1, w[0][1], one, w[1][1], one, w[0][1], w[1][1]);
#pragma unroll
  for (int j = 2; j < N; j += 2) {
    mma16(s0, w[j][0], one, w[j + 1][0], one, w[j][0], w[j + 1][0]); mma16(s1, w[j][1], one, w[j + 1][1], one, w[j][1], w[j + 1][1]);
  }
  const bool od = g & 1;
  return make_float4(od ? s0[3] : s0[2], od ? s0[1] : s0[0], od ? s1[3] : s1[2], od ? s1[1] : s1[0]);
}
DEV uint32_t ln_sums(float s, float q) { const float m = s * (1.f / 512.f); return ln_word(m, fmaxf(q * (1.f / 512.f) - m * m, 0.f)); }
DEV void cmul(float& orr, float& oi, float ar, float ai, float br, float bi) {
  float r = ar * br - ai * bi, i = ar * bi + ai * br; orr = r; oi = i;
}
DEV void cexp_(float al, float bt, float s, float& er, float& ei) {
  float mag = ex2(al * s), ph = bt * s;
  ph -= rintf(ph);
  float ang = ph * 6.283185307179586f;
  er = mag * __cosf(ang); ei = mag * __sinf(ang);
}

DEV void kgen(const Params& P, int c, int wm, int lane) {
  const int chl = wm >> 1, mh = wm & 1, g = lane >> 2, t = lane & 3;
  const int ch = 256 * (chl >> 1) + 2 * c + (chl & 1);
  const int mo = ch * 64 + mh * 32 + lane;
  const uint32_t vAr = ldnc1((const uint32_t*)P.Are + mo), vAi = ldnc1((const uint32_t*)P.Aim + mo);
  const uint32_t vBr = ldnc1((const uint32_t*)P.Bre + mo), vBi = ldnc1((const uint32_t*)P.Bim + mo);
  const uint32_t vCr = ldnc1((const uint32_t*)P.Cre + mo), vCi = ldnc1((const uint32_t*)P.Cim + mo);
  const uint32_t vld = ldnc1((const uint32_t*)P.logdt + (ch >> 1)) >> (16 * (ch & 1)), vds = ldnc1((const uint32_t*)P.dskip + (ch >> 1)) >> (16 * (ch & 1));
  PROF(45);
  asm volatile("setmaxnreg.inc.sync.aligned.u32 %0;" :: "n"(REG_MAIN));
  bar_sync(0, NTHR);
  PROF(44);
  {
    const uint32_t tz = SM_TAP + chl * TAP_SZ + (mh * 32 + lane) * 16;
#pragma unroll
    for (int k = 0; k < 3; ++k) sts4(tz + k * 1024, 0, 0, 0, 0);
    static_assert(TAP_SZ > 3072 && TAP_SZ <= 4096, "");
    if (mh * 32 + lane < TAP_SZ / 16 - 192) sts4(tz + 3072, 0, 0, 0, 0);
  }
  const float dt = bfr(__expf(bflo(vld)));
  const uint32_t tb = slot(wm);
  float acc[5][4];
#pragma unroll
  for (int i = 0; i < 5; ++i) { acc[i][0] = acc[i][1] = acc[i][2] = acc[i][3] = 0.f; }
  float k2048 = 0.f;
#pragma unroll 1
  for (int r = 0; r < 2; ++r) {
    const float are = r ? bfhi(vAr) : bflo(vAr), aim = r ? bfhi(vAi) : bflo(vAi);
    const float bre = r ? bfhi(vBr) : bflo(vBr), bim = r ? bfhi(vBi) : bflo(vBi);
    const float cre = r ? bfhi(vCr) : bflo(vCr), cim = r ? bfhi(vCi) : bflo(vCi);
    const float al = dt * are * 1.4426950408889634f, bt = dt * aim * 0.15915494309189535f;
    float wr, wi; cmul(wr, wi, cre, cim, dt * bre, dt * bim);
    if (r == 0) PROFD(2, __float_as_uint(wr + al + bt));
    float e1r, e1i, e8r, e8i, eLr, eLi;
    cexp_(al, bt, 1.f, e1r, e1i); cexp_(al, bt, 8.f, e8r, e8i); cexp_(al, bt, 128.f, eLr, eLi);
    const uint32_t tw = tb + lane * 4;
    float pr[8], pi[8];
    pr[1] = e1r; pi[1] = e1i;
#pragma unroll
    for (int k = 2; k < 8; ++k) cmul(pr[k], pi[k], pr[k - 1], pi[k - 1], e1r, e1i);
    float yr = 1.f, yi = 0.f, qr = wr, qi = wi;
#pragma unroll
    for (int a = 0; a < 16; ++a) {
      sts1(tw + a * 144, pack2(yr, -yi));
      if (a == 0) { yr = e8r; yi = e8i; } else if (a < 15) cmul(yr, yi, yr, yi, e8r, e8i);
      const int step = a < 2 ? 1 : a < 4 ? 2 : a < 8 ? 4 : 8;
      const int row0 = 16 + (a < 2 ? 8 * a : a < 4 ? 16 + 4 * (a - 2) : a < 8 ? 24 + 2 * (a - 4) : 32 + (a - 8));
      sts1(tw + row0 * 144, pack2(qr, qi));
#pragma unroll
      for (int k = step; k < 8; k += step) {
        float xr, xi; cmul(xr, xi, qr, qi, pr[k], pi[k]);
        sts1(tw + (row0 + k / step) * 144, pack2(xr, xi));
      }
      cmul(qr, qi, qr, qi, eLr, eLi);
    }
    k2048 += qr;
    __syncwarp();
    if (r == 0) PROF(3);
#pragma unroll
    for (int kp = 0; kp < 2; ++kp) {
      uint32_t a0[4], a1[4];
      const uint32_t aa = tb + ((lane & 7) + 8 * ((lane >> 3) & 1)) * 144 + (lane >> 4) * 16 + kp * 64;
      ldsm4(a0, aa); ldsm4(a1, aa + 32);
#pragma unroll
      for (int tl = 0; tl < 5; ++tl) {
        uint32_t b[4];
        ldsm4(b, tb + (16 + 8 * tl + (lane & 7)) * 144 + (lane >> 3) * 16 + kp * 64);
        mma16(acc[tl], a0[0], a0[1], a0[2], a0[3], b[0], b[1]);
        mma16(acc[tl], a1[0], a1[1], a1[2], a1[3], b[2], b[3]);
      }
    }
    __syncwarp();
  }
#pragma unroll
  for (int o = 16; o > 0; o >>= 1) k2048 += __shfl_xor_sync(0xffffffffu, k2048, o);
  if (mh == 0) {
    sts4f(tb + lane * 16, acc[2][0], acc[2][1], acc[2][2], acc[2][3]);
    sts4f(tb + 512 + lane * 16, acc[3][0], acc[3][1], acc[3][2], acc[3][3]);
  } else {
    sts4f(tb + lane * 16, acc[0][0], acc[0][1], acc[0][2], acc[0][3]);
    sts4f(tb + 512 + lane * 16, acc[1][0], acc[1][1], acc[1][2], acc[1][3]);
    sts4f(tb + 1024 + lane * 16, acc[4][0], acc[4][1], acc[4][2], acc[4][3]);
    if (lane == 0) sts1(tb + 1536, __float_as_uint(k2048));
  }
  PROF(4);
  bar_sync(NB_K + chl, 64);
  const uint32_t ob = slot(wm ^ 1), tp = SM_TAP + chl * TAP_SZ;
  if (mh == 0) {
#pragma unroll
    for (int tl = 0; tl < 2; ++tl) {
      float4 o = lds4f(ob + tl * 512 + lane * 16);
      if (tl == 0 && lane == 0) o.x += bflo(vds);
      uint32_t v0 = pack2(acc[tl][0] + o.x, acc[tl][1] + o.y), v1 = pack2(acc[tl][2] + o.z, acc[tl][3] + o.w);
      const int l = 128 * tl + 8 * g + 2 * t;
      sts16(tp + T_E + 2 * (0 - l), v0); sts16(tp + T_E + 2 * (-1 - l), v0 >> 16);
      sts16(tp + T_O + 2 * (0 - l), v0); sts16(tp + T_O + 2 * (-1 - l), v0 >> 16);
      sts16(tp + T_E + 2 * (-64 - l), v1); sts16(tp + T_E + 2 * (-65 - l), v1 >> 16);
      sts16(tp + T_O + 2 * (-64 - l), v1); sts16(tp + T_O + 2 * (-65 - l), v1 >> 16);
    }
    float4 o = lds4f(ob + 1024 + lane * 16);
    uint32_t v0 = pack2(acc[4][0] + o.x, acc[4][1] + o.y), v1 = pack2(acc[4][2] + o.z, acc[4][3] + o.w);
    const int x = 32 * t + g - 1;
    if (lane == 0) { sts16(tp + T_E - 2 * (X_5 + 63), v0); sts16(tp + T_O - 2 * (X_5 + 63), v0); sts1(tp + T_K, prmt(v0, v0, 0x1010)); }
    else sts16(tp + T_C - 2 * x, v0);
    sts16(tp + T_C - 2 * (x + 16), v0 >> 16);
    sts16(tp + T_C - 2 * (x + 8), v1);
    sts16(tp + T_C - 2 * (x + 24), v1 >> 16);
    if (lane == 0) sts16(tp + T_C - 2 * 127, pack2(k2048 + __uint_as_float(lds1(ob + 1536)), 0.f));
  } else {
    float4 o2 = lds4f(ob + lane * 16), o3 = lds4f(ob + 512 + lane * 16);
    uint32_t v0 = pack2(acc[2][0] + o2.x, acc[2][1] + o2.y), v1 = pack2(acc[2][2] + o2.z, acc[2][3] + o2.w);
    const int l0 = 256 + 128 * (t >> 1) + 4 * (t & 1) + 8 * g;
    if (lane != 0) { sts16(tp + T_E + 2 * (1 - l0), v0); sts16(tp + T_O + 2 * (1 - l0), v0); }
    sts16(tp + T_E + 2 * (0 - l0), v0); sts16(tp + T_O + 2 * (0 - l0), v0);
    sts16(tp + T_E + 2 * (-1 - l0), v0); sts16(tp + T_O + 2 * (-1 - l0), v0);
    sts16(tp + T_E + 2 * (-2 - l0), v0 >> 16); sts16(tp + T_O + 2 * (-2 - l0), v0 >> 16);
    sts16(tp + T_E + 2 * (-63 - l0), v1); sts16(tp + T_O + 2 * (-63 - l0), v1);
    sts16(tp + T_E + 2 * (-64 - l0), v1); sts16(tp + T_O + 2 * (-64 - l0), v1);
    sts16(tp + T_E + 2 * (-65 - l0), v1); sts16(tp + T_O + 2 * (-65 - l0), v1);
    sts16(tp + T_E + 2 * (-66 - l0), v1 >> 16); sts16(tp + T_O + 2 * (-66 - l0), v1 >> 16);
    uint32_t w0 = pack2(acc[3][0] + o3.x, acc[3][1] + o3.y), w1 = pack2(acc[3][2] + o3.z, acc[3][3] + o3.w);
    const int x = 16 * t + g;
    if (lane == 0) {
      const uint32_t k = prmt(w0, w0, 0x1010);
      sts1(tp + T_E - 2 * 514, k); sts1(tp + T_E - 2 * 512, k);
      sts16(tp + T_O - 2 * 514, k); sts1(tp + T_O - 2 * 513, k); sts16(tp + T_O - 2 * 511, k);
    } else { sts16(tp + T_E - 2 * (X_5 - 1 + x), w0); sts16(tp + T_O - 2 * (X_5 - 1 + x), w0); }
    sts16(tp + T_E - 2 * (X_3 + x), w0 >> 16); sts16(tp + T_O - 2 * (X_3 + x), w0 >> 16);
    sts16(tp + T_E - 2 * (X_5 + 7 + x), w1); sts16(tp + T_O - 2 * (X_5 + 7 + x), w1);
    sts16(tp + T_E - 2 * (X_3 + 8 + x), w1 >> 16); sts16(tp + T_O - 2 * (X_3 + 8 + x), w1 >> 16);
  }
}

DEV bool bad8(const uint4& v) { return min(v.x, v.z) == 0u; }
DEV uint32_t uchunk(uint32_t reg, int x) { return reg + R_U + (x ^ ((x >> 3) & 3)) * 16; }
DEV uint32_t& xword(uint4 (&x)[2], int e, int tp) { uint4& v = x[tp >> 1]; return tp & 1 ? (e ? v.w : v.z) : (e ? v.y : v.x); }

DEV void sload(const Params& P, int c, int j, int layer, uint4 (&s)[2][2]) {
  const uint4* st = &SCR->SR[layer][c >> 4][opq(j)];
  mbar_wait(B_U, layer);
  PROF(layer ? 25 : 10);
#pragma unroll
  for (int z = 0; z < 4; ++z) s[z >> 1][z & 1] = ldr4(st + z * 128);
}
DEV void uload(const Params& P, int c, int j, int layer, uint4 (&x)[2][2][2], uint4 (&s)[2][2]) {
  j = opq(j);
  const uint4* st = &SCR->SR[layer][c >> 4][j];
  const int o0 = 2 * j + ((j >> 2) & 1), o1 = o0 ^ 1;
#pragma unroll
  for (int z = 0; z < 4; ++z) { uint4& v = s[z >> 1][z & 1]; ldr4_if(v, st + z * 128, bad8(v)); }
  PROF(layer ? 26 : 11);
  mbar_wait(B_E, layer);
#pragma unroll
  for (int z = 0; z < 8; ++z) x[z >> 2][(z >> 1) & 1][z & 1] = lds4(SM_X + 16 * (z & 1 ? o1 : o0) + (z >> 1) * 4096);
  PROF(layer ? 27 : 14);
  for (int it = 0;; ++it) {
    uint32_t m = ~0u;
#pragma unroll
    for (int z = 0; z < 4; ++z) { const uint4& v = s[z >> 1][z & 1]; m = min(m, min(v.x, v.z)); }
#pragma unroll
    for (int z = 0; z < 8; ++z) { const uint4& v = x[z >> 2][(z >> 1) & 1][z & 1]; m = min(m, min(v.x, v.z)); }
    if (!RARE(m == 0)) break;
#pragma unroll
    for (int z = 0; z < 4; ++z) { uint4& v = s[z >> 1][z & 1]; ldr4_if(v, st + z * 128, bad8(v)); }
#pragma unroll
    for (int z = 0; z < 8; ++z) {
      uint4& v = x[z >> 2][(z >> 1) & 1][z & 1];
      ldr4_if(v, &SCR->XG[layer][c * 1024 + (opq(o0) ^ (z & 1)) + (z >> 1) * 256], bad8(v));
    }
    spin_guard(it);
  }
  PROF(4 + 12 * layer);
}
DEV void uprep(int j, int k, uint4 (&x)[2][2], uint4 (&s)[2], uint32_t (&u)[4][4]) {
  const uint32_t ua = uchunk(0, opq(j)) + k * 2048;
#pragma unroll
  for (int chl = 0; chl < 4; ++chl) {
#pragma unroll
    for (int tp = 0; tp < 4; ++tp) u[chl][tp] = hmul2(hsub2(xword(x[chl >> 1], chl & 1, tp), xword(s, 1, tp)), xword(s, 0, tp));
    sts4(ua + region(chl), u[chl][0], u[chl][1], u[chl][2], u[chl][3]);
  }
}

template <bool FULL> DEV void box_unit(uint32_t reg, int s, const uint2& a, const uint4& b, const uint32_t (&d)[4], uint32_t (&pv)[4]) {
  const uint32_t u[9] = {a.x, a.y, b.x, b.y, b.z, b.w, d[0], d[1], d[2]};
  uint32_t v[8], p[8];
#pragma unroll
  for (int j = 0; j < 8; ++j) { v[j] = prmt(u[j], u[j + 1], 0x5432); p[j] = hadd2(u[j], v[j]); }
  const uint32_t o = reg + s * 16;
  uint32_t x[4], y[4];
#pragma unroll
  for (int j = 0; j < 4; ++j) { x[j] = hadd2(hadd2(p[1 + j], p[2 + j]), u[3 + j]); y[j] = hadd2(v[3 + j], p[4 + j]); pv[j] = p[4 + j]; }
  sts4(o + R_X5, x[0], x[1], x[2], x[3]);
  sts4(o + R_X3, y[0], y[1], y[2], y[3]);
  if (FULL) {
#pragma unroll
    for (int j = 0; j < 4; ++j) { y[j] = hadd2(hadd2(v[j], v[3 + j]), x[j]); x[j] = hadd2(hadd2(u[j], u[4 + j]), y[j]); }
    const bool od = s & 1;
    sts4(o + R_BO, od ? y[0] : x[0], od ? y[1] : x[1], od ? y[2] : x[2], od ? y[3] : x[3]);
    sts4(o + R_BE + 16, od ? x[0] : y[0], od ? x[1] : y[1], od ? x[2] : y[2], od ? x[3] : y[3]);
  }
}
DEV void box_full(int j, uint32_t (&u)[4][4]) {
  const uint32_t a2 = uchunk(8, j - 2), a1 = uchunk(0, j - 1);
  uint2 a[4]; uint4 b[4];
#pragma unroll
  for (int chl = 0; chl < KBL; ++chl) { a[chl] = lds2(region(chl) + a2); b[chl] = lds4(region(chl) + a1); }
#pragma unroll
  for (int chl = 0; chl < 4; ++chl) {
    const uint32_t d[4] = {u[chl][0], u[chl][1], u[chl][2], u[chl][3]};
    box_unit<true>(region(chl), j, a[chl], b[chl], d, u[chl]);
    if (chl + KBL < 4) { a[(chl + KBL) & 3] = lds2(region(chl + KBL) + a2); b[(chl + KBL) & 3] = lds4(region(chl + KBL) + a1); }
    if (chl != 2) {
      fence_async_smem();
      if (chl == 3) bar_arrive(NB_B + 2, 288);
      bar_arrive(NB_B + chl, 288);
    }
    if (chl == 0) PROF(31);
  }
}
DEV void box_help(int chl, int lane) {
  const uint32_t reg = region(chl);
#pragma unroll 1
  for (int s = 128 + opq(lane); s < 192; s += 32) {
    const uint4 d = lds4(uchunk(reg, s));
    const uint32_t u[4] = {d.x, d.y, d.z, d.w};
    uint32_t v[4];
    box_unit<false>(reg, s, lds2(uchunk(reg, s - 2) + 8), lds4(uchunk(reg, s - 1)), u, v);
  }
  fence_async_smem();
  bar_arrive(NB_B + chl, 288);
}

DEV uint4 hadd8(const uint4& a, const uint4& b) { return make_uint4(hadd2(a.x, b.x), hadd2(a.y, b.y), hadd2(a.z, b.z), hadd2(a.w, b.w)); }
DEV void conv_out(int c, int j, int chl, uint4 (&x)[2][2][2], const uint32_t (&v)[4], uint4* XF) {
  const int rho = chl >> 1, e = chl & 1;
  const uint32_t ua = uchunk(region(chl), j), fa = region(chl) + R_X5 + j * 16, ha = region(chl) + R_X3 + (j & 1) * 1088 + (j >> 1) * 16;
  const int m8 = ((j & 4) + ((j >> 1) & 1)) ^ ((2 * c + e) & 7);
  uint2* xo = (uint2*)XF + (((j >> 3) * 512 + 256 * rho + 2 * c + e) * 16 + (j & 1));
  bar_sync(NB_Y + e + 7 * rho, 256);
  uint4 y[2], f[2], h[2];
#pragma unroll
  for (int k = 0; k < 2; ++k) {
    y[k] = lds4(ua + k * 2048);
    f[k] = lds4z(ua + k * 2048 + R_BO - R_U, k || j >= 36);
    h[k] = lds4z(fa + k * 2048 - 1024, k || j >= 64);
  }
  const uint32_t q = lds1(SM_TAP + chl * TAP_SZ + T_K);
  const uint4 r = lds4(ha);
  h[1] = hadd8(h[1], make_uint4(hfma2(q, v[0], r.x), hfma2(q, v[1], r.y), hfma2(q, v[2], r.z), hfma2(q, v[3], r.w)));
#pragma unroll
  for (int k = 0; k < 2; ++k) {
    const uint4 o = hadd8(hadd8(y[k], hadd8(f[k], h[k])), make_uint4(xword(x[k][rho], e, 0), xword(x[k][rho], e, 1), xword(x[k][rho], e, 2), xword(x[k][rho], e, 3)));
    str2(xo + k * 131072 + 2 * m8, prmt(o.x, o.y, 0x5410), prmt(o.z, o.w, 0x5410));
    str2(xo + k * 131072 + 2 * (m8 ^ 2), prmt(o.x, o.y, 0x7632), prmt(o.z, o.w, 0x7632));
  }
  if (e) { __syncwarp(); mbar_arrive1(B_RD + rho * 8); }
}

DEV void conv_round(int e, int rho, int w, int lane) {
  const int g = lane >> 2, t = lane & 3, chl = 2 * rho + e;
  const uint32_t reg = region(chl), tp = SM_TAP + chl * TAP_SZ;
  const uint32_t g0 = tp + ((g & 1) ? T_O : T_E) + 2 * (2 * t - g) - 16;
  const uint32_t ga = g0 - 32 * (w & 1) - 576 * (w >> 1), id = opq(0x3210u);
  float acc[32], f1[24], f2[16];
  uint32_t q[12][4];
  {
    uint32_t qn[18][4];
    qn[0][2] = lds1(ga + 64);
#pragma unroll
    for (int n = 0; n < 18; ++n) {
      const bool nz = n < 15 || w < 2 || (n == 15 && w == 2);
      qn[n][0] = n < 15 ? lds1(ga + 48 - 32 * n) : lds1z(ga + 48 - 32 * n, nz);
      qn[n][1] = n < 15 ? lds1(ga + 32 - 32 * n) : lds1z(ga + 32 - 32 * n, nz);
    }
#pragma unroll
    for (int n = 0; n < 18; ++n) { qn[n][3] = cpy(qn[n][0], id); if (n) qn[n][2] = cpy(qn[n - 1][1], id); }
#pragma unroll
    for (int n = 0; n < 8; ++n) {
      const int i = n & 3;
      const uint32_t a = g0 + 16 - 16 * w - 2 * (n < 4 ? X_5 : X_3) + 16 * i;
      uint32_t (&q1)[4] = q[(n & 4) + (i >> 1)], (&q2)[4] = q[(n & 4) + 2 + (i >> 1)];
      q1[2 * (i & 1)] = lds1z(a, i <= w); q1[2 * (i & 1) + 1] = lds1(a - 64);
      q2[2 * (i & 1)] = cpy(0, id); q2[2 * (i & 1) + 1] = lds1z(a - 128, i >= w);
    }
    const uint32_t gc = tp + T_C - 2 + 4 * (t - g - 8 * w);
#pragma unroll
    for (int kk = 0; kk < 4; ++kk) {
      q[8 + kk][0] = lds1z(gc + 32 * kk, w >= kk); q[8 + kk][2] = lds1z(gc + 32 * kk + 16, w >= kk);
      q[8 + kk][1] = lds1(gc + 32 * kk - 128); q[8 + kk][3] = lds1(gc + 32 * kk - 112);
    }
    PROFD(rho ? 43 : 47, qn[17][2] ^ q[11][3]);
    bar_sync_if(NB_U, NBARU, 1 - rho);
    bar_sync_if(NB_T + 1 - e, 256, chl);
    const uint64_t db = mkdesc(reg + R_U, 16, 512, 2) + 2;
    undef(acc);
    wg_fence();
#pragma unroll
    for (int n = 0; n < 18; ++n) {
      if (n) wg_rs64k<1>(acc, qn[n], db - 2 * n); else wg_rs64k<0>(acc, qn[0], db);
      if (n == 9) wg_commit();
    }
    wg_commit();
  }
  wg_wait<1>();
  PROF(12);
  bar_sync(NB_B + chl, 288);
  const uint64_t d1 = mkdesc(reg + R_X5, 128, 512, 0), d2 = mkdesc(reg + R_BO, 128, 1024, 0);
  undef(f1); undef(f2);
  wg_fence();
#pragma unroll
  for (int n = 0; n < 8; ++n) {
    const uint64_t d = d1 + (n >> 2) * ((R_X3 - R_X5) / 16) + 16 * (n & 1) - 16 * (n & 2);
    if (n) wg_rs48t<1>(f1, q[n], d); else wg_rs48t<0>(f1, q[0], d);
    if (n & 1) { if (n > 1) wg_rs32t<1>(f2, q[8 + (n >> 1)], d2 + 16 * (n >> 1)); else wg_rs32t<0>(f2, q[8], d2); }
  }
  wg_commit();
  wg_wait<1>();
  PROF(13);
  bar_arrive_if(NB_T + e, 256, chl - 3);
  wg_wait<0>();
  PROF(14);
  bar_sync(NB_WG + e, 128);
  {
    const int p = (lane + 9 * (w >> 1)) & 31;
    const uint32_t ya = reg + ((w >> 1) ? R_BO : R_U) + p * 64 + (((2 * (w & 1)) ^ ((p >> 1) & 3)) * 16);
    const uint32_t up = p < lane ? 2048 : 0;
#pragma unroll
    for (int z = 0; z < 4; ++z) {
      const float* a = acc + 16 * (z >> 1) + 2 * (z & 1);
      stsm4t((ya + (up ^ ((z >> 1) * 2048))) ^ ((z & 1) * 16), pack2(a[0], a[1]), pack2(a[4], a[5]), pack2(a[8], a[9]), pack2(a[12], a[13]));
    }
  }
  {
    const uint32_t fa = reg + R_X5 + (8 * w + (lane & 7)) * 16 + (lane >> 3) * 512;
    uint32_t h[6];
#pragma unroll
    for (int p = 0; p < 6; ++p) h[p] = p ? pack2(f1[4 * p] + f1[4 * p - 2], f1[4 * p + 1] + f1[4 * p - 1]) : pack2(f1[0], f1[1]);
    stsm4(fa, h[0], h[1], h[2], h[3]);
    stsm2(fa + 2048, h[4], h[5]);
    stsm4(reg + R_X3 + (lane < 16 ? 1088 : 0) + (8 * w + (lane & 7) + 4 * (lane & 8)) * 16, pack2(f2[0], f2[1]), pack2(f2[2] + f2[4], f2[3] + f2[5]),
          pack2(f2[8], f2[9]), pack2(f2[10] + f2[12], f2[11] + f2[13]));
  }
  bar_arrive(NB_Y + e + 7 * rho, 256);
}
constexpr uint32_t FILL = 0xFFFFFFFFu;
template <int N> DEV void fixo(uint4 (&A)[N], const uint4* p) {
#pragma unroll 1
  for (int it = 0; it < SPIN_LIMIT; ++it) {
    uint32_t m = A[0].x;
#pragma unroll
    for (int k = 1; k < N; ++k) m = max(m, A[k].x);
    if (__all_sync(0xffffffffu, m != FILL)) break;
#pragma unroll
    for (int k = 0; k < N; ++k) ldr4_if(A[k], p + k * 32, A[k].x == FILL);
  }
}
DEV bool rows_nan(float a, float b) {
  return __any_sync(0xffffffffu, a != a || b != b);
}
template <int N> DEV void slow_step(float (&acc)[N], float a0, float a1, const uint16_t* wr, uint32_t zero) {
#pragma unroll
  for (int j = 0; j < N / 4; ++j) {
    const uint32_t v = __ldg((const uint32_t*)(wr + (j >> 3) * 512 + 8 * (j & 7)));
    acc[4 * j] += a0 * bflo(v); acc[4 * j + 1] += a0 * bfhi(v); acc[4 * j + 2] += a1 * bflo(v); acc[4 * j + 3] += a1 * bfhi(v);
    if ((j & 3) == 3) wr += __float_as_uint(acc[4 * j]) & zero;
  }
}
DEV int res_off(int w, int lane) { return ((lane & 7) + 8 * (lane >> 4)) * 8 + ((2 * (w & 2) + (w & 1) + ((lane >> 2) & 2)) ^ (lane & 7)); }
DEV void res_load(uint32_t (&res)[8][2], uint32_t sa, int w, int lane) {
  const uint32_t a = sa + res_off(w, opq(lane)) * 16;
#pragma unroll
  for (int j = 0; j < 8; j += 2) {
    uint32_t r[4];
    ldsm4t(r, a + j * 1024);
    res[j][0] = r[0]; res[j][1] = r[1]; res[j + 1][0] = r[2]; res[j + 1][1] = r[3];
  }
}

DEV uint32_t after(uint32_t b, const uint32_t (&res)[8][2], uint32_t zero) {
  return b + ((res[0][0] ^ res[2][0] ^ res[4][0] ^ res[6][0]) & zero);
}

DEV void attn_phase(const Params& P, int c, int e, int w, int lane, int layer) {
  lane = opq(lane); c = opq(c);
  const int i = c >> 3, cg = c & 7, J = 16 * e + i, G = 4 * J + w;
  const int g = lane >> 2, t = lane & 3;
  float acc[96];
  uint32_t res[8][2];
  float2 cs[16];
  float4 st;
  const uint32_t csb = opq(SM_CS + 8 * t);
  {
    const uint32_t sa = SM_A + e * A_E, ba = B_A + 16 * e;
    const uint64_t da = mkdesc(sa, 8192, 1024, 1), db = mkdesc(SB, 8192, 1024, 1);
    undef(acc);
#pragma unroll
    for (int j = 0; j < 8; ++j) asm volatile("" : "=r"(res[j][0]), "=r"(res[j][1]));
    mbar_wait(B_WF, layer);
    mbar_wait(ba, 0);
    mbar_wait(B_RD + 8, layer);
    bar_sync_if(NB_T, 256, e);
    PROF(24);
#pragma unroll
    for (int j = 0; j < 4; ++j) {
      if (j == 1) { mbar_wait(ba + 8, 0); PROF(39); }
      wg_fence();
#pragma unroll
      for (int k = 0; k < 4; ++k) {
        if (j | k) wg_ss192<1>(acc, da + j * 512 + k * 128, db + wslot(j) * 512 + k * 128); else wg_ss192<0>(acc, da, db);
        if (j == 3 && k == 1) wg_commit();
      }
      wg_commit();
      if (j == 1 || j == 2) { wg_wait<1>(); mbar_arrive1_if(B_F + 8 * (j - 1), e); }
    }
    wg_wait<1>();
    bar_arrive(NB_T + e, 256);
    wg_wait<0>();
    if (cg < 4) res_load(res, sa + cg * 8192, w, lane);
    mbar_arrive1(after(B_AE + 8 * e, res, P.zero));
    PROF(25);
    mbar_wait(B_CS, 0);
#pragma unroll 1
    for (uint32_t late = P.zero;; late = 1) {
      if (late) {
        const uint16_t* xr = (const uint16_t*)SCR->XF[layer] + opq(J) * 32768;
        zero(acc);
#pragma unroll 1
        for (int k = 0; k < 512; ++k)
          slow_step(acc, ldnan(xr + k * 64 + ((2 * w) ^ (k & 7)) * 8 + g), ldnan(xr + k * 64 + ((2 * w + 1) ^ (k & 7)) * 8 + g),
                    P.wqkv + (k * 1536 + 64 * cg + 2 * t), P.zero);
        const uint32_t* q = (const uint32_t*)xr + ((64 * cg + g) * 32 + t);
        const int m8 = (2 * (w & 2) + (w & 1)) ^ g;
#pragma unroll 1
        for (int it = 0; it < SPIN_LIMIT; ++it) {
          uint32_t m = 0;
#pragma unroll
          for (int z = 0; z < 16; ++z) { const uint32_t x = ldr1(q + (z >> 1) * 256 + (m8 ^ (2 * (z & 1))) * 4); m = max(m, x); res[z >> 1][z & 1] = movm(x); }
          if (__all_sync(0xffffffffu, m != FILL)) break;
        }
#pragma unroll
        for (int z = 0; z < 16; ++z) cs[z] = lds2f(csb + 256 + z * 32);
      } else {
#pragma unroll
        for (int z = 0; z < 16; ++z) cs[z] = lds2f(csb + 256 + z * 32);
        mbar_wait(B_W4, layer);
        mbar_wait(ba, 1);
        bar_sync(NB_T + 1 - e, 256);
        PROF(26);
#pragma unroll
        for (int j = 4; j < 8; ++j) {
          if (j == 5) mbar_wait(ba + 8, 1);
          if (j >= 6) mbar_wait(B_W6 + 8 * (j - 6), layer);
          if (j > 4) PROF(31 + j);
          wg_fence();
#pragma unroll
          for (int k = 0; k < 4; ++k) {
            wg_ss192<1>(acc, da + (j & 3) * 512 + k * 128, db + wslot(j) * 512 + k * 128);
            if (j == 7 && k == 1) wg_commit();
          }
          wg_commit();
          if (j == 5) {
            if (cg >= 4) res_load(res, sa + (cg - 4) * 8192, w, lane);
            wg_wait<1>(); mbar_arrive1_if(B_F + 16, e); PROF(40);
          }
        }
      }
      uint32_t rs = hadd2(res[0][0], res[0][1]);
#pragma unroll
      for (int z = 2; z < 16; ++z) rs = hadd2(rs, res[z >> 1][z & 1]);
      const float rn = bflo(rs) + bfhi(rs);
      wg_wait<1>();
      bar_arrive_if(NB_T, 256, !(e | late));
      mbar_wait(B_ST + 8 * e, layer);
      st = lds4f(SM_STAT + ((4 * e + w) * 8 + g) * 16);
      PROF(34 + layer);
      wg_wait<0>();
      if (!rows_nan(acc[0] + rn, acc[2]) || late) break;
    }
  }
  mbar_arrive1(B_QE);
  PROF(8 + 12 * layer);
  uint32_t Q[4][4], K[4][2][2], V[4][2][2];
  {
#pragma unroll
    for (int z = 0; z < 8; ++z) {
      const float* a = acc + 32 + 4 * z; const float* b = acc + 64 + 4 * z;
      K[z >> 1][1][z & 1] = pack2((a[2] - st.z * cs[z].x) * st.w, (a[3] - st.z * cs[z].y) * st.w);
      V[z >> 1][1][z & 1] = movm(pack2((b[2] - st.z * cs[8 + z].x) * st.w, (b[3] - st.z * cs[8 + z].y) * st.w));
    }
    const uint32_t kv = SM_KV + (2 * e + (w & 1)) * 2048 + lane * 16;
    uint4* h = SCR->H[layer] + ((J * 8 + cg) * 256 + (w & 1) * 128 + lane);
    if (w >= 2) {
#pragma unroll
      for (int z = 0; z < 4; ++z) str4(h + 2048 + z * 32, K[z][1][0], K[z][1][1], V[z][1][0], V[z][1][1]);
    } else {
      mbar_wait(B_F + 16, layer);
#pragma unroll
      for (int z = 0; z < 4; ++z) sts4(kv + z * 512, K[z][1][0], K[z][1][1], V[z][1][0], V[z][1][1]);
      bar_arrive(NB_WG + e, 128);
    }
    PROF(42);
#pragma unroll
    for (int z = 0; z < 8; ++z) {
      const float* a = acc + 32 + 4 * z; const float* b = acc + 64 + 4 * z;
      K[z >> 1][0][z & 1] = pack2((a[0] - st.x * cs[z].x) * st.y, (a[1] - st.x * cs[z].y) * st.y);
      V[z >> 1][0][z & 1] = movm(pack2((b[0] - st.x * cs[8 + z].x) * st.y, (b[1] - st.x * cs[8 + z].y) * st.y));
    }
#pragma unroll
    for (int z = 0; z < 8; ++z) {
      const float2 cq = lds2f(csb + z * 32);
      const float* a = acc + 4 * z;
      Q[z >> 1][2 * (z & 1)] = pack2(a[0] - st.x * cq.x, a[1] - st.x * cq.y);
      Q[z >> 1][2 * (z & 1) + 1] = pack2(a[2] - st.z * cq.x, a[3] - st.z * cq.y);
    }
    PROF(27);
    uint4 hv[4];
    if (w >= 2) {
      bar_sync(NB_WG + e, 128);
#pragma unroll
      for (int z = 0; z < 4; ++z) hv[z] = lds4(kv + z * 512);
    } else {
#pragma unroll
      for (int z = 0; z < 4; ++z) { hv[z] = make_uint4(0, 0, 0, 0); ldr4_if(hv[z], h + z * 32, G >= 2); }
    }
    const bool p0 = 2 * t > g, p1 = 2 * t + 1 > g, first = G < 2;
    float s[4][4], mx[4][2];
#pragma unroll
    for (int z = 0; z < 4; ++z) {
      float S[4];
      mma16z(s[z], Q[z][0], Q[z][1], Q[z][2], Q[z][3], K[z][0][0], K[z][0][1]);
      mma16z(S, Q[z][0], Q[z][1], Q[z][2], Q[z][3], K[z][1][0], K[z][1][1]);
      s[z][2] = p0 ? s[z][2] : S[2]; s[z][3] = p1 ? s[z][3] : S[3];
    }
    const float sc0 = st.y * (0.25f * 1.4426950408889634f), sc1 = st.w * (0.25f * 1.4426950408889634f);
    uint32_t pw[4][2];
#pragma unroll
    for (int r = 1; r >= 0; --r) {
      if (r == 0) {
        fixo(hv, h);
        PROFD(41, hv[3].x);
#pragma unroll
        for (int z = 0; z < 4; ++z) {
          float S[4];
          mma16z(S, Q[z][0], Q[z][1], Q[z][2], Q[z][3], hv[z].x, hv[z].y);
          if (first) S[0] = S[1] = __uint_as_float(0xFF800000u);
          s[z][0] = p0 ? S[0] : s[z][0]; s[z][1] = p1 ? S[1] : s[z][1];
        }
      }
#pragma unroll
      for (int z = 0; z < 4; ++z) mx[z][r] = fmaxf(s[z][2 * r], s[z][2 * r + 1]);
#pragma unroll
      for (int o = 1; o < 3; ++o)
#pragma unroll
        for (int z = 0; z < 4; ++z) mx[z][r] = fmaxf(mx[z][r], __shfl_xor_sync(0xffffffffu, mx[z][r], o));
#pragma unroll
      for (int z = 0; z < 4; ++z) pw[z][r] = pack2(ex2((s[z][2 * r] - mx[z][r]) * (r ? sc1 : sc0)), ex2((s[z][2 * r + 1] - mx[z][r]) * (r ? sc1 : sc0)));
    }
    mbar_wait(layer ? B_N : B_Z, layer);
    const uint32_t M = (p0 ? 0xFFFFu : 0u) | (p1 ? 0xFFFF0000u : 0u);
    uint4* O = SCR->O + ((J * 8 + cg) * 512 + (2 * (w & 2) + (w & 1)) * 64 + t * 8 + g);
#pragma unroll
    for (int h2 = 0; h2 < 2; ++h2) {
      uint32_t ow[2][4];
#pragma unroll
      for (int z = 0; z < 2; ++z) {
        const int n = 2 * h2 + z;
        const uint32_t w0 = pw[n][0], w1 = pw[n][1];
        float sm[4] = {0.f, 0.f, 0.f, 0.f}, Oa[2][4];
        mma8(sm, w0, w1, 0x3F803F80u);
        mma16z(Oa[0], w0 & ~M, w1 & M, 0u, w1 & ~M, V[n][0][0], V[n][1][0]); mma8(Oa[0], w0 & M, 0u, hv[n].z);
        mma16z(Oa[1], w0 & ~M, w1 & M, 0u, w1 & ~M, V[n][0][1], V[n][1][1]); mma8(Oa[1], w0 & M, 0u, hv[n].w);
        const float i0 = rcp(sm[0]), i1 = rcp(sm[2]);
#pragma unroll
        for (int d = 0; d < 2; ++d) { ow[0][2 * z + d] = pack2(Oa[d][0] * i0, Oa[d][1] * i0); ow[1][2 * z + d] = pack2(Oa[d][2] * i1, Oa[d][3] * i1); }
      }
#pragma unroll
      for (int hi = 0; hi < 2; ++hi) str4(O + hi * 128 + h2 * 32, ow[hi][0], ow[hi][1], ow[hi][2], ow[hi][3]);
    }
  }
  if (lane == 0) str1(SCR->OF[layer] + (J * 32 + cg * 4 + w), 1);
  __syncwarp();
  mbar_arrive1(B_AT + 8 * e + (lds1(csb) & P.zero));
  PROF(9 + 12 * layer);
  float ac[32];
  undef(ac);
  const uint32_t so = SM_O + e * O_E;
  {
    const uint32_t bo = B_O + 32 * e;
    const uint64_t dw = mkdesc(SM_WO, 8192, 1024, 1), da = mkdesc(so, 512, 1024, 0);
    mbar_wait(B_WO, layer);
#pragma unroll
    for (int j = 0; j < 4; ++j) {
      mbar_wait(bo + 8 * j, layer);
      if (j == 0) { PROF(32 + layer); mbar_wait(B_AT + 8, layer); }
      wg_fence();
#pragma unroll
      for (int k = 8 * j; k < 8 * j + 8; ++k) {
        const uint64_t a = da + (k >> 2) * 512 + (k & 3) * 8, b = dw + (k & 3) * 1024 + (k >> 2) * 128;
        if (k) wg_ss64<1>(ac, a, b); else wg_ss64<0>(ac, a, b);
      }
      wg_commit();
    }
#pragma unroll 1
    for (uint32_t late = P.zero;; late = 1) {
      if (late) {
        const uint16_t* op = (const uint16_t*)(SCR->O + (J * 4096 + w * 128 + g));
        wg_wait<0>();
        zero(ac);
#pragma unroll 1
        for (int k = 0; k < 512; ++k) {
          const uint16_t* q = op + (k >> 6) * 4096 + (k & 56) * 8 + (k & 7);
          slow_step(ac, ldnan(q), ldnan(q + 512), P.wo + (((k & ~31) + 4 * (k & 6) + ((k >> 2) & 6) + (k & 1)) * 512 + 64 * cg + 2 * t), P.zero);
        }
      }
      wg_wait<0>();
      if (!rows_nan(ac[0], ac[2]) || late) break;
    }
  }
  PROF(10 + 12 * layer);
#pragma unroll
  for (int j = 0; j < 8; ++j) {
    res[j][0] = hadd2(res[j][0], pack2(ac[4 * j], ac[4 * j + 1]));
    res[j][1] = hadd2(res[j][1], pack2(ac[4 * j + 2], ac[4 * j + 3]));
  }
  if (layer == 0) {
    const float4 s = gram(res, g);
    if (t == (g >> 1))
      str4(&SCR->PS[(G * 8 + cg) * 8 + g], nzmap(__float_as_uint(s.x)), __float_as_uint(s.y), __float_as_uint(s.z), __float_as_uint(s.w));
    const int xo = (32 * (cg & 3) + t) * 2048 + (cg >> 2) * 512 + xg_off(G, g);
#pragma unroll
    for (int j = 0; j < 8; ++j) {
      str2((uint2*)SCR->XG[1] + (xo + j * 8192), nzmap(prmt(res[j][0], res[j][1], 0x5410)), prmt(res[j][0], res[j][1], 0x7632));
    }
    __syncwarp();
    mbar_arrive1(B_ED + 8 * e);
  } else {
    const uint32_t stg = so + w * 2048;
    const int row = (lane & 7) + 8 * ((lane >> 3) & 1);
    bar_sync(NB_WG + e, 128);
#pragma unroll
    for (int j = 0; j < 8; j += 2)
      stsm4(stg + row * 128 + (((j + (lane >> 4)) ^ (row & 7)) * 16), res[j][0], res[j][1], res[j + 1][0], res[j + 1][1]);
    __syncwarp();
#pragma unroll
    for (int k = 0; k < 4; ++k) {
      const int r = 4 * k + (lane >> 3);
      const uint4 v = lds4(stg + r * 128 + (((lane & 7) ^ (r & 7)) * 16));
      stw4(P.out + ((16 * G + 2 * (lane >> 3)) * 512 + 64 * cg + 8 * (lane & 7)) + ((k & 1) * 8 + (k >> 1)) * 512, v.x, v.y, v.z, v.w);
    }
  }
  PROF(11 + 12 * layer);
}

DEV void aux_prologue(const Params& P, int c, int wa, int lane, uint4 (&s0)[2][2]) {
  const int i = c >> 3, cg = c & 7, g = lane >> 2, t = lane & 3, G = stat_group(c);
  uint4 wv[8];
  {
    uint32_t w[16][2];
    const uint16_t* row = P.x0 + ((16 * G + 2 * g) * 512 + 128 * wa + 8 * t);
#pragma unroll
    for (int z = 0; z < 8; ++z) {
      const uint4 v = ldnc4(row + (z & 1) * 512 + (z >> 1) * 32);
      const int o = 4 * (z >> 1);
      w[o][z & 1] = v.x; w[o + 1][z & 1] = v.y; w[o + 2][z & 1] = v.z; w[o + 3][z & 1] = v.w;
    }
    PROF(34);
    bar_sync(0, NTHR);
    PROFD(35, w[0][0]);
    PROFD(36, w[15][1]);
    uint2* xo = (uint2*)SCR->XG[0] + ((64 * (wa & 1) + 4 * t) * 2048 + (wa >> 1) * 512 + xg_off(G, g));
#pragma unroll
    for (int n = 0; n < 16; ++n) str2(xo + (16 * (n >> 2) + (n & 3)) * 2048, nzmap(prmt(w[n][0], w[n][1], 0x5410)), prmt(w[n][0], w[n][1], 0x7632));
    const float4 s = gram(w, g);
    if (t == (g >> 1)) sts4f(SM_MISC + (wa * 8 + g) * 16, s.x, s.y, s.z, s.w);
    bar_arrive(NB_P0, 192);
  }
  PROF(2);
  if (wa < 3) {
#pragma unroll
    for (int k = 0; k < 8; ++k) wv[k] = ldnc4(P.wqkv + ((32 * i + (lane >> 3)) * 1536 + wa * 512 + 64 * cg + 8 * (lane & 7)) + 4 * k * 1536);
  } else if (lane == 0) {
    asm volatile("cp.async.bulk.prefetch.L2.global [%0],4096;" :: "l"(P.wo + (size_t)c * 2048) : "memory");
  }
  if (wa < 3) {
    float cs[8];
#pragma unroll
    for (int k = 0; k < 8; ++k) cs[k] = 0.f;
#pragma unroll
    for (int k = 0; k < 8; ++k) {
      cs[0] += bflo(wv[k].x); cs[1] += bfhi(wv[k].x); cs[2] += bflo(wv[k].y); cs[3] += bfhi(wv[k].y);
      cs[4] += bflo(wv[k].z); cs[5] += bfhi(wv[k].z); cs[6] += bflo(wv[k].w); cs[7] += bfhi(wv[k].w);
    }
#pragma unroll
    for (int k = 0; k < 8; ++k) { cs[k] += __shfl_xor_sync(0xffffffffu, cs[k], 8); cs[k] += __shfl_xor_sync(0xffffffffu, cs[k], 16); }
    if (lane < 16) {
      const int hf = lane >> 3;
      str4(&SCR->CS[(i * 1536 + wa * 512 + 64 * cg + 8 * (lane & 7)) / 4 + hf],
           __float_as_uint(hf ? cs[4] : cs[0]), __float_as_uint(hf ? cs[5] : cs[1]), __float_as_uint(hf ? cs[6] : cs[2]), __float_as_uint(hf ? cs[7] : cs[3]));
    }
  }
  bar_arrive(NB_P0 + 1, 160);
  sload(P, c, 32 * wa + lane, 0, s0);
}

DEV void stat_part(const Params& P, int c, int wa, int lane, int layer, int h, float (&v)[2]) {
  lane = opq(lane);
  const int e = wa >> 1;
  uint32_t x[4][4];
  mbar_wait(B_A + 16 * e, h); mbar_wait(B_A + 16 * e + 8, h);
#pragma unroll
  for (int k = 0; k < 4; ++k) ldsm4t(x[k], SM_A + e * A_E + (128 * (wa & 1) + lane) * 128 + (((c ^ lane) & 7) * 16) + k * 4096);
  float s[4] = {0.f, 0.f, 0.f, 0.f};
#pragma unroll
  for (int k = 0; k < 16; ++k) { const float a = bflo(x[k >> 2][k & 3]), b = bfhi(x[k >> 2][k & 3]); s[0] += a; s[1] += a * a; s[2] += b; s[3] += b * b; }
  s[0] += s[2]; s[1] += s[3];
  if (RARE(s[1] != s[1])) {
    const uint16_t* q = (const uint16_t*)(SCR->XF[layer] + ((32 * e + 2 * (c >> 3) + h) * 2048 + (wa & 1) * 1024)) + (lane >> 2);
    s[0] = s[1] = 0.f;
#pragma unroll 1
    for (int k = 0; k < 32; ++k) {
      const int r = 2 * (lane & 3) + (k & 1);
      const float a = ldnan(q + ((k >> 1) * 8 + r) * 64 + ((c ^ r) & 7) * 8);
      s[0] += a; s[1] += a * a;
    }
  }
  v[0] += s[0]; v[1] += s[1];
  __syncwarp();
}
DEV void stat_finish(const Params& P, int c, int wa, int lane, int layer, float (&v)[2]) {
  lane = opq(lane);
  const bool b = lane & 1;
  const float s = (b ? v[1] : v[0]) + __shfl_xor_sync(0xffffffffu, b ? v[0] : v[1], 1);
  str1((uint32_t*)SCR->ST[layer] + ((128 * (wa >> 1) + c) * 64 + (wa & 1) * 32 + lane), nzmap(__float_as_uint(s)));
  const uint4* sp = SCR->ST[layer] + ((128 * (wa >> 1) + (c & ~7) + 4 * (wa & 1) + (lane >> 3)) * 16 + (lane & 7));
  uint4 x, y;
  for (int it = 0;; ++it) {
    x = ldr4(sp); y = ldr4(sp + 8);
    if (__all_sync(0xffffffffu, min(min(min(x.x, x.y), min(x.z, x.w)), min(min(y.x, y.y), min(y.z, y.w))) != 0u)) break;
    spin_guard(it);
  }
  const uint32_t q = ln_sums((__uint_as_float(x.x) + __uint_as_float(x.z)) + (__uint_as_float(y.x) + __uint_as_float(y.z)),
                             (__uint_as_float(x.y) + __uint_as_float(x.w)) + (__uint_as_float(y.y) + __uint_as_float(y.w)));
  sts2f(SM_STAT + (16 * wa + (lane >> 4) * 8 + (lane & 7)) * 16 + (lane & 8), bflo(q), rcp(bfhi(q)));
  __syncwarp();
  mbar_arrive1(B_ST + 4 * (wa & 2));
}

DEV void nan_source(uint32_t a, int lane) {
#pragma unroll
  for (int k = 0; k < 4; ++k) sts4(a + k * 512 + lane * 16, FILL, FILL, FILL, FILL);
  fence_async_smem();
  __syncwarp();
}
DEV void load_a(const Params& P, int J, int e, int layer, int h) {
  const uint4* src = SCR->XF[layer] + (2 * J + h) * 2048;
  const uint32_t dst = SM_A + e * A_E, b = B_A + 16 * e;
  mbar_expect1(b, 8192); bulk(dst, src, 8192, b);
  mbar_expect1(b + 8, 24576); bulk(dst + 8192, src + 512, 24576, b + 8);
}
__global__ void __launch_bounds__(NTHR, 1)
fused_kernel(const __grid_constant__ Params P, const __grid_constant__ CUtensorMap mapW, const __grid_constant__ CUtensorMap mapWo,
             const __grid_constant__ CUtensorMap mapX) {
  extern __shared__ __align__(1024) uint8_t smem_raw[];
  const int warp = __shfl_sync(0xffffffffu, threadIdx.x >> 5, 0), lane = threadIdx.x & 31;
  uint32_t smid; asm volatile("mov.u32 %0,%%smid;" : "=r"(smid));
  const uint32_t* pw = (const uint32_t*)&P + threadIdx.y;
  const int role = P.role[smid + threadIdx.y] + (pw[0] & pw[12]);
  const int c = __shfl_sync(0xffffffffu, pw[1] ? role : blockIdx.x, 0);
  if (c >= 128) {
#pragma unroll 1
    for (int k = (c - 128) * NTHR + threadIdx.x; k < 131072; k += P.spare * NTHR) str4(SCR->XG[1] + k, 0, 0, 0, 0);
    __threadfence();
    __syncthreads();
    if (warp == 0) { cnt_wait(SCR->C + 1, lane); cnt_add1(SCR->C + 6); }
    __syncthreads();
#pragma unroll 1
    for (int k = (c - 128) * NTHR + threadIdx.x; k < 131072; k += P.spare * NTHR) str4(SCR->XG[0] + k, 0, 0, 0, 0);
    return;
  }
#define DONE() do {} while (0)
  const int cg = c & 7;
  if (warp < 8) {
    PROF(46);
    kgen(P, c, warp, lane);
    bar_sync(0, 256);
    PROF(1);
#pragma unroll 1
    for (int layer = 0; layer < 2; ++layer) {
#pragma unroll 1
      for (int rho = 0; rho < 2; ++rho) {
        const int wz = warp + ((rho + layer) & P.zero);
        conv_round(wz >> 2, rho, wz & 3, lane_id());
        PROF(6 + rho + 12 * layer);
      }
      const int z = layer & P.zero;
      attn_phase(P, c + z, (warp + z) >> 2, (warp + z) & 3, lane_id(), layer);
    }
    DONE();
  } else if (warp < 12) {
    asm volatile("setmaxnreg.dec.sync.aligned.u32 %0;" :: "n"(REG_AUX));
    uint4 x[2][2][2], s[2][2];
    aux_prologue(P, c, warp - 8, lane, s);
    PROF(1);
    const int c0 = c;
#pragma unroll 1
    for (int layer = 0;; ++layer) {
      const int c = c0 + (layer & P.zero), cg = c & 7, wa = warp - 8 + (layer & P.zero);
#define lane lane_id()
#define j (32 * wa + lane_id())
      {
        const uint32_t za = region(wa) + lane * 16 - 512;
        sts4(za + R_U, 0, 0, 0, 0); sts4(za + R_X5, 0, 0, 0, 0); sts4(za + R_X3, 0, 0, 0, 0);
      }
      if (lane == 0) sts4(region(wa) + R_BE, 0, 0, 0, 0);
      uint32_t u[4][4];
      uload(P, c, j, layer, x, s);
      uprep(j, 1, x[1], s[1], u);
      uprep(j, 0, x[0], s[0], u);
      fence_async_smem();
      bar_arrive(NB_U, NBARU);
      bar_sync(NB_H, 192);
      PROF(5 + 12 * layer);
      box_full(j, u);
      PROF(3 + 12 * layer);
      mbar_wait(B_Z, 0);
      conv_out(c, j, 0, x, u[0], SCR->XF[layer]);
      PROF(32);
      conv_out(c, j, 1, x, u[1], SCR->XF[layer]);
      PROF(6 + 12 * layer);
      conv_out(c, j, 2, x, u[2], SCR->XF[layer]);
      PROF(33);
      conv_out(c, j, 3, x, u[3], SCR->XF[layer]);
      PROF(7 + 12 * layer);
      float v[2];
      zero(v);
      stat_part(P, c, wa, lane, layer, 0, v);
      mbar_arrive1(B_AE + 4 * (wa & 2));
      if (layer == 0 && wa < 3) {
        const int ln = opq(lane);
        float a = 0.f, b = 0.f;
#pragma unroll
        for (int k = 0; k < 16; ++k) { const uint2 q = ldr2((const float*)SCR->CS + (wa * 512 + 64 * cg + 2 * ln) + k * 1536); a += __uint_as_float(q.x); b += __uint_as_float(q.y); }
        sts2f(SM_CS + wa * 256 + ln * 8, a, b);
        __syncwarp();
        mbar_arrive1(B_CS);
      }
      stat_part(P, c, wa, lane, layer, 1, v);
      PROF(9 + 12 * layer);
      stat_finish(P, c, wa, lane, layer, v);
      PROF(8 + 12 * layer);
      if (layer) break;
      sload(P, c, j, 1, s);
#undef lane
#undef j
    }
    DONE();
  } else {
    asm volatile("setmaxnreg.dec.sync.aligned.u32 %0;" :: "n"(REG_PROD));
    if (s2u(smem_raw) != SB) __trap();
#pragma unroll 1
    for (int n = warp - 12; n < 37; n += 4)
      asm volatile("{.reg .pred p; elect.sync _|p,0xffffffff; @p mbarrier.init.shared::cta.b64 [%0],%1;}"
                   :: "r"(SM_BAR + n * 8), "r"(n > 14 ? 1 : (int)(0x322866444444444ull >> (4 * n)) & 15) : "memory");
    fence_async_smem();
    bar_sync(0, NTHR);
    PROF(1);
    if (warp == 12) {
      if (lane == 0) {
        asm volatile("prefetch.tensormap [%0];" :: "l"(&mapW) : "memory");
        asm volatile("prefetch.tensormap [%0];" :: "l"(&mapWo) : "memory");
        asm volatile("prefetch.tensormap [%0];" :: "l"(&mapX) : "memory");
      }
      __syncwarp();
#pragma unroll 1
      for (int layer = 0; layer < 2; ++layer) {
        bar_sync(NB_U, NBARU);
        if (layer == 1 && c < 4 && ((0x47 >> lane) & 1)) str1(SCR->C + c * 32 + lane, 0);
        mbar_wait(B_Z, 0);
        mbar_expect1(B_WF, 4 * 24576);
#pragma unroll
        for (int k = 0; k < 4; ++k) tma3(slot(wslot(k)), &mapW, 64 * cg, 64 * k, 0, B_WF);
        mbar_wait(B_WF, layer);
        mbar_expect1(B_W4, 2 * 24576);
#pragma unroll
        for (int k = 4; k < 6; ++k) tma3(slot(wslot(k)), &mapW, 64 * cg, 64 * k, 0, B_W4);
        bar_sync(NB_AUX, 64);
#pragma unroll 1
        for (int k = 0; k < 2; ++k) {
          mbar_expect1(B_W6 + 8 * k, 24576);
          mbar_wait(B_F + 8 * k, layer);
          tma3(slot(3 * k), &mapW, 64 * cg, 384 + 64 * k, 0, B_W6 + 8 * k);
        }
        mbar_expect1(B_WO, 65536);
        mbar_wait(B_AE + 8, layer);
        nan_source(slot(12), lane);
        uint4* fp = layer ? SCR->O + c * 512 : SCR->XF[1] + c * 512;
#pragma unroll 1
        for (int r = 7; r >= 0; --r) {
          __nanosleep(KWOP);
          if (r >= 4) {
            bulk_store(fp + (r & 3) * 128, slot(12), 2048); bulk_store(fp + 65536 + (r & 3) * 128, slot(12), 2048);
            if (layer == 0) bulk_store(SCR->H[1] + ((c + 8) * 256 + (r & 2) * 16384 + (r & 1) * 128), slot(12), 2048);
          }
          if (r == KFR) { bulk_wait(); __threadfence(); mbar_arrive1(B_N); PROF(9 + 12 * layer); }
          if (r == 1) mbar_wait(B_F + 16, layer);
          tma4(SM_WO + r * 8192, &mapWo, 64 * cg, 0, r >> 1, 32 * (r & 1), B_WO);
        }
        PROF(8 + 12 * layer);
      }
      DONE();
    } else if (warp == 13) {
      const int G = stat_group(c);
#pragma unroll 1
      for (int layer = 0; layer < 2; ++layer) {
        float z[4];
        if (layer == 0) {
          bar_sync(NB_P0, 192);
          const float4 a = lds4f(SM_MISC + lane * 16);
          z[0] = a.x; z[1] = a.y; z[2] = a.z; z[3] = a.w;
        } else {
          mbar_wait(B_ED + 2 * (c & 4), 0);
          uint4* ps = &SCR->PS[G * 64 + lane];
          uint4 a, b;
          for (int it = 0;; ++it) {
            a = ldr4(ps); b = ldr4(ps + 32);
            if (__all_sync(0xffffffffu, min(a.x, b.x) != 0u)) break;
            spin_guard(it);
          }
          z[0] = __uint_as_float(a.x) + __uint_as_float(b.x); z[1] = __uint_as_float(a.y) + __uint_as_float(b.y);
          z[2] = __uint_as_float(a.z) + __uint_as_float(b.z); z[3] = __uint_as_float(a.w) + __uint_as_float(b.w);
        }
#pragma unroll
        for (int o = 8; o < 32; o <<= 1)
#pragma unroll
          for (int k = 0; k < 4; ++k) z[k] += __shfl_xor_sync(0xffffffffu, z[k], o);
        const uint32_t w0 = ln_sums(z[0], z[1]), w1 = ln_sums(z[2], z[3]);
        const uint32_t r = nzmap(pack2(rcp(bfhi(w0)), rcp(bfhi(w1)))), m = prmt(w0, w1, 0x5410);
        uint2* so = (uint2*)&SCR->SR[layer][lane >> 3][sr_off(G, lane)] + (lane & 1);
        str2(so, r, m); str2(so + 4 * 1024, r, m);
        PROF(4 + 12 * layer);
        bar_sync(NB_H, 192);
        box_help(0, lane);
        box_help(2, lane);
        PROF(6 + 12 * layer);
      }
      DONE();
    } else if (warp == 14) {
#pragma unroll 1
      for (int layer = 0; layer < 2; ++layer) {
        if (layer) { mbar_wait(B_N, 0); mbar_wait(B_ED, 0); mbar_wait(B_ED + 8, 0); } else bar_sync(NB_P0, 192);
        cnt_add1(SCR->C + (c >> 5) * 32 + 3 * layer);
        mbar_expect1(B_E, 16384);
        PROF(4 + 12 * layer);
        cnt_wait(SCR->C + 3 * layer, lane);
        mbar_arrive1(B_U);
        bulk(SM_X, SCR->XG[layer] + c * 1024, 16384, B_E);
        PROF(5 + 12 * layer);
        if (layer == 0) {
          nan_source(slot(12), lane);
          mbar_wait(B_E, 0);
#pragma unroll 1
          for (int k = 0; k < 8; ++k) tma2_store(&mapX, slot(12), 128 * c, 8 * k);
#pragma unroll 1
          for (int k = 0; k < 4; ++k) bulk_store(SCR->H[0] + ((c + 8) * 256 + (k >> 1) * 32768 + (k & 1) * 128), slot(12), 2048);
#pragma unroll 1
          for (int k = 0; k < 8; ++k) bulk_store(SCR->O + (c * 512 + (k >> 2) * 65536 + (k & 3) * 128), slot(12), 2048);
          bulk_wait();
          mbar_arrive1(B_Z);
          PROF(24);
          __threadfence();
          mbar_arrive1(B_Z + 8);
          PROF(11);
        }
        mbar_wait(B_RD, layer);
        cnt_wait(SCR->C + 3 * layer + 1, lane);
        load_a(P, c >> 3, 0, layer, 0);
        PROF(6 + 12 * layer);
        mbar_wait(B_RD + 8, layer);
        load_a(P, 16 + (c >> 3), 1, layer, 0);
        cnt_wait(SCR->C + 3 * layer + 2, lane);
        PROF(7 + 12 * layer);
        mbar_wait(B_AE, layer);
        load_a(P, c >> 3, 0, layer, 1);
        bar_arrive(NB_AUX, 64);
        PROF(8 + 12 * layer);
        mbar_wait(B_AE + 8, layer);
        load_a(P, 16 + (c >> 3), 1, layer, 1);
        if (layer == 0)
          for (int it = 0; ldr1(SCR->C + 6) < P.spare; ++it) spin_guard(it);
        mbar_wait(B_QE, layer);
#pragma unroll 1
        for (int e = 0; e < 2; ++e) {
          const int J = 16 * e + (c >> 3);
          mbar_wait(B_AT + 8 * e, layer);
          uint32_t todo = 0x01010101u;
#pragma unroll 1
          for (int it = 0; todo; ++it) {
            uint32_t m = __ballot_sync(0xffffffffu, ldr1(SCR->OF[layer] + J * 32 + lane) != 0u);
            m &= m >> 4; m &= m >> 2; m &= m >> 1; m &= todo;
            todo ^= m;
#pragma unroll 1
            for (; m; m &= m - 1) {
              const int j = __ffs(m) - 1;
              mbar_expect1(B_O + 32 * e + j, 16384);
              bulk(SM_O + e * O_E + 2048 * j, SCR->O + (J * 4096 + j * 128), 16384, B_O + 32 * e + j);
            }
            spin_guard(it);
          }
          PROF(9 + e + 12 * layer);
        }
      }
      DONE();
    }
    if (warp == 15) {
      const int G = stat_group(c);
      str4(&SCR->ST[0][(lane >> 4) * 2048 + c * 16 + (lane & 15)], 0, 0, 0, 0); str4(&SCR->ST[1][(lane >> 4) * 2048 + c * 16 + (lane & 15)], 0, 0, 0, 0);
      if (lane < 4) str4(SCR->OF[lane >> 1] + ((lane & 1) * 512 + c * 4), 0, 0, 0, 0);
      str4(&SCR->PS[G * 64 + lane], 0, 0, 0, 0); str4(&SCR->PS[G * 64 + 32 + lane], 0, 0, 0, 0);
      str4(&SCR->SR[1][lane >> 2][sr_off(G, 2 * lane)], 0, 0, 0, 0);
      if (c < 4 && lane < 3) str1(SCR->C + c * 32 + 3 + lane, 0);
      bar_sync(NB_P0 + 1, 160);
      __threadfence();
#pragma unroll 1
      for (int layer = 0; layer < 2; ++layer) {
        PROF(4 + 12 * layer);
        bar_sync(NB_H, 192);
        box_help(1, lane);
        box_help(3, lane);
        if (layer) str4(&SCR->SR[0][lane >> 2][sr_off(G, 2 * lane)], 0, 0, 0, 0);
        mbar_wait(B_Z + 8, 0);
        mbar_wait(B_RD, layer);
        cnt_add1(SCR->C + (c >> 5) * 32 + 3 * layer + 1);
        mbar_wait(B_RD + 8, layer);
        cnt_add1(SCR->C + (c >> 5) * 32 + 3 * layer + 2);
        if (P.spare == 0) {
#pragma unroll 1
          for (int k = 0; k < 32; ++k) str4(SCR->XG[layer] + (c * 1024 + k * 32 + lane), 0, 0, 0, 0);
        }
      }
    }
  }
}

typedef CUresult (*EncodeFn)(CUtensorMap*, CUtensorMapDataType, cuuint32_t, void*, const cuuint64_t*, const cuuint64_t*,
                             const cuuint32_t*, const cuuint32_t*, CUtensorMapInterleave, CUtensorMapSwizzle,
                             CUtensorMapL2promotion, CUtensorMapFloatOOBfill);

static int place_roles(uint8_t* role) {
  int dev = 0, nsm = 0;
  cudaGetDevice(&dev);
  cudaDeviceGetAttribute(&nsm, cudaDevAttrMultiProcessorCount, dev);
  if (nsm <= 128 || nsm > 144 || (nsm & 1)) return 0;
  cudaFuncSetAttribute(fused_kernel, cudaFuncAttributeNonPortableClusterSizeAllowed, 1);
  int occ[9] = {0};
  for (int k = 2; k <= 8; ++k) {
    cudaLaunchConfig_t cfg = {};
    cudaLaunchAttribute at[1];
    at[0].id = cudaLaunchAttributeClusterDimension;
    at[0].val.clusterDim.x = 2 * k; at[0].val.clusterDim.y = 1; at[0].val.clusterDim.z = 1;
    cfg.gridDim = dim3(2 * k); cfg.blockDim = dim3(NTHR); cfg.dynamicSmemBytes = SM_TOTAL; cfg.attrs = at; cfg.numAttrs = 1;
    if (cudaOccupancyMaxActiveClusters(&occ[k], fused_kernel, &cfg) != cudaSuccess) { cudaGetLastError(); occ[k] = 0; }
  }
  int n[10];
  n[7] = occ[8]; n[6] = occ[7]; n[5] = occ[6] - 0; n[4] = occ[5];
  n[3] = occ[4] - n[7]; n[1] = occ[2] - n[3] - n[5] - n[7]; n[0] = n[2] = n[1];
  n[8] = occ[3] - n[2] - n[5];
  const int ntpc = nsm / 2;
  int sum = 0;
  bool ok = n[0] > 0 && n[0] <= 8;
  for (int r = 0; r < 9; ++r) { ok = ok && n[r] >= 0 && (r == 0 || n[r] <= n[r - 1]); sum += n[r]; }
  if (!ok || sum > ntpc) { for (int r = 0; r < 9; ++r) n[r] = r < 8 ? 8 : 0; sum = 64; }
  int tp[8][9], cnt[8] = {0}, pool[72], np = 0, id = 0;
  for (int r = 0; r < 9; ++r)
    for (int g = n[0] - n[r]; g < n[0]; ++g) tp[g][cnt[g]++] = id++;
  for (; id < ntpc; ++id) pool[np++] = id;
  int order[72], no = 0;
  for (int g = 0; g < n[0]; ++g) {
    const int full = cnt[g] / 4 * 4;
    for (int k = 0; k < cnt[g]; ++k) { if (k < full) order[no++] = tp[g][k]; else pool[np++] = tp[g][k]; }
  }
  for (int k = 0; k < np; ++k) order[no++] = pool[k];
  for (int k = 0; k < ntpc; ++k) { role[2 * order[k]] = 2 * k; role[2 * order[k] + 1] = 2 * k + 1; }
  return nsm;
}

extern "C" void kernel_launch(void* const* d_in, const int* in_sizes, int n_in, void* d_out, int out_size) {
  (void)in_sizes; (void)n_in; (void)out_size;
  static EncodeFn enc = nullptr;
  static uint8_t role[144];
  static int nsm = 0;
  static Scratch* scratch = nullptr;
  if (!enc) {
    void* fn = nullptr;
    cudaDriverEntryPointQueryResult qr;
    cudaGetDriverEntryPoint("cuTensorMapEncodeTiled", &fn, cudaEnableDefault, &qr);
    enc = (EncodeFn)fn;
    cudaFuncSetAttribute(fused_kernel, cudaFuncAttributeMaxDynamicSharedMemorySize, SM_TOTAL);
    nsm = place_roles(role);
    cudaGetSymbolAddress((void**)&scratch, g_S);
  }
  CUtensorMap mW, mWo, mX;
  {
    cuuint64_t dim[3] = {512, 512, 3}, str[2] = {3072, 1024};
    cuuint32_t box[3] = {64, 64, 3}, es[3] = {1, 1, 1};
    enc(&mW, CU_TENSOR_MAP_DATA_TYPE_BFLOAT16, 3, d_in[10], dim, str, box, es, CU_TENSOR_MAP_INTERLEAVE_NONE,
        CU_TENSOR_MAP_SWIZZLE_128B, CU_TENSOR_MAP_L2_PROMOTION_NONE, CU_TENSOR_MAP_FLOAT_OOB_FILL_NONE);
  }
  {
    cuuint64_t dim[4] = {512, 2, 4, 64}, str[3] = {1024, 2048, 8192};
    cuuint32_t box[4] = {64, 2, 1, 32}, es[4] = {1, 1, 1, 1};
    enc(&mWo, CU_TENSOR_MAP_DATA_TYPE_BFLOAT16, 4, d_in[11], dim, str, box, es, CU_TENSOR_MAP_INTERLEAVE_NONE,
        CU_TENSOR_MAP_SWIZZLE_128B, CU_TENSOR_MAP_L2_PROMOTION_NONE, CU_TENSOR_MAP_FLOAT_OOB_FILL_NONE);
  }
  {
    cuuint64_t dim[2] = {16384, 64}, str[1] = {32768};
    cuuint32_t box[2] = {128, 8}, es[2] = {1, 1};
    enc(&mX, CU_TENSOR_MAP_DATA_TYPE_BFLOAT16, 2, scratch->XF[0], dim, str, box, es, CU_TENSOR_MAP_INTERLEAVE_NONE,
        CU_TENSOR_MAP_SWIZZLE_NONE, CU_TENSOR_MAP_L2_PROMOTION_NONE, CU_TENSOR_MAP_FLOAT_OOB_FILL_NONE);
  }
  Params P;
  P.x0 = (const uint16_t*)d_in[0]; P.Are = (const uint16_t*)d_in[1]; P.Aim = (const uint16_t*)d_in[2];
  P.Bre = (const uint16_t*)d_in[3]; P.Bim = (const uint16_t*)d_in[4]; P.Cre = (const uint16_t*)d_in[5];
  P.Cim = (const uint16_t*)d_in[6]; P.logdt = (const uint16_t*)d_in[7]; P.dskip = (const uint16_t*)d_in[8];
  P.wqkv = (const uint16_t*)d_in[10]; P.wo = (const uint16_t*)d_in[11]; P.out = (uint16_t*)d_out;
  for (int k = 0; k < 144; ++k) P.role[k] = role[k];
  P.zero = 0;
  P.mid = (char*)scratch->C;
  P.spare = nsm > 0 ? nsm - 128 : 0;
  fused_kernel<<<nsm > 0 ? nsm : 128, NTHR, SM_TOTAL, cudaStreamPerThread>>>(P, mW, mWo, mX);
}
```

```cpp
#include <cuda_runtime.h>
#include <cuda_bf16.h>
#include <cuda.h>
#include <stdint.h>
#include <stddef.h>

#define DEV __device__ __forceinline__
#define RARE(x) __builtin_expect(!!(x), 0)

#define KWOP 30
#define KFR 3
#define KBL 2
#define KCS 1
#define KPFIRST 100
#define KFILL 2
#define KPAUSE 2
#define KDR 0
constexpr int NTHR = 512;
#define KRM 192
#define KRA 96
#define KRP 32
constexpr int REG_MAIN = KRM, REG_AUX = KRA, REG_PROD = KRP;
constexpr int NBARU = 384;
constexpr int SPIN_LIMIT = 1 << 22;

constexpr uint32_t SB = 1024;
__host__ __device__ constexpr uint32_t slot(int n) { return SB + n * 8192; }
__host__ __device__ constexpr int wslot(int k) { return k < 2 ? 3 * k : k < 4 ? 3 * k + 6 : k < 6 ? 21 - 3 * k : 3 * k - 18; }
constexpr uint32_t SM_A = slot(22), A_E = 0u - 32768;
constexpr uint32_t SM_O = slot(18), O_E = 0u - 147456;
constexpr uint32_t SM_WO = slot(10), SM_X = slot(8), SM_KV = slot(9);
constexpr uint32_t SM_TAP  = slot(26);
constexpr int TAP_SZ = 3440;
constexpr uint32_t SM_STAT = SM_TAP + 4 * TAP_SZ;
constexpr uint32_t SM_CS   = SM_STAT + 1024;
constexpr uint32_t SM_MISC = SM_CS + 768;
constexpr uint32_t SM_BAR  = SM_MISC + 528;
constexpr int SM_TOTAL = SM_BAR + 304 - SB;
static_assert(SM_TOTAL <= 232448, "");
constexpr int R_SZ = 16384, R_U = 512, R_X5 = 5120, R_X3 = 8704, R_BO = 11776, R_BE = 13824;
constexpr int X_5 = 576, X_3 = 648, T_E = 2 * 720, T_O = 1600 + 2 * 721, T_C = 3390, T_K = 3424;
constexpr uint32_t B_RD = SM_BAR, B_ED = SM_BAR + 16, B_F = SM_BAR + 32, B_AT = SM_BAR + 56;
constexpr uint32_t B_AE = SM_BAR + 72, B_QE = SM_BAR + 88, B_ST = SM_BAR + 96, B_CS = SM_BAR + 112;
constexpr uint32_t B_WO = SM_BAR + 120, B_W6 = SM_BAR + 128, B_U = SM_BAR + 144, B_E = SM_BAR + 152, B_A = SM_BAR + 160, B_O = SM_BAR + 192,
                   B_Z = SM_BAR + 256, B_WF = SM_BAR + 272, B_W4 = SM_BAR + 280, B_N = SM_BAR + 288, B_V = SM_BAR + 296;
constexpr int NB_U = 1, NB_B = 2, NB_K = 8, NB_Y = 6, NB_WG = 8, NB_T = 10, NB_AUX = 12, NB_P0 = 13, NB_H = 15;

struct Scratch {
  uint4    XG[2][128 * 1024];
  uint4    O[32 * 8 * 512];
  uint32_t C[8 * 32];
  uint32_t OF[2][32 * 32];
  uint4    CS[16 * 1536 / 4];
  uint4    PS[128 * 64];
  uint4    ST[2][32 * 128];
  uint4    SR[2][8][512];
  uint4    XF[2][32 * 512 * 8];
  uint4    H[2][33 * 8 * 256];
};
__device__ __align__(1024) Scratch g_S;
#define SCR ((Scratch*)(P.mid - offsetof(Scratch, C)))
#define PROFD(slot, v) do {} while (0)
#define PROF(slot) do {} while (0)

DEV uint32_t s2u(const void* p) { return (uint32_t)__cvta_generic_to_shared(p); }
template <class T> DEV T opq(T x) { asm volatile("" : "+r"(x)); return x; }
DEV int lane_id() { int l; asm volatile("mov.u32 %0,%%laneid;" : "=r"(l)); return l; }
DEV uint32_t pack2(float lo, float hi) { uint32_t d; asm("cvt.rn.bf16x2.f32 %0,%1,%2;" : "=r"(d) : "f"(hi), "f"(lo)); return d; }
DEV float bflo(uint32_t v) { return __uint_as_float(v << 16); }
DEV float bfhi(uint32_t v) { return __uint_as_float(v & 0xFFFF0000u); }
DEV float bfr(float x) { return bflo(pack2(x, 0.f)); }
DEV uint32_t hadd2(uint32_t a, uint32_t b) { uint32_t d; asm("add.rn.bf16x2 %0,%1,%2;" : "=r"(d) : "r"(a), "r"(b)); return d; }
DEV uint32_t hsub2(uint32_t a, uint32_t b) { uint32_t d; asm("sub.rn.bf16x2 %0,%1,%2;" : "=r"(d) : "r"(a), "r"(b)); return d; }
DEV uint32_t hmul2(uint32_t a, uint32_t b) { uint32_t d; asm("mul.rn.bf16x2 %0,%1,%2;" : "=r"(d) : "r"(a), "r"(b)); return d; }
DEV uint32_t hfma2(uint32_t a, uint32_t b, uint32_t c) { uint32_t d; asm("fma.rn.bf16x2 %0,%1,%2,%3;" : "=r"(d) : "r"(a), "r"(b), "r"(c)); return d; }
DEV uint32_t hmax2(uint32_t a, uint32_t b) { uint32_t d; asm("max.bf16x2 %0,%1,%2;" : "=r"(d) : "r"(a), "r"(b)); return d; }
DEV uint32_t prmt(uint32_t a, uint32_t b, uint32_t s) { uint32_t d; asm("prmt.b32 %0,%1,%2,%3;" : "=r"(d) : "r"(a), "r"(b), "r"(s)); return d; }
DEV uint32_t nzmap(uint32_t v) { return v == 0u ? 0x80000000u : v; }
DEV float rcp(float x) { float y; asm("rcp.approx.ftz.f32 %0,%1;" : "=f"(y) : "f"(x)); return y; }
DEV float sqrt_(float x) { float y; asm("sqrt.approx.ftz.f32 %0,%1;" : "=f"(y) : "f"(x)); return y; }
DEV float ex2(float x) { float y; asm("ex2.approx.ftz.f32 %0,%1;" : "=f"(y) : "f"(x)); return y; }

DEV uint4 ldr4(const void* p) { uint4 v; asm volatile("ld.relaxed.gpu.global.v4.u32 {%0,%1,%2,%3},[%4];" : "=r"(v.x), "=r"(v.y), "=r"(v.z), "=r"(v.w) : "l"(p) : "memory"); return v; }
DEV void ldr4_if(uint4& v, const void* p, bool c) {
  asm volatile("{.reg .pred q; setp.ne.u32 q,%5,0; @q ld.relaxed.gpu.global.v4.u32 {%0,%1,%2,%3},[%4];}"
    : "+r"(v.x), "+r"(v.y), "+r"(v.z), "+r"(v.w) : "l"(p), "r"((uint32_t)c) : "memory");
}
DEV uint2 ldr2(const void* p) { uint2 v; asm volatile("ld.relaxed.gpu.global.v2.u32 {%0,%1},[%2];" : "=r"(v.x), "=r"(v.y) : "l"(p) : "memory"); return v; }
DEV void ldr2_if(uint2& v, const void* p, bool c) {
  asm volatile("{.reg .pred q; setp.ne.u32 q,%3,0; @q ld.relaxed.gpu.global.v2.u32 {%0,%1},[%2];}" : "+r"(v.x), "+r"(v.y) : "l"(p), "r"((uint32_t)c) : "memory");
}
DEV uint32_t ldr1(const void* p) { uint32_t v; asm volatile("ld.relaxed.gpu.global.u32 %0,[%1];" : "=r"(v) : "l"(p) : "memory"); return v; }
DEV float ldnan(const uint16_t* p) {
  uint32_t v = 0xFFFFu;
#pragma unroll 1
  for (int it = 0; it < SPIN_LIMIT && v == 0xFFFFu; ++it) asm volatile("ld.relaxed.gpu.global.u16 %0,[%1];" : "=r"(v) : "l"(p) : "memory");
  return __uint_as_float(v << 16);
}
DEV uint4 ldw4(const void* p) { uint4 v; asm volatile("ld.global.v4.u32 {%0,%1,%2,%3},[%4];" : "=r"(v.x), "=r"(v.y), "=r"(v.z), "=r"(v.w) : "l"(p) : "memory"); return v; }
DEV uint2 ldw2(const void* p) { uint2 v; asm volatile("ld.global.v2.u32 {%0,%1},[%2];" : "=r"(v.x), "=r"(v.y) : "l"(p) : "memory"); return v; }
DEV uint32_t ldw1(const void* p) { uint32_t v; asm volatile("ld.global.u32 %0,[%1];" : "=r"(v) : "l"(p) : "memory"); return v; }
DEV void str4(void* p, uint32_t a, uint32_t b, uint32_t c, uint32_t d) { asm volatile("st.relaxed.gpu.global.v4.u32 [%0],{%1,%2,%3,%4};" :: "l"(p), "r"(a), "r"(b), "r"(c), "r"(d) : "memory"); }
DEV void str2(void* p, uint32_t a, uint32_t b) { asm volatile("st.relaxed.gpu.global.v2.u32 [%0],{%1,%2};" :: "l"(p), "r"(a), "r"(b) : "memory"); }
DEV void str1(void* p, uint32_t a) { asm volatile("st.relaxed.gpu.global.u32 [%0],%1;" :: "l"(p), "r"(a) : "memory"); }
DEV void stw4(void* p, uint32_t a, uint32_t b, uint32_t c, uint32_t d) { asm volatile("st.global.v4.u32 [%0],{%1,%2,%3,%4};" :: "l"(p), "r"(a), "r"(b), "r"(c), "r"(d) : "memory"); }
DEV uint4 ldnc4(const void* p) { uint4 v; asm volatile("ld.global.nc.v4.u32 {%0,%1,%2,%3},[%4];" : "=r"(v.x), "=r"(v.y), "=r"(v.z), "=r"(v.w) : "l"(p)); return v; }
DEV uint32_t ldnc1(const void* p) { uint32_t v; asm volatile("ld.global.nc.u32 %0,[%1];" : "=r"(v) : "l"(p)); return v; }
DEV uint2 ldnc2(const void* p) { uint2 v; asm volatile("ld.global.nc.v2.u32 {%0,%1},[%2];" : "=r"(v.x), "=r"(v.y) : "l"(p)); return v; }

DEV uint2 lds2(uint32_t a) { uint2 v; asm volatile("ld.volatile.shared.v2.u32 {%0,%1},[%2];" : "=r"(v.x), "=r"(v.y) : "r"(a)); return v; }
DEV float lds16f(uint32_t a) { uint32_t v; asm volatile("ld.shared.u16 %0,[%1];" : "=r"(v) : "r"(a)); return __uint_as_float(v << 16); }
DEV void sts2(uint32_t a, uint32_t x, uint32_t y) { asm volatile("st.shared.v2.u32 [%0],{%1,%2};" :: "r"(a), "r"(x), "r"(y) : "memory"); }
DEV uint32_t lds1(uint32_t a) { uint32_t v; asm volatile("ld.volatile.shared.u32 %0,[%1];" : "=r"(v) : "r"(a)); return v; }
DEV uint32_t lds1z(uint32_t a, bool c) {
  uint32_t v; asm volatile("{.reg .pred q; setp.ne.u32 q,%2,0; mov.u32 %0,0; @q ld.volatile.shared.u32 %0,[%1];}" : "=r"(v) : "r"(a), "r"((uint32_t)c)); return v;
}
DEV uint4 lds4z(uint32_t a, bool c) {
  uint4 v = make_uint4(0, 0, 0, 0);
  asm volatile("{.reg .pred q; setp.ne.u32 q,%5,0; @q ld.volatile.shared.v4.u32 {%0,%1,%2,%3},[%4];}" : "+r"(v.x), "+r"(v.y), "+r"(v.z), "+r"(v.w) : "r"(a), "r"((uint32_t)c));
  return v;
}
DEV float lds1f(uint32_t a) { float v; asm volatile("ld.shared.f32 %0,[%1];" : "=f"(v) : "r"(a)); return v; }
DEV float2 lds2f(uint32_t a) { float2 v; asm volatile("ld.shared.v2.f32 {%0,%1},[%2];" : "=f"(v.x), "=f"(v.y) : "r"(a)); return v; }
DEV float4 lds4f(uint32_t a) { float4 v; asm volatile("ld.shared.v4.f32 {%0,%1,%2,%3},[%4];" : "=f"(v.x), "=f"(v.y), "=f"(v.z), "=f"(v.w) : "r"(a)); return v; }
DEV uint4 lds4(uint32_t a) { uint4 v; asm volatile("ld.volatile.shared.v4.u32 {%0,%1,%2,%3},[%4];" : "=r"(v.x), "=r"(v.y), "=r"(v.z), "=r"(v.w) : "r"(a)); return v; }
DEV void sts1(uint32_t a, uint32_t v) { asm volatile("st.shared.u32 [%0],%1;" :: "r"(a), "r"(v) : "memory"); }
DEV void sts16(uint32_t a, uint32_t v) { asm volatile("{.reg .b16 h; cvt.u16.u32 h,%1; st.shared.u16 [%0],h;}" :: "r"(a), "r"(v) : "memory"); }
DEV void sts2f(uint32_t a, float x, float y) { asm volatile("st.shared.v2.f32 [%0],{%1,%2};" :: "r"(a), "f"(x), "f"(y) : "memory"); }
DEV void sts4f(uint32_t a, float x, float y, float z, float w) { asm volatile("st.shared.v4.f32 [%0],{%1,%2,%3,%4};" :: "r"(a), "f"(x), "f"(y), "f"(z), "f"(w) : "memory"); }
DEV void sts4(uint32_t a, uint32_t x, uint32_t y, uint32_t z, uint32_t w) { asm volatile("st.shared.v4.u32 [%0],{%1,%2,%3,%4};" :: "r"(a), "r"(x), "r"(y), "r"(z), "r"(w) : "memory"); }

DEV void ldsm4(uint32_t (&r)[4], uint32_t a) { asm volatile("ldmatrix.sync.aligned.m8n8.x4.shared.b16 {%0,%1,%2,%3},[%4];" : "=r"(r[0]), "=r"(r[1]), "=r"(r[2]), "=r"(r[3]) : "r"(a) : "memory"); }
DEV void ldsm4t(uint32_t (&r)[4], uint32_t a) { asm volatile("ldmatrix.sync.aligned.m8n8.x4.trans.shared.b16 {%0,%1,%2,%3},[%4];" : "=r"(r[0]), "=r"(r[1]), "=r"(r[2]), "=r"(r[3]) : "r"(a) : "memory"); }
DEV void ldsm2(uint32_t (&r)[2], uint32_t a) { asm volatile("ldmatrix.sync.aligned.m8n8.x2.shared.b16 {%0,%1},[%2];" : "=r"(r[0]), "=r"(r[1]) : "r"(a) : "memory"); }
DEV void stsm4(uint32_t a, uint32_t r0, uint32_t r1, uint32_t r2, uint32_t r3) { asm volatile("stmatrix.sync.aligned.m8n8.x4.shared.b16 [%0],{%1,%2,%3,%4};" :: "r"(a), "r"(r0), "r"(r1), "r"(r2), "r"(r3) : "memory"); }
DEV void stsm2(uint32_t a, uint32_t r0, uint32_t r1) { asm volatile("stmatrix.sync.aligned.m8n8.x2.shared.b16 [%0],{%1,%2};" :: "r"(a), "r"(r0), "r"(r1) : "memory"); }
DEV void stsm4t(uint32_t a, uint32_t r0, uint32_t r1, uint32_t r2, uint32_t r3) { asm volatile("stmatrix.sync.aligned.m8n8.x4.trans.shared.b16 [%0],{%1,%2,%3,%4};" :: "r"(a), "r"(r0), "r"(r1), "r"(r2), "r"(r3) : "memory"); }
DEV uint32_t movm(uint32_t a) { uint32_t d; asm volatile("movmatrix.sync.aligned.m8n8.trans.b16 %0,%1;" : "=r"(d) : "r"(a)); return d; }
DEV void mma16(float (&d)[4], uint32_t a0, uint32_t a1, uint32_t a2, uint32_t a3, uint32_t b0, uint32_t b1) {
  asm volatile("mma.sync.aligned.m16n8k16.row.col.f32.bf16.bf16.f32 {%0,%1,%2,%3},{%4,%5,%6,%7},{%8,%9},{%0,%1,%2,%3};"
    : "+f"(d[0]), "+f"(d[1]), "+f"(d[2]), "+f"(d[3]) : "r"(a0), "r"(a1), "r"(a2), "r"(a3), "r"(b0), "r"(b1));
}
DEV void mma16z(float (&d)[4], uint32_t a0, uint32_t a1, uint32_t a2, uint32_t a3, uint32_t b0, uint32_t b1) {
  asm volatile("mma.sync.aligned.m16n8k16.row.col.f32.bf16.bf16.f32 {%0,%1,%2,%3},{%4,%5,%6,%7},{%8,%9},{%10,%10,%10,%10};"
    : "=f"(d[0]), "=f"(d[1]), "=f"(d[2]), "=f"(d[3]) : "r"(a0), "r"(a1), "r"(a2), "r"(a3), "r"(b0), "r"(b1), "f"(0.f));
}
DEV void mma8(float (&d)[4], uint32_t a0, uint32_t a1, uint32_t b0) {
  asm volatile("mma.sync.aligned.m16n8k8.row.col.f32.bf16.bf16.f32 {%0,%1,%2,%3},{%4,%5},{%6},{%0,%1,%2,%3};"
    : "+f"(d[0]), "+f"(d[1]), "+f"(d[2]), "+f"(d[3]) : "r"(a0), "r"(a1), "r"(b0));
}

DEV void bar_sync(int id, int n) { asm volatile("bar.sync %0,%1;" :: "r"(id), "r"(n) : "memory"); }
DEV void bar_sync_if(int id, int n, int c) { asm volatile("{.reg .pred q; setp.ne.s32 q,%2,0; @q bar.sync %0,%1;}" :: "r"(id), "r"(n), "r"(c) : "memory"); }
DEV void bar_arrive_if(int id, int n, int c) { asm volatile("{.reg .pred q; setp.ne.s32 q,%2,0; @q bar.arrive %0,%1;}" :: "r"(id), "r"(n), "r"(c) : "memory"); }
DEV bool bar_any(int id, int n, bool c) {
  uint32_t r; asm volatile("{.reg .pred p,q; setp.ne.u32 q,%3,0; bar.red.or.pred p,%1,%2,q; selp.u32 %0,1,0,p;}" : "=r"(r) : "r"(id), "r"(n), "r"((uint32_t)c) : "memory");
  return __any_sync(0xffffffffu, r);
}
DEV void bar_arrive(int id, int n) { asm volatile("bar.arrive %0,%1;" :: "r"(id), "r"(n) : "memory"); }
DEV void fence_async_glob() { asm volatile("fence.proxy.async.global;" ::: "memory"); }
DEV void fence_async_smem() { asm volatile("fence.proxy.async.shared::cta;" ::: "memory"); }
DEV void mbar_init(uint32_t b, int n) { asm volatile("mbarrier.init.shared::cta.b64 [%0],%1;" :: "r"(b), "r"(n) : "memory"); }
DEV void mbar_arrive(uint32_t b) { asm volatile("mbarrier.arrive.shared::cta.b64 _,[%0];" :: "r"(b) : "memory"); }
DEV void mbar_expect(uint32_t b, int bytes) { asm volatile("mbarrier.arrive.expect_tx.shared::cta.b64 _,[%0],%1;" :: "r"(b), "r"(bytes) : "memory"); }
DEV void mbar_wait(uint32_t b, uint32_t ph) {
  asm volatile("{\n.reg .pred p,q;\n.reg .u32 n;\n"
               "mbarrier.try_wait.parity.shared::cta.b64 p,[%0],%1;\n@p bra D;\nmov.u32 n,0;\n"
               "W: mbarrier.try_wait.parity.shared::cta.b64 p,[%0],%1;\n@p bra D;\n"
               "add.u32 n,n,1;\nsetp.lt.u32 q,n,%2;\n@q bra W;\ntrap;\nD:\n}"
               :: "r"(b), "r"(ph), "n"(SPIN_LIMIT) : "memory");
}
DEV void spin_guard(int it) { asm volatile("{.reg .pred p; setp.gt.s32 p,%0,%1; @p trap;}" :: "r"(it), "n"(SPIN_LIMIT)); }
DEV void split(uint32_t zero) {
  asm volatile("{.reg .pred p; setp.ne.u32 p,%0,0; @p trap;}" :: "r"(zero) : "memory");
}
DEV void cnt_wait(const uint32_t* k, int lane) {
  for (int it = 0; !__all_sync(0xffffffffu, ldr1(k + (lane & 3) * 32) >= 32); ++it) spin_guard(it);
}
DEV void mbar_arrive1(uint32_t b) { asm volatile("{.reg .pred p; elect.sync _|p,0xffffffff; @p mbarrier.arrive.shared::cta.b64 _,[%0];}" :: "r"(b) : "memory"); }
DEV void mbar_arrive1_if(uint32_t b, int c) {
  asm volatile("{.reg .pred p,q; setp.ne.s32 q,%1,0; elect.sync _|p,0xffffffff; and.pred p,p,q; @p mbarrier.arrive.shared::cta.b64 _,[%0];}" :: "r"(b), "r"(c) : "memory");
}
DEV void mbar_expect1(uint32_t b, int bytes) { asm volatile("{.reg .pred p; elect.sync _|p,0xffffffff; @p mbarrier.arrive.expect_tx.shared::cta.b64 _,[%0],%1;}" :: "r"(b), "r"(bytes) : "memory"); }
DEV void cnt_add1(uint32_t* q) { asm volatile("{.reg .pred p; elect.sync _|p,0xffffffff; @p red.relaxed.gpu.global.add.u32 [%0],1;}" :: "l"(q) : "memory"); }
DEV void tma4(uint32_t dst, const CUtensorMap* m, int c0, int c1, int c2, int c3, uint32_t bar) {
  asm volatile("{.reg .pred p; elect.sync _|p,0xffffffff;\n"
    "@p cp.async.bulk.tensor.4d.shared::cluster.global.mbarrier::complete_tx::bytes [%0],[%1,{%2,%3,%4,%5}],[%6];}"
    :: "r"(dst), "l"(m), "r"(c0), "r"(c1), "r"(c2), "r"(c3), "r"(bar) : "memory");
}
DEV void tma3(uint32_t dst, const CUtensorMap* m, int c0, int c1, int c2, uint32_t bar) {
  asm volatile("{.reg .pred p; elect.sync _|p,0xffffffff;\n"
    "@p cp.async.bulk.tensor.3d.shared::cluster.global.mbarrier::complete_tx::bytes [%0],[%1,{%2,%3,%4}],[%5];}"
    :: "r"(dst), "l"(m), "r"(c0), "r"(c1), "r"(c2), "r"(bar) : "memory");
}
DEV void bulk(uint32_t dst, const void* src, int bytes, uint32_t bar) {
  asm volatile("{.reg .pred p; elect.sync _|p,0xffffffff;\n@p cp.async.bulk.shared::cluster.global.mbarrier::complete_tx::bytes [%0],[%1],%2,[%3];}" :: "r"(dst), "l"(src), "r"(bytes), "r"(bar) : "memory");
}

DEV void bulk_store(void* dst, uint32_t src, int bytes) {
  asm volatile("{.reg .pred p; elect.sync _|p,0xffffffff;\n@p cp.async.bulk.global.shared::cta.bulk_group [%0],[%1],%2;}" :: "l"(dst), "r"(src), "r"(bytes) : "memory");
}
DEV void tma2_store(const CUtensorMap* m, uint32_t src, int c0, int c1) {
  asm volatile("{.reg .pred p; elect.sync _|p,0xffffffff;\n@p cp.async.bulk.tensor.2d.global.shared::cta.bulk_group [%0,{%2,%3}],[%1];}" :: "l"(m), "r"(src), "r"(c0), "r"(c1) : "memory");
}
DEV void bulk_wait() { asm volatile("cp.async.bulk.commit_group;\ncp.async.bulk.wait_group 0;\nfence.proxy.async.global;" ::: "memory"); }

DEV uint64_t mkdesc(uint32_t addr, uint32_t lbo, uint32_t sbo, uint32_t swz) {
  return (uint64_t)((addr >> 4) | ((lbo >> 4) << 16)) | ((uint64_t)((sbo >> 4) | (swz << 30)) << 32);
}
DEV void wg_fence() { asm volatile("wgmma.fence.sync.aligned;" ::: "memory"); }
DEV void wg_commit() { asm volatile("wgmma.commit_group.sync.aligned;" ::: "memory"); }
template <int N> DEV void wg_wait() { asm volatile("wgmma.wait_group.sync.aligned %0;" :: "n"(N) : "memory"); }
template <int N> DEV void zero(float (&d)[N]) {
#pragma unroll
  for (int i = 0; i < N; ++i) d[i] = 0.f;
}
template <int N> DEV void zerov(float (&d)[N]) {
#pragma unroll
  for (int i = 0; i < N; ++i) asm volatile("mov.b32 %0,0;" : "=f"(d[i]));
}
template <int N> DEV void undef(float (&d)[N]) {
#pragma unroll
  for (int i = 0; i < N; ++i) asm volatile("" : "=f"(d[i]));
}
#define R4(d, o) "+f"(d[o]), "+f"(d[o + 1]), "+f"(d[o + 2]), "+f"(d[o + 3])
#define R8(d, o) R4(d, o), R4(d, o + 4)
#define R16(d, o) R8(d, o), R8(d, o + 8)
template <int ACC> DEV void wg_rs64k(float (&d)[32], const uint32_t (&a)[4], uint64_t db) {
  asm volatile("{.reg .pred p; setp.ne.s32 p,%37,0;\nwgmma.mma_async.sync.aligned.m64n64k16.f32.bf16.bf16 {%0,%1,%2,%3,%4,%5,%6,%7,%8,%9,%10,%11,%12,%13,%14,%15,%16,%17,%18,%19,%20,%21,%22,%23,%24,%25,%26,%27,%28,%29,%30,%31},{%32,%33,%34,%35},%36,p,1,1,0;}"
    : R16(d, 0), R16(d, 16) : "r"(a[0]), "r"(a[1]), "r"(a[2]), "r"(a[3]), "l"(db), "n"(ACC));
}
template <int ACC> DEV void wg_rs48t(float (&d)[24], const uint32_t (&a)[4], uint64_t db) {
  asm volatile("{.reg .pred p; setp.ne.s32 p,%29,0;\nwgmma.mma_async.sync.aligned.m64n48k16.f32.bf16.bf16 {%0,%1,%2,%3,%4,%5,%6,%7,%8,%9,%10,%11,%12,%13,%14,%15,%16,%17,%18,%19,%20,%21,%22,%23},{%24,%25,%26,%27},%28,p,1,1,1;}"
    : R16(d, 0), R8(d, 16) : "r"(a[0]), "r"(a[1]), "r"(a[2]), "r"(a[3]), "l"(db), "n"(ACC));
}
template <int ACC> DEV void wg_rs32t(float (&d)[16], const uint32_t (&a)[4], uint64_t db) {
  asm volatile("{.reg .pred p; setp.ne.s32 p,%21,0;\nwgmma.mma_async.sync.aligned.m64n32k16.f32.bf16.bf16 {%0,%1,%2,%3,%4,%5,%6,%7,%8,%9,%10,%11,%12,%13,%14,%15},{%16,%17,%18,%19},%20,p,1,1,1;}"
    : R16(d, 0) : "r"(a[0]), "r"(a[1]), "r"(a[2]), "r"(a[3]), "l"(db), "n"(ACC));
}
template <int ACC> DEV void wg_ss192(float (&d)[96], uint64_t da, uint64_t db) {
  asm volatile("{.reg .pred p; setp.ne.s32 p,%98,0;\nwgmma.mma_async.sync.aligned.m64n192k16.f32.bf16.bf16 {"
    "%0,%1,%2,%3,%4,%5,%6,%7,%8,%9,%10,%11,%12,%13,%14,%15,%16,%17,%18,%19,%20,%21,%22,%23,%24,%25,%26,%27,%28,%29,%30,%31,"
    "%32,%33,%34,%35,%36,%37,%38,%39,%40,%41,%42,%43,%44,%45,%46,%47,%48,%49,%50,%51,%52,%53,%54,%55,%56,%57,%58,%59,%60,%61,%62,%63,"
    "%64,%65,%66,%67,%68,%69,%70,%71,%72,%73,%74,%75,%76,%77,%78,%79,%80,%81,%82,%83,%84,%85,%86,%87,%88,%89,%90,%91,%92,%93,%94,%95},"
    "%96,%97,p,1,1,1,1;}"
    : R16(d, 0), R16(d, 16), R16(d, 32), R16(d, 48), R16(d, 64), R16(d, 80) : "l"(da), "l"(db), "n"(ACC));
}
template <int ACC> DEV void wg_ss64(float (&d)[32], uint64_t da, uint64_t db) {
  asm volatile("{.reg .pred p; setp.ne.s32 p,%34,0;\nwgmma.mma_async.sync.aligned.m64n64k16.f32.bf16.bf16 {%0,%1,%2,%3,%4,%5,%6,%7,%8,%9,%10,%11,%12,%13,%14,%15,%16,%17,%18,%19,%20,%21,%22,%23,%24,%25,%26,%27,%28,%29,%30,%31},%32,%33,p,1,1,0,1;}"
    : R8(d, 0), R8(d, 8), R8(d, 16), R8(d, 24) : "l"(da), "l"(db), "n"(ACC));
}

DEV uint32_t cpy(uint32_t v, uint32_t id) {
  uint32_t d; asm volatile("prmt.b32 %0,%1,%1,%2;" : "=r"(d) : "r"(v), "r"(id)); return d;
}
struct Params {
  uint32_t zero, spare;
  char* mid;
  const uint16_t *x0, *Are, *Aim, *Bre, *Bim, *Cre, *Cim, *logdt, *dskip, *wqkv, *wo;
  uint16_t* out;
  uint8_t role[144];
};

DEV uint32_t ln_word(float mean, float var) {
  float v = bfr(var);
  float s = sqrt_(bfr(v + 1e-5f));
  return pack2(mean, s);
}

DEV int stat_group(int c) { return 16 * (c & 4) + 4 * (c >> 3) + (c & 3); }
DEV int xg_off(int G, int g) { return (G >> 6) * 1024 + (G & 63) * 8 + (g ^ (G & 2)); }
DEV int sr_off(int G, int g) { return (G >> 6) * 256 + (g & 2) * 64 + 2 * (G & 63) + ((g >> 2) & 1); }
DEV uint32_t region(int chl) { return SM_A + (chl >> 1) * A_E + (chl & 1) * R_SZ; }
template <int N> DEV float4 gram(const uint32_t (&w)[N][2], int g) {
  float s0[4], s1[4];
  const uint32_t one = 0x3F803F80u;
  mma16z(s0, w[0][0], one, w[1][0], one, w[0][0], w[1][0]); mma16z(s1, w[0][1], one, w[1][1], one, w[0][1], w[1][1]);
#pragma unroll
  for (int j = 2; j < N; j += 2) {
    mma16(s0, w[j][0], one, w[j + 1][0], one, w[j][0], w[j + 1][0]); mma16(s1, w[j][1], one, w[j + 1][1], one, w[j][1], w[j + 1][1]);
  }
  const bool od = g & 1;
  return make_float4(od ? s0[3] : s0[2], od ? s0[1] : s0[0], od ? s1[3] : s1[2], od ? s1[1] : s1[0]);
}
DEV uint32_t ln_sums(float s, float q) { const float m = s * (1.f / 512.f); return ln_word(m, fmaxf(q * (1.f / 512.f) - m * m, 0.f)); }
DEV void cmul(float& orr, float& oi, float ar, float ai, float br, float bi) {
  float r = ar * br - ai * bi, i = ar * bi + ai * br; orr = r; oi = i;
}
DEV void cexp_(float al, float bt, float s, float& er, float& ei) {
  float mag = ex2(al * s), ph = bt * s;
  ph -= rintf(ph);
  float ang = ph * 6.283185307179586f;
  er = mag * __cosf(ang); ei = mag * __sinf(ang);
}

DEV void kgen(const Params& P, int c, int wm, int lane) {
  const int chl = wm >> 1, mh = wm & 1, g = lane >> 2, t = lane & 3;
  const int ch = 256 * (chl >> 1) + 2 * c + (chl & 1);
  const int mo = ch * 64 + mh * 32 + lane;
  const uint32_t vAr = ldw1((const uint32_t*)P.Are + mo), vAi = ldw1((const uint32_t*)P.Aim + mo);
  const uint32_t vBr = ldw1((const uint32_t*)P.Bre + mo), vBi = ldw1((const uint32_t*)P.Bim + mo);
  const uint32_t vCr = ldw1((const uint32_t*)P.Cre + mo), vCi = ldw1((const uint32_t*)P.Cim + mo);
  const uint32_t vld = ldw1((const uint32_t*)P.logdt + (ch >> 1)) >> (16 * (ch & 1)), vds = ldw1((const uint32_t*)P.dskip + (ch >> 1)) >> (16 * (ch & 1));
  bar_arrive(NB_Y, 384);
  PROF(45);
  asm volatile("setmaxnreg.inc.sync.aligned.u32 %0;" :: "n"(REG_MAIN));
  bar_sync(0, NTHR);
  PROF(44);
  {
    const uint32_t tz = SM_TAP + chl * TAP_SZ + (mh * 32 + lane) * 16;
#pragma unroll
    for (int k = 0; k < 3; ++k) sts4(tz + k * 1024, 0, 0, 0, 0);
    static_assert(TAP_SZ > 3072 && TAP_SZ <= 4096, "");
    if (mh * 32 + lane < TAP_SZ / 16 - 192) sts4(tz + 3072, 0, 0, 0, 0);
  }
  const float dt = bfr(__expf(bflo(vld)));
  const uint32_t tb = slot(wm);
  float acc[5][4];
#pragma unroll
  for (int i = 0; i < 5; ++i) { acc[i][0] = acc[i][1] = acc[i][2] = acc[i][3] = 0.f; }
  float k2048 = 0.f;
#pragma unroll 1
  for (int r = 0; r < 2; ++r) {
    const float are = r ? bfhi(vAr) : bflo(vAr), aim = r ? bfhi(vAi) : bflo(vAi);
    const float bre = r ? bfhi(vBr) : bflo(vBr), bim = r ? bfhi(vBi) : bflo(vBi);
    const float cre = r ? bfhi(vCr) : bflo(vCr), cim = r ? bfhi(vCi) : bflo(vCi);
    const float al = dt * are * 1.4426950408889634f, bt = dt * aim * 0.15915494309189535f;
    float wr, wi; cmul(wr, wi, cre, cim, dt * bre, dt * bim);
    if (r == 0) PROFD(2, __float_as_uint(wr + al + bt));
    float e1r, e1i, e8r, e8i, eLr, eLi;
    cexp_(al, bt, 1.f, e1r, e1i); cexp_(al, bt, 8.f, e8r, e8i); cexp_(al, bt, 128.f, eLr, eLi);
    const uint32_t tw = tb + lane * 4;
    float pr[8], pi[8];
    pr[1] = e1r; pi[1] = e1i;
#pragma unroll
    for (int k = 2; k < 8; ++k) cmul(pr[k], pi[k], pr[k - 1], pi[k - 1], e1r, e1i);
    float yr = 1.f, yi = 0.f, qr = wr, qi = wi;
#pragma unroll
    for (int a = 0; a < 16; ++a) {
      sts1(tw + a * 144, pack2(yr, -yi));
      if (a == 0) { yr = e8r; yi = e8i; } else if (a < 15) cmul(yr, yi, yr, yi, e8r, e8i);
      const int step = a < 2 ? 1 : a < 4 ? 2 : a < 8 ? 4 : 8;
      const int row0 = 16 + (a < 2 ? 8 * a : a < 4 ? 16 + 4 * (a - 2) : a < 8 ? 24 + 2 * (a - 4) : 32 + (a - 8));
      sts1(tw + row0 * 144, pack2(qr, qi));
#pragma unroll
      for (int k = step; k < 8; k += step) {
        float xr, xi; cmul(xr, xi, qr, qi, pr[k], pi[k]);
        sts1(tw + (row0 + k / step) * 144, pack2(xr, xi));
      }
      cmul(qr, qi, qr, qi, eLr, eLi);
    }
    k2048 += qr;
    __syncwarp();
    if (r == 0) PROF(3);
#pragma unroll
    for (int kp = 0; kp < 2; ++kp) {
      uint32_t a0[4], a1[4];
      const uint32_t aa = tb + ((lane & 7) + 8 * ((lane >> 3) & 1)) * 144 + (lane >> 4) * 16 + kp * 64;
      ldsm4(a0, aa); ldsm4(a1, aa + 32);
#pragma unroll
      for (int tl = 0; tl < 5; ++tl) {
        uint32_t b[4];
        ldsm4(b, tb + (16 + 8 * tl + (lane & 7)) * 144 + (lane >> 3) * 16 + kp * 64);
        mma16(acc[tl], a0[0], a0[1], a0[2], a0[3], b[0], b[1]);
        mma16(acc[tl], a1[0], a1[1], a1[2], a1[3], b[2], b[3]);
      }
    }
    __syncwarp();
    bar_sync_if(NB_P0 + 1, 288, 1 - r);
  }
#pragma unroll
  for (int o = 16; o > 0; o >>= 1) k2048 += __shfl_xor_sync(0xffffffffu, k2048, o);
  if (mh == 0) {
    sts4f(tb + lane * 16, acc[2][0], acc[2][1], acc[2][2], acc[2][3]);
    sts4f(tb + 512 + lane * 16, acc[3][0], acc[3][1], acc[3][2], acc[3][3]);
  } else {
    sts4f(tb + lane * 16, acc[0][0], acc[0][1], acc[0][2], acc[0][3]);
    sts4f(tb + 512 + lane * 16, acc[1][0], acc[1][1], acc[1][2], acc[1][3]);
    sts4f(tb + 1024 + lane * 16, acc[4][0], acc[4][1], acc[4][2], acc[4][3]);
    if (lane == 0) sts1(tb + 1536, __float_as_uint(k2048));
  }
  PROF(4);
  bar_sync(NB_K + chl, 64);
  const uint32_t ob = slot(wm ^ 1), tp = SM_TAP + chl * TAP_SZ;
  if (mh == 0) {
#pragma unroll
    for (int tl = 0; tl < 2; ++tl) {
      float4 o = lds4f(ob + tl * 512 + lane * 16);
      if (tl == 0 && lane == 0) o.x += bflo(vds);
      uint32_t v0 = pack2(acc[tl][0] + o.x, acc[tl][1] + o.y), v1 = pack2(acc[tl][2] + o.z, acc[tl][3] + o.w);
      const int l = 128 * tl + 8 * g + 2 * t;
      sts16(tp + T_E + 2 * (0 - l), v0); sts16(tp + T_E + 2 * (-1 - l), v0 >> 16);
      sts16(tp + T_O + 2 * (0 - l), v0); sts16(tp + T_O + 2 * (-1 - l), v0 >> 16);
      sts16(tp + T_E + 2 * (-64 - l), v1); sts16(tp + T_E + 2 * (-65 - l), v1 >> 16);
      sts16(tp + T_O + 2 * (-64 - l), v1); sts16(tp + T_O + 2 * (-65 - l), v1 >> 16);
    }
    float4 o = lds4f(ob + 1024 + lane * 16);
    uint32_t v0 = pack2(acc[4][0] + o.x, acc[4][1] + o.y), v1 = pack2(acc[4][2] + o.z, acc[4][3] + o.w);
    const int x = 32 * t + g - 1;
    if (lane == 0) { sts16(tp + T_E - 2 * (X_5 + 63), v0); sts16(tp + T_O - 2 * (X_5 + 63), v0); sts1(tp + T_K, prmt(v0, v0, 0x1010)); }
    else sts16(tp + T_C - 2 * x, v0);
    sts16(tp + T_C - 2 * (x + 16), v0 >> 16);
    sts16(tp + T_C - 2 * (x + 8), v1);
    sts16(tp + T_C - 2 * (x + 24), v1 >> 16);
    if (lane == 0) sts16(tp + T_C - 2 * 127, pack2(k2048 + __uint_as_float(lds1(ob + 1536)), 0.f));
  } else {
    float4 o2 = lds4f(ob + lane * 16), o3 = lds4f(ob + 512 + lane * 16);
    uint32_t v0 = pack2(acc[2][0] + o2.x, acc[2][1] + o2.y), v1 = pack2(acc[2][2] + o2.z, acc[2][3] + o2.w);
    const int l0 = 256 + 128 * (t >> 1) + 4 * (t & 1) + 8 * g;
    if (lane != 0) { sts16(tp + T_E + 2 * (1 - l0), v0); sts16(tp + T_O + 2 * (1 - l0), v0); }
    sts16(tp + T_E + 2 * (0 - l0), v0); sts16(tp + T_O + 2 * (0 - l0), v0);
    sts16(tp + T_E + 2 * (-1 - l0), v0); sts16(tp + T_O + 2 * (-1 - l0), v0);
    sts16(tp + T_E + 2 * (-2 - l0), v0 >> 16); sts16(tp + T_O + 2 * (-2 - l0), v0 >> 16);
    sts16(tp + T_E + 2 * (-63 - l0), v1); sts16(tp + T_O + 2 * (-63 - l0), v1);
    sts16(tp + T_E + 2 * (-64 - l0), v1); sts16(tp + T_O + 2 * (-64 - l0), v1);
    sts16(tp + T_E + 2 * (-65 - l0), v1); sts16(tp + T_O + 2 * (-65 - l0), v1);
    sts16(tp + T_E + 2 * (-66 - l0), v1 >> 16); sts16(tp + T_O + 2 * (-66 - l0), v1 >> 16);
    uint32_t w0 = pack2(acc[3][0] + o3.x, acc[3][1] + o3.y), w1 = pack2(acc[3][2] + o3.z, acc[3][3] + o3.w);
    const int x = 16 * t + g;
    if (lane == 0) {
      const uint32_t k = prmt(w0, w0, 0x1010);
      sts1(tp + T_E - 2 * 514, k); sts1(tp + T_E - 2 * 512, k);
      sts16(tp + T_O - 2 * 514, k); sts1(tp + T_O - 2 * 513, k); sts16(tp + T_O - 2 * 511, k);
    } else { sts16(tp + T_E - 2 * (X_5 - 1 + x), w0); sts16(tp + T_O - 2 * (X_5 - 1 + x), w0); }
    sts16(tp + T_E - 2 * (X_3 + x), w0 >> 16); sts16(tp + T_O - 2 * (X_3 + x), w0 >> 16);
    sts16(tp + T_E - 2 * (X_5 + 7 + x), w1); sts16(tp + T_O - 2 * (X_5 + 7 + x), w1);
    sts16(tp + T_E - 2 * (X_3 + 8 + x), w1 >> 16); sts16(tp + T_O - 2 * (X_3 + 8 + x), w1 >> 16);
  }
}

DEV bool bad8(const uint4& v) { return min(v.x, v.z) == 0u; }
DEV uint32_t uchunk(uint32_t reg, int x) { return reg + R_U + (x ^ ((x >> 3) & 3)) * 16; }
DEV uint32_t& xword(uint4 (&x)[2], int e, int tp) { uint4& v = x[tp >> 1]; return tp & 1 ? (e ? v.w : v.z) : (e ? v.y : v.x); }

DEV void sload(const Params& P, int c, int j, int layer, uint4 (&s)[2][2]) {
  const uint4* st = &SCR->SR[layer][c >> 4][opq(j)];
  mbar_wait(B_U, layer);
  PROF(layer ? 25 : 10);
#pragma unroll
  for (int z = 0; z < 4; ++z) s[z >> 1][z & 1] = ldr4(st + z * 128);
}
DEV void uload(const Params& P, int c, int j, int layer, uint4 (&x)[2][2][2], uint4 (&s)[2][2]) {
  j = opq(j);
  const uint4* st = &SCR->SR[layer][c >> 4][j];
  const int o0 = 2 * j + ((j >> 2) & 1), o1 = o0 ^ 1;
#pragma unroll
  for (int z = 0; z < 4; ++z) { uint4& v = s[z >> 1][z & 1]; ldr4_if(v, st + z * 128, bad8(v)); }
  PROF(layer ? 26 : 11);
  mbar_wait(B_E, layer);
#pragma unroll
  for (int z = 0; z < 8; ++z) x[z >> 2][(z >> 1) & 1][z & 1] = lds4(SM_X + 16 * (z & 1 ? o1 : o0) + (z >> 1) * 4096);
  PROF(layer ? 27 : 14);
  for (int it = 0;; ++it) {
    uint32_t m = ~0u;
#pragma unroll
    for (int z = 0; z < 4; ++z) { const uint4& v = s[z >> 1][z & 1]; m = min(m, min(v.x, v.z)); }
#pragma unroll
    for (int z = 0; z < 8; ++z) { const uint4& v = x[z >> 2][(z >> 1) & 1][z & 1]; m = min(m, min(v.x, v.z)); }
    if (!RARE(m == 0)) break;
#pragma unroll
    for (int z = 0; z < 4; ++z) { uint4& v = s[z >> 1][z & 1]; ldr4_if(v, st + z * 128, bad8(v)); }
#pragma unroll
    for (int z = 0; z < 8; ++z) {
      uint4& v = x[z >> 2][(z >> 1) & 1][z & 1];
      ldr4_if(v, &SCR->XG[layer][c * 1024 + (opq(o0) ^ (z & 1)) + (z >> 1) * 256], bad8(v));
    }
    spin_guard(it);
  }
  PROF(4 + 12 * layer);
}
DEV void uprep(int j, int k, uint4 (&x)[2][2], uint4 (&s)[2], uint32_t (&u)[4][4]) {
  const uint32_t ua = uchunk(0, opq(j)) + k * 2048;
#pragma unroll
  for (int chl = 0; chl < 4; ++chl) {
#pragma unroll
    for (int tp = 0; tp < 4; ++tp) u[chl][tp] = hmul2(hsub2(xword(x[chl >> 1], chl & 1, tp), xword(s, 1, tp)), xword(s, 0, tp));
    sts4(ua + region(chl), u[chl][0], u[chl][1], u[chl][2], u[chl][3]);
  }
}

template <bool FULL> DEV void box_unit(uint32_t reg, int s, const uint2& a, const uint4& b, const uint32_t (&d)[4], uint32_t (&pv)[4]) {
  const uint32_t u[9] = {a.x, a.y, b.x, b.y, b.z, b.w, d[0], d[1], d[2]};
  uint32_t v[8], p[8];
#pragma unroll
  for (int j = 0; j < 8; ++j) { v[j] = prmt(u[j], u[j + 1], 0x5432); p[j] = hadd2(u[j], v[j]); }
  const uint32_t o = reg + s * 16;
  uint32_t x[4], y[4];
#pragma unroll
  for (int j = 0; j < 4; ++j) { x[j] = hadd2(hadd2(p[1 + j], p[2 + j]), u[3 + j]); y[j] = hadd2(v[3 + j], p[4 + j]); pv[j] = p[4 + j]; }
  sts4(o + R_X5, x[0], x[1], x[2], x[3]);
  sts4(o + R_X3, y[0], y[1], y[2], y[3]);
  if (FULL) {
#pragma unroll
    for (int j = 0; j < 4; ++j) { y[j] = hadd2(hadd2(v[j], v[3 + j]), x[j]); x[j] = hadd2(hadd2(u[j], u[4 + j]), y[j]); }
    const bool od = s & 1;
    sts4(o + R_BO, od ? y[0] : x[0], od ? y[1] : x[1], od ? y[2] : x[2], od ? y[3] : x[3]);
    sts4(o + R_BE + 16, od ? x[0] : y[0], od ? x[1] : y[1], od ? x[2] : y[2], od ? x[3] : y[3]);
  }
}
DEV void box_full(int j, uint32_t (&u)[4][4], uint32_t zero) {
  const uint32_t a2 = uchunk(8, j - 2), a1 = uchunk(0, j - 1);
  uint2 a[4]; uint4 b[4];
#pragma unroll
  for (int chl = 0; chl < KBL; ++chl) { a[chl] = lds2(region(chl) + a2); b[chl] = lds4(region(chl) + a1); }
  split(zero);
#pragma unroll
  for (int chl = 0; chl < 4; ++chl) {
    const uint32_t d[4] = {u[chl][0], u[chl][1], u[chl][2], u[chl][3]};
    box_unit<true>(region(chl), j, a[chl], b[chl], d, u[chl]);
    if (chl + KBL < 4) { a[(chl + KBL) & 3] = lds2(region(chl + KBL) + a2); b[(chl + KBL) & 3] = lds4(region(chl + KBL) + a1); }
    if (chl != 2) {
      fence_async_smem();
      if (chl == 3) bar_arrive(NB_B + 2, 288);
      bar_arrive(NB_B + chl, 288);
    }
    if (chl == 0) PROF(31);
  }
}
DEV void box_help(int chl, int lane) {
  const uint32_t reg = region(chl);
#pragma unroll 1
  for (int s = 128 + opq(lane); s < 192; s += 32) {
    const uint4 d = lds4(uchunk(reg, s));
    const uint32_t u[4] = {d.x, d.y, d.z, d.w};
    uint32_t v[4];
    box_unit<false>(reg, s, lds2(uchunk(reg, s - 2) + 8), lds4(uchunk(reg, s - 1)), u, v);
  }
  fence_async_smem();
  bar_arrive(NB_B + chl, 288);
}

DEV uint4 hadd8(const uint4& a, const uint4& b) { return make_uint4(hadd2(a.x, b.x), hadd2(a.y, b.y), hadd2(a.z, b.z), hadd2(a.w, b.w)); }
DEV void conv_out(int c, int j, int chl, uint4 (&x)[2][2][2], const uint32_t (&v)[4], uint4* XF, uint32_t zero) {
  const int rho = chl >> 1, e = chl & 1;
  const uint32_t ua = uchunk(region(chl), j), fa = region(chl) + R_X5 + j * 16, ha = region(chl) + R_X3 + (j & 1) * 1088 + (j >> 1) * 16;
  const int m8 = ((j & 4) + ((j >> 1) & 1)) ^ ((2 * c + e) & 7);
  uint2* xo = (uint2*)XF + (((j >> 3) * 512 + 256 * rho + 2 * c + e) * 16 + (j & 1));
  bar_sync(NB_Y + e + 7 * rho, 256);
  uint4 y[2], f[2], h[2];
#pragma unroll
  for (int k = 0; k < 2; ++k) {
    y[k] = lds4(ua + k * 2048);
    f[k] = lds4z(ua + k * 2048 + R_BO - R_U, k || j >= 36);
    h[k] = lds4z(fa + k * 2048 - 1024, k || j >= 64);
  }
  const uint32_t q = lds1(SM_TAP + chl * TAP_SZ + T_K);
  const uint4 r = lds4(ha);
  split(zero);
  h[1] = hadd8(h[1], make_uint4(hfma2(q, v[0], r.x), hfma2(q, v[1], r.y), hfma2(q, v[2], r.z), hfma2(q, v[3], r.w)));
#pragma unroll
  for (int k = 0; k < 2; ++k) {
    const uint4 o = hadd8(hadd8(y[k], hadd8(f[k], h[k])), make_uint4(xword(x[k][rho], e, 0), xword(x[k][rho], e, 1), xword(x[k][rho], e, 2), xword(x[k][rho], e, 3)));
    str2(xo + k * 131072 + 2 * m8, prmt(o.x, o.y, 0x5410), prmt(o.z, o.w, 0x5410));
    str2(xo + k * 131072 + 2 * (m8 ^ 2), prmt(o.x, o.y, 0x7632), prmt(o.z, o.w, 0x7632));
  }
  if (e) { __syncwarp(); mbar_arrive1(B_RD + rho * 8); }
}

DEV void conv_round(int e, int rho, int w, int lane) {
  const int g = lane >> 2, t = lane & 3, chl = 2 * rho + e;
  const uint32_t reg = region(chl), tp = SM_TAP + chl * TAP_SZ;
  const uint32_t g0 = tp + ((g & 1) ? T_O : T_E) + 2 * (2 * t - g) - 16;
  const uint32_t ga = g0 - 32 * (w & 1) - 576 * (w >> 1), id = opq(0x3210u);
  float acc[32], f1[24], f2[16];
  uint32_t q[12][4];
  {
    uint32_t qn[18][4];
    qn[0][2] = lds1(ga + 64);
#pragma unroll
    for (int n = 0; n < 18; ++n) {
      const bool nz = n < 15 || w < 2 || (n == 15 && w == 2);
      qn[n][0] = n < 15 ? lds1(ga + 48 - 32 * n) : lds1z(ga + 48 - 32 * n, nz);
      qn[n][1] = n < 15 ? lds1(ga + 32 - 32 * n) : lds1z(ga + 32 - 32 * n, nz);
    }
#pragma unroll
    for (int n = 0; n < 18; ++n) { qn[n][3] = cpy(qn[n][0], id); if (n) qn[n][2] = cpy(qn[n - 1][1], id); }
#pragma unroll
    for (int n = 0; n < 8; ++n) {
      const int i = n & 3;
      const uint32_t a = g0 + 16 - 16 * w - 2 * (n < 4 ? X_5 : X_3) + 16 * i;
      uint32_t (&q1)[4] = q[(n & 4) + (i >> 1)], (&q2)[4] = q[(n & 4) + 2 + (i >> 1)];
      q1[2 * (i & 1)] = lds1z(a, i <= w); q1[2 * (i & 1) + 1] = lds1(a - 64);
      q2[2 * (i & 1)] = cpy(0, id); q2[2 * (i & 1) + 1] = lds1z(a - 128, i >= w);
    }
    const uint32_t gc = tp + T_C - 2 + 4 * (t - g - 8 * w);
#pragma unroll
    for (int kk = 0; kk < 4; ++kk) {
      q[8 + kk][0] = lds1z(gc + 32 * kk, w >= kk); q[8 + kk][2] = lds1z(gc + 32 * kk + 16, w >= kk);
      q[8 + kk][1] = lds1(gc + 32 * kk - 128); q[8 + kk][3] = lds1(gc + 32 * kk - 112);
    }
    PROFD(rho ? 43 : 47, qn[17][2] ^ q[11][3]);
    bar_sync_if(NB_U, NBARU, 1 - rho);
    mbar_arrive1_if(B_V, chl == 1 && w == 0);
    bar_sync_if(NB_T + 1 - e, 256, chl);
    const uint64_t db = mkdesc(reg + R_U, 16, 512, 2) + 2;
    undef(acc);
    wg_fence();
#pragma unroll
    for (int n = 0; n < 18; ++n) {
      if (n) wg_rs64k<1>(acc, qn[n], db - 2 * n); else wg_rs64k<0>(acc, qn[0], db);
      if (n == 9) wg_commit();
    }
    wg_commit();
  }
  wg_wait<1>();
  PROF(12);
  bar_sync(NB_B + chl, 288);
  const uint64_t d1 = mkdesc(reg + R_X5, 128, 512, 0), d2 = mkdesc(reg + R_BO, 128, 1024, 0);
  undef(f1); undef(f2);
  wg_fence();
#pragma unroll
  for (int n = 0; n < 8; ++n) {
    const uint64_t d = d1 + (n >> 2) * ((R_X3 - R_X5) / 16) + 16 * (n & 1) - 16 * (n & 2);
    if (n) wg_rs48t<1>(f1, q[n], d); else wg_rs48t<0>(f1, q[0], d);
    if (n & 1) { if (n > 1) wg_rs32t<1>(f2, q[8 + (n >> 1)], d2 + 16 * (n >> 1)); else wg_rs32t<0>(f2, q[8], d2); }
  }
  wg_commit();
  wg_wait<1>();
  PROF(13);
  bar_arrive_if(NB_T + e, 256, chl - 3);
  wg_wait<0>();
  PROF(14);
  bar_sync(NB_WG + e, 128);
  {
    const int p = (lane + 9 * (w >> 1)) & 31;
    const uint32_t ya = reg + ((w >> 1) ? R_BO : R_U) + p * 64 + (((2 * (w & 1)) ^ ((p >> 1) & 3)) * 16);
    const uint32_t up = p < lane ? 2048 : 0;
#pragma unroll
    for (int z = 0; z < 4; ++z) {
      const float* a = acc + 16 * (z >> 1) + 2 * (z & 1);
      stsm4t((ya + (up ^ ((z >> 1) * 2048))) ^ ((z & 1) * 16), pack2(a[0], a[1]), pack2(a[4], a[5]), pack2(a[8], a[9]), pack2(a[12], a[13]));
    }
  }
  {
    const uint32_t fa = reg + R_X5 + (8 * w + (lane & 7)) * 16 + (lane >> 3) * 512;
    uint32_t h[6];
#pragma unroll
    for (int p = 0; p < 6; ++p) h[p] = p ? pack2(f1[4 * p] + f1[4 * p - 2], f1[4 * p + 1] + f1[4 * p - 1]) : pack2(f1[0], f1[1]);
    stsm4(fa, h[0], h[1], h[2], h[3]);
    stsm2(fa + 2048, h[4], h[5]);
    stsm4(reg + R_X3 + (lane < 16 ? 1088 : 0) + (8 * w + (lane & 7) + 4 * (lane & 8)) * 16, pack2(f2[0], f2[1]), pack2(f2[2] + f2[4], f2[3] + f2[5]),
          pack2(f2[8], f2[9]), pack2(f2[10] + f2[12], f2[11] + f2[13]));
  }
  bar_arrive(NB_Y + e + 7 * rho, 256);
}
constexpr uint32_t FILL = 0xFFFFFFFFu;
template <int N> DEV void fixo(uint4 (&A)[N], const uint4* p) {
#pragma unroll 1
  for (int it = 0; it < SPIN_LIMIT; ++it) {
    uint32_t m = A[0].x;
#pragma unroll
    for (int k = 1; k < N; ++k) m = max(m, A[k].x);
    if (__all_sync(0xffffffffu, m != FILL)) break;
#pragma unroll
    for (int k = 0; k < N; ++k) ldr4_if(A[k], p + k * 32, A[k].x == FILL);
  }
}
DEV bool rows_nan(float a, float b) {
  return __any_sync(0xffffffffu, a != a || b != b);
}
template <int N> DEV void slow_step(float (&acc)[N], float a0, float a1, const uint16_t* wr, uint32_t zero) {
#pragma unroll
  for (int j = 0; j < N / 4; ++j) {
    const uint32_t v = __ldg((const uint32_t*)(wr + (j >> 3) * 512 + 8 * (j & 7)));
    acc[4 * j] += a0 * bflo(v); acc[4 * j + 1] += a0 * bfhi(v); acc[4 * j + 2] += a1 * bflo(v); acc[4 * j + 3] += a1 * bfhi(v);
    if ((j & 3) == 3) wr += __float_as_uint(acc[4 * j]) & zero;
  }
}
DEV int res_off(int w, int lane) { return ((lane & 7) + 8 * (lane >> 4)) * 8 + ((2 * (w & 2) + (w & 1) + ((lane >> 2) & 2)) ^ (lane & 7)); }
DEV void res_load(uint32_t (&res)[8][2], uint32_t sa, int w, int lane) {
  const uint32_t a = sa + res_off(w, opq(lane)) * 16;
#pragma unroll
  for (int j = 0; j < 8; j += 2) {
    uint32_t r[4];
    ldsm4t(r, a + j * 1024);
    res[j][0] = r[0]; res[j][1] = r[1]; res[j + 1][0] = r[2]; res[j + 1][1] = r[3];
  }
}

DEV uint32_t after(uint32_t b, const uint32_t (&res)[8][2], uint32_t zero) {
  return b + ((res[0][0] ^ res[2][0] ^ res[4][0] ^ res[6][0]) & zero);
}

DEV void attn_phase(const Params& P, int c, int e, int w, int lane, int layer) {
  lane = opq(lane); c = opq(c);
  const int i = c >> 3, cg = c & 7, J = 16 * e + i, G = 4 * J + w;
  const int g = lane >> 2, t = lane & 3;
  float acc[96];
  uint32_t res[8][2];
  float2 cs[16];
  float4 st;
  const uint32_t csb = opq(SM_CS + 8 * t);
  {
    const uint32_t sa = SM_A + e * A_E, ba = B_A + 16 * e;
    const uint64_t da = mkdesc(sa, 8192, 1024, 1), db = mkdesc(SB, 8192, 1024, 1);
    undef(acc);
#pragma unroll
    for (int j = 0; j < 8; ++j) asm volatile("" : "=r"(res[j][0]), "=r"(res[j][1]));
    mbar_wait(B_WF, layer);
    mbar_wait(ba, 0);
    mbar_wait(B_RD + 8, layer);
    bar_sync_if(NB_T, 256, e);
    PROF(24);
#pragma unroll
    for (int j = 0; j < 4; ++j) {
      if (j == 1) { mbar_wait(ba + 8, 0); PROF(39); }
      wg_fence();
#pragma unroll
      for (int k = 0; k < 4; ++k) {
        if (j | k) wg_ss192<1>(acc, da + j * 512 + k * 128, db + wslot(j) * 512 + k * 128); else wg_ss192<0>(acc, da, db);
        if (j == 3 && k == 1) wg_commit();
      }
      wg_commit();
      if (j == 1 || j == 2) { wg_wait<1>(); mbar_arrive1_if(B_F + 8 * (j - 1), e); }
    }
    wg_wait<1>();
    bar_arrive(NB_T + e, 256);
    wg_wait<0>();
    if (cg < 4) res_load(res, sa + cg * 8192, w, lane);
    mbar_arrive1(after(B_AE + 8 * e, res, P.zero));
    PROF(25);
#pragma unroll 1
    for (uint32_t late = P.zero;; late = 1) {
      if (late) {
        const uint16_t* xr = (const uint16_t*)SCR->XF[layer] + opq(J) * 32768;
        zero(acc);
#pragma unroll 1
        for (int k = 0; k < 512; ++k)
          slow_step(acc, ldnan(xr + k * 64 + ((2 * w) ^ (k & 7)) * 8 + g), ldnan(xr + k * 64 + ((2 * w + 1) ^ (k & 7)) * 8 + g),
                    P.wqkv + (k * 1536 + 64 * cg + 2 * t), P.zero);
        const uint32_t* q = (const uint32_t*)xr + ((64 * cg + g) * 32 + t);
        const int m8 = (2 * (w & 2) + (w & 1)) ^ g;
#pragma unroll 1
        for (int it = 0; it < SPIN_LIMIT; ++it) {
          uint32_t m = 0;
#pragma unroll
          for (int z = 0; z < 16; ++z) { const uint32_t x = ldr1(q + (z >> 1) * 256 + (m8 ^ (2 * (z & 1))) * 4); m = max(m, x); res[z >> 1][z & 1] = movm(x); }
          if (__all_sync(0xffffffffu, m != FILL)) break;
        }
#pragma unroll
        for (int z = 0; z < 16; ++z) cs[z] = lds2f(csb + 256 + z * 32);
      } else {
        mbar_wait(B_CS, 0);
#pragma unroll
        for (int z = 0; z < 16; ++z) cs[z] = lds2f(csb + 256 + z * 32);
        mbar_wait(B_W4, layer);
        mbar_wait(ba, 1);
        bar_sync(NB_T + 1 - e, 256);
        PROF(26);
#pragma unroll
        for (int j = 4; j < 8; ++j) {
          if (j == 5) mbar_wait(ba + 8, 1);
          if (j >= 6) mbar_wait(B_W6 + 8 * (j - 6), layer);
          if (j > 4) PROF(31 + j);
          wg_fence();
#pragma unroll
          for (int k = 0; k < 4; ++k) {
            wg_ss192<1>(acc, da + (j & 3) * 512 + k * 128, db + wslot(j) * 512 + k * 128);
            if (j == 7 && k == 1) wg_commit();
          }
          wg_commit();
          if (j == 5) {
            if (cg >= 4) res_load(res, sa + (cg - 4) * 8192, w, lane);
            wg_wait<1>(); mbar_arrive1_if(B_F + 16, e); PROF(40);
          }

        }
      }
      uint32_t rs = hadd2(res[0][0], res[0][1]);
#pragma unroll
      for (int z = 2; z < 16; ++z) rs = hadd2(rs, res[z >> 1][z & 1]);
      const float rn = bflo(rs) + bfhi(rs);
      wg_wait<1>();
      bar_arrive_if(NB_T, 256, !(e | late));
      mbar_wait(B_ST + 8 * e, layer);
      st = lds4f(SM_STAT + ((4 * e + w) * 8 + g) * 16);
      PROF(34 + layer);
      wg_wait<0>();
      if (!rows_nan(acc[0] + rn, acc[2]) || late) break;
    }
  }
  mbar_arrive1(B_QE);
  PROF(8 + 12 * layer);
  uint32_t Q[4][4], K[4][2][2], V[4][2][2];
  {
#pragma unroll
    for (int z = 0; z < 8; ++z) {
      const float* a = acc + 32 + 4 * z; const float* b = acc + 64 + 4 * z;
      K[z >> 1][1][z & 1] = pack2((a[2] - st.z * cs[z].x) * st.w, (a[3] - st.z * cs[z].y) * st.w);
      V[z >> 1][1][z & 1] = movm(pack2((b[2] - st.z * cs[8 + z].x) * st.w, (b[3] - st.z * cs[8 + z].y) * st.w));
    }
    const uint32_t kv = SM_KV + (2 * e + (w & 1)) * 2048 + lane * 16;
    uint4* h = SCR->H[layer] + ((J * 8 + cg) * 256 + (w & 1) * 128 + lane);
    if (w >= 2) {
#pragma unroll
      for (int z = 0; z < 4; ++z) str4(h + 2048 + z * 32, K[z][1][0], K[z][1][1], V[z][1][0], V[z][1][1]);
    } else {
      mbar_wait(B_F + 16, layer);
#pragma unroll
      for (int z = 0; z < 4; ++z) sts4(kv + z * 512, K[z][1][0], K[z][1][1], V[z][1][0], V[z][1][1]);
      bar_arrive(NB_WG + e, 128);
    }
    PROF(42);
#pragma unroll
    for (int z = 0; z < 8; ++z) {
      const float* a = acc + 32 + 4 * z; const float* b = acc + 64 + 4 * z;
      K[z >> 1][0][z & 1] = pack2((a[0] - st.x * cs[z].x) * st.y, (a[1] - st.x * cs[z].y) * st.y);
      V[z >> 1][0][z & 1] = movm(pack2((b[0] - st.x * cs[8 + z].x) * st.y, (b[1] - st.x * cs[8 + z].y) * st.y));
    }
#pragma unroll
    for (int z = 0; z < 8; ++z) {
      const float2 cq = lds2f(csb + z * 32);
      const float* a = acc + 4 * z;
      Q[z >> 1][2 * (z & 1)] = pack2(a[0] - st.x * cq.x, a[1] - st.x * cq.y);
      Q[z >> 1][2 * (z & 1) + 1] = pack2(a[2] - st.z * cq.x, a[3] - st.z * cq.y);
    }
    PROF(27);
    uint4 hv[4];
    if (w >= 2) {
      bar_sync(NB_WG + e, 128);
#pragma unroll
      for (int z = 0; z < 4; ++z) hv[z] = lds4(kv + z * 512);
    } else {
#pragma unroll
      for (int z = 0; z < 4; ++z) { hv[z] = make_uint4(0, 0, 0, 0); ldr4_if(hv[z], h + z * 32, G >= 2); }
    }
    const bool p0 = 2 * t > g, p1 = 2 * t + 1 > g, first = G < 2;
    float s[4][4], mx[4][2];
#pragma unroll
    for (int z = 0; z < 4; ++z) {
      float S[4];
      mma16z(s[z], Q[z][0], Q[z][1], Q[z][2], Q[z][3], K[z][0][0], K[z][0][1]);
      mma16z(S, Q[z][0], Q[z][1], Q[z][2], Q[z][3], K[z][1][0], K[z][1][1]);
      s[z][2] = p0 ? s[z][2] : S[2]; s[z][3] = p1 ? s[z][3] : S[3];
    }
    const float sc0 = st.y * (0.25f * 1.4426950408889634f), sc1 = st.w * (0.25f * 1.4426950408889634f);
    uint32_t pw[4][2];
#pragma unroll
    for (int r = 1; r >= 0; --r) {
      if (r == 0) {
        fixo(hv, h);
        PROFD(41, hv[3].x);
#pragma unroll
        for (int z = 0; z < 4; ++z) {
          float S[4];
          mma16z(S, Q[z][0], Q[z][1], Q[z][2], Q[z][3], hv[z].x, hv[z].y);
          if (first) S[0] = S[1] = __uint_as_float(0xFF800000u);
          s[z][0] = p0 ? S[0] : s[z][0]; s[z][1] = p1 ? S[1] : s[z][1];
        }
      }
#pragma unroll
      for (int z = 0; z < 4; ++z) mx[z][r] = fmaxf(s[z][2 * r], s[z][2 * r + 1]);
#pragma unroll
      for (int o = 1; o < 3; ++o)
#pragma unroll
        for (int z = 0; z < 4; ++z) mx[z][r] = fmaxf(mx[z][r], __shfl_xor_sync(0xffffffffu, mx[z][r], o));
#pragma unroll
      for (int z = 0; z < 4; ++z) pw[z][r] = pack2(ex2((s[z][2 * r] - mx[z][r]) * (r ? sc1 : sc0)), ex2((s[z][2 * r + 1] - mx[z][r]) * (r ? sc1 : sc0)));
    }
    mbar_wait(layer ? B_N : B_Z, layer);
    const uint32_t M = (p0 ? 0xFFFFu : 0u) | (p1 ? 0xFFFF0000u : 0u);
    uint4* O = SCR->O + ((J * 8 + cg) * 512 + (2 * (w & 2) + (w & 1)) * 64 + t * 8 + g);
#pragma unroll
    for (int h2 = 0; h2 < 2; ++h2) {
      uint32_t ow[2][4];
#pragma unroll
      for (int z = 0; z < 2; ++z) {
        const int n = 2 * h2 + z;
        const uint32_t w0 = pw[n][0], w1 = pw[n][1];
        float sm[4] = {0.f, 0.f, 0.f, 0.f}, Oa[2][4];
        mma8(sm, w0, w1, 0x3F803F80u);
        mma16z(Oa[0], w0 & ~M, w1 & M, 0u, w1 & ~M, V[n][0][0], V[n][1][0]); mma8(Oa[0], w0 & M, 0u, hv[n].z);
        mma16z(Oa[1], w0 & ~M, w1 & M, 0u, w1 & ~M, V[n][0][1], V[n][1][1]); mma8(Oa[1], w0 & M, 0u, hv[n].w);
        const float i0 = rcp(sm[0]), i1 = rcp(sm[2]);
#pragma unroll
        for (int d = 0; d < 2; ++d) { ow[0][2 * z + d] = pack2(Oa[d][0] * i0, Oa[d][1] * i0); ow[1][2 * z + d] = pack2(Oa[d][2] * i1, Oa[d][3] * i1); }
      }
#pragma unroll
      for (int hi = 0; hi < 2; ++hi) str4(O + hi * 128 + h2 * 32, ow[hi][0], ow[hi][1], ow[hi][2], ow[hi][3]);
    }
  }
  if (lane == 0) str1(SCR->OF[layer] + (J * 32 + cg * 4 + w), 1);
  __syncwarp();
  mbar_arrive1(B_AT + 8 * e + (lds1(csb) & P.zero));
  PROF(9 + 12 * layer);
  float ac[32];
  undef(ac);
  const uint32_t so = SM_O + e * O_E;
  {
    const uint32_t bo = B_O + 32 * e;
    const uint64_t dw = mkdesc(SM_WO, 8192, 1024, 1), da = mkdesc(so, 512, 1024, 0);
    mbar_wait(B_WO, layer);
#pragma unroll
    for (int j = 0; j < 4; ++j) {
      mbar_wait(bo + 8 * j, layer);
      if (j == 0) { PROF(32 + layer); mbar_wait(B_AT + 8, layer); }
      wg_fence();
#pragma unroll
      for (int k = 8 * j; k < 8 * j + 8; ++k) {
        const uint64_t a = da + (k >> 2) * 512 + (k & 3) * 8, b = dw + (k & 3) * 1024 + (k >> 2) * 128;
        if (k) wg_ss64<1>(ac, a, b); else wg_ss64<0>(ac, a, b);
      }
      wg_commit();
    }
#pragma unroll 1
    for (uint32_t late = P.zero;; late = 1) {
      if (late) {
        const uint16_t* op = (const uint16_t*)(SCR->O + (J * 4096 + w * 128 + g));
        wg_wait<0>();
        zero(ac);
#pragma unroll 1
        for (int k = 0; k < 512; ++k) {
          const uint16_t* q = op + (k >> 6) * 4096 + (k & 56) * 8 + (k & 7);
          slow_step(ac, ldnan(q), ldnan(q + 512), P.wo + (((k & ~31) + 4 * (k & 6) + ((k >> 2) & 6) + (k & 1)) * 512 + 64 * cg + 2 * t), P.zero);
        }
      }
      wg_wait<0>();
      if (!rows_nan(ac[0], ac[2]) || late) break;
    }
  }
  PROF(10 + 12 * layer);
#pragma unroll
  for (int j = 0; j < 8; ++j) {
    res[j][0] = hadd2(res[j][0], pack2(ac[4 * j], ac[4 * j + 1]));
    res[j][1] = hadd2(res[j][1], pack2(ac[4 * j + 2], ac[4 * j + 3]));
  }
  if (layer == 0) {
    const float4 s = gram(res, g);
    if (t == (g >> 1))
      str4(&SCR->PS[(G * 8 + cg) * 8 + g], nzmap(__float_as_uint(s.x)), __float_as_uint(s.y), __float_as_uint(s.z), __float_as_uint(s.w));
    const int xo = (32 * (cg & 3) + t) * 2048 + (cg >> 2) * 512 + xg_off(G, g);
#pragma unroll
    for (int j = 0; j < 8; ++j) {
      str2((uint2*)SCR->XG[1] + (xo + j * 8192), nzmap(prmt(res[j][0], res[j][1], 0x5410)), prmt(res[j][0], res[j][1], 0x7632));
    }
    __syncwarp();
    mbar_arrive1(B_ED + 8 * e);
  } else {
    const uint32_t stg = so + w * 2048;
    const int row = (lane & 7) + 8 * ((lane >> 3) & 1);
    bar_sync(NB_WG + e, 128);
#pragma unroll
    for (int j = 0; j < 8; j += 2)
      stsm4(stg + row * 128 + (((j + (lane >> 4)) ^ (row & 7)) * 16), res[j][0], res[j][1], res[j + 1][0], res[j + 1][1]);
    __syncwarp();
#pragma unroll
    for (int k = 0; k < 4; ++k) {
      const int r = 4 * k + (lane >> 3);
      const uint4 v = lds4(stg + r * 128 + (((lane & 7) ^ (r & 7)) * 16));
      stw4(P.out + ((16 * G + 2 * (lane >> 3)) * 512 + 64 * cg + 8 * (lane & 7)) + ((k & 1) * 8 + (k >> 1)) * 512, v.x, v.y, v.z, v.w);
    }
  }
  PROF(11 + 12 * layer);
}

DEV void col_sums(const Params& P, int c, int wa, int lane) {
  const int i = c >> 3, cg = c & 7;
  uint4 wv[8];
#pragma unroll
  for (int k = 0; k < 8; ++k) wv[k] = ldnc4(P.wqkv + ((32 * i + (lane >> 3)) * 1536 + wa * 512 + 64 * cg + 8 * (lane & 7)) + 4 * k * 1536);
  float cs[8];
  zero(cs);
#pragma unroll
  for (int k = 0; k < 8; ++k) {
    cs[0] += bflo(wv[k].x); cs[1] += bfhi(wv[k].x); cs[2] += bflo(wv[k].y); cs[3] += bfhi(wv[k].y);
    cs[4] += bflo(wv[k].z); cs[5] += bfhi(wv[k].z); cs[6] += bflo(wv[k].w); cs[7] += bfhi(wv[k].w);
  }
  const bool b4 = lane & 16, b3 = lane & 8;
#pragma unroll
  for (int k = 0; k < 4; ++k) cs[k] = (b4 ? cs[k + 4] : cs[k]) + __shfl_xor_sync(0xffffffffu, b4 ? cs[k] : cs[k + 4], 16);
#pragma unroll
  for (int k = 0; k < 2; ++k) cs[k] = (b3 ? cs[k + 2] : cs[k]) + __shfl_xor_sync(0xffffffffu, b3 ? cs[k] : cs[k + 2], 8);
  str2((uint2*)SCR->CS + (i * 768 + wa * 256 + 32 * cg + 4 * (lane & 7) + (lane >> 3)), nzmap(__float_as_uint(cs[0])), __float_as_uint(cs[1]));
}
DEV void col_gather(const Params& P, int c, int wa, int lane) {
  const uint2* p = (const uint2*)SCR->CS + (wa * 256 + 32 * (c & 7) + lane);
#pragma unroll 1
  for (int it = 0;; ++it) {
    float a = 0.f, b = 0.f;
    uint32_t m = ~0u;
#pragma unroll
    for (int k = 0; k < 16; ++k) { const uint2 q = ldr2(p + k * 768); m = min(m, q.x); a += __uint_as_float(q.x); b += __uint_as_float(q.y); }
    if (__all_sync(0xffffffffu, m != 0u)) { sts2f(SM_CS + wa * 256 + lane * 8, a, b); break; }
    spin_guard(it);
  }
  __syncwarp();
  mbar_arrive1(B_CS);
}

DEV void aux_prologue(const Params& P, int c, int wa, int lane, uint4 (&s0)[2][2]) {
  const int g = lane >> 2, t = lane & 3, G = stat_group(c);
  {
    uint32_t w[16][2];
    const uint16_t* row = P.x0 + ((16 * G + 2 * g) * 512 + 128 * wa + 8 * t);
    bar_sync(NB_Y, 384);
    __nanosleep(KPFIRST);
#pragma unroll
    for (int z = 0; z < 8; ++z) {
      const uint4 v = ldw4(row + (z & 1) * 512 + (z >> 1) * 32);
      const int o = 4 * (z >> 1);
      w[o][z & 1] = v.x; w[o + 1][z & 1] = v.y; w[o + 2][z & 1] = v.z; w[o + 3][z & 1] = v.w;
    }
    PROF(34);
    bar_sync(0, NTHR);
    PROFD(35, w[0][0]);
    PROFD(36, w[15][1]);
    uint2* xo = (uint2*)SCR->XG[0] + ((64 * (wa & 1) + 4 * t) * 2048 + (wa >> 1) * 512 + xg_off(G, g));
#pragma unroll
    for (int n = 0; n < 16; ++n) str2(xo + (16 * (n >> 2) + (n & 3)) * 2048, nzmap(prmt(w[n][0], w[n][1], 0x5410)), prmt(w[n][0], w[n][1], 0x7632));
    const float4 s = gram(w, g);
    if (t == (g >> 1)) sts4f(SM_MISC + (wa * 8 + g) * 16, s.x, s.y, s.z, s.w);
    bar_arrive(NB_P0, 192);
  }
  PROF(2);
  if (lane == 0)
    asm volatile("cp.async.bulk.prefetch.L2.global [%0],4096;" :: "l"(wa < 3 ? P.wqkv + (3 * c + wa) * 2048 : P.wo + c * 2048) : "memory");
  sload(P, c, 32 * wa + lane, 0, s0);
}

DEV void stat_part(const Params& P, int c, int wa, int lane, int layer, int h, float (&v)[2]) {
  lane = opq(lane);
  const int e = wa >> 1;
  uint32_t x[4][4];
  mbar_wait(B_A + 16 * e, h); mbar_wait(B_A + 16 * e + 8, h);
#pragma unroll
  for (int k = 0; k < 4; ++k) ldsm4t(x[k], SM_A + e * A_E + (128 * (wa & 1) + lane) * 128 + (((c ^ lane) & 7) * 16) + k * 4096);
  float s[4] = {0.f, 0.f, 0.f, 0.f};
#pragma unroll
  for (int k = 0; k < 16; ++k) { const float a = bflo(x[k >> 2][k & 3]), b = bfhi(x[k >> 2][k & 3]); s[0] += a; s[1] += a * a; s[2] += b; s[3] += b * b; }
  s[0] += s[2]; s[1] += s[3];
  if (RARE(s[1] != s[1])) {
    const uint16_t* q = (const uint16_t*)(SCR->XF[layer] + ((32 * e + 2 * (c >> 3) + h) * 2048 + (wa & 1) * 1024)) + (lane >> 2);
    s[0] = s[1] = 0.f;
#pragma unroll 1
    for (int k = 0; k < 32; ++k) {
      const int r = 2 * (lane & 3) + (k & 1);
      const float a = ldnan(q + ((k >> 1) * 8 + r) * 64 + ((c ^ r) & 7) * 8);
      s[0] += a; s[1] += a * a;
    }
  }
  v[0] += s[0]; v[1] += s[1];
  __syncwarp();
}
DEV void stat_finish(const Params& P, int c, int wa, int lane, int layer, float (&v)[2]) {
  lane = opq(lane);
  const bool b = lane & 1;
  const float s = (b ? v[1] : v[0]) + __shfl_xor_sync(0xffffffffu, b ? v[0] : v[1], 1);
  str1((uint32_t*)SCR->ST[layer] + ((128 * (wa >> 1) + c) * 64 + (wa & 1) * 32 + lane), nzmap(__float_as_uint(s)));
  const uint4* sp = SCR->ST[layer] + ((128 * (wa >> 1) + (c & ~7) + 4 * (wa & 1) + (lane >> 3)) * 16 + (lane & 7));
  uint4 x, y;
  for (int it = 0;; ++it) {
    x = ldr4(sp); y = ldr4(sp + 8);
    if (__all_sync(0xffffffffu, min(min(min(x.x, x.y), min(x.z, x.w)), min(min(y.x, y.y), min(y.z, y.w))) != 0u)) break;
    spin_guard(it);
  }
  const uint32_t q = ln_sums((__uint_as_float(x.x) + __uint_as_float(x.z)) + (__uint_as_float(y.x) + __uint_as_float(y.z)),
                             (__uint_as_float(x.y) + __uint_as_float(x.w)) + (__uint_as_float(y.y) + __uint_as_float(y.w)));
  sts2f(SM_STAT + (16 * wa + (lane >> 4) * 8 + (lane & 7)) * 16 + (lane & 8), bflo(q), rcp(bfhi(q)));
  __syncwarp();
  mbar_arrive1(B_ST + 4 * (wa & 2));
}

DEV void nan_source(uint32_t a, int lane) {
#pragma unroll
  for (int k = 0; k < 4; ++k) sts4(a + k * 512 + lane * 16, FILL, FILL, FILL, FILL);
  fence_async_smem();
  __syncwarp();
}
DEV void load_a(const Params& P, int J, int e, int layer, int h) {
  const uint4* src = SCR->XF[layer] + (2 * J + h) * 2048;
  const uint32_t dst = SM_A + e * A_E, b = B_A + 16 * e;
  mbar_expect1(b, 8192); bulk(dst, src, 8192, b);
  mbar_expect1(b + 8, 24576); bulk(dst + 8192, src + 512, 24576, b + 8);
}
__global__ void __launch_bounds__(NTHR, 1)
fused_kernel(const __grid_constant__ Params P, const __grid_constant__ CUtensorMap mapW, const __grid_constant__ CUtensorMap mapWo,
             const __grid_constant__ CUtensorMap mapX) {
  extern __shared__ __align__(1024) uint8_t smem_raw[];
  const int warp = __shfl_sync(0xffffffffu, threadIdx.x >> 5, 0), lane = threadIdx.x & 31;
  uint32_t smid; asm volatile("mov.u32 %0,%%smid;" : "=r"(smid));
  const uint32_t* pw = (const uint32_t*)&P + threadIdx.y;
  const int role = P.role[smid + threadIdx.y] + (pw[0] & pw[12]);
  const int c = __shfl_sync(0xffffffffu, pw[1] ? role : blockIdx.x, 0);
  if (c >= 128) {
#pragma unroll 1
    for (int k = (c - 128) * NTHR + threadIdx.x; k < 131072; k += P.spare * NTHR) str4(SCR->XG[1] + k, 0, 0, 0, 0);
    __threadfence();
    __syncthreads();
    if (warp == 0) { cnt_wait(SCR->C + 1, lane); cnt_add1(SCR->C + 6); }
    __syncthreads();
#pragma unroll 1
    for (int k = (c - 128) * NTHR + threadIdx.x; k < 131072; k += P.spare * NTHR) str4(SCR->XG[0] + k, 0, 0, 0, 0);
    return;
  }
#define DONE() do {} while (0)
  const int cg = c & 7;
  if (warp < 8) {
    PROF(46);
    kgen(P, c, warp, lane);
    bar_sync(0, 256);
    PROF(1);
#pragma unroll 1
    for (int layer = 0; layer < 2; ++layer) {
#pragma unroll 1
      for (int rho = 0; rho < 2; ++rho) {
        const int wz = warp + ((rho + layer) & P.zero);
        conv_round(wz >> 2, rho, wz & 3, lane_id());
        PROF(6 + rho + 12 * layer);
      }
      const int z = layer & P.zero;
      attn_phase(P, c + z, (warp + z) >> 2, (warp + z) & 3, lane_id(), layer);
    }
    DONE();
  } else if (warp < 12) {
    asm volatile("setmaxnreg.dec.sync.aligned.u32 %0;" :: "n"(REG_AUX));
    uint4 x[2][2][2], s[2][2];
    aux_prologue(P, c, warp - 8, lane, s);
    PROF(1);
    const int c0 = c;
#pragma unroll 1
    for (int layer = 0;; ++layer) {
      const int c = c0 + (layer & P.zero), wa = warp - 8 + (layer & P.zero);
#define lane lane_id()
#define j (32 * wa + lane_id())
      {
        const uint32_t za = region(wa) + lane * 16 - 512;
        sts4(za + R_U, 0, 0, 0, 0); sts4(za + R_X5, 0, 0, 0, 0); sts4(za + R_X3, 0, 0, 0, 0);
      }
      if (lane == 0) sts4(region(wa) + R_BE, 0, 0, 0, 0);
      uint32_t u[4][4];
      uload(P, c, j, layer, x, s);
      uprep(j, 1, x[1], s[1], u);
      uprep(j, 0, x[0], s[0], u);
      fence_async_smem();
      bar_arrive(NB_U, NBARU);
      bar_sync(NB_H, 192);
      PROF(5 + 12 * layer);
      box_full(j, u, P.zero);
      PROF(3 + 12 * layer);
      mbar_wait(B_Z, 0);
      conv_out(c, j, 0, x, u[0], SCR->XF[layer], P.zero);
      PROF(32);
      conv_out(c, j, 1, x, u[1], SCR->XF[layer], P.zero);
      PROF(6 + 12 * layer);
      if (layer == 0 && wa < 3) col_sums(P, c, wa, lane);
      conv_out(c, j, 2, x, u[2], SCR->XF[layer], P.zero);
      PROF(33);
      conv_out(c, j, 3, x, u[3], SCR->XF[layer], P.zero);
      PROF(7 + 12 * layer);
      float v[2];
      zero(v);
      stat_part(P, c, wa, lane, layer, 0, v);
      mbar_arrive1(B_AE + 4 * (wa & 2));
      if (layer == 0 && wa < 3) col_gather(P, c, wa, lane);
      stat_part(P, c, wa, lane, layer, 1, v);
      PROF(9 + 12 * layer);
      stat_finish(P, c, wa, lane, layer, v);
      PROF(8 + 12 * layer);
      if (layer) break;
      sload(P, c, j, 1, s);
#undef lane
#undef j
    }
    DONE();
  } else {
    asm volatile("setmaxnreg.dec.sync.aligned.u32 %0;" :: "n"(REG_PROD));
    if (s2u(smem_raw) != SB) __trap();
#pragma unroll 1
    for (int n = warp - 12; n < 38; n += 4)
      asm volatile("{.reg .pred p; elect.sync _|p,0xffffffff; @p mbarrier.init.shared::cta.b64 [%0],%1;}"
                   :: "r"(SM_BAR + n * 8), "r"(n > 14 ? 1 : (int)(0x322866444444444ull >> (4 * n)) & 15) : "memory");
    fence_async_smem();
    bar_sync(0, NTHR);
    PROF(1);
    if (warp == 12) {
      if (lane == 0) {
        asm volatile("prefetch.tensormap [%0];" :: "l"(&mapW) : "memory");
        asm volatile("prefetch.tensormap [%0];" :: "l"(&mapWo) : "memory");
        asm volatile("prefetch.tensormap [%0];" :: "l"(&mapX) : "memory");
      }
      nan_source(slot(12), lane);
      mbar_wait(B_U, 0);
#pragma unroll 1
      for (int k = 0; k < 8; ++k) tma2_store(&mapX, slot(12), 128 * c, 8 * k);
#pragma unroll 1
      for (int k = 0; k < 4; ++k) bulk_store(SCR->H[0] + ((c + 8) * 256 + (k >> 1) * 32768 + (k & 1) * 128), slot(12), 2048);
#pragma unroll 1
      for (int k = 0; k < 8; ++k) bulk_store(SCR->O + (c * 512 + (k >> 2) * 65536 + (k & 3) * 128), slot(12), 2048);
      bulk_wait();
      mbar_arrive1(B_Z);
      PROF(24);
#pragma unroll 1
      for (int layer = 0; layer < 2; ++layer) {
        mbar_wait(B_V, layer);
        if (layer == 1 && c < 4 && ((0x47 >> lane) & 1)) str1(SCR->C + c * 32 + lane, 0);
        mbar_expect1(B_WF, 4 * 24576);
#pragma unroll
        for (int k = 0; k < 4; ++k) tma3(slot(wslot(k)), &mapW, 64 * cg, 64 * k, 0, B_WF);
        mbar_wait(B_WF, layer);
        mbar_expect1(B_W4, 2 * 24576);
#pragma unroll
        for (int k = 4; k < 6; ++k) tma3(slot(wslot(k)), &mapW, 64 * cg, 64 * k, 0, B_W4);
        bar_sync(NB_AUX, 64);
#pragma unroll 1
        for (int k = 0; k < 2; ++k) {
          mbar_expect1(B_W6 + 8 * k, 24576);
          mbar_wait(B_F + 8 * k, layer);
          tma3(slot(3 * k), &mapW, 64 * cg, 384 + 64 * k, 0, B_W6 + 8 * k);
        }
        mbar_expect1(B_WO, 65536);
        mbar_wait(B_AE + 8, layer);
        nan_source(slot(12), lane);
        uint4* fp = layer ? SCR->O + c * 512 : SCR->XF[1] + c * 512;
#pragma unroll 1
        for (int r = 7; r >= 0; --r) {
          __nanosleep(KWOP);
          if (r >= 4) {
            bulk_store(fp + (r & 3) * 128, slot(12), 2048); bulk_store(fp + 65536 + (r & 3) * 128, slot(12), 2048);
            if (layer == 0) bulk_store(SCR->H[1] + ((c + 8) * 256 + (r & 2) * 16384 + (r & 1) * 128), slot(12), 2048);
          }
          if (r == KFR) { bulk_wait(); __threadfence(); mbar_arrive1(B_N); PROF(9 + 12 * layer); }
          if (r == 1) mbar_wait(B_F + 16, layer);
          tma4(SM_WO + r * 8192, &mapWo, 64 * cg, 0, r >> 1, 32 * (r & 1), B_WO);
        }
        PROF(8 + 12 * layer);
      }
      DONE();
    } else if (warp == 13) {
      const int G = stat_group(c);
#pragma unroll 1
      for (int layer = 0; layer < 2; ++layer) {
        float z[4];
        if (layer == 0) {
          bar_sync(NB_P0, 192);
          const float4 a = lds4f(SM_MISC + lane * 16);
          z[0] = a.x; z[1] = a.y; z[2] = a.z; z[3] = a.w;
        } else {
          mbar_wait(B_ED + 2 * (c & 4), 0);
          uint4* ps = &SCR->PS[G * 64 + lane];
          uint4 a, b;
          for (int it = 0;; ++it) {
            a = ldr4(ps); b = ldr4(ps + 32);
            if (__all_sync(0xffffffffu, min(a.x, b.x) != 0u)) break;
            spin_guard(it);
          }
          z[0] = __uint_as_float(a.x) + __uint_as_float(b.x); z[1] = __uint_as_float(a.y) + __uint_as_float(b.y);
          z[2] = __uint_as_float(a.z) + __uint_as_float(b.z); z[3] = __uint_as_float(a.w) + __uint_as_float(b.w);
        }
#pragma unroll
        for (int o = 8; o < 32; o <<= 1)
#pragma unroll
          for (int k = 0; k < 4; ++k) z[k] += __shfl_xor_sync(0xffffffffu, z[k], o);
        const uint32_t w0 = ln_sums(z[0], z[1]), w1 = ln_sums(z[2], z[3]);
        const uint32_t r = nzmap(pack2(rcp(bfhi(w0)), rcp(bfhi(w1)))), m = prmt(w0, w1, 0x5410);
        uint2* so = (uint2*)&SCR->SR[layer][lane >> 3][sr_off(G, lane)] + (lane & 1);
        str2(so, r, m); str2(so + 4 * 1024, r, m);
        PROF(4 + 12 * layer);
        bar_sync(NB_H, 192);
        box_help(0, lane);
        box_help(2, lane);
        PROF(6 + 12 * layer);
      }
      DONE();
    } else if (warp == 14) {
#pragma unroll 1
      for (int layer = 0; layer < 2; ++layer) {
        if (layer) { mbar_wait(B_N, 0); mbar_wait(B_ED, 0); mbar_wait(B_ED + 8, 0); } else bar_sync(NB_P0, 192);
        cnt_add1(SCR->C + (c >> 5) * 32 + 3 * layer);
        if (layer == 0) bar_arrive(NB_P0 + 1, 288);
        mbar_expect1(B_E, 16384);
        PROF(4 + 12 * layer);
        cnt_wait(SCR->C + 3 * layer, lane);
        mbar_arrive1(B_U);
        bulk(SM_X, SCR->XG[layer] + c * 1024, 16384, B_E);
        PROF(5 + 12 * layer);
        if (layer == 0) {
          mbar_wait(B_Z, 0);
          __threadfence();
          mbar_arrive1(B_Z + 8);
          PROF(11);
        }
        mbar_wait(B_RD, layer);
        cnt_wait(SCR->C + 3 * layer + 1, lane);
        load_a(P, c >> 3, 0, layer, 0);
        PROF(6 + 12 * layer);
        mbar_wait(B_RD + 8, layer);
        load_a(P, 16 + (c >> 3), 1, layer, 0);
        cnt_wait(SCR->C + 3 * layer + 2, lane);
        PROF(7 + 12 * layer);
        mbar_wait(B_AE, layer);
        load_a(P, c >> 3, 0, layer, 1);
        bar_arrive(NB_AUX, 64);
        PROF(8 + 12 * layer);
        mbar_wait(B_AE + 8, layer);
        load_a(P, 16 + (c >> 3), 1, layer, 1);
        if (layer == 0)
          for (int it = 0; ldr1(SCR->C + 6) < P.spare; ++it) spin_guard(it);
        mbar_wait(B_QE, layer);
#pragma unroll 1
        for (int e = 0; e < 2; ++e) {
          const int J = 16 * e + (c >> 3);
          mbar_wait(B_AT + 8 * e, layer);
          uint32_t todo = 0x01010101u;
#pragma unroll 1
          for (int it = 0; todo; ++it) {
            uint32_t m = __ballot_sync(0xffffffffu, ldr1(SCR->OF[layer] + J * 32 + lane) != 0u);
            m &= m >> 4; m &= m >> 2; m &= m >> 1; m &= todo;
            todo ^= m;
#pragma unroll 1
            for (; m; m &= m - 1) {
              const int j = __ffs(m) - 1;
              mbar_expect1(B_O + 32 * e + j, 16384);
              bulk(SM_O + e * O_E + 2048 * j, SCR->O + (J * 4096 + j * 128), 16384, B_O + 32 * e + j);
            }
            spin_guard(it);
          }
          PROF(9 + e + 12 * layer);
        }
      }
      DONE();
    }
    if (warp == 15) {
      const int G = stat_group(c);
      str4(&SCR->ST[0][(lane >> 4) * 2048 + c * 16 + (lane & 15)], 0, 0, 0, 0); str4(&SCR->ST[1][(lane >> 4) * 2048 + c * 16 + (lane & 15)], 0, 0, 0, 0);
      if (lane < 4) str4(SCR->OF[lane >> 1] + ((lane & 1) * 512 + c * 4), 0, 0, 0, 0);
      str4(&SCR->PS[G * 64 + lane], 0, 0, 0, 0); str4(&SCR->PS[G * 64 + 32 + lane], 0, 0, 0, 0);
      str4(&SCR->SR[1][lane >> 2][sr_off(G, 2 * lane)], 0, 0, 0, 0);
      if (c < 4 && lane < 3) str1(SCR->C + c * 32 + 3 + lane, 0);
#pragma unroll
      for (int k = 0; k < 3; ++k) str2((uint2*)SCR->CS + ((c >> 3) * 768 + k * 256 + 32 * cg + lane), 0, 0);
      __threadfence();
#pragma unroll 1
      for (int layer = 0; layer < 2; ++layer) {
        PROF(4 + 12 * layer);
        bar_sync(NB_H, 192);
        box_help(1, lane);
        box_help(3, lane);
        if (layer) str4(&SCR->SR[0][lane >> 2][sr_off(G, 2 * lane)], 0, 0, 0, 0);
        mbar_wait(B_Z + 8, 0);
        mbar_wait(B_RD, layer);
        cnt_add1(SCR->C + (c >> 5) * 32 + 3 * layer + 1);
        mbar_wait(B_RD + 8, layer);
        cnt_add1(SCR->C + (c >> 5) * 32 + 3 * layer + 2);
        if (P.spare == 0) {
#pragma unroll 1
          for (int k = 0; k < 32; ++k) str4(SCR->XG[layer] + (c * 1024 + k * 32 + lane), 0, 0, 0, 0);
        }
      }
    }
  }
}

typedef CUresult (*EncodeFn)(CUtensorMap*, CUtensorMapDataType, cuuint32_t, void*, const cuuint64_t*, const cuuint64_t*,
                             const cuuint32_t*, const cuuint32_t*, CUtensorMapInterleave, CUtensorMapSwizzle,
                             CUtensorMapL2promotion, CUtensorMapFloatOOBfill);

static int place_roles(uint8_t* role) {
  int dev = 0, nsm = 0;
  cudaGetDevice(&dev);
  cudaDeviceGetAttribute(&nsm, cudaDevAttrMultiProcessorCount, dev);
  if (nsm <= 128 || nsm > 144 || (nsm & 1)) return 0;
  cudaFuncSetAttribute(fused_kernel, cudaFuncAttributeNonPortableClusterSizeAllowed, 1);
  int occ[9] = {0};
  for (int k = 2; k <= 8; ++k) {
    cudaLaunchConfig_t cfg = {};
    cudaLaunchAttribute at[1];
    at[0].id = cudaLaunchAttributeClusterDimension;
    at[0].val.clusterDim.x = 2 * k; at[0].val.clusterDim.y = 1; at[0].val.clusterDim.z = 1;
    cfg.gridDim = dim3(2 * k); cfg.blockDim = dim3(NTHR); cfg.dynamicSmemBytes = SM_TOTAL; cfg.attrs = at; cfg.numAttrs = 1;
    if (cudaOccupancyMaxActiveClusters(&occ[k], fused_kernel, &cfg) != cudaSuccess) { cudaGetLastError(); occ[k] = 0; }
  }
  int n[10];
  n[7] = occ[8]; n[6] = occ[7]; n[5] = occ[6] - 0; n[4] = occ[5];
  n[3] = occ[4] - n[7]; n[1] = occ[2] - n[3] - n[5] - n[7]; n[0] = n[2] = n[1];
  n[8] = occ[3] - n[2] - n[5];
  const int ntpc = nsm / 2;
  int sum = 0;
  bool ok = n[0] > 0 && n[0] <= 8;
  for (int r = 0; r < 9; ++r) { ok = ok && n[r] >= 0 && (r == 0 || n[r] <= n[r - 1]); sum += n[r]; }
  if (!ok || sum > ntpc) { for (int r = 0; r < 9; ++r) n[r] = r < 8 ? 8 : 0; sum = 64; }
  int tp[8][9], cnt[8] = {0}, pool[72], np = 0, id = 0;
  for (int r = 0; r < 9; ++r)
    for (int g = n[0] - n[r]; g < n[0]; ++g) tp[g][cnt[g]++] = id++;
  for (; id < ntpc; ++id) pool[np++] = id;
  int order[72], no = 0;
  for (int g = 0; g < n[0]; ++g) {
    const int full = cnt[g] / 4 * 4;
    for (int k = 0; k < cnt[g]; ++k) { if (k < full) order[no++] = tp[g][k]; else pool[np++] = tp[g][k]; }
  }
  for (int k = 0; k < np; ++k) order[no++] = pool[k];
  for (int k = 0; k < ntpc; ++k) { role[2 * order[k]] = 2 * k; role[2 * order[k] + 1] = 2 * k + 1; }
  return nsm;
}

extern "C" void kernel_launch(void* const* d_in, const int* in_sizes, int n_in, void* d_out, int out_size) {
  (void)in_sizes; (void)n_in; (void)out_size;
  static EncodeFn enc = nullptr;
  static uint8_t role[144];
  static int nsm = 0;
  static Scratch* scratch = nullptr;
  if (!enc) {
    void* fn = nullptr;
    cudaDriverEntryPointQueryResult qr;
    cudaGetDriverEntryPoint("cuTensorMapEncodeTiled", &fn, cudaEnableDefault, &qr);
    enc = (EncodeFn)fn;
    cudaFuncSetAttribute(fused_kernel, cudaFuncAttributeMaxDynamicSharedMemorySize, SM_TOTAL);
    nsm = place_roles(role);
    cudaGetSymbolAddress((void**)&scratch, g_S);
  }
  CUtensorMap mW, mWo, mX;
  {
    cuuint64_t dim[3] = {512, 512, 3}, str[2] = {3072, 1024};
    cuuint32_t box[3] = {64, 64, 3}, es[3] = {1, 1, 1};
    enc(&mW, CU_TENSOR_MAP_DATA_TYPE_BFLOAT16, 3, d_in[10], dim, str, box, es, CU_TENSOR_MAP_INTERLEAVE_NONE,
        CU_TENSOR_MAP_SWIZZLE_128B, CU_TENSOR_MAP_L2_PROMOTION_NONE, CU_TENSOR_MAP_FLOAT_OOB_FILL_NONE);
  }
  {
    cuuint64_t dim[4] = {512, 2, 4, 64}, str[3] = {1024, 2048, 8192};
    cuuint32_t box[4] = {64, 2, 1, 32}, es[4] = {1, 1, 1, 1};
    enc(&mWo, CU_TENSOR_MAP_DATA_TYPE_BFLOAT16, 4, d_in[11], dim, str, box, es, CU_TENSOR_MAP_INTERLEAVE_NONE,
        CU_TENSOR_MAP_SWIZZLE_128B, CU_TENSOR_MAP_L2_PROMOTION_NONE, CU_TENSOR_MAP_FLOAT_OOB_FILL_NONE);
  }
  {
    cuuint64_t dim[2] = {16384, 64}, str[1] = {32768};
    cuuint32_t box[2] = {128, 8}, es[2] = {1, 1};
    enc(&mX, CU_TENSOR_MAP_DATA_TYPE_BFLOAT16, 2, scratch->XF[0], dim, str, box, es, CU_TENSOR_MAP_INTERLEAVE_NONE,
        CU_TENSOR_MAP_SWIZZLE_NONE, CU_TENSOR_MAP_L2_PROMOTION_NONE, CU_TENSOR_MAP_FLOAT_OOB_FILL_NONE);
  }
  Params P;
  P.x0 = (const uint16_t*)d_in[0]; P.Are = (const uint16_t*)d_in[1]; P.Aim = (const uint16_t*)d_in[2];
  P.Bre = (const uint16_t*)d_in[3]; P.Bim = (const uint16_t*)d_in[4]; P.Cre = (const uint16_t*)d_in[5];
  P.Cim = (const uint16_t*)d_in[6]; P.logdt = (const uint16_t*)d_in[7]; P.dskip = (const uint16_t*)d_in[8];
  P.wqkv = (const uint16_t*)d_in[10]; P.wo = (const uint16_t*)d_in[11]; P.out = (uint16_t*)d_out;
  for (int k = 0; k < 144; ++k) P.role[k] = role[k];
  P.zero = 0;
  P.mid = (char*)scratch->C;
  P.spare = nsm > 0 ? nsm - 128 : 0;
  fused_kernel<<<nsm > 0 ? nsm : 128, NTHR, SM_TOTAL, cudaStreamPerThread>>>(P, mW, mWo, mX);
}
```

```cpp
#include <cuda_runtime.h>
#include <cuda_bf16.h>
#include <cuda.h>
#include <stdint.h>
#include <stddef.h>

#define DEV __device__ __forceinline__
#define RARE(x) __builtin_expect(!!(x), 0)

constexpr int NTHR = 512;
constexpr int REG_MAIN = 192, REG_AUX = 96, REG_PROD = 32;
constexpr int NBARU = 384;
constexpr int SPIN_LIMIT = 1 << 22;

constexpr uint32_t SB = 1024;
__host__ __device__ constexpr uint32_t slot(int n) { return SB + n * 8192; }
__host__ __device__ constexpr int wslot(int k) { return k < 2 ? 3 * k : k < 4 ? 3 * k + 6 : k < 6 ? 21 - 3 * k : 3 * k - 18; }
constexpr uint32_t SM_A = slot(22), A_E = 0u - 32768;
constexpr uint32_t SM_O = slot(18), O_E = 0u - 147456;
constexpr uint32_t SM_WO = slot(10), SM_X = slot(8), SM_KV = slot(9);
constexpr uint32_t SM_TAP  = slot(26);
constexpr int TAP_SZ = 3440;
constexpr uint32_t SM_STAT = SM_TAP + 4 * TAP_SZ;
constexpr uint32_t SM_CS   = SM_STAT + 1024;
constexpr uint32_t SM_MISC = SM_CS + 768;
constexpr uint32_t SM_BAR  = SM_MISC + 528;
constexpr int SM_TOTAL = SM_BAR + 304 - SB;
static_assert(SM_TOTAL <= 232448, "");
constexpr int R_SZ = 16384, R_U = 512, R_X5 = 5120, R_X3 = 8704, R_BO = 11776, R_BE = 13824;
constexpr int X_5 = 576, X_3 = 648, T_E = 2 * 720, T_O = 1600 + 2 * 721, T_C = 3390, T_K = 3424;
constexpr uint32_t B_RD = SM_BAR, B_ED = SM_BAR + 16, B_F = SM_BAR + 32, B_AT = SM_BAR + 56;
constexpr uint32_t B_AE = SM_BAR + 72, B_QE = SM_BAR + 88, B_ST = SM_BAR + 96, B_CS = SM_BAR + 112;
constexpr uint32_t B_WO = SM_BAR + 120, B_W6 = SM_BAR + 128, B_U = SM_BAR + 144, B_E = SM_BAR + 152, B_A = SM_BAR + 160, B_O = SM_BAR + 192,
                   B_Z = SM_BAR + 256, B_WF = SM_BAR + 272, B_W4 = SM_BAR + 280, B_N = SM_BAR + 288, B_V = SM_BAR + 296;
constexpr int NB_U = 1, NB_B = 2, NB_K = 8, NB_Y = 6, NB_WG = 8, NB_T = 10, NB_AUX = 12, NB_P0 = 13, NB_H = 15;

struct Scratch {
  uint4    XG[2][128 * 1024];
  uint4    O[32 * 8 * 512];
  uint32_t C[8 * 32];
  uint32_t OF[2][32 * 32];
  uint4    CS[16 * 1536 / 4];
  uint4    PS[128 * 64];
  uint4    ST[2][32 * 128];
  uint4    SR[2][8][512];
  uint4    XF[2][32 * 512 * 8];
  uint4    H[2][33 * 8 * 256];
};
__device__ __align__(1024) Scratch g_S;
#define SCR ((Scratch*)(P.mid - offsetof(Scratch, C)))
#define PROFD(slot, v) do {} while (0)
#define PROF(slot) do {} while (0)

DEV uint32_t s2u(const void* p) { return (uint32_t)__cvta_generic_to_shared(p); }
template <class T> DEV T opq(T x) { asm volatile("" : "+r"(x)); return x; }
DEV int lane_id() { int l; asm volatile("mov.u32 %0,%%laneid;" : "=r"(l)); return l; }
DEV uint32_t pack2(float lo, float hi) { uint32_t d; asm("cvt.rn.bf16x2.f32 %0,%1,%2;" : "=r"(d) : "f"(hi), "f"(lo)); return d; }
DEV float bflo(uint32_t v) { return __uint_as_float(v << 16); }
DEV float bfhi(uint32_t v) { return __uint_as_float(v & 0xFFFF0000u); }
DEV float bfr(float x) { return bflo(pack2(x, 0.f)); }
DEV uint32_t hadd2(uint32_t a, uint32_t b) { uint32_t d; asm("add.rn.bf16x2 %0,%1,%2;" : "=r"(d) : "r"(a), "r"(b)); return d; }
DEV uint32_t hsub2(uint32_t a, uint32_t b) { uint32_t d; asm("sub.rn.bf16x2 %0,%1,%2;" : "=r"(d) : "r"(a), "r"(b)); return d; }
DEV uint32_t hmul2(uint32_t a, uint32_t b) { uint32_t d; asm("mul.rn.bf16x2 %0,%1,%2;" : "=r"(d) : "r"(a), "r"(b)); return d; }
DEV uint32_t hfma2(uint32_t a, uint32_t b, uint32_t c) { uint32_t d; asm("fma.rn.bf16x2 %0,%1,%2,%3;" : "=r"(d) : "r"(a), "r"(b), "r"(c)); return d; }
DEV uint32_t hmax2(uint32_t a, uint32_t b) { uint32_t d; asm("max.bf16x2 %0,%1,%2;" : "=r"(d) : "r"(a), "r"(b)); return d; }
DEV uint32_t prmt(uint32_t a, uint32_t b, uint32_t s) { uint32_t d; asm("prmt.b32 %0,%1,%2,%3;" : "=r"(d) : "r"(a), "r"(b), "r"(s)); return d; }
DEV uint32_t nzmap(uint32_t v) { return v == 0u ? 0x80000000u : v; }
DEV float rcp(float x) { float y; asm("rcp.approx.ftz.f32 %0,%1;" : "=f"(y) : "f"(x)); return y; }
DEV float sqrt_(float x) { float y; asm("sqrt.approx.ftz.f32 %0,%1;" : "=f"(y) : "f"(x)); return y; }
DEV float ex2(float x) { float y; asm("ex2.approx.ftz.f32 %0,%1;" : "=f"(y) : "f"(x)); return y; }

DEV uint4 ldr4(const void* p) { uint4 v; asm volatile("ld.relaxed.gpu.global.v4.u32 {%0,%1,%2,%3},[%4];" : "=r"(v.x), "=r"(v.y), "=r"(v.z), "=r"(v.w) : "l"(p) : "memory"); return v; }
DEV void ldr4_if(uint4& v, const void* p, bool c) {
  asm volatile("{.reg .pred q; setp.ne.u32 q,%5,0; @q ld.relaxed.gpu.global.v4.u32 {%0,%1,%2,%3},[%4];}"
    : "+r"(v.x), "+r"(v.y), "+r"(v.z), "+r"(v.w) : "l"(p), "r"((uint32_t)c) : "memory");
}
DEV uint2 ldr2(const void* p) { uint2 v; asm volatile("ld.relaxed.gpu.global.v2.u32 {%0,%1},[%2];" : "=r"(v.x), "=r"(v.y) : "l"(p) : "memory"); return v; }
DEV void ldr2_if(uint2& v, const void* p, bool c) {
  asm volatile("{.reg .pred q; setp.ne.u32 q,%3,0; @q ld.relaxed.gpu.global.v2.u32 {%0,%1},[%2];}" : "+r"(v.x), "+r"(v.y) : "l"(p), "r"((uint32_t)c) : "memory");
}
DEV uint32_t ldr1(const void* p) { uint32_t v; asm volatile("ld.relaxed.gpu.global.u32 %0,[%1];" : "=r"(v) : "l"(p) : "memory"); return v; }
DEV float ldnan(const uint16_t* p) {
  uint32_t v = 0xFFFFu;
#pragma unroll 1
  for (int it = 0; it < SPIN_LIMIT && __any_sync(0xffffffffu, v == 0xFFFFu); ++it) asm volatile("ld.relaxed.gpu.global.u16 %0,[%1];" : "=r"(v) : "l"(p) : "memory");
  return __uint_as_float(v << 16);
}
DEV uint4 ldw4(const void* p) { uint4 v; asm volatile("ld.global.v4.u32 {%0,%1,%2,%3},[%4];" : "=r"(v.x), "=r"(v.y), "=r"(v.z), "=r"(v.w) : "l"(p) : "memory"); return v; }
DEV uint2 ldw2(const void* p) { uint2 v; asm volatile("ld.global.v2.u32 {%0,%1},[%2];" : "=r"(v.x), "=r"(v.y) : "l"(p) : "memory"); return v; }
DEV uint32_t ldw1(const void* p) { uint32_t v; asm volatile("ld.global.u32 %0,[%1];" : "=r"(v) : "l"(p) : "memory"); return v; }
DEV void str4(void* p, uint32_t a, uint32_t b, uint32_t c, uint32_t d) { asm volatile("st.relaxed.gpu.global.v4.u32 [%0],{%1,%2,%3,%4};" :: "l"(p), "r"(a), "r"(b), "r"(c), "r"(d) : "memory"); }
DEV void str2(void* p, uint32_t a, uint32_t b) { asm volatile("st.relaxed.gpu.global.v2.u32 [%0],{%1,%2};" :: "l"(p), "r"(a), "r"(b) : "memory"); }
DEV void str1(void* p, uint32_t a) { asm volatile("st.relaxed.gpu.global.u32 [%0],%1;" :: "l"(p), "r"(a) : "memory"); }
DEV void str4_if(void* p, uint32_t a, uint32_t b, uint32_t c, uint32_t d, bool q) {
  asm volatile("{.reg .pred q; setp.ne.u32 q,%5,0; @q st.relaxed.gpu.global.v4.u32 [%0],{%1,%2,%3,%4};}" :: "l"(p), "r"(a), "r"(b), "r"(c), "r"(d), "r"((uint32_t)q) : "memory");
}
DEV void stw4(void* p, uint32_t a, uint32_t b, uint32_t c, uint32_t d) { asm volatile("st.global.v4.u32 [%0],{%1,%2,%3,%4};" :: "l"(p), "r"(a), "r"(b), "r"(c), "r"(d) : "memory"); }
DEV uint4 ldnc4(const void* p) { uint4 v; asm volatile("ld.global.nc.v4.u32 {%0,%1,%2,%3},[%4];" : "=r"(v.x), "=r"(v.y), "=r"(v.z), "=r"(v.w) : "l"(p)); return v; }
DEV uint32_t ldnc1(const void* p) { uint32_t v; asm volatile("ld.global.nc.u32 %0,[%1];" : "=r"(v) : "l"(p)); return v; }
DEV uint2 ldnc2(const void* p) { uint2 v; asm volatile("ld.global.nc.v2.u32 {%0,%1},[%2];" : "=r"(v.x), "=r"(v.y) : "l"(p)); return v; }

DEV uint2 lds2(uint32_t a) { uint2 v; asm volatile("ld.volatile.shared.v2.u32 {%0,%1},[%2];" : "=r"(v.x), "=r"(v.y) : "r"(a)); return v; }
DEV float lds16f(uint32_t a) { uint32_t v; asm volatile("ld.shared.u16 %0,[%1];" : "=r"(v) : "r"(a)); return __uint_as_float(v << 16); }
DEV void sts2(uint32_t a, uint32_t x, uint32_t y) { asm volatile("st.shared.v2.u32 [%0],{%1,%2};" :: "r"(a), "r"(x), "r"(y) : "memory"); }
DEV uint32_t lds1(uint32_t a) { uint32_t v; asm volatile("ld.volatile.shared.u32 %0,[%1];" : "=r"(v) : "r"(a)); return v; }
DEV uint32_t lds1z(uint32_t a, bool c) {
  uint32_t v; asm volatile("{.reg .pred q; setp.ne.u32 q,%2,0; mov.u32 %0,0; @q ld.volatile.shared.u32 %0,[%1];}" : "=r"(v) : "r"(a), "r"((uint32_t)c)); return v;
}
DEV uint4 lds4z(uint32_t a, bool c) {
  uint4 v = make_uint4(0, 0, 0, 0);
  asm volatile("{.reg .pred q; setp.ne.u32 q,%5,0; @q ld.volatile.shared.v4.u32 {%0,%1,%2,%3},[%4];}" : "+r"(v.x), "+r"(v.y), "+r"(v.z), "+r"(v.w) : "r"(a), "r"((uint32_t)c));
  return v;
}
DEV float lds1f(uint32_t a) { float v; asm volatile("ld.shared.f32 %0,[%1];" : "=f"(v) : "r"(a)); return v; }
DEV float2 lds2f(uint32_t a) { float2 v; asm volatile("ld.shared.v2.f32 {%0,%1},[%2];" : "=f"(v.x), "=f"(v.y) : "r"(a)); return v; }
DEV float4 lds4f(uint32_t a) { float4 v; asm volatile("ld.shared.v4.f32 {%0,%1,%2,%3},[%4];" : "=f"(v.x), "=f"(v.y), "=f"(v.z), "=f"(v.w) : "r"(a)); return v; }
DEV uint4 lds4(uint32_t a) { uint4 v; asm volatile("ld.volatile.shared.v4.u32 {%0,%1,%2,%3},[%4];" : "=r"(v.x), "=r"(v.y), "=r"(v.z), "=r"(v.w) : "r"(a)); return v; }
DEV void sts1(uint32_t a, uint32_t v) { asm volatile("st.shared.u32 [%0],%1;" :: "r"(a), "r"(v) : "memory"); }
DEV void sts16(uint32_t a, uint32_t v) { asm volatile("{.reg .b16 h; cvt.u16.u32 h,%1; st.shared.u16 [%0],h;}" :: "r"(a), "r"(v) : "memory"); }
DEV void sts2f(uint32_t a, float x, float y) { asm volatile("st.shared.v2.f32 [%0],{%1,%2};" :: "r"(a), "f"(x), "f"(y) : "memory"); }
DEV void sts4f(uint32_t a, float x, float y, float z, float w) { asm volatile("st.shared.v4.f32 [%0],{%1,%2,%3,%4};" :: "r"(a), "f"(x), "f"(y), "f"(z), "f"(w) : "memory"); }
DEV void sts4(uint32_t a, uint32_t x, uint32_t y, uint32_t z, uint32_t w) { asm volatile("st.shared.v4.u32 [%0],{%1,%2,%3,%4};" :: "r"(a), "r"(x), "r"(y), "r"(z), "r"(w) : "memory"); }

DEV void ldsm4(uint32_t (&r)[4], uint32_t a) { asm volatile("ldmatrix.sync.aligned.m8n8.x4.shared.b16 {%0,%1,%2,%3},[%4];" : "=r"(r[0]), "=r"(r[1]), "=r"(r[2]), "=r"(r[3]) : "r"(a) : "memory"); }
DEV void ldsm4t(uint32_t (&r)[4], uint32_t a) { asm volatile("ldmatrix.sync.aligned.m8n8.x4.trans.shared.b16 {%0,%1,%2,%3},[%4];" : "=r"(r[0]), "=r"(r[1]), "=r"(r[2]), "=r"(r[3]) : "r"(a) : "memory"); }
DEV void ldsm2(uint32_t (&r)[2], uint32_t a) { asm volatile("ldmatrix.sync.aligned.m8n8.x2.shared.b16 {%0,%1},[%2];" : "=r"(r[0]), "=r"(r[1]) : "r"(a) : "memory"); }
DEV void stsm4(uint32_t a, uint32_t r0, uint32_t r1, uint32_t r2, uint32_t r3) { asm volatile("stmatrix.sync.aligned.m8n8.x4.shared.b16 [%0],{%1,%2,%3,%4};" :: "r"(a), "r"(r0), "r"(r1), "r"(r2), "r"(r3) : "memory"); }
DEV void stsm2(uint32_t a, uint32_t r0, uint32_t r1) { asm volatile("stmatrix.sync.aligned.m8n8.x2.shared.b16 [%0],{%1,%2};" :: "r"(a), "r"(r0), "r"(r1) : "memory"); }
DEV void stsm4t(uint32_t a, uint32_t r0, uint32_t r1, uint32_t r2, uint32_t r3) { asm volatile("stmatrix.sync.aligned.m8n8.x4.trans.shared.b16 [%0],{%1,%2,%3,%4};" :: "r"(a), "r"(r0), "r"(r1), "r"(r2), "r"(r3) : "memory"); }
DEV uint32_t movm(uint32_t a) { uint32_t d; asm volatile("movmatrix.sync.aligned.m8n8.trans.b16 %0,%1;" : "=r"(d) : "r"(a)); return d; }
DEV void mma16(float (&d)[4], uint32_t a0, uint32_t a1, uint32_t a2, uint32_t a3, uint32_t b0, uint32_t b1) {
  asm volatile("mma.sync.aligned.m16n8k16.row.col.f32.bf16.bf16.f32 {%0,%1,%2,%3},{%4,%5,%6,%7},{%8,%9},{%0,%1,%2,%3};"
    : "+f"(d[0]), "+f"(d[1]), "+f"(d[2]), "+f"(d[3]) : "r"(a0), "r"(a1), "r"(a2), "r"(a3), "r"(b0), "r"(b1));
}
DEV void mma16z(float (&d)[4], uint32_t a0, uint32_t a1, uint32_t a2, uint32_t a3, uint32_t b0, uint32_t b1) {
  asm volatile("mma.sync.aligned.m16n8k16.row.col.f32.bf16.bf16.f32 {%0,%1,%2,%3},{%4,%5,%6,%7},{%8,%9},{%10,%10,%10,%10};"
    : "=f"(d[0]), "=f"(d[1]), "=f"(d[2]), "=f"(d[3]) : "r"(a0), "r"(a1), "r"(a2), "r"(a3), "r"(b0), "r"(b1), "f"(0.f));
}
DEV void mma8(float (&d)[4], uint32_t a0, uint32_t a1, uint32_t b0) {
  asm volatile("mma.sync.aligned.m16n8k8.row.col.f32.bf16.bf16.f32 {%0,%1,%2,%3},{%4,%5},{%6},{%0,%1,%2,%3};"
    : "+f"(d[0]), "+f"(d[1]), "+f"(d[2]), "+f"(d[3]) : "r"(a0), "r"(a1), "r"(b0));
}

DEV void bar_sync(int id, int n) { asm volatile("bar.sync %0,%1;" :: "r"(id), "r"(n) : "memory"); }
DEV void bar_sync_if(int id, int n, int c) { asm volatile("{.reg .pred q; setp.ne.s32 q,%2,0; @q bar.sync %0,%1;}" :: "r"(id), "r"(n), "r"(c) : "memory"); }
DEV void bar_arrive_if(int id, int n, int c) { asm volatile("{.reg .pred q; setp.ne.s32 q,%2,0; @q bar.arrive %0,%1;}" :: "r"(id), "r"(n), "r"(c) : "memory"); }
DEV bool bar_any(int id, int n, bool c) {
  uint32_t r; asm volatile("{.reg .pred p,q; setp.ne.u32 q,%3,0; bar.red.or.pred p,%1,%2,q; selp.u32 %0,1,0,p;}" : "=r"(r) : "r"(id), "r"(n), "r"((uint32_t)c) : "memory");
  return __any_sync(0xffffffffu, r);
}
DEV void bar_arrive(int id, int n) { asm volatile("bar.arrive %0,%1;" :: "r"(id), "r"(n) : "memory"); }
DEV void fence_async_glob() { asm volatile("fence.proxy.async.global;" ::: "memory"); }
DEV void fence_async_smem() { asm volatile("fence.proxy.async.shared::cta;" ::: "memory"); }
DEV void mbar_init(uint32_t b, int n) { asm volatile("mbarrier.init.shared::cta.b64 [%0],%1;" :: "r"(b), "r"(n) : "memory"); }
DEV void mbar_arrive(uint32_t b) { asm volatile("mbarrier.arrive.shared::cta.b64 _,[%0];" :: "r"(b) : "memory"); }
DEV void mbar_expect(uint32_t b, int bytes) { asm volatile("mbarrier.arrive.expect_tx.shared::cta.b64 _,[%0],%1;" :: "r"(b), "r"(bytes) : "memory"); }
DEV void mbar_wait(uint32_t b, uint32_t ph) {
  asm volatile("{\n.reg .pred p;\nW: mbarrier.try_wait.parity.shared::cta.b64 p,[%0],%1;\n@!p bra W;\n}" :: "r"(b), "r"(ph) : "memory");
}
DEV void mbar_watch(uint32_t b, uint32_t ph) {
  asm volatile("{\n.reg .pred p,q;\n.reg .u32 n;\nmov.u32 n,0;\n"
               "W: mbarrier.try_wait.parity.shared::cta.b64 p,[%0],%1;\n@p bra D;\n"
               "add.u32 n,n,1;\nsetp.lt.u32 q,n,%2;\n@q bra W;\ntrap;\nD:\n}"
               :: "r"(b), "r"(ph), "n"(SPIN_LIMIT) : "memory");
}
DEV void spin_guard(int it) { asm volatile("{.reg .pred p; setp.gt.s32 p,%0,%1; @p trap;}" :: "r"(it), "n"(SPIN_LIMIT)); }
DEV void split(uint32_t zero) {
  asm volatile("{.reg .pred p; setp.ne.u32 p,%0,0; @p trap;}" :: "r"(zero) : "memory");
}
DEV void pause(int n) {
  uint32_t t0, t; asm volatile("mov.u32 %0,%%clock;" : "=r"(t0));
  do asm volatile("mov.u32 %0,%%clock;" : "=r"(t)); while (t - t0 < n);
}
DEV void cnt_wait(const uint32_t* k, int lane) {
#pragma unroll 1
  for (int it = 0;; ++it) {
    spin_guard(it);
    if (__all_sync(0xffffffffu, ldr1(k + (lane & 3) * 32) >= 32)) break;
  }
}
DEV void mbar_arrive1(uint32_t b) { asm volatile("{.reg .pred p; elect.sync _|p,0xffffffff; @p mbarrier.arrive.shared::cta.b64 _,[%0];}" :: "r"(b) : "memory"); }
DEV void mbar_arrive1_if(uint32_t b, int c) {
  asm volatile("{.reg .pred p,q; setp.ne.s32 q,%1,0; elect.sync _|p,0xffffffff; and.pred p,p,q; @p mbarrier.arrive.shared::cta.b64 _,[%0];}" :: "r"(b), "r"(c) : "memory");
}
DEV void mbar_expect1(uint32_t b, int bytes) { asm volatile("{.reg .pred p; elect.sync _|p,0xffffffff; @p mbarrier.arrive.expect_tx.shared::cta.b64 _,[%0],%1;}" :: "r"(b), "r"(bytes) : "memory"); }
DEV void cnt_add1(uint32_t* q) { asm volatile("{.reg .pred p; elect.sync _|p,0xffffffff; @p red.relaxed.gpu.global.add.u32 [%0],1;}" :: "l"(q) : "memory"); }
DEV void tma4(uint32_t dst, const CUtensorMap* m, int c0, int c1, int c2, int c3, uint32_t bar) {
  asm volatile("{.reg .pred p; elect.sync _|p,0xffffffff;\n"
    "@p cp.async.bulk.tensor.4d.shared::cluster.global.mbarrier::complete_tx::bytes [%0],[%1,{%2,%3,%4,%5}],[%6];}"
    :: "r"(dst), "l"(m), "r"(c0), "r"(c1), "r"(c2), "r"(c3), "r"(bar) : "memory");
}
DEV void tma3(uint32_t dst, const CUtensorMap* m, int c0, int c1, int c2, uint32_t bar) {
  asm volatile("{.reg .pred p; elect.sync _|p,0xffffffff;\n"
    "@p cp.async.bulk.tensor.3d.shared::cluster.global.mbarrier::complete_tx::bytes [%0],[%1,{%2,%3,%4}],[%5];}"
    :: "r"(dst), "l"(m), "r"(c0), "r"(c1), "r"(c2), "r"(bar) : "memory");
}
DEV void bulk(uint32_t dst, const void* src, int bytes, uint32_t bar) {
  asm volatile("{.reg .pred p; elect.sync _|p,0xffffffff;\n@p cp.async.bulk.shared::cluster.global.mbarrier::complete_tx::bytes [%0],[%1],%2,[%3];}" :: "r"(dst), "l"(src), "r"(bytes), "r"(bar) : "memory");
}

DEV void bulk_store(void* dst, uint32_t src, int bytes) {
  asm volatile("{.reg .pred p; elect.sync _|p,0xffffffff;\n@p cp.async.bulk.global.shared::cta.bulk_group [%0],[%1],%2;}" :: "l"(dst), "r"(src), "r"(bytes) : "memory");
}
DEV void tma2_store(const CUtensorMap* m, uint32_t src, int c0, int c1) {
  asm volatile("{.reg .pred p; elect.sync _|p,0xffffffff;\n@p cp.async.bulk.tensor.2d.global.shared::cta.bulk_group [%0,{%2,%3}],[%1];}" :: "l"(m), "r"(src), "r"(c0), "r"(c1) : "memory");
}
DEV void bulk_wait() { asm volatile("cp.async.bulk.commit_group;\ncp.async.bulk.wait_group 0;\nfence.proxy.async.global;" ::: "memory"); }

DEV uint32_t dlo(uint32_t addr, uint32_t lbo) { return __shfl_sync(0xffffffffu, (addr >> 4) | ((lbo >> 4) << 16), 0); }
__host__ __device__ constexpr uint32_t dhi(uint32_t sbo, uint32_t swz) { return (sbo >> 4) | (swz << 30); }
DEV void wg_fence() { asm volatile("wgmma.fence.sync.aligned;" ::: "memory"); }
DEV void wg_commit() { asm volatile("wgmma.commit_group.sync.aligned;" ::: "memory"); }
template <int N> DEV void wg_wait() { asm volatile("wgmma.wait_group.sync.aligned %0;" :: "n"(N) : "memory"); }
template <int N> DEV void zero(float (&d)[N]) {
#pragma unroll
  for (int i = 0; i < N; ++i) d[i] = 0.f;
}
template <int N> DEV void zerov(float (&d)[N]) {
#pragma unroll
  for (int i = 0; i < N; ++i) asm volatile("mov.b32 %0,0;" : "=f"(d[i]));
}
template <int N> DEV void undef(float (&d)[N]) {
#pragma unroll
  for (int i = 0; i < N; ++i) asm volatile("" : "=f"(d[i]));
}
#define R4(d, o) "+f"(d[o]), "+f"(d[o + 1]), "+f"(d[o + 2]), "+f"(d[o + 3])
#define R8(d, o) R4(d, o), R4(d, o + 4)
#define R16(d, o) R8(d, o), R8(d, o + 8)
template <int ACC> DEV void wg_rs64k(float (&d)[32], const uint32_t (&a)[4], uint32_t db) {
  asm volatile("{.reg .pred p; .reg .b64 b; setp.ne.s32 p,%38,0; mov.b64 b,{%36,%37};\n"
    "wgmma.mma_async.sync.aligned.m64n64k16.f32.bf16.bf16 {%0,%1,%2,%3,%4,%5,%6,%7,%8,%9,%10,%11,%12,%13,%14,%15,%16,%17,%18,%19,%20,%21,%22,%23,%24,%25,%26,%27,%28,%29,%30,%31},{%32,%33,%34,%35},b,p,1,1,0;}"
    : R16(d, 0), R16(d, 16) : "r"(a[0]), "r"(a[1]), "r"(a[2]), "r"(a[3]), "r"(db), "n"(dhi(512, 2)), "n"(ACC));
}
template <int ACC> DEV void wg_rs48t(float (&d)[24], const uint32_t (&a)[4], uint32_t db) {
  asm volatile("{.reg .pred p; .reg .b64 b; setp.ne.s32 p,%30,0; mov.b64 b,{%28,%29};\n"
    "wgmma.mma_async.sync.aligned.m64n48k16.f32.bf16.bf16 {%0,%1,%2,%3,%4,%5,%6,%7,%8,%9,%10,%11,%12,%13,%14,%15,%16,%17,%18,%19,%20,%21,%22,%23},{%24,%25,%26,%27},b,p,1,1,1;}"
    : R16(d, 0), R8(d, 16) : "r"(a[0]), "r"(a[1]), "r"(a[2]), "r"(a[3]), "r"(db), "n"(dhi(512, 0)), "n"(ACC));
}
template <int ACC> DEV void wg_rs32t(float (&d)[16], const uint32_t (&a)[4], uint32_t db) {
  asm volatile("{.reg .pred p; .reg .b64 b; setp.ne.s32 p,%22,0; mov.b64 b,{%20,%21};\n"
    "wgmma.mma_async.sync.aligned.m64n32k16.f32.bf16.bf16 {%0,%1,%2,%3,%4,%5,%6,%7,%8,%9,%10,%11,%12,%13,%14,%15},{%16,%17,%18,%19},b,p,1,1,1;}"
    : R16(d, 0) : "r"(a[0]), "r"(a[1]), "r"(a[2]), "r"(a[3]), "r"(db), "n"(dhi(1024, 0)), "n"(ACC));
}
template <int ACC> DEV void wg_ss192(float (&d)[96], uint32_t da, uint32_t db) {
  asm volatile("{.reg .pred p; .reg .b64 a,b; setp.ne.s32 p,%100,0; mov.b64 a,{%96,%98}; mov.b64 b,{%97,%99};\n"
    "wgmma.mma_async.sync.aligned.m64n192k16.f32.bf16.bf16 {"
    "%0,%1,%2,%3,%4,%5,%6,%7,%8,%9,%10,%11,%12,%13,%14,%15,%16,%17,%18,%19,%20,%21,%22,%23,%24,%25,%26,%27,%28,%29,%30,%31,"
    "%32,%33,%34,%35,%36,%37,%38,%39,%40,%41,%42,%43,%44,%45,%46,%47,%48,%49,%50,%51,%52,%53,%54,%55,%56,%57,%58,%59,%60,%61,%62,%63,"
    "%64,%65,%66,%67,%68,%69,%70,%71,%72,%73,%74,%75,%76,%77,%78,%79,%80,%81,%82,%83,%84,%85,%86,%87,%88,%89,%90,%91,%92,%93,%94,%95},a,b,p,1,1,1,1;}"
    : R16(d, 0), R16(d, 16), R16(d, 32), R16(d, 48), R16(d, 64), R16(d, 80) : "r"(da), "r"(db), "n"(dhi(1024, 1)), "n"(dhi(1024, 1)), "n"(ACC));
}
template <int ACC> DEV void wg_ss64(float (&d)[32], uint32_t da, uint32_t db) {
  asm volatile("{.reg .pred p; .reg .b64 a,b; setp.ne.s32 p,%36,0; mov.b64 a,{%32,%34}; mov.b64 b,{%33,%35};\n"
    "wgmma.mma_async.sync.aligned.m64n64k16.f32.bf16.bf16 {"
    "%0,%1,%2,%3,%4,%5,%6,%7,%8,%9,%10,%11,%12,%13,%14,%15,%16,%17,%18,%19,%20,%21,%22,%23,%24,%25,%26,%27,%28,%29,%30,%31},a,b,p,1,1,0,1;}"
    : R16(d, 0), R16(d, 16) : "r"(da), "r"(db), "n"(dhi(1024, 0)), "n"(dhi(1024, 1)), "n"(ACC));
}

DEV uint32_t cpy(uint32_t v, uint32_t id) {
  uint32_t d; asm volatile("prmt.b32 %0,%1,%1,%2;" : "=r"(d) : "r"(v), "r"(id)); return d;
}
struct Params {
  uint32_t zero, spare;
  char* mid;
  const uint16_t *x0, *Are, *Aim, *Bre, *Bim, *Cre, *Cim, *logdt, *dskip, *wqkv, *wo;
  uint16_t* out;
  uint8_t role[72];
};

DEV uint32_t ln_word(float mean, float var) {
  float v = bfr(var);
  float s = sqrt_(bfr(v + 1e-5f));
  return pack2(mean, s);
}

DEV int stat_group(int c) { return 16 * (c & 4) + 4 * (c >> 3) + (c & 3); }
DEV int xg_off(int G, int g) { return (G >> 6) * 1024 + (G & 63) * 8 + (g ^ (G & 2)); }
DEV int sr_off(int G, int g) { return (G >> 6) * 256 + (g & 2) * 64 + 2 * (G & 63) + ((g >> 2) & 1); }
DEV uint32_t region(int chl) { return SM_A + (chl >> 1) * A_E + (chl & 1) * R_SZ; }
template <int N> DEV float4 gram(const uint32_t (&w)[N][2], int g) {
  float s0[4], s1[4];
  const uint32_t one = 0x3F803F80u;
  mma16z(s0, w[0][0], one, w[1][0], one, w[0][0], w[1][0]); mma16z(s1, w[0][1], one, w[1][1], one, w[0][1], w[1][1]);
#pragma unroll
  for (int j = 2; j < N; j += 2) {
    mma16(s0, w[j][0], one, w[j + 1][0], one, w[j][0], w[j + 1][0]); mma16(s1, w[j][1], one, w[j + 1][1], one, w[j][1], w[j + 1][1]);
  }
  const bool od = g & 1;
  return make_float4(od ? s0[3] : s0[2], od ? s0[1] : s0[0], od ? s1[3] : s1[2], od ? s1[1] : s1[0]);
}
DEV uint32_t ln_sums(float s, float q) { const float m = s * (1.f / 512.f); return ln_word(m, fmaxf(q * (1.f / 512.f) - m * m, 0.f)); }
DEV void cmul(float& orr, float& oi, float ar, float ai, float br, float bi) {
  float r = ar * br - ai * bi, i = ar * bi + ai * br; orr = r; oi = i;
}
DEV void cexp_(float al, float bt, float s, float& er, float& ei) {
  float mag = ex2(al * s), ph = bt * s;
  ph -= rintf(ph);
  float ang = ph * 6.283185307179586f;
  er = mag * __cosf(ang); ei = mag * __sinf(ang);
}

DEV void kgen(const Params& P, int c, int wm, int lane) {
  const int chl = wm >> 1, mh = wm & 1, g = lane >> 2, t = lane & 3;
  const int ch = 256 * (chl >> 1) + 2 * c + (chl & 1);
  const int mo = ch * 64 + mh * 32 + lane;
  const uint32_t vAr = ldw1((const uint32_t*)P.Are + mo), vAi = ldw1((const uint32_t*)P.Aim + mo);
  const uint32_t vBr = ldw1((const uint32_t*)P.Bre + mo), vBi = ldw1((const uint32_t*)P.Bim + mo);
  const uint32_t vCr = ldw1((const uint32_t*)P.Cre + mo), vCi = ldw1((const uint32_t*)P.Cim + mo);
  const uint32_t vld = ldw1((const uint32_t*)P.logdt + (ch >> 1)) >> (16 * (ch & 1)), vds = ldw1((const uint32_t*)P.dskip + (ch >> 1)) >> (16 * (ch & 1));
  bar_arrive(NB_Y, 384);
  PROF(45);
  asm volatile("setmaxnreg.inc.sync.aligned.u32 %0;" :: "n"(REG_MAIN));
  PROF(44);
  {
    const uint32_t tz = SM_TAP + chl * TAP_SZ + (mh * 32 + lane) * 16;
#pragma unroll
    for (int k = 0; k < 3; ++k) sts4(tz + k * 1024, 0, 0, 0, 0);
    static_assert(TAP_SZ > 3072 && TAP_SZ <= 4096, "");
    if (mh * 32 + lane < TAP_SZ / 16 - 192) sts4(tz + 3072, 0, 0, 0, 0);
  }
  const float dt = bfr(__expf(bflo(vld)));
  const uint32_t tb = slot(wm);
  float acc[5][4];
#pragma unroll
  for (int i = 0; i < 5; ++i) { acc[i][0] = acc[i][1] = acc[i][2] = acc[i][3] = 0.f; }
  float k2048 = 0.f;
#pragma unroll 1
  for (int r = 0; r < 2; ++r) {
    const float are = r ? bfhi(vAr) : bflo(vAr), aim = r ? bfhi(vAi) : bflo(vAi);
    const float bre = r ? bfhi(vBr) : bflo(vBr), bim = r ? bfhi(vBi) : bflo(vBi);
    const float cre = r ? bfhi(vCr) : bflo(vCr), cim = r ? bfhi(vCi) : bflo(vCi);
    const float al = dt * are * 1.4426950408889634f, bt = dt * aim * 0.15915494309189535f;
    float wr, wi; cmul(wr, wi, cre, cim, dt * bre, dt * bim);
    if (r == 0) PROFD(2, __float_as_uint(wr + al + bt));
    float e1r, e1i, e8r, e8i, eLr, eLi;
    cexp_(al, bt, 1.f, e1r, e1i); cexp_(al, bt, 8.f, e8r, e8i); cexp_(al, bt, 128.f, eLr, eLi);
    const uint32_t tw = tb + lane * 4;
    float pr[8], pi[8];
    pr[1] = e1r; pi[1] = e1i;
#pragma unroll
    for (int k = 2; k < 8; ++k) cmul(pr[k], pi[k], pr[k - 1], pi[k - 1], e1r, e1i);
    float yr = 1.f, yi = 0.f, qr = wr, qi = wi;
#pragma unroll
    for (int a = 0; a < 16; ++a) {
      sts1(tw + a * 144, pack2(yr, -yi));
      if (a == 0) { yr = e8r; yi = e8i; } else if (a < 15) cmul(yr, yi, yr, yi, e8r, e8i);
      const int step = a < 2 ? 1 : a < 4 ? 2 : a < 8 ? 4 : 8;
      const int row0 = 16 + (a < 2 ? 8 * a : a < 4 ? 16 + 4 * (a - 2) : a < 8 ? 24 + 2 * (a - 4) : 32 + (a - 8));
      sts1(tw + row0 * 144, pack2(qr, qi));
#pragma unroll
      for (int k = step; k < 8; k += step) {
        float xr, xi; cmul(xr, xi, qr, qi, pr[k], pi[k]);
        sts1(tw + (row0 + k / step) * 144, pack2(xr, xi));
      }
      cmul(qr, qi, qr, qi, eLr, eLi);
    }
    k2048 += qr;
    __syncwarp();
    if (r == 0) PROF(3);
#pragma unroll
    for (int kp = 0; kp < 2; ++kp) {
      uint32_t a0[4], a1[4];
      const uint32_t aa = tb + ((lane & 7) + 8 * ((lane >> 3) & 1)) * 144 + (lane >> 4) * 16 + kp * 64;
      ldsm4(a0, aa); ldsm4(a1, aa + 32);
#pragma unroll
      for (int tl = 0; tl < 5; ++tl) {
        uint32_t b[4];
        ldsm4(b, tb + (16 + 8 * tl + (lane & 7)) * 144 + (lane >> 3) * 16 + kp * 64);
        mma16(acc[tl], a0[0], a0[1], a0[2], a0[3], b[0], b[1]);
        mma16(acc[tl], a1[0], a1[1], a1[2], a1[3], b[2], b[3]);
      }
    }
    __syncwarp();
    bar_sync_if(NB_P0 + 1, 288, 1 - r);
  }
#pragma unroll
  for (int o = 16; o > 0; o >>= 1) k2048 += __shfl_xor_sync(0xffffffffu, k2048, o);
  if (mh == 0) {
    sts4f(tb + lane * 16, acc[2][0], acc[2][1], acc[2][2], acc[2][3]);
    sts4f(tb + 512 + lane * 16, acc[3][0], acc[3][1], acc[3][2], acc[3][3]);
  } else {
    sts4f(tb + lane * 16, acc[0][0], acc[0][1], acc[0][2], acc[0][3]);
    sts4f(tb + 512 + lane * 16, acc[1][0], acc[1][1], acc[1][2], acc[1][3]);
    sts4f(tb + 1024 + lane * 16, acc[4][0], acc[4][1], acc[4][2], acc[4][3]);
    if (lane == 0) sts1(tb + 1536, __float_as_uint(k2048));
  }
  PROF(4);
  bar_sync(NB_K + chl, 64);
  const uint32_t ob = slot(wm ^ 1), tp = SM_TAP + chl * TAP_SZ;
  if (mh == 0) {
#pragma unroll
    for (int tl = 0; tl < 2; ++tl) {
      float4 o = lds4f(ob + tl * 512 + lane * 16);
      if (tl == 0 && lane == 0) o.x += bflo(vds);
      uint32_t v0 = pack2(acc[tl][0] + o.x, acc[tl][1] + o.y), v1 = pack2(acc[tl][2] + o.z, acc[tl][3] + o.w);
      const int l = 128 * tl + 8 * g + 2 * t;
      sts16(tp + T_E + 2 * (0 - l), v0); sts16(tp + T_E + 2 * (-1 - l), v0 >> 16);
      sts16(tp + T_O + 2 * (0 - l), v0); sts16(tp + T_O + 2 * (-1 - l), v0 >> 16);
      sts16(tp + T_E + 2 * (-64 - l), v1); sts16(tp + T_E + 2 * (-65 - l), v1 >> 16);
      sts16(tp + T_O + 2 * (-64 - l), v1); sts16(tp + T_O + 2 * (-65 - l), v1 >> 16);
    }
    float4 o = lds4f(ob + 1024 + lane * 16);
    uint32_t v0 = pack2(acc[4][0] + o.x, acc[4][1] + o.y), v1 = pack2(acc[4][2] + o.z, acc[4][3] + o.w);
    const int x = 32 * t + g - 1;
    if (lane == 0) { sts16(tp + T_E - 2 * (X_5 + 63), v0); sts16(tp + T_O - 2 * (X_5 + 63), v0); sts1(tp + T_K, prmt(v0, v0, 0x1010)); }
    else sts16(tp + T_C - 2 * x, v0);
    sts16(tp + T_C - 2 * (x + 16), v0 >> 16);
    sts16(tp + T_C - 2 * (x + 8), v1);
    sts16(tp + T_C - 2 * (x + 24), v1 >> 16);
    if (lane == 0) sts16(tp + T_C - 2 * 127, pack2(k2048 + __uint_as_float(lds1(ob + 1536)), 0.f));
  } else {
    float4 o2 = lds4f(ob + lane * 16), o3 = lds4f(ob + 512 + lane * 16);
    uint32_t v0 = pack2(acc[2][0] + o2.x, acc[2][1] + o2.y), v1 = pack2(acc[2][2] + o2.z, acc[2][3] + o2.w);
    const int l0 = 256 + 128 * (t >> 1) + 4 * (t & 1) + 8 * g;
    if (lane != 0) { sts16(tp + T_E + 2 * (1 - l0), v0); sts16(tp + T_O + 2 * (1 - l0), v0); }
    sts16(tp + T_E + 2 * (0 - l0), v0); sts16(tp + T_O + 2 * (0 - l0), v0);
    sts16(tp + T_E + 2 * (-1 - l0), v0); sts16(tp + T_O + 2 * (-1 - l0), v0);
    sts16(tp + T_E + 2 * (-2 - l0), v0 >> 16); sts16(tp + T_O + 2 * (-2 - l0), v0 >> 16);
    sts16(tp + T_E + 2 * (-63 - l0), v1); sts16(tp + T_O + 2 * (-63 - l0), v1);
    sts16(tp + T_E + 2 * (-64 - l0), v1); sts16(tp + T_O + 2 * (-64 - l0), v1);
    sts16(tp + T_E + 2 * (-65 - l0), v1); sts16(tp + T_O + 2 * (-65 - l0), v1);
    sts16(tp + T_E + 2 * (-66 - l0), v1 >> 16); sts16(tp + T_O + 2 * (-66 - l0), v1 >> 16);
    uint32_t w0 = pack2(acc[3][0] + o3.x, acc[3][1] + o3.y), w1 = pack2(acc[3][2] + o3.z, acc[3][3] + o3.w);
    const int x = 16 * t + g;
    if (lane == 0) {
      const uint32_t k = prmt(w0, w0, 0x1010);
      sts1(tp + T_E - 2 * 514, k); sts1(tp + T_E - 2 * 512, k);
      sts16(tp + T_O - 2 * 514, k); sts1(tp + T_O - 2 * 513, k); sts16(tp + T_O - 2 * 511, k);
    } else { sts16(tp + T_E - 2 * (X_5 - 1 + x), w0); sts16(tp + T_O - 2 * (X_5 - 1 + x), w0); }
    sts16(tp + T_E - 2 * (X_3 + x), w0 >> 16); sts16(tp + T_O - 2 * (X_3 + x), w0 >> 16);
    sts16(tp + T_E - 2 * (X_5 + 7 + x), w1); sts16(tp + T_O - 2 * (X_5 + 7 + x), w1);
    sts16(tp + T_E - 2 * (X_3 + 8 + x), w1 >> 16); sts16(tp + T_O - 2 * (X_3 + 8 + x), w1 >> 16);
  }
}

DEV bool bad8(const uint4& v) { return min(v.x, v.z) == 0u; }
DEV uint32_t uchunk(uint32_t reg, int x) { return reg + R_U + (x ^ ((x >> 3) & 3)) * 16; }
DEV uint32_t& xword(uint4 (&x)[2], int e, int tp) { uint4& v = x[tp >> 1]; return tp & 1 ? (e ? v.w : v.z) : (e ? v.y : v.x); }

DEV void sload(const Params& P, int c, int j, int layer, uint4 (&s)[2][2]) {
  const uint4* st = &SCR->SR[layer][c >> 4][opq(j)];
  mbar_wait(B_U, layer);
  PROF(layer ? 25 : 10);
#pragma unroll
  for (int z = 0; z < 4; ++z) s[z >> 1][z & 1] = ldr4(st + z * 128);
}
DEV void uload(const Params& P, int c, int j, int layer, uint4 (&x)[2][2][2], uint4 (&s)[2][2]) {
  j = opq(j);
  const uint4* st = &SCR->SR[layer][c >> 4][j];
  const int o0 = 2 * j + ((j >> 2) & 1), o1 = o0 ^ 1;
#pragma unroll
  for (int z = 0; z < 4; ++z) { uint4& v = s[z >> 1][z & 1]; ldr4_if(v, st + z * 128, bad8(v)); }
  PROF(layer ? 26 : 11);
  mbar_wait(B_E, layer);
#pragma unroll
  for (int z = 0; z < 8; ++z) x[z >> 2][(z >> 1) & 1][z & 1] = lds4(SM_X + 16 * (z & 1 ? o1 : o0) + (z >> 1) * 4096);
  PROF(layer ? 27 : 14);
  for (int it = 0;; ++it) {
    uint32_t m = ~0u;
#pragma unroll
    for (int z = 0; z < 4; ++z) { const uint4& v = s[z >> 1][z & 1]; m = min(m, min(v.x, v.z)); }
#pragma unroll
    for (int z = 0; z < 8; ++z) { const uint4& v = x[z >> 2][(z >> 1) & 1][z & 1]; m = min(m, min(v.x, v.z)); }
    if (!RARE(__any_sync(0xffffffffu, m == 0))) break;
#pragma unroll
    for (int z = 0; z < 4; ++z) { uint4& v = s[z >> 1][z & 1]; ldr4_if(v, st + z * 128, bad8(v)); }
#pragma unroll
    for (int z = 0; z < 8; ++z) {
      uint4& v = x[z >> 2][(z >> 1) & 1][z & 1];
      ldr4_if(v, &SCR->XG[layer][c * 1024 + (opq(o0) ^ (z & 1)) + (z >> 1) * 256], bad8(v));
    }
    spin_guard(it);
  }
  PROF(4 + 12 * layer);
}
DEV void uprep(int j, int k, uint4 (&x)[2][2], uint4 (&s)[2], uint32_t (&u)[4][4]) {
  const uint32_t ua = uchunk(0, opq(j)) + k * 2048;
#pragma unroll
  for (int chl = 0; chl < 4; ++chl) {
#pragma unroll
    for (int tp = 0; tp < 4; ++tp) u[chl][tp] = hmul2(hsub2(xword(x[chl >> 1], chl & 1, tp), xword(s, 1, tp)), xword(s, 0, tp));
    sts4(ua + region(chl), u[chl][0], u[chl][1], u[chl][2], u[chl][3]);
  }
}

template <bool FULL> DEV void box_unit(uint32_t reg, int s, const uint2& a, const uint4& b, const uint32_t (&d)[4], uint32_t (&pv)[4]) {
  const uint32_t u[9] = {a.x, a.y, b.x, b.y, b.z, b.w, d[0], d[1], d[2]};
  uint32_t v[8], p[8];
#pragma unroll
  for (int j = 0; j < 8; ++j) { v[j] = prmt(u[j], u[j + 1], 0x5432); p[j] = hadd2(u[j], v[j]); }
  const uint32_t o = reg + s * 16;
  uint32_t x[4], y[4];
#pragma unroll
  for (int j = 0; j < 4; ++j) { x[j] = hadd2(hadd2(p[1 + j], p[2 + j]), u[3 + j]); y[j] = hadd2(v[3 + j], p[4 + j]); pv[j] = p[4 + j]; }
  sts4(o + R_X5, x[0], x[1], x[2], x[3]);
  sts4(o + R_X3, y[0], y[1], y[2], y[3]);
  if (FULL) {
#pragma unroll
    for (int j = 0; j < 4; ++j) { y[j] = hadd2(hadd2(v[j], v[3 + j]), x[j]); x[j] = hadd2(hadd2(u[j], u[4 + j]), y[j]); }
    const bool od = s & 1;
    sts4(o + R_BO, od ? y[0] : x[0], od ? y[1] : x[1], od ? y[2] : x[2], od ? y[3] : x[3]);
    sts4(o + R_BE + 16, od ? x[0] : y[0], od ? x[1] : y[1], od ? x[2] : y[2], od ? x[3] : y[3]);
  }
}
DEV void box_full(int j, uint32_t (&u)[4][4], uint32_t zero) {
  const uint32_t a2 = uchunk(8, j - 2), a1 = uchunk(0, j - 1);
  uint2 a[4]; uint4 b[4];
#pragma unroll
  for (int chl = 0; chl < 2; ++chl) { a[chl] = lds2(region(chl) + a2); b[chl] = lds4(region(chl) + a1); }
  split(zero);
#pragma unroll
  for (int chl = 0; chl < 4; ++chl) {
    const uint32_t d[4] = {u[chl][0], u[chl][1], u[chl][2], u[chl][3]};
    box_unit<true>(region(chl), j, a[chl], b[chl], d, u[chl]);
    if (chl + 2 < 4) { a[(chl + 2) & 3] = lds2(region(chl + 2) + a2); b[(chl + 2) & 3] = lds4(region(chl + 2) + a1); }
    if (chl != 2) {
      fence_async_smem();
      if (chl == 3) bar_arrive(NB_B + 2, 288);
      bar_arrive(NB_B + chl, 288);
    }
    if (chl == 0) PROF(31);
  }
}
DEV void box_help(int e, int lane) {
  bar_sync(NB_H, 192);
#pragma unroll 1
  for (int n = 0; n < 4; ++n) {
    const int chl = e + (n & 2), s = 128 + 32 * (n & 1) + lane;
    const uint32_t reg = region(chl);
    const uint4 d = lds4(uchunk(reg, s));
    const uint32_t u[4] = {d.x, d.y, d.z, d.w};
    uint32_t v[4];
    box_unit<false>(reg, s, lds2(uchunk(reg, s - 2) + 8), lds4(uchunk(reg, s - 1)), u, v);
    if (n & 1) { fence_async_smem(); bar_arrive(NB_B + chl, 288); }
  }
}

DEV uint4 hadd8(const uint4& a, const uint4& b) { return make_uint4(hadd2(a.x, b.x), hadd2(a.y, b.y), hadd2(a.z, b.z), hadd2(a.w, b.w)); }
DEV void conv_out(int c, int j, int chl, uint4 (&x)[2][2][2], const uint32_t (&v)[4], uint4* XF, uint32_t zero) {
  const int rho = chl >> 1, e = chl & 1;
  const uint32_t ua = uchunk(region(chl), j), fa = region(chl) + R_X5 + j * 16, ha = region(chl) + R_X3 + (j & 1) * 1088 + (j >> 1) * 16;
  const int m8 = ((j & 4) + ((j >> 1) & 1)) ^ ((2 * c + e) & 7);
  uint2* xo = (uint2*)XF + (((j >> 3) * 512 + 256 * rho + 2 * c + e) * 16 + (j & 1));
  bar_sync(NB_Y + e + 7 * rho, 256);
  uint4 y[2], f[2], h[2];
#pragma unroll
  for (int k = 0; k < 2; ++k) {
    y[k] = lds4(ua + k * 2048);
    f[k] = lds4z(ua + k * 2048 + R_BO - R_U, k || j >= 36);
    h[k] = lds4z(fa + k * 2048 - 1024, k || j >= 64);
  }
  const uint32_t q = lds1(SM_TAP + chl * TAP_SZ + T_K);
  const uint4 r = lds4(ha);
  split(zero);
  h[1] = hadd8(h[1], make_uint4(hfma2(q, v[0], r.x), hfma2(q, v[1], r.y), hfma2(q, v[2], r.z), hfma2(q, v[3], r.w)));
#pragma unroll
  for (int k = 0; k < 2; ++k) {
    const uint4 o = hadd8(hadd8(y[k], hadd8(f[k], h[k])), make_uint4(xword(x[k][rho], e, 0), xword(x[k][rho], e, 1), xword(x[k][rho], e, 2), xword(x[k][rho], e, 3)));
    str2(xo + k * 131072 + 2 * m8, prmt(o.x, o.y, 0x5410), prmt(o.z, o.w, 0x5410));
    str2(xo + k * 131072 + 2 * (m8 ^ 2), prmt(o.x, o.y, 0x7632), prmt(o.z, o.w, 0x7632));
  }
  if (e) { __syncwarp(); mbar_arrive1(B_RD + rho * 8); }
}

DEV void conv_round(int e, int rho, int w, int lane) {
  const int g = lane >> 2, t = lane & 3, chl = 2 * rho + e;
  const uint32_t reg = region(chl), tp = SM_TAP + chl * TAP_SZ, dr = dlo(reg, 128);
  const uint32_t g0 = tp + ((g & 1) ? T_O : T_E) + 2 * (2 * t - g) - 16;
  const uint32_t ga = g0 - 32 * (w & 1) - 576 * (w >> 1), id = opq(0x3210u);
  float acc[32], f1[24], f2[16];
  uint32_t q[12][4];
  {
    uint32_t qn[18][4];
    qn[0][2] = lds1(ga + 64);
#pragma unroll
    for (int n = 0; n < 18; ++n) {
      const bool nz = n < 15 || w < 2 || (n == 15 && w == 2);
      qn[n][0] = n < 15 ? lds1(ga + 48 - 32 * n) : lds1z(ga + 48 - 32 * n, nz);
      qn[n][1] = n < 15 ? lds1(ga + 32 - 32 * n) : lds1z(ga + 32 - 32 * n, nz);
    }
#pragma unroll
    for (int n = 0; n < 18; ++n) { qn[n][3] = cpy(qn[n][0], id); if (n) qn[n][2] = cpy(qn[n - 1][1], id); }
#pragma unroll
    for (int n = 0; n < 8; ++n) {
      const int i = n & 3;
      const uint32_t a = g0 + 16 - 16 * w - 2 * (n < 4 ? X_5 : X_3) + 16 * i;
      uint32_t (&q1)[4] = q[(n & 4) + (i >> 1)], (&q2)[4] = q[(n & 4) + 2 + (i >> 1)];
      q1[2 * (i & 1)] = lds1z(a, i <= w); q1[2 * (i & 1) + 1] = lds1(a - 64);
      q2[2 * (i & 1)] = cpy(0, id); q2[2 * (i & 1) + 1] = lds1z(a - 128, i >= w);
    }
    const uint32_t gc = tp + T_C - 2 + 4 * (t - g - 8 * w);
#pragma unroll
    for (int kk = 0; kk < 4; ++kk) {
      q[8 + kk][0] = lds1z(gc + 32 * kk, w >= kk); q[8 + kk][2] = lds1z(gc + 32 * kk + 16, w >= kk);
      q[8 + kk][1] = lds1(gc + 32 * kk - 128); q[8 + kk][3] = lds1(gc + 32 * kk - 112);
    }
    PROFD(rho ? 43 : 47, qn[17][2] ^ q[11][3]);
    bar_sync_if(NB_U, NBARU, 1 - rho);
    mbar_arrive1_if(B_V, chl == 1 && w == 0);
    bar_sync_if(NB_T + 1 - e, 256, chl);
    const uint32_t db = dr + (R_U + 32) / 16;
    undef(acc);
    wg_fence();
#pragma unroll
    for (int n = 0; n < 18; ++n) {
      if (n) wg_rs64k<1>(acc, qn[n], db - 2 * n); else wg_rs64k<0>(acc, qn[0], db);
      if (n == 9) wg_commit();
    }
    wg_commit();
  }
  wg_wait<1>();
  PROF(12);
  bar_sync(NB_B + chl, 288);
  const uint32_t d1 = dr + R_X5 / 16, d2 = dr + R_BO / 16;
  undef(f1); undef(f2);
  wg_fence();
#pragma unroll
  for (int n = 0; n < 8; ++n) {
    const uint32_t d = d1 + (n >> 2) * ((R_X3 - R_X5) / 16) + 16 * (n & 1) - 16 * (n & 2);
    if (n) wg_rs48t<1>(f1, q[n], d); else wg_rs48t<0>(f1, q[0], d);
    if (n & 1) { if (n > 1) wg_rs32t<1>(f2, q[8 + (n >> 1)], d2 + 16 * (n >> 1)); else wg_rs32t<0>(f2, q[8], d2); }
  }
  wg_commit();
  wg_wait<1>();
  PROF(13);
  bar_arrive_if(NB_T + e, 256, chl - 3);
  wg_wait<0>();
  PROF(14);
  bar_sync(NB_WG + e, 128);
  {
    const int p = (lane + 9 * (w >> 1)) & 31;
    const uint32_t ya = reg + ((w >> 1) ? R_BO : R_U) + p * 64 + (((2 * (w & 1)) ^ ((p >> 1) & 3)) * 16);
    const uint32_t up = p < lane ? 2048 : 0;
#pragma unroll
    for (int z = 0; z < 4; ++z) {
      const float* a = acc + 16 * (z >> 1) + 2 * (z & 1);
      stsm4t((ya + (up ^ ((z >> 1) * 2048))) ^ ((z & 1) * 16), pack2(a[0], a[1]), pack2(a[4], a[5]), pack2(a[8], a[9]), pack2(a[12], a[13]));
    }
  }
  {
    const uint32_t fa = reg + R_X5 + (8 * w + (lane & 7)) * 16 + (lane >> 3) * 512;
    uint32_t h[6];
#pragma unroll
    for (int p = 0; p < 6; ++p) h[p] = p ? pack2(f1[4 * p] + f1[4 * p - 2], f1[4 * p + 1] + f1[4 * p - 1]) : pack2(f1[0], f1[1]);
    stsm4(fa, h[0], h[1], h[2], h[3]);
    stsm2(fa + 2048, h[4], h[5]);
    stsm4(reg + R_X3 + (lane < 16 ? 1088 : 0) + (8 * w + (lane & 7) + 4 * (lane & 8)) * 16, pack2(f2[0], f2[1]), pack2(f2[2] + f2[4], f2[3] + f2[5]),
          pack2(f2[8], f2[9]), pack2(f2[10] + f2[12], f2[11] + f2[13]));
  }
  bar_arrive(NB_Y + e + 7 * rho, 256);
}
constexpr uint32_t FILL = 0xFFFFFFFFu;
template <int N> DEV void fixo(uint4 (&A)[N], const uint4* p) {
#pragma unroll 1
  for (int it = 0; it < SPIN_LIMIT; ++it) {
    uint32_t m = A[0].x;
#pragma unroll
    for (int k = 1; k < N; ++k) m = max(m, A[k].x);
    if (__all_sync(0xffffffffu, m != FILL)) break;
#pragma unroll
    for (int k = 0; k < N; ++k) ldr4_if(A[k], p + k * 32, A[k].x == FILL);
  }
}
DEV bool rows_nan(float a, float b) {
  return __any_sync(0xffffffffu, a != a || b != b);
}
template <int N> DEV void slow_step(float (&acc)[N], float a0, float a1, const uint16_t* wr, uint32_t zero) {
#pragma unroll
  for (int j = 0; j < N / 4; ++j) {
    const uint32_t v = __ldg((const uint32_t*)(wr + (j >> 3) * 512 + 8 * (j & 7)));
    acc[4 * j] += a0 * bflo(v); acc[4 * j + 1] += a0 * bfhi(v); acc[4 * j + 2] += a1 * bflo(v); acc[4 * j + 3] += a1 * bfhi(v);
    if ((j & 3) == 3) wr += __float_as_uint(acc[4 * j]) & zero;
  }
}
DEV int res_off(int w, int lane) { return ((lane & 7) + 8 * (lane >> 4)) * 8 + ((2 * (w & 2) + (w & 1) + ((lane >> 2) & 2)) ^ (lane & 7)); }
DEV void res_load(uint32_t (&res)[8][2], uint32_t sa, int w, int lane) {
  const uint32_t a = sa + res_off(w, opq(lane)) * 16;
#pragma unroll
  for (int j = 0; j < 8; j += 2) {
    uint32_t r[4];
    ldsm4t(r, a + j * 1024);
    res[j][0] = r[0]; res[j][1] = r[1]; res[j + 1][0] = r[2]; res[j + 1][1] = r[3];
  }
}

DEV uint32_t after(uint32_t b, const uint32_t (&res)[8][2], uint32_t zero) {
  return b + ((res[0][0] ^ res[2][0] ^ res[4][0] ^ res[6][0]) & zero);
}

DEV void attn_phase(const Params& P, int c, int e, int w, int lane, int layer) {
  lane = opq(lane); c = opq(c);
  const int i = c >> 3, cg = c & 7, J = 16 * e + i, G = 4 * J + w;
  const int g = lane >> 2, t = lane & 3;
  float acc[96];
  uint32_t res[8][2];
  float2 cs[16];
  float4 st;
  const uint32_t csb = opq(SM_CS + 8 * t);
  {
    const uint32_t sa = SM_A + e * A_E, ba = B_A + 16 * e;
    const uint32_t da = dlo(sa, 8192), db = (SB >> 4) | (512 << 16);
    undef(acc);
#pragma unroll
    for (int j = 0; j < 8; ++j) asm volatile("" : "=r"(res[j][0]), "=r"(res[j][1]));
    mbar_wait(B_WF, layer);
    mbar_wait(ba, 0);
    mbar_wait(B_RD + 8, layer);
    bar_sync_if(NB_T, 256, e);
    PROF(24);
#pragma unroll
    for (int j = 0; j < 4; ++j) {
      if (j == 1) { mbar_wait(ba + 8, 0); PROF(39); }
      wg_fence();
#pragma unroll
      for (int k = 0; k < 4; ++k) {
        if (j | k) wg_ss192<1>(acc, da + j * 512 + k * 128, db + wslot(j) * 512 + k * 128); else wg_ss192<0>(acc, da, db);
        if (j == 3 && k == 1) wg_commit();
      }
      wg_commit();
      if (j == 1 || j == 2) { wg_wait<1>(); mbar_arrive1_if(B_F + 8 * (j - 1), e); }
    }
    wg_wait<1>();
    bar_arrive(NB_T + e, 256);
    wg_wait<0>();
    if (cg < 4) res_load(res, sa + cg * 8192, w, lane);
    mbar_arrive1(after(B_AE + 8 * e, res, P.zero));
    PROF(25);
#pragma unroll 1
    for (uint32_t late = P.zero;; late = 1) {
      if (late) {
        const uint16_t* xr = (const uint16_t*)SCR->XF[layer] + opq(J) * 32768;
        zero(acc);
#pragma unroll 1
        for (int k = 0; k < 512; ++k)
          slow_step(acc, ldnan(xr + k * 64 + ((2 * w) ^ (k & 7)) * 8 + g), ldnan(xr + k * 64 + ((2 * w + 1) ^ (k & 7)) * 8 + g),
                    P.wqkv + (k * 1536 + 64 * cg + 2 * t), P.zero);
        const uint32_t* q = (const uint32_t*)xr + ((64 * cg + g) * 32 + t);
        const int m8 = (2 * (w & 2) + (w & 1)) ^ g;
#pragma unroll 1
        for (int it = 0; it < SPIN_LIMIT; ++it) {
          uint32_t m = 0;
#pragma unroll
          for (int z = 0; z < 16; ++z) { const uint32_t x = ldr1(q + (z >> 1) * 256 + (m8 ^ (2 * (z & 1))) * 4); m = max(m, x); res[z >> 1][z & 1] = movm(x); }
          if (__all_sync(0xffffffffu, m != FILL)) break;
        }
#pragma unroll
        for (int z = 0; z < 16; ++z) cs[z] = lds2f(csb + 256 + z * 32);
      } else {
        mbar_wait(B_CS, 0);
#pragma unroll
        for (int z = 0; z < 16; ++z) cs[z] = lds2f(csb + 256 + z * 32);
        mbar_wait(B_W4, layer);
        mbar_wait(ba, 1);
        bar_sync(NB_T + 1 - e, 256);
        PROF(26);
#pragma unroll
        for (int j = 4; j < 8; ++j) {
          if (j == 5) mbar_wait(ba + 8, 1);
          if (j >= 6) mbar_wait(B_W6 + 8 * (j - 6), layer);
          if (j > 4) PROF(31 + j);
          wg_fence();
#pragma unroll
          for (int k = 0; k < 4; ++k) {
            wg_ss192<1>(acc, da + (j & 3) * 512 + k * 128, db + wslot(j) * 512 + k * 128);
            if (j == 7 && k == 1) wg_commit();
          }
          wg_commit();
          if (j == 5) {
            if (cg >= 4) res_load(res, sa + (cg - 4) * 8192, w, lane);
            wg_wait<1>(); mbar_arrive1_if(B_F + 16, e); PROF(40);
          }

        }
      }
      uint32_t rs = hadd2(res[0][0], res[0][1]);
#pragma unroll
      for (int z = 2; z < 16; ++z) rs = hadd2(rs, res[z >> 1][z & 1]);
      const float rn = bflo(rs) + bfhi(rs);
      wg_wait<1>();
      bar_arrive_if(NB_T, 256, !(e | late));
      mbar_wait(B_ST + 8 * e, layer);
      st = lds4f(SM_STAT + ((4 * e + w) * 8 + g) * 16);
      PROF(34 + layer);
      wg_wait<0>();
      if (!rows_nan(acc[0] + rn, acc[2]) || late) break;
    }
  }
  mbar_arrive1(B_QE);
  PROF(8 + 12 * layer);
  uint32_t Q[4][4], K[4][2][2], V[4][2][2];
  {
#pragma unroll
    for (int z = 0; z < 8; ++z) {
      const float* a = acc + 32 + 4 * z; const float* b = acc + 64 + 4 * z;
      K[z >> 1][1][z & 1] = pack2((a[2] - st.z * cs[z].x) * st.w, (a[3] - st.z * cs[z].y) * st.w);
      V[z >> 1][1][z & 1] = movm(pack2((b[2] - st.z * cs[8 + z].x) * st.w, (b[3] - st.z * cs[8 + z].y) * st.w));
    }
    const uint32_t kv = SM_KV + (2 * e + (w & 1)) * 2048 + lane * 16;
    uint4* h = SCR->H[layer] + ((J * 8 + cg) * 256 + (w & 1) * 128 + lane);
    if (w >= 2) {
#pragma unroll
      for (int z = 0; z < 4; ++z) str4(h + 2048 + z * 32, K[z][1][0], K[z][1][1], V[z][1][0], V[z][1][1]);
    } else {
      mbar_wait(B_F + 16, layer);
#pragma unroll
      for (int z = 0; z < 4; ++z) sts4(kv + z * 512, K[z][1][0], K[z][1][1], V[z][1][0], V[z][1][1]);
      bar_arrive(NB_WG + e, 128);
    }
    PROF(42);
#pragma unroll
    for (int z = 0; z < 8; ++z) {
      const float* a = acc + 32 + 4 * z; const float* b = acc + 64 + 4 * z;
      K[z >> 1][0][z & 1] = pack2((a[0] - st.x * cs[z].x) * st.y, (a[1] - st.x * cs[z].y) * st.y);
      V[z >> 1][0][z & 1] = movm(pack2((b[0] - st.x * cs[8 + z].x) * st.y, (b[1] - st.x * cs[8 + z].y) * st.y));
    }
#pragma unroll
    for (int z = 0; z < 8; ++z) {
      const float2 cq = lds2f(csb + z * 32);
      const float* a = acc + 4 * z;
      Q[z >> 1][2 * (z & 1)] = pack2(a[0] - st.x * cq.x, a[1] - st.x * cq.y);
      Q[z >> 1][2 * (z & 1) + 1] = pack2(a[2] - st.z * cq.x, a[3] - st.z * cq.y);
    }
    PROF(27);
    uint4 hv[4];
    if (w >= 2) {
      bar_sync(NB_WG + e, 128);
#pragma unroll
      for (int z = 0; z < 4; ++z) hv[z] = lds4(kv + z * 512);
    } else {
#pragma unroll
      for (int z = 0; z < 4; ++z) { hv[z] = make_uint4(0, 0, 0, 0); ldr4_if(hv[z], h + z * 32, G >= 2); }
    }
    const bool p0 = 2 * t > g, p1 = 2 * t + 1 > g, first = G < 2;
    float s[4][4], mx[4][2];
#pragma unroll
    for (int z = 0; z < 4; ++z) {
      float S[4];
      mma16z(s[z], Q[z][0], Q[z][1], Q[z][2], Q[z][3], K[z][0][0], K[z][0][1]);
      mma16z(S, Q[z][0], Q[z][1], Q[z][2], Q[z][3], K[z][1][0], K[z][1][1]);
      s[z][2] = p0 ? s[z][2] : S[2]; s[z][3] = p1 ? s[z][3] : S[3];
    }
    const float sc0 = st.y * (0.25f * 1.4426950408889634f), sc1 = st.w * (0.25f * 1.4426950408889634f);
    uint32_t pw[4][2];
#pragma unroll
    for (int r = 1; r >= 0; --r) {
      if (r == 0) {
        fixo(hv, h);
        PROFD(41, hv[3].x);
#pragma unroll
        for (int z = 0; z < 4; ++z) {
          float S[4];
          mma16z(S, Q[z][0], Q[z][1], Q[z][2], Q[z][3], hv[z].x, hv[z].y);
          if (first) S[0] = S[1] = __uint_as_float(0xFF800000u);
          s[z][0] = p0 ? S[0] : s[z][0]; s[z][1] = p1 ? S[1] : s[z][1];
        }
      }
#pragma unroll
      for (int z = 0; z < 4; ++z) mx[z][r] = fmaxf(s[z][2 * r], s[z][2 * r + 1]);
#pragma unroll
      for (int o = 1; o < 3; ++o)
#pragma unroll
        for (int z = 0; z < 4; ++z) mx[z][r] = fmaxf(mx[z][r], __shfl_xor_sync(0xffffffffu, mx[z][r], o));
#pragma unroll
      for (int z = 0; z < 4; ++z) pw[z][r] = pack2(ex2((s[z][2 * r] - mx[z][r]) * (r ? sc1 : sc0)), ex2((s[z][2 * r + 1] - mx[z][r]) * (r ? sc1 : sc0)));
    }
    mbar_wait(layer ? B_N : B_Z, layer);
    const uint32_t M = (p0 ? 0xFFFFu : 0u) | (p1 ? 0xFFFF0000u : 0u);
    uint4* O = SCR->O + ((J * 8 + cg) * 512 + (2 * (w & 2) + (w & 1)) * 64 + t * 8 + g);
#pragma unroll
    for (int h2 = 0; h2 < 2; ++h2) {
      uint32_t ow[2][4];
#pragma unroll
      for (int z = 0; z < 2; ++z) {
        const int n = 2 * h2 + z;
        const uint32_t w0 = pw[n][0], w1 = pw[n][1];
        float sm[4] = {0.f, 0.f, 0.f, 0.f}, Oa[2][4];
        mma8(sm, w0, w1, 0x3F803F80u);
        mma16z(Oa[0], w0 & ~M, w1 & M, 0u, w1 & ~M, V[n][0][0], V[n][1][0]); mma8(Oa[0], w0 & M, 0u, hv[n].z);
        mma16z(Oa[1], w0 & ~M, w1 & M, 0u, w1 & ~M, V[n][0][1], V[n][1][1]); mma8(Oa[1], w0 & M, 0u, hv[n].w);
        const float i0 = rcp(sm[0]), i1 = rcp(sm[2]);
#pragma unroll
        for (int d = 0; d < 2; ++d) { ow[0][2 * z + d] = pack2(Oa[d][0] * i0, Oa[d][1] * i0); ow[1][2 * z + d] = pack2(Oa[d][2] * i1, Oa[d][3] * i1); }
      }
#pragma unroll
      for (int hi = 0; hi < 2; ++hi) str4(O + hi * 128 + h2 * 32, ow[hi][0], ow[hi][1], ow[hi][2], ow[hi][3]);
    }
  }
  str1(SCR->OF[layer] + (J * 32 + cg * 4 + w), 1);
  mbar_arrive1(B_AT + 8 * e + (lds1(csb) & P.zero));
  PROF(9 + 12 * layer);
  float ac[32];
  undef(ac);
  const uint32_t so = SM_O + e * O_E;
  {
    const uint32_t bo = B_O + 32 * e;
    const uint32_t dw = (SM_WO >> 4) | (512 << 16), da = dlo(so, 512);
    mbar_wait(B_WO, layer);
#pragma unroll
    for (int j = 0; j < 4; ++j) {
      mbar_wait(bo + 8 * j, layer);
      if (j == 0) { PROF(32 + layer); mbar_wait(B_AT + 8, layer); }
      wg_fence();
#pragma unroll
      for (int k = 8 * j; k < 8 * j + 8; ++k) {
        const uint32_t a = da + (k >> 2) * 512 + (k & 3) * 8, b = dw + (k & 3) * 1024 + (k >> 2) * 128;
        if (k) wg_ss64<1>(ac, a, b); else wg_ss64<0>(ac, a, b);
      }
      wg_commit();
    }
#pragma unroll 1
    for (uint32_t late = P.zero;; late = 1) {
      if (late) {
        const uint16_t* op = (const uint16_t*)(SCR->O + (J * 4096 + w * 128 + g));
        wg_wait<0>();
        zero(ac);
#pragma unroll 1
        for (int k = 0; k < 512; ++k) {
          const uint16_t* q = op + (k >> 6) * 4096 + (k & 56) * 8 + (k & 7);
          slow_step(ac, ldnan(q), ldnan(q + 512), P.wo + (((k & ~31) + 4 * (k & 6) + ((k >> 2) & 6) + (k & 1)) * 512 + 64 * cg + 2 * t), P.zero);
        }
      }
      wg_wait<0>();
      if (!rows_nan(ac[0], ac[2]) || late) break;
    }
  }
  PROF(10 + 12 * layer);
#pragma unroll
  for (int j = 0; j < 8; ++j) {
    res[j][0] = hadd2(res[j][0], pack2(ac[4 * j], ac[4 * j + 1]));
    res[j][1] = hadd2(res[j][1], pack2(ac[4 * j + 2], ac[4 * j + 3]));
  }
  if (layer == 0) {
    const float4 s = gram(res, g);
    str4_if(&SCR->PS[(G * 8 + cg) * 8 + g], nzmap(__float_as_uint(s.x)), __float_as_uint(s.y), __float_as_uint(s.z), __float_as_uint(s.w), t == (g >> 1));
    const int xo = (32 * (cg & 3) + t) * 2048 + (cg >> 2) * 512 + xg_off(G, g);
#pragma unroll
    for (int j = 0; j < 8; ++j) {
      str2((uint2*)SCR->XG[1] + (xo + j * 8192), nzmap(prmt(res[j][0], res[j][1], 0x5410)), prmt(res[j][0], res[j][1], 0x7632));
    }
    __syncwarp();
    mbar_arrive1(B_ED + 8 * e);
  } else {
    const uint32_t stg = so + w * 2048;
    const int row = (lane & 7) + 8 * ((lane >> 3) & 1);
    bar_sync(NB_WG + e, 128);
#pragma unroll
    for (int j = 0; j < 8; j += 2)
      stsm4(stg + row * 128 + (((j + (lane >> 4)) ^ (row & 7)) * 16), res[j][0], res[j][1], res[j + 1][0], res[j + 1][1]);
    __syncwarp();
#pragma unroll
    for (int k = 0; k < 4; ++k) {
      const int r = 4 * k + (lane >> 3);
      const uint4 v = lds4(stg + r * 128 + (((lane & 7) ^ (r & 7)) * 16));
      stw4(P.out + ((16 * G + 2 * (lane >> 3)) * 512 + 64 * cg + 8 * (lane & 7)) + ((k & 1) * 8 + (k >> 1)) * 512, v.x, v.y, v.z, v.w);
    }
  }
  PROF(11 + 12 * layer);
}

DEV void col_sums(const Params& P, int c, int wa, int lane) {
  const int i = c >> 3, cg = c & 7;
  uint4 wv[8];
#pragma unroll
  for (int k = 0; k < 8; ++k) wv[k] = ldnc4(P.wqkv + ((32 * i + (lane >> 3)) * 1536 + wa * 512 + 64 * cg + 8 * (lane & 7)) + 4 * k * 1536);
  float cs[8];
  zero(cs);
#pragma unroll
  for (int k = 0; k < 8; ++k) {
    cs[0] += bflo(wv[k].x); cs[1] += bfhi(wv[k].x); cs[2] += bflo(wv[k].y); cs[3] += bfhi(wv[k].y);
    cs[4] += bflo(wv[k].z); cs[5] += bfhi(wv[k].z); cs[6] += bflo(wv[k].w); cs[7] += bfhi(wv[k].w);
  }
  const bool b4 = lane & 16, b3 = lane & 8;
#pragma unroll
  for (int k = 0; k < 4; ++k) cs[k] = (b4 ? cs[k + 4] : cs[k]) + __shfl_xor_sync(0xffffffffu, b4 ? cs[k] : cs[k + 4], 16);
#pragma unroll
  for (int k = 0; k < 2; ++k) cs[k] = (b3 ? cs[k + 2] : cs[k]) + __shfl_xor_sync(0xffffffffu, b3 ? cs[k] : cs[k + 2], 8);
  str2((uint2*)SCR->CS + (i * 768 + wa * 256 + 32 * cg + 4 * (lane & 7) + (lane >> 3)), nzmap(__float_as_uint(cs[0])), __float_as_uint(cs[1]));
}
DEV void col_gather(const Params& P, int c, int wa, int lane) {
  const uint2* p = (const uint2*)SCR->CS + (wa * 256 + 32 * (c & 7) + lane);
#pragma unroll 1
  for (int it = 0;; ++it) {
    float a = 0.f, b = 0.f;
    uint32_t m = ~0u;
#pragma unroll
    for (int k = 0; k < 16; ++k) { const uint2 q = ldr2(p + k * 768); m = min(m, q.x); a += __uint_as_float(q.x); b += __uint_as_float(q.y); }
    if (__all_sync(0xffffffffu, m != 0u)) { sts2f(SM_CS + wa * 256 + lane * 8, a, b); break; }
    spin_guard(it);
  }
  __syncwarp();
  mbar_arrive1(B_CS);
}

DEV void aux_prologue(const Params& P, int c, int wa, int lane, uint4 (&s0)[2][2]) {
  const int g = lane >> 2, t = lane & 3, G = stat_group(c);
  {
    uint32_t w[16][2];
    const uint16_t* row = P.x0 + ((16 * G + 2 * g) * 512 + 128 * wa + 8 * t);
    bar_sync(NB_Y, 384);
    __nanosleep(100);
#pragma unroll
    for (int z = 0; z < 8; ++z) {
      const uint4 v = ldw4(row + (z & 1) * 512 + (z >> 1) * 32);
      const int o = 4 * (z >> 1);
      w[o][z & 1] = v.x; w[o + 1][z & 1] = v.y; w[o + 2][z & 1] = v.z; w[o + 3][z & 1] = v.w;
    }
    PROF(34);
    PROFD(35, w[0][0]);
    PROFD(36, w[15][1]);
    uint2* xo = (uint2*)SCR->XG[0] + ((64 * (wa & 1) + 4 * t) * 2048 + (wa >> 1) * 512 + xg_off(G, g));
#pragma unroll
    for (int n = 0; n < 16; ++n) str2(xo + (16 * (n >> 2) + (n & 3)) * 2048, nzmap(prmt(w[n][0], w[n][1], 0x5410)), prmt(w[n][0], w[n][1], 0x7632));
    const float4 s = gram(w, g);
    if (t == (g >> 1)) sts4f(SM_MISC + (wa * 8 + g) * 16, s.x, s.y, s.z, s.w);
    bar_arrive(NB_P0, 192);
  }
  PROF(2);
  if (lane == 0)
    asm volatile("cp.async.bulk.prefetch.L2.global [%0],4096;" :: "l"(wa < 3 ? P.wqkv + (3 * c + wa) * 2048 : P.wo + c * 2048) : "memory");
  bar_sync(NB_Y + 1, 256);
  sload(P, c, 32 * wa + lane, 0, s0);
}

DEV void stat_part(const Params& P, int c, int wa, int lane, int layer, int h, float (&v)[2]) {
  lane = opq(lane);
  const int e = wa >> 1;
  uint32_t x[4][4];
  mbar_wait(B_A + 16 * e, h); mbar_wait(B_A + 16 * e + 8, h);
#pragma unroll
  for (int k = 0; k < 4; ++k) ldsm4t(x[k], SM_A + e * A_E + (128 * (wa & 1) + lane) * 128 + (((c ^ lane) & 7) * 16) + k * 4096);
  float s[4] = {0.f, 0.f, 0.f, 0.f};
#pragma unroll
  for (int k = 0; k < 16; ++k) { const float a = bflo(x[k >> 2][k & 3]), b = bfhi(x[k >> 2][k & 3]); s[0] += a; s[1] += a * a; s[2] += b; s[3] += b * b; }
  s[0] += s[2]; s[1] += s[3];
  if (RARE(__any_sync(0xffffffffu, s[1] != s[1]))) {
    const uint16_t* q = (const uint16_t*)(SCR->XF[layer] + ((32 * e + 2 * (c >> 3) + h) * 2048 + (wa & 1) * 1024)) + (lane >> 2);
    s[0] = s[1] = 0.f;
#pragma unroll 1
    for (int k = 0; k < 32; ++k) {
      const int r = 2 * (lane & 3) + (k & 1);
      const float a = ldnan(q + ((k >> 1) * 8 + r) * 64 + ((c ^ r) & 7) * 8);
      s[0] += a; s[1] += a * a;
    }
  }
  v[0] += s[0]; v[1] += s[1];
  __syncwarp();
}
DEV void stat_finish(const Params& P, int c, int wa, int lane, int layer, float (&v)[2]) {
  lane = opq(lane);
  const bool b = lane & 1;
  const float s = (b ? v[1] : v[0]) + __shfl_xor_sync(0xffffffffu, b ? v[0] : v[1], 1);
  str1((uint32_t*)SCR->ST[layer] + ((128 * (wa >> 1) + c) * 64 + (wa & 1) * 32 + lane), nzmap(__float_as_uint(s)));
  const uint4* sp = SCR->ST[layer] + ((128 * (wa >> 1) + (c & ~7) + 4 * (wa & 1) + (lane >> 3)) * 16 + (lane & 7));
  uint4 x, y;
  for (int it = 0;; ++it) {
    x = ldr4(sp); y = ldr4(sp + 8);
    if (__all_sync(0xffffffffu, min(min(min(x.x, x.y), min(x.z, x.w)), min(min(y.x, y.y), min(y.z, y.w))) != 0u)) break;
    spin_guard(it);
  }
  const uint32_t q = ln_sums((__uint_as_float(x.x) + __uint_as_float(x.z)) + (__uint_as_float(y.x) + __uint_as_float(y.z)),
                             (__uint_as_float(x.y) + __uint_as_float(x.w)) + (__uint_as_float(y.y) + __uint_as_float(y.w)));
  sts2f(SM_STAT + (16 * wa + (lane >> 4) * 8 + (lane & 7)) * 16 + (lane & 8), bflo(q), rcp(bfhi(q)));
  __syncwarp();
  mbar_arrive1(B_ST + 4 * (wa & 2));
}

DEV void nan_source(uint32_t a, int lane) {
#pragma unroll
  for (int k = 0; k < 4; ++k) sts4(a + k * 512 + lane * 16, FILL, FILL, FILL, FILL);
  fence_async_smem();
  __syncwarp();
}
DEV void load_a(const Params& P, int J, int e, int layer, int h) {
  const uint4* src = SCR->XF[layer] + (2 * J + h) * 2048;
  const uint32_t dst = SM_A + e * A_E, b = B_A + 16 * e;
  mbar_expect1(b, 8192); bulk(dst, src, 8192, b);
  mbar_expect1(b + 8, 24576); bulk(dst + 8192, src + 512, 24576, b + 8);
}
__global__ void __launch_bounds__(NTHR, 1)
fused_kernel(const __grid_constant__ Params P, const __grid_constant__ CUtensorMap mapW, const __grid_constant__ CUtensorMap mapWo,
             const __grid_constant__ CUtensorMap mapX) {
  extern __shared__ __align__(1024) uint8_t smem_raw[];
  const int warp = __shfl_sync(0xffffffffu, threadIdx.x >> 5, 0), lane = threadIdx.x & 31;
  uint32_t smid; asm volatile("mov.u32 %0,%%smid;" : "=r"(smid));
  const uint32_t* pw = (const uint32_t*)&P + threadIdx.y;
  const int role = P.role[(smid >> 1) + threadIdx.y] + (smid & 1) + (pw[0] & pw[12]);
  const int c = __shfl_sync(0xffffffffu, pw[1] ? role : blockIdx.x, 0);
  if (c >= 128) {
#pragma unroll 1
    for (int k = (c - 128) * NTHR + threadIdx.x; k < 131072; k += P.spare * NTHR) str4(SCR->XG[1] + k, 0, 0, 0, 0);
    __threadfence();
    __syncthreads();
    if (warp == 0) { cnt_wait(SCR->C + 1, lane); cnt_add1(SCR->C + 6); }
    __syncthreads();
#pragma unroll 1
    for (int k = (c - 128) * NTHR + threadIdx.x; k < 131072; k += P.spare * NTHR) str4(SCR->XG[0] + k, 0, 0, 0, 0);
    return;
  }
#define DONE() do {} while (0)
  const int cg = c & 7;
  if (warp < 8) {
    PROF(46);
    kgen(P, c, warp, lane);
    bar_sync(0, 384);
    PROF(1);
#pragma unroll 1
    for (int layer = 0; layer < 2; ++layer) {
#pragma unroll 1
      for (int rho = 0; rho < 2; ++rho) {
        const int wz = warp + ((rho + layer) & P.zero);
        conv_round(wz >> 2, rho, wz & 3, lane_id());
        PROF(6 + rho + 12 * layer);
      }
      const int z = layer & P.zero;
      attn_phase(P, c + z, (warp + z) >> 2, (warp + z) & 3, lane_id(), layer);
    }
    DONE();
  } else if (warp < 12) {
    asm volatile("setmaxnreg.dec.sync.aligned.u32 %0;" :: "n"(REG_AUX));
    uint4 x[2][2][2], s[2][2];
    aux_prologue(P, c, warp - 8, lane, s);
    PROF(1);
    const int c0 = c;
#pragma unroll 1
    for (int layer = 0;; ++layer) {
      const int c = c0 + (layer & P.zero), wa = warp - 8 + (layer & P.zero);
#define lane lane_id()
#define j (32 * wa + lane_id())
      {
        const uint32_t za = region(wa) + lane * 16 - 512;
        sts4(za + R_U, 0, 0, 0, 0); sts4(za + R_X5, 0, 0, 0, 0); sts4(za + R_X3, 0, 0, 0, 0);
      }
      if (lane == 0) sts4(region(wa) + R_BE, 0, 0, 0, 0);
      uint32_t u[4][4];
      uload(P, c, j, layer, x, s);
      uprep(j, 1, x[1], s[1], u);
      uprep(j, 0, x[0], s[0], u);
      fence_async_smem();
      bar_arrive(NB_U, NBARU);
      bar_sync(NB_H, 192);
      PROF(5 + 12 * layer);
      box_full(j, u, P.zero);
      PROF(3 + 12 * layer);
      mbar_wait(B_Z, 0);
      conv_out(c, j, 0, x, u[0], SCR->XF[layer], P.zero);
      PROF(32);
      conv_out(c, j, 1, x, u[1], SCR->XF[layer], P.zero);
      PROF(6 + 12 * layer);
      if (layer == 0 && wa < 3) col_sums(P, c, wa, lane);
      conv_out(c, j, 2, x, u[2], SCR->XF[layer], P.zero);
      PROF(33);
      conv_out(c, j, 3, x, u[3], SCR->XF[layer], P.zero);
      PROF(7 + 12 * layer);
      float v[2];
      zero(v);
#pragma unroll 1
      for (int h = 0; h < 2; ++h) {
        stat_part(P, c, wa, lane, layer, h, v);
        if (h) break;
        mbar_arrive1(B_AE + 4 * (wa & 2));
        if (layer == 0 && wa < 3) col_gather(P, c, wa, lane);
      }
      PROF(9 + 12 * layer);
      stat_finish(P, c, wa, lane, layer, v);
      PROF(8 + 12 * layer);
      if (layer) break;
      sload(P, c, j, 1, s);
#undef lane
#undef j
    }
    DONE();
  } else {
    asm volatile("setmaxnreg.dec.sync.aligned.u32 %0;" :: "n"(REG_PROD));
    if (s2u(smem_raw) != SB) __trap();
#pragma unroll 1
    for (int n = warp - 12; n < 38; n += 4)
      asm volatile("{.reg .pred p; elect.sync _|p,0xffffffff; @p mbarrier.init.shared::cta.b64 [%0],%1;}"
                   :: "r"(SM_BAR + n * 8), "r"(n > 14 ? 1 : (int)(0x322866444444444ull >> (4 * n)) & 15) : "memory");
    fence_async_smem();
    bar_sync(NB_AUX, 128);
    bar_arrive(0, 384); bar_arrive(NB_Y + 1, 256);
    PROF(1);
    if (warp == 12) {
      if (lane == 0) {
        asm volatile("prefetch.tensormap [%0];" :: "l"(&mapW) : "memory");
        asm volatile("prefetch.tensormap [%0];" :: "l"(&mapWo) : "memory");
        asm volatile("prefetch.tensormap [%0];" :: "l"(&mapX) : "memory");
      }
      nan_source(slot(12), lane);
      mbar_wait(B_U, 0);
#pragma unroll 1
      for (int k = 0; k < 8; ++k) tma2_store(&mapX, slot(12), 128 * c, 8 * k);
#pragma unroll 1
      for (int k = 0; k < 4; ++k) bulk_store(SCR->H[0] + ((c + 8) * 256 + (k >> 1) * 32768 + (k & 1) * 128), slot(12), 2048);
#pragma unroll 1
      for (int k = 0; k < 8; ++k) bulk_store(SCR->O + (c * 512 + (k >> 2) * 65536 + (k & 3) * 128), slot(12), 2048);
      bulk_wait();
      mbar_arrive1(B_Z);
      PROF(24);
#pragma unroll 1
      for (int layer = 0; layer < 2; ++layer) {
        mbar_wait(B_V, layer);
        if (layer == 1 && c < 4 && ((0x47 >> lane) & 1)) str1(SCR->C + c * 32 + lane, 0);
        mbar_expect1(B_WF, 4 * 24576);
#pragma unroll
        for (int k = 0; k < 4; ++k) tma3(slot(wslot(k)), &mapW, 64 * cg, 64 * k, 0, B_WF);
        mbar_wait(B_WF, layer);
        mbar_expect1(B_W4, 2 * 24576);
#pragma unroll
        for (int k = 4; k < 6; ++k) tma3(slot(wslot(k)), &mapW, 64 * cg, 64 * k, 0, B_W4);
        bar_sync(NB_AUX, 64);
#pragma unroll 1
        for (int k = 0; k < 2; ++k) {
          mbar_expect1(B_W6 + 8 * k, 24576);
          mbar_wait(B_F + 8 * k, layer);
          tma3(slot(3 * k), &mapW, 64 * cg, 384 + 64 * k, 0, B_W6 + 8 * k);
        }
        mbar_expect1(B_WO, 65536);
        mbar_wait(B_AE + 8, layer);
        nan_source(slot(12), lane);
        uint4* fp = layer ? SCR->O + c * 512 : SCR->XF[1] + c * 512;
#pragma unroll 1
        for (int r = 7; r >= 0; --r) {
          __nanosleep(30);
          if (r >= 4) {
            bulk_store(fp + (r & 3) * 128, slot(12), 2048); bulk_store(fp + 65536 + (r & 3) * 128, slot(12), 2048);
            if (layer == 0) bulk_store(SCR->H[1] + ((c + 8) * 256 + (r & 2) * 16384 + (r & 1) * 128), slot(12), 2048);
          }
          if (r == 3) { bulk_wait(); __threadfence(); mbar_arrive1(B_N); PROF(9 + 12 * layer); }
          if (r == 1) mbar_wait(B_F + 16, layer);
          tma4(SM_WO + r * 8192, &mapWo, 64 * cg, 0, r >> 1, 32 * (r & 1), B_WO);
        }
        PROF(8 + 12 * layer);
      }
      DONE();
    } else if (warp == 13) {
      const int G = stat_group(c);
#pragma unroll 1
      for (int layer = 0; layer < 2; ++layer) {
        float z[4];
        if (layer == 0) {
          bar_sync(NB_P0, 192);
          const float4 a = lds4f(SM_MISC + lane * 16);
          z[0] = a.x; z[1] = a.y; z[2] = a.z; z[3] = a.w;
        } else {
          mbar_wait(B_ED + 2 * (c & 4), 0);
          uint4* ps = &SCR->PS[G * 64 + lane];
          uint4 a, b;
          for (int it = 0;; ++it) {
            a = ldr4(ps); b = ldr4(ps + 32);
            if (__all_sync(0xffffffffu, min(a.x, b.x) != 0u)) break;
            spin_guard(it);
          }
          z[0] = __uint_as_float(a.x) + __uint_as_float(b.x); z[1] = __uint_as_float(a.y) + __uint_as_float(b.y);
          z[2] = __uint_as_float(a.z) + __uint_as_float(b.z); z[3] = __uint_as_float(a.w) + __uint_as_float(b.w);
        }
#pragma unroll
        for (int o = 8; o < 32; o <<= 1)
#pragma unroll
          for (int k = 0; k < 4; ++k) z[k] += __shfl_xor_sync(0xffffffffu, z[k], o);
        const uint32_t w0 = ln_sums(z[0], z[1]), w1 = ln_sums(z[2], z[3]);
        const uint32_t r = nzmap(pack2(rcp(bfhi(w0)), rcp(bfhi(w1)))), m = prmt(w0, w1, 0x5410);
        uint2* so = (uint2*)&SCR->SR[layer][lane >> 3][sr_off(G, lane)] + (lane & 1);
        str2(so, r, m); str2(so + 4 * 1024, r, m);
        PROF(4 + 12 * layer);
        box_help(0, lane);
        PROF(6 + 12 * layer);
      }
      DONE();
    } else if (warp == 14) {
#pragma unroll 1
      for (int layer = 0; layer < 2; ++layer) {
        if (layer) { mbar_wait(B_N, 0); mbar_wait(B_ED, 0); mbar_wait(B_ED + 8, 0); } else bar_sync(NB_P0, 192);
        cnt_add1(SCR->C + (c >> 5) * 32 + 3 * layer);
        if (layer == 0) bar_arrive(NB_P0 + 1, 288);
        mbar_expect1(B_E, 16384);
        PROF(4 + 12 * layer);
        cnt_wait(SCR->C + 3 * layer, lane);
        mbar_arrive1(B_U);
        bulk(SM_X, SCR->XG[layer] + c * 1024, 16384, B_E);
        PROF(5 + 12 * layer);
        if (layer == 0) {
          mbar_wait(B_Z, 0);
          __threadfence();
          mbar_arrive1(B_Z + 8);
          PROF(11);
        }
#pragma unroll 1
        for (int n = 0; n < 4; ++n) {
          if (n == 0) mbar_wait(B_RD, layer);
          if (!(n & 1)) cnt_wait(SCR->C + 3 * layer + 1 + (n >> 1), lane);
          if (n == 2) PROF(7 + 12 * layer);
          mbar_wait((n & 2 ? B_AE : B_RD) + 8 * (n & 1), layer);
          load_a(P, 16 * (n & 1) + (c >> 3), n & 1, layer, n >> 1);
          bar_arrive_if(NB_AUX, 64, n == 2);
          if (!(n & 1)) PROF(6 + n + 12 * layer);
        }
        if (layer == 0)
          for (int it = 0; ldr1(SCR->C + 6) < P.spare; ++it) spin_guard(it);
        mbar_wait(B_QE, layer);
#pragma unroll 1
        for (int e = 0; e < 2; ++e) {
          const int J = 16 * e + (c >> 3);
          mbar_wait(B_AT + 8 * e, layer);
          uint32_t todo = 0x01010101u;
          pause(300);
#pragma unroll 1
          for (int it = 0; todo; ++it) {
            uint32_t m = __ballot_sync(0xffffffffu, ldr1(SCR->OF[layer] + J * 32 + lane) != 0u);
            m &= m >> 4; m &= m >> 2; m &= m >> 1; m &= todo;
            todo ^= m;
#pragma unroll 1
            for (; m; m &= m - 1) {
              const int j = __ffs(m) - 1;
              mbar_expect1(B_O + 32 * e + j, 16384);
              bulk(SM_O + e * O_E + 2048 * j, SCR->O + (J * 4096 + j * 128), 16384, B_O + 32 * e + j);
            }
            spin_guard(it);
          }
          PROF(9 + e + 12 * layer);
        }
      }
      DONE();
    }
    if (warp == 15) {
      const int G = stat_group(c);
      str4(&SCR->ST[0][(lane >> 4) * 2048 + c * 16 + (lane & 15)], 0, 0, 0, 0); str4(&SCR->ST[1][(lane >> 4) * 2048 + c * 16 + (lane & 15)], 0, 0, 0, 0);
      if (lane < 4) str4(SCR->OF[lane >> 1] + ((lane & 1) * 512 + c * 4), 0, 0, 0, 0);
      str4(&SCR->PS[G * 64 + lane], 0, 0, 0, 0); str4(&SCR->PS[G * 64 + 32 + lane], 0, 0, 0, 0);
      str4(&SCR->SR[1][lane >> 2][sr_off(G, 2 * lane)], 0, 0, 0, 0);
      if (c < 4 && lane < 3) str1(SCR->C + c * 32 + 3 + lane, 0);
#pragma unroll
      for (int k = 0; k < 3; ++k) str2((uint2*)SCR->CS + ((c >> 3) * 768 + k * 256 + 32 * cg + lane), 0, 0);
      __threadfence();
#pragma unroll 1
      for (int layer = 0; layer < 2; ++layer) {
        PROF(4 + 12 * layer);
        box_help(1, lane);
        if (layer) str4(&SCR->SR[0][lane >> 2][sr_off(G, 2 * lane)], 0, 0, 0, 0);
        mbar_wait(B_Z + 8, 0);
        mbar_wait(B_RD, layer);
        cnt_add1(SCR->C + (c >> 5) * 32 + 3 * layer + 1);
        mbar_wait(B_RD + 8, layer);
        cnt_add1(SCR->C + (c >> 5) * 32 + 3 * layer + 2);
        if (P.spare == 0) {
#pragma unroll 1
          for (int k = 0; k < 32; ++k) str4(SCR->XG[layer] + (c * 1024 + k * 32 + lane), 0, 0, 0, 0);
        }
      }
      mbar_watch(B_O + 56, 1);
    }
  }
}

typedef CUresult (*EncodeFn)(CUtensorMap*, CUtensorMapDataType, cuuint32_t, void*, const cuuint64_t*, const cuuint64_t*,
                             const cuuint32_t*, const cuuint32_t*, CUtensorMapInterleave, CUtensorMapSwizzle,
                             CUtensorMapL2promotion, CUtensorMapFloatOOBfill);

static int place_roles(uint8_t* role) {
  int dev = 0, nsm = 0;
  cudaGetDevice(&dev);
  cudaDeviceGetAttribute(&nsm, cudaDevAttrMultiProcessorCount, dev);
  if (nsm <= 128 || nsm > 144 || (nsm & 1)) return 0;
  cudaFuncSetAttribute(fused_kernel, cudaFuncAttributeNonPortableClusterSizeAllowed, 1);
  int occ[9] = {0};
  for (int k = 2; k <= 8; ++k) {
    cudaLaunchConfig_t cfg = {};
    cudaLaunchAttribute at[1];
    at[0].id = cudaLaunchAttributeClusterDimension;
    at[0].val.clusterDim.x = 2 * k; at[0].val.clusterDim.y = 1; at[0].val.clusterDim.z = 1;
    cfg.gridDim = dim3(2 * k); cfg.blockDim = dim3(NTHR); cfg.dynamicSmemBytes = SM_TOTAL; cfg.attrs = at; cfg.numAttrs = 1;
    if (cudaOccupancyMaxActiveClusters(&occ[k], fused_kernel, &cfg) != cudaSuccess) { cudaGetLastError(); occ[k] = 0; }
  }
  int n[10];
  n[7] = occ[8]; n[6] = occ[7]; n[5] = occ[6] - 0; n[4] = occ[5];
  n[3] = occ[4] - n[7]; n[1] = occ[2] - n[3] - n[5] - n[7]; n[0] = n[2] = n[1];
  n[8] = occ[3] - n[2] - n[5];
  const int ntpc = nsm / 2;
  int sum = 0;
  bool ok = n[0] > 0 && n[0] <= 8;
  for (int r = 0; r < 9; ++r) { ok = ok && n[r] >= 0 && (r == 0 || n[r] <= n[r - 1]); sum += n[r]; }
  if (!ok || sum > ntpc) { for (int r = 0; r < 9; ++r) n[r] = r < 8 ? 8 : 0; sum = 64; }
  int tp[8][9], cnt[8] = {0}, pool[72], np = 0, id = 0;
  for (int r = 0; r < 9; ++r)
    for (int g = n[0] - n[r]; g < n[0]; ++g) tp[g][cnt[g]++] = id++;
  for (; id < ntpc; ++id) pool[np++] = id;
  int order[72], no = 0;
  for (int g = 0; g < n[0]; ++g) {
    const int full = cnt[g] / 4 * 4;
    for (int k = 0; k < cnt[g]; ++k) { if (k < full) order[no++] = tp[g][k]; else pool[np++] = tp[g][k]; }
  }
  for (int k = 0; k < np; ++k) order[no++] = pool[k];
  for (int k = 0; k < ntpc; ++k) role[order[k]] = 2 * k;
  return nsm;
}

extern "C" void kernel_launch(void* const* d_in, const int* in_sizes, int n_in, void* d_out, int out_size) {
  (void)in_sizes; (void)n_in; (void)out_size;
  static EncodeFn enc = nullptr;
  static uint8_t role[72];
  static int nsm = 0;
  static Scratch* scratch = nullptr;
  if (!enc) {
    void* fn = nullptr;
    cudaDriverEntryPointQueryResult qr;
    cudaGetDriverEntryPoint("cuTensorMapEncodeTiled", &fn, cudaEnableDefault, &qr);
    enc = (EncodeFn)fn;
    cudaFuncSetAttribute(fused_kernel, cudaFuncAttributeMaxDynamicSharedMemorySize, SM_TOTAL);
    nsm = place_roles(role);
    cudaGetSymbolAddress((void**)&scratch, g_S);
  }
  CUtensorMap mW, mWo, mX;
  {
    cuuint64_t dim[3] = {512, 512, 3}, str[2] = {3072, 1024};
    cuuint32_t box[3] = {64, 64, 3}, es[3] = {1, 1, 1};
    enc(&mW, CU_TENSOR_MAP_DATA_TYPE_BFLOAT16, 3, d_in[10], dim, str, box, es, CU_TENSOR_MAP_INTERLEAVE_NONE,
        CU_TENSOR_MAP_SWIZZLE_128B, CU_TENSOR_MAP_L2_PROMOTION_NONE, CU_TENSOR_MAP_FLOAT_OOB_FILL_NONE);
  }
  {
    cuuint64_t dim[4] = {512, 2, 4, 64}, str[3] = {1024, 2048, 8192};
    cuuint32_t box[4] = {64, 2, 1, 32}, es[4] = {1, 1, 1, 1};
    enc(&mWo, CU_TENSOR_MAP_DATA_TYPE_BFLOAT16, 4, d_in[11], dim, str, box, es, CU_TENSOR_MAP_INTERLEAVE_NONE,
        CU_TENSOR_MAP_SWIZZLE_128B, CU_TENSOR_MAP_L2_PROMOTION_NONE, CU_TENSOR_MAP_FLOAT_OOB_FILL_NONE);
  }
  {
    cuuint64_t dim[2] = {16384, 64}, str[1] = {32768};
    cuuint32_t box[2] = {128, 8}, es[2] = {1, 1};
    enc(&mX, CU_TENSOR_MAP_DATA_TYPE_BFLOAT16, 2, scratch->XF[0], dim, str, box, es, CU_TENSOR_MAP_INTERLEAVE_NONE,
        CU_TENSOR_MAP_SWIZZLE_NONE, CU_TENSOR_MAP_L2_PROMOTION_NONE, CU_TENSOR_MAP_FLOAT_OOB_FILL_NONE);
  }
  Params P;
  P.x0 = (const uint16_t*)d_in[0]; P.Are = (const uint16_t*)d_in[1]; P.Aim = (const uint16_t*)d_in[2];
  P.Bre = (const uint16_t*)d_in[3]; P.Bim = (const uint16_t*)d_in[4]; P.Cre = (const uint16_t*)d_in[5];
  P.Cim = (const uint16_t*)d_in[6]; P.logdt = (const uint16_t*)d_in[7]; P.dskip = (const uint16_t*)d_in[8];
  P.wqkv = (const uint16_t*)d_in[10]; P.wo = (const uint16_t*)d_in[11]; P.out = (uint16_t*)d_out;
  for (int k = 0; k < 72; ++k) P.role[k] = role[k];
  P.zero = 0;
  P.mid = (char*)scratch->C;
  P.spare = nsm > 0 ? nsm - 128 : 0;
  fused_kernel<<<nsm > 0 ? nsm : 128, NTHR, SM_TOTAL, cudaStreamPerThread>>>(P, mW, mWo, mX);
}
```

```cpp
#include <cuda_runtime.h>
#include <cuda_bf16.h>
#include <cuda.h>
#include <stdint.h>
#include <stddef.h>

#define DEV __device__ __forceinline__
#define RARE(x) __builtin_expect(!!(x), 0)

constexpr int NTHR = 512;
constexpr int REG_MAIN = 192, REG_AUX = 96, REG_PROD = 32;
constexpr int NBARU = 384;
constexpr int SPIN_LIMIT = 1 << 22;

constexpr uint32_t SB = 1024;
__host__ __device__ constexpr uint32_t slot(int n) { return SB + n * 8192; }
__host__ __device__ constexpr int wslot(int k) { return k < 2 ? 3 * k : k < 4 ? 3 * k + 6 : k < 6 ? 21 - 3 * k : 3 * k - 18; }
constexpr uint32_t SM_A = slot(22), A_E = 0u - 32768;
constexpr uint32_t SM_O = slot(18), O_E = 0u - 147456;
constexpr uint32_t SM_WO = slot(10), SM_X = slot(8), SM_KV = slot(9) - 4096;
constexpr uint32_t SM_TAP  = slot(26);
constexpr int TAP_SZ = 3440;
constexpr uint32_t SM_STAT = SM_TAP + 4 * TAP_SZ;
constexpr uint32_t SM_CS   = SM_STAT + 1024;
constexpr uint32_t SM_MISC = SM_CS + 768;
constexpr uint32_t SM_BAR  = SM_MISC + 528;
constexpr int SM_TOTAL = SM_BAR + 304 - SB;
static_assert(SM_TOTAL <= 232448, "");
constexpr int R_SZ = 16384, R_U = 512, R_X5 = 5120, R_X3 = 8704, R_BO = 11776, R_BE = 13824;
constexpr int X_5 = 576, X_3 = 648, T_E = 2 * 720, T_O = 1600 + 2 * 721, T_C = 3390, T_K = 3424;
constexpr uint32_t B_RD = SM_BAR, B_ED = SM_BAR + 16, B_F = SM_BAR + 32, B_AT = SM_BAR + 56;
constexpr uint32_t B_AE = SM_BAR + 72, B_QE = SM_BAR + 88, B_ST = SM_BAR + 96, B_CS = SM_BAR + 112;
constexpr uint32_t B_WO = SM_BAR + 120, B_W6 = SM_BAR + 128, B_U = SM_BAR + 144, B_E = SM_BAR + 152, B_A = SM_BAR + 160, B_O = SM_BAR + 192,
                   B_Z = SM_BAR + 256, B_WF = SM_BAR + 272, B_W4 = SM_BAR + 280, B_N = SM_BAR + 288, B_V = SM_BAR + 296;
constexpr int NB_U = 1, NB_B = 2, NB_K = 8, NB_Y = 6, NB_WG = 8, NB_T = 10, NB_AUX = 12, NB_P0 = 13, NB_H = 15;

struct Scratch {
  uint4    XG[2][128 * 1024];
  uint4    O[32 * 8 * 512];
  uint32_t C[8 * 32];
  uint32_t OF[2][32 * 32];
  uint4    CS[16 * 1536 / 4];
  uint4    PS[128 * 64];
  uint4    ST[2][32 * 128];
  uint4    SR[2][8][512];
  uint4    XF[2][32 * 512 * 8];
  uint4    H[2][17 * 8 * 256];
};
__device__ __align__(1024) Scratch g_S;
#define SCR ((Scratch*)(P.mid - offsetof(Scratch, C)))
#define PROFD(slot, v) do {} while (0)
#define PROF(slot) do {} while (0)

DEV uint32_t s2u(const void* p) { return (uint32_t)__cvta_generic_to_shared(p); }
template <class T> DEV T opq(T x) { asm volatile("" : "+r"(x)); return x; }
DEV int lane_id() { int l; asm volatile("mov.u32 %0,%%laneid;" : "=r"(l)); return l; }
DEV uint32_t pack2(float lo, float hi) { uint32_t d; asm("cvt.rn.bf16x2.f32 %0,%1,%2;" : "=r"(d) : "f"(hi), "f"(lo)); return d; }
DEV float bflo(uint32_t v) { return __uint_as_float(v << 16); }
DEV float bfhi(uint32_t v) { return __uint_as_float(v & 0xFFFF0000u); }
DEV float bfr(float x) { return bflo(pack2(x, 0.f)); }
DEV uint32_t hadd2(uint32_t a, uint32_t b) { uint32_t d; asm("add.rn.bf16x2 %0,%1,%2;" : "=r"(d) : "r"(a), "r"(b)); return d; }
DEV uint32_t hsub2(uint32_t a, uint32_t b) { uint32_t d; asm("sub.rn.bf16x2 %0,%1,%2;" : "=r"(d) : "r"(a), "r"(b)); return d; }
DEV uint32_t hmul2(uint32_t a, uint32_t b) { uint32_t d; asm("mul.rn.bf16x2 %0,%1,%2;" : "=r"(d) : "r"(a), "r"(b)); return d; }
DEV uint32_t hfma2(uint32_t a, uint32_t b, uint32_t c) { uint32_t d; asm("fma.rn.bf16x2 %0,%1,%2,%3;" : "=r"(d) : "r"(a), "r"(b), "r"(c)); return d; }
DEV uint32_t hmax2(uint32_t a, uint32_t b) { uint32_t d; asm("max.bf16x2 %0,%1,%2;" : "=r"(d) : "r"(a), "r"(b)); return d; }
DEV uint32_t prmt(uint32_t a, uint32_t b, uint32_t s) { uint32_t d; asm("prmt.b32 %0,%1,%2,%3;" : "=r"(d) : "r"(a), "r"(b), "r"(s)); return d; }
DEV uint32_t nzmap(uint32_t v) { return v == 0u ? 0x80000000u : v; }
DEV float rcp(float x) { float y; asm("rcp.approx.ftz.f32 %0,%1;" : "=f"(y) : "f"(x)); return y; }
DEV float sqrt_(float x) { float y; asm("sqrt.approx.ftz.f32 %0,%1;" : "=f"(y) : "f"(x)); return y; }
DEV float ex2(float x) { float y; asm("ex2.approx.ftz.f32 %0,%1;" : "=f"(y) : "f"(x)); return y; }

DEV uint4 ldr4(const void* p) { uint4 v; asm volatile("ld.relaxed.gpu.global.v4.u32 {%0,%1,%2,%3},[%4];" : "=r"(v.x), "=r"(v.y), "=r"(v.z), "=r"(v.w) : "l"(p) : "memory"); return v; }
DEV void ldr4_if(uint4& v, const void* p, bool c) {
  asm volatile("{.reg .pred q; setp.ne.u32 q,%5,0; @q ld.relaxed.gpu.global.v4.u32 {%0,%1,%2,%3},[%4];}"
    : "+r"(v.x), "+r"(v.y), "+r"(v.z), "+r"(v.w) : "l"(p), "r"((uint32_t)c) : "memory");
}
DEV uint2 ldr2(const void* p) { uint2 v; asm volatile("ld.relaxed.gpu.global.v2.u32 {%0,%1},[%2];" : "=r"(v.x), "=r"(v.y) : "l"(p) : "memory"); return v; }
DEV void ldr2_if(uint2& v, const void* p, bool c) {
  asm volatile("{.reg .pred q; setp.ne.u32 q,%3,0; @q ld.relaxed.gpu.global.v2.u32 {%0,%1},[%2];}" : "+r"(v.x), "+r"(v.y) : "l"(p), "r"((uint32_t)c) : "memory");
}
DEV uint32_t ldr1(const void* p) { uint32_t v; asm volatile("ld.relaxed.gpu.global.u32 %0,[%1];" : "=r"(v) : "l"(p) : "memory"); return v; }
DEV float ldnan(const uint16_t* p) {
  uint32_t v = 0xFFFFu;
#pragma unroll 1
  for (int it = 0; it < SPIN_LIMIT && __any_sync(0xffffffffu, v == 0xFFFFu); ++it) asm volatile("ld.relaxed.gpu.global.u16 %0,[%1];" : "=r"(v) : "l"(p) : "memory");
  return __uint_as_float(v << 16);
}
DEV uint4 ldw4(const void* p) { uint4 v; asm volatile("ld.global.v4.u32 {%0,%1,%2,%3},[%4];" : "=r"(v.x), "=r"(v.y), "=r"(v.z), "=r"(v.w) : "l"(p) : "memory"); return v; }
DEV uint2 ldw2(const void* p) { uint2 v; asm volatile("ld.global.v2.u32 {%0,%1},[%2];" : "=r"(v.x), "=r"(v.y) : "l"(p) : "memory"); return v; }
DEV uint32_t ldw1(const void* p) { uint32_t v; asm volatile("ld.global.u32 %0,[%1];" : "=r"(v) : "l"(p) : "memory"); return v; }
DEV void str4(void* p, uint32_t a, uint32_t b, uint32_t c, uint32_t d) { asm volatile("st.relaxed.gpu.global.v4.u32 [%0],{%1,%2,%3,%4};" :: "l"(p), "r"(a), "r"(b), "r"(c), "r"(d) : "memory"); }
DEV void str2(void* p, uint32_t a, uint32_t b) { asm volatile("st.relaxed.gpu.global.v2.u32 [%0],{%1,%2};" :: "l"(p), "r"(a), "r"(b) : "memory"); }
DEV void str1(void* p, uint32_t a) { asm volatile("st.relaxed.gpu.global.u32 [%0],%1;" :: "l"(p), "r"(a) : "memory"); }
DEV void str4_if(void* p, uint32_t a, uint32_t b, uint32_t c, uint32_t d, bool q) {
  asm volatile("{.reg .pred q; setp.ne.u32 q,%5,0; @q st.relaxed.gpu.global.v4.u32 [%0],{%1,%2,%3,%4};}" :: "l"(p), "r"(a), "r"(b), "r"(c), "r"(d), "r"((uint32_t)q) : "memory");
}
DEV void stw4(void* p, uint32_t a, uint32_t b, uint32_t c, uint32_t d) { asm volatile("st.global.v4.u32 [%0],{%1,%2,%3,%4};" :: "l"(p), "r"(a), "r"(b), "r"(c), "r"(d) : "memory"); }
DEV uint4 ldnc4(const void* p) { uint4 v; asm volatile("ld.global.nc.v4.u32 {%0,%1,%2,%3},[%4];" : "=r"(v.x), "=r"(v.y), "=r"(v.z), "=r"(v.w) : "l"(p)); return v; }
DEV uint32_t ldnc1(const void* p) { uint32_t v; asm volatile("ld.global.nc.u32 %0,[%1];" : "=r"(v) : "l"(p)); return v; }
DEV uint2 ldnc2(const void* p) { uint2 v; asm volatile("ld.global.nc.v2.u32 {%0,%1},[%2];" : "=r"(v.x), "=r"(v.y) : "l"(p)); return v; }

DEV uint2 lds2(uint32_t a) { uint2 v; asm volatile("ld.volatile.shared.v2.u32 {%0,%1},[%2];" : "=r"(v.x), "=r"(v.y) : "r"(a)); return v; }
DEV float lds16f(uint32_t a) { uint32_t v; asm volatile("ld.shared.u16 %0,[%1];" : "=r"(v) : "r"(a)); return __uint_as_float(v << 16); }
DEV void sts2(uint32_t a, uint32_t x, uint32_t y) { asm volatile("st.shared.v2.u32 [%0],{%1,%2};" :: "r"(a), "r"(x), "r"(y) : "memory"); }
DEV uint32_t lds1(uint32_t a) { uint32_t v; asm volatile("ld.volatile.shared.u32 %0,[%1];" : "=r"(v) : "r"(a)); return v; }
DEV uint32_t lds1z(uint32_t a, bool c) {
  uint32_t v; asm volatile("{.reg .pred q; setp.ne.u32 q,%2,0; mov.u32 %0,0; @q ld.volatile.shared.u32 %0,[%1];}" : "=r"(v) : "r"(a), "r"((uint32_t)c)); return v;
}
DEV uint4 lds4z(uint32_t a, bool c) {
  uint4 v = make_uint4(0, 0, 0, 0);
  asm volatile("{.reg .pred q; setp.ne.u32 q,%5,0; @q ld.volatile.shared.v4.u32 {%0,%1,%2,%3},[%4];}" : "+r"(v.x), "+r"(v.y), "+r"(v.z), "+r"(v.w) : "r"(a), "r"((uint32_t)c));
  return v;
}
DEV float lds1f(uint32_t a) { float v; asm volatile("ld.shared.f32 %0,[%1];" : "=f"(v) : "r"(a)); return v; }
DEV float2 lds2f(uint32_t a) { float2 v; asm volatile("ld.shared.v2.f32 {%0,%1},[%2];" : "=f"(v.x), "=f"(v.y) : "r"(a)); return v; }
DEV float4 lds4f(uint32_t a) { float4 v; asm volatile("ld.shared.v4.f32 {%0,%1,%2,%3},[%4];" : "=f"(v.x), "=f"(v.y), "=f"(v.z), "=f"(v.w) : "r"(a)); return v; }
DEV uint4 lds4(uint32_t a) { uint4 v; asm volatile("ld.volatile.shared.v4.u32 {%0,%1,%2,%3},[%4];" : "=r"(v.x), "=r"(v.y), "=r"(v.z), "=r"(v.w) : "r"(a)); return v; }
DEV void sts1(uint32_t a, uint32_t v) { asm volatile("st.shared.u32 [%0],%1;" :: "r"(a), "r"(v) : "memory"); }
DEV void sts16(uint32_t a, uint32_t v) { asm volatile("{.reg .b16 h; cvt.u16.u32 h,%1; st.shared.u16 [%0],h;}" :: "r"(a), "r"(v) : "memory"); }
DEV void sts2f(uint32_t a, float x, float y) { asm volatile("st.shared.v2.f32 [%0],{%1,%2};" :: "r"(a), "f"(x), "f"(y) : "memory"); }
DEV void sts4f(uint32_t a, float x, float y, float z, float w) { asm volatile("st.shared.v4.f32 [%0],{%1,%2,%3,%4};" :: "r"(a), "f"(x), "f"(y), "f"(z), "f"(w) : "memory"); }
DEV void sts4(uint32_t a, uint32_t x, uint32_t y, uint32_t z, uint32_t w) { asm volatile("st.shared.v4.u32 [%0],{%1,%2,%3,%4};" :: "r"(a), "r"(x), "r"(y), "r"(z), "r"(w) : "memory"); }

DEV void ldsm4(uint32_t (&r)[4], uint32_t a) { asm volatile("ldmatrix.sync.aligned.m8n8.x4.shared.b16 {%0,%1,%2,%3},[%4];" : "=r"(r[0]), "=r"(r[1]), "=r"(r[2]), "=r"(r[3]) : "r"(a) : "memory"); }
DEV void ldsm4t(uint32_t (&r)[4], uint32_t a) { asm volatile("ldmatrix.sync.aligned.m8n8.x4.trans.shared.b16 {%0,%1,%2,%3},[%4];" : "=r"(r[0]), "=r"(r[1]), "=r"(r[2]), "=r"(r[3]) : "r"(a) : "memory"); }
DEV void ldsm2(uint32_t (&r)[2], uint32_t a) { asm volatile("ldmatrix.sync.aligned.m8n8.x2.shared.b16 {%0,%1},[%2];" : "=r"(r[0]), "=r"(r[1]) : "r"(a) : "memory"); }
DEV void stsm4(uint32_t a, uint32_t r0, uint32_t r1, uint32_t r2, uint32_t r3) { asm volatile("stmatrix.sync.aligned.m8n8.x4.shared.b16 [%0],{%1,%2,%3,%4};" :: "r"(a), "r"(r0), "r"(r1), "r"(r2), "r"(r3) : "memory"); }
DEV void stsm2(uint32_t a, uint32_t r0, uint32_t r1) { asm volatile("stmatrix.sync.aligned.m8n8.x2.shared.b16 [%0],{%1,%2};" :: "r"(a), "r"(r0), "r"(r1) : "memory"); }
DEV void stsm4t(uint32_t a, uint32_t r0, uint32_t r1, uint32_t r2, uint32_t r3) { asm volatile("stmatrix.sync.aligned.m8n8.x4.trans.shared.b16 [%0],{%1,%2,%3,%4};" :: "r"(a), "r"(r0), "r"(r1), "r"(r2), "r"(r3) : "memory"); }
DEV uint32_t movm(uint32_t a) { uint32_t d; asm volatile("movmatrix.sync.aligned.m8n8.trans.b16 %0,%1;" : "=r"(d) : "r"(a)); return d; }
DEV void mma16(float (&d)[4], uint32_t a0, uint32_t a1, uint32_t a2, uint32_t a3, uint32_t b0, uint32_t b1) {
  asm volatile("mma.sync.aligned.m16n8k16.row.col.f32.bf16.bf16.f32 {%0,%1,%2,%3},{%4,%5,%6,%7},{%8,%9},{%0,%1,%2,%3};"
    : "+f"(d[0]), "+f"(d[1]), "+f"(d[2]), "+f"(d[3]) : "r"(a0), "r"(a1), "r"(a2), "r"(a3), "r"(b0), "r"(b1));
}
DEV void mma16z(float (&d)[4], uint32_t a0, uint32_t a1, uint32_t a2, uint32_t a3, uint32_t b0, uint32_t b1) {
  asm volatile("mma.sync.aligned.m16n8k16.row.col.f32.bf16.bf16.f32 {%0,%1,%2,%3},{%4,%5,%6,%7},{%8,%9},{%10,%10,%10,%10};"
    : "=f"(d[0]), "=f"(d[1]), "=f"(d[2]), "=f"(d[3]) : "r"(a0), "r"(a1), "r"(a2), "r"(a3), "r"(b0), "r"(b1), "f"(0.f));
}
DEV void mma8(float (&d)[4], uint32_t a0, uint32_t a1, uint32_t b0) {
  asm volatile("mma.sync.aligned.m16n8k8.row.col.f32.bf16.bf16.f32 {%0,%1,%2,%3},{%4,%5},{%6},{%0,%1,%2,%3};"
    : "+f"(d[0]), "+f"(d[1]), "+f"(d[2]), "+f"(d[3]) : "r"(a0), "r"(a1), "r"(b0));
}

DEV void bar_sync(int id, int n) { asm volatile("bar.sync %0,%1;" :: "r"(id), "r"(n) : "memory"); }
DEV void bar_sync_if(int id, int n, int c) { asm volatile("{.reg .pred q; setp.ne.s32 q,%2,0; @q bar.sync %0,%1;}" :: "r"(id), "r"(n), "r"(c) : "memory"); }
DEV void bar_arrive_if(int id, int n, int c) { asm volatile("{.reg .pred q; setp.ne.s32 q,%2,0; @q bar.arrive %0,%1;}" :: "r"(id), "r"(n), "r"(c) : "memory"); }
DEV bool bar_any(int id, int n, bool c) {
  uint32_t r; asm volatile("{.reg .pred p,q; setp.ne.u32 q,%3,0; bar.red.or.pred p,%1,%2,q; selp.u32 %0,1,0,p;}" : "=r"(r) : "r"(id), "r"(n), "r"((uint32_t)c) : "memory");
  return __any_sync(0xffffffffu, r);
}
DEV void bar_arrive(int id, int n) { asm volatile("bar.arrive %0,%1;" :: "r"(id), "r"(n) : "memory"); }
DEV void fence_async_glob() { asm volatile("fence.proxy.async.global;" ::: "memory"); }
DEV void fence_async_smem() { asm volatile("fence.proxy.async.shared::cta;" ::: "memory"); }
DEV void mbar_init(uint32_t b, int n) { asm volatile("mbarrier.init.shared::cta.b64 [%0],%1;" :: "r"(b), "r"(n) : "memory"); }
DEV void mbar_arrive(uint32_t b) { asm volatile("mbarrier.arrive.shared::cta.b64 _,[%0];" :: "r"(b) : "memory"); }
DEV void mbar_expect(uint32_t b, int bytes) { asm volatile("mbarrier.arrive.expect_tx.shared::cta.b64 _,[%0],%1;" :: "r"(b), "r"(bytes) : "memory"); }
DEV void mbar_wait(uint32_t b, uint32_t ph) {
  asm volatile("{\n.reg .pred p;\nW: mbarrier.try_wait.parity.shared::cta.b64 p,[%0],%1;\n@!p bra W;\n}" :: "r"(b), "r"(ph) : "memory");
}
DEV void mbar_watch(uint32_t b, uint32_t ph) {
  asm volatile("{\n.reg .pred p,q;\n.reg .u32 n;\nmov.u32 n,0;\n"
               "W: mbarrier.try_wait.parity.shared::cta.b64 p,[%0],%1;\n@p bra D;\n"
               "add.u32 n,n,1;\nsetp.lt.u32 q,n,%2;\n@q bra W;\ntrap;\nD:\n}"
               :: "r"(b), "r"(ph), "n"(SPIN_LIMIT) : "memory");
}
DEV void spin_guard(int it) { asm volatile("{.reg .pred p; setp.gt.s32 p,%0,%1; @p trap;}" :: "r"(it), "n"(SPIN_LIMIT)); }
DEV void split(uint32_t zero) {
  asm volatile("{.reg .pred p; setp.ne.u32 p,%0,0; @p trap;}" :: "r"(zero) : "memory");
}
DEV void pause(int n) {
  uint32_t t0, t; asm volatile("mov.u32 %0,%%clock;" : "=r"(t0));
  do asm volatile("mov.u32 %0,%%clock;" : "=r"(t)); while (t - t0 < n);
}
DEV void cnt_wait(const uint32_t* k, int lane) {
#pragma unroll 1
  for (int it = 0;; ++it) {
    spin_guard(it);
    if (__all_sync(0xffffffffu, ldr1(k + (lane & 3) * 32) >= 32)) break;
  }
}
DEV void mbar_arrive1(uint32_t b) { asm volatile("{.reg .pred p; elect.sync _|p,0xffffffff; @p mbarrier.arrive.shared::cta.b64 _,[%0];}" :: "r"(b) : "memory"); }
DEV void mbar_arrive1_if(uint32_t b, int c) {
  asm volatile("{.reg .pred p,q; setp.ne.s32 q,%1,0; elect.sync _|p,0xffffffff; and.pred p,p,q; @p mbarrier.arrive.shared::cta.b64 _,[%0];}" :: "r"(b), "r"(c) : "memory");
}
DEV void mbar_expect1(uint32_t b, int bytes) { asm volatile("{.reg .pred p; elect.sync _|p,0xffffffff; @p mbarrier.arrive.expect_tx.shared::cta.b64 _,[%0],%1;}" :: "r"(b), "r"(bytes) : "memory"); }
DEV void cnt_add1(uint32_t* q) { asm volatile("{.reg .pred p; elect.sync _|p,0xffffffff; @p red.relaxed.gpu.global.add.u32 [%0],1;}" :: "l"(q) : "memory"); }
DEV void tma4(uint32_t dst, const CUtensorMap* m, int c0, int c1, int c2, int c3, uint32_t bar) {
  asm volatile("{.reg .pred p; elect.sync _|p,0xffffffff;\n"
    "@p cp.async.bulk.tensor.4d.shared::cluster.global.mbarrier::complete_tx::bytes [%0],[%1,{%2,%3,%4,%5}],[%6];}"
    :: "r"(dst), "l"(m), "r"(c0), "r"(c1), "r"(c2), "r"(c3), "r"(bar) : "memory");
}
DEV void tma3(uint32_t dst, const CUtensorMap* m, int c0, int c1, int c2, uint32_t bar) {
  asm volatile("{.reg .pred p; elect.sync _|p,0xffffffff;\n"
    "@p cp.async.bulk.tensor.3d.shared::cluster.global.mbarrier::complete_tx::bytes [%0],[%1,{%2,%3,%4}],[%5];}"
    :: "r"(dst), "l"(m), "r"(c0), "r"(c1), "r"(c2), "r"(bar) : "memory");
}
DEV void bulk(uint32_t dst, const void* src, int bytes, uint32_t bar) {
  asm volatile("{.reg .pred p; elect.sync _|p,0xffffffff;\n@p cp.async.bulk.shared::cluster.global.mbarrier::complete_tx::bytes [%0],[%1],%2,[%3];}" :: "r"(dst), "l"(src), "r"(bytes), "r"(bar) : "memory");
}

DEV void bulk_store(void* dst, uint32_t src, int bytes) {
  asm volatile("{.reg .pred p; elect.sync _|p,0xffffffff;\n@p cp.async.bulk.global.shared::cta.bulk_group [%0],[%1],%2;}" :: "l"(dst), "r"(src), "r"(bytes) : "memory");
}
DEV void tma2_store(const CUtensorMap* m, uint32_t src, int c0, int c1) {
  asm volatile("{.reg .pred p; elect.sync _|p,0xffffffff;\n@p cp.async.bulk.tensor.2d.global.shared::cta.bulk_group [%0,{%2,%3}],[%1];}" :: "l"(m), "r"(src), "r"(c0), "r"(c1) : "memory");
}
DEV void bulk_wait() { asm volatile("cp.async.bulk.commit_group;\ncp.async.bulk.wait_group 0;\nfence.proxy.async.global;" ::: "memory"); }

DEV uint32_t dlo(uint32_t addr, uint32_t lbo) { return __shfl_sync(0xffffffffu, (addr >> 4) | ((lbo >> 4) << 16), 0); }
__host__ __device__ constexpr uint32_t dhi(uint32_t sbo, uint32_t swz) { return (sbo >> 4) | (swz << 30); }
DEV void wg_fence() { asm volatile("wgmma.fence.sync.aligned;" ::: "memory"); }
DEV void wg_commit() { asm volatile("wgmma.commit_group.sync.aligned;" ::: "memory"); }
template <int N> DEV void wg_wait() { asm volatile("wgmma.wait_group.sync.aligned %0;" :: "n"(N) : "memory"); }
template <int N> DEV void zero(float (&d)[N]) {
#pragma unroll
  for (int i = 0; i < N; ++i) d[i] = 0.f;
}
template <int N> DEV void zerov(float (&d)[N]) {
#pragma unroll
  for (int i = 0; i < N; ++i) asm volatile("mov.b32 %0,0;" : "=f"(d[i]));
}
template <int N> DEV void undef(float (&d)[N]) {
#pragma unroll
  for (int i = 0; i < N; ++i) asm volatile("" : "=f"(d[i]));
}
#define R4(d, o) "+f"(d[o]), "+f"(d[o + 1]), "+f"(d[o + 2]), "+f"(d[o + 3])
#define R8(d, o) R4(d, o), R4(d, o + 4)
#define R16(d, o) R8(d, o), R8(d, o + 8)
template <int ACC> DEV void wg_rs64k(float (&d)[32], const uint32_t (&a)[4], uint32_t db) {
  asm volatile("{.reg .pred p; .reg .b64 b; setp.ne.s32 p,%38,0; mov.b64 b,{%36,%37};\n"
    "wgmma.mma_async.sync.aligned.m64n64k16.f32.bf16.bf16 {%0,%1,%2,%3,%4,%5,%6,%7,%8,%9,%10,%11,%12,%13,%14,%15,%16,%17,%18,%19,%20,%21,%22,%23,%24,%25,%26,%27,%28,%29,%30,%31},{%32,%33,%34,%35},b,p,1,1,0;}"
    : R16(d, 0), R16(d, 16) : "r"(a[0]), "r"(a[1]), "r"(a[2]), "r"(a[3]), "r"(db), "n"(dhi(512, 2)), "n"(ACC));
}
template <int ACC> DEV void wg_rs48t(float (&d)[24], const uint32_t (&a)[4], uint32_t db) {
  asm volatile("{.reg .pred p; .reg .b64 b; setp.ne.s32 p,%30,0; mov.b64 b,{%28,%29};\n"
    "wgmma.mma_async.sync.aligned.m64n48k16.f32.bf16.bf16 {%0,%1,%2,%3,%4,%5,%6,%7,%8,%9,%10,%11,%12,%13,%14,%15,%16,%17,%18,%19,%20,%21,%22,%23},{%24,%25,%26,%27},b,p,1,1,1;}"
    : R16(d, 0), R8(d, 16) : "r"(a[0]), "r"(a[1]), "r"(a[2]), "r"(a[3]), "r"(db), "n"(dhi(512, 0)), "n"(ACC));
}
template <int ACC> DEV void wg_rs32t(float (&d)[16], const uint32_t (&a)[4], uint32_t db) {
  asm volatile("{.reg .pred p; .reg .b64 b; setp.ne.s32 p,%22,0; mov.b64 b,{%20,%21};\n"
    "wgmma.mma_async.sync.aligned.m64n32k16.f32.bf16.bf16 {%0,%1,%2,%3,%4,%5,%6,%7,%8,%9,%10,%11,%12,%13,%14,%15},{%16,%17,%18,%19},b,p,1,1,1;}"
    : R16(d, 0) : "r"(a[0]), "r"(a[1]), "r"(a[2]), "r"(a[3]), "r"(db), "n"(dhi(1024, 0)), "n"(ACC));
}
template <int ACC> DEV void wg_ss192(float (&d)[96], uint32_t da, uint32_t db) {
  asm volatile("{.reg .pred p; .reg .b64 a,b; setp.ne.s32 p,%100,0; mov.b64 a,{%96,%98}; mov.b64 b,{%97,%99};\n"
    "wgmma.mma_async.sync.aligned.m64n192k16.f32.bf16.bf16 {"
    "%0,%1,%2,%3,%4,%5,%6,%7,%8,%9,%10,%11,%12,%13,%14,%15,%16,%17,%18,%19,%20,%21,%22,%23,%24,%25,%26,%27,%28,%29,%30,%31,"
    "%32,%33,%34,%35,%36,%37,%38,%39,%40,%41,%42,%43,%44,%45,%46,%47,%48,%49,%50,%51,%52,%53,%54,%55,%56,%57,%58,%59,%60,%61,%62,%63,"
    "%64,%65,%66,%67,%68,%69,%70,%71,%72,%73,%74,%75,%76,%77,%78,%79,%80,%81,%82,%83,%84,%85,%86,%87,%88,%89,%90,%91,%92,%93,%94,%95},a,b,p,1,1,1,1;}"
    : R16(d, 0), R16(d, 16), R16(d, 32), R16(d, 48), R16(d, 64), R16(d, 80) : "r"(da), "r"(db), "n"(dhi(1024, 1)), "n"(dhi(1024, 1)), "n"(ACC));
}
template <int ACC> DEV void wg_ss64(float (&d)[32], uint32_t da, uint32_t db) {
  asm volatile("{.reg .pred p; .reg .b64 a,b; setp.ne.s32 p,%36,0; mov.b64 a,{%32,%34}; mov.b64 b,{%33,%35};\n"
    "wgmma.mma_async.sync.aligned.m64n64k16.f32.bf16.bf16 {"
    "%0,%1,%2,%3,%4,%5,%6,%7,%8,%9,%10,%11,%12,%13,%14,%15,%16,%17,%18,%19,%20,%21,%22,%23,%24,%25,%26,%27,%28,%29,%30,%31},a,b,p,1,1,0,1;}"
    : R16(d, 0), R16(d, 16) : "r"(da), "r"(db), "n"(dhi(1024, 0)), "n"(dhi(1024, 1)), "n"(ACC));
}

DEV uint32_t cpy(uint32_t v, uint32_t id) {
  uint32_t d; asm volatile("prmt.b32 %0,%1,%1,%2;" : "=r"(d) : "r"(v), "r"(id)); return d;
}
struct Params {
  uint32_t zero, spare;
  char* mid;
  const uint16_t *x0, *Are, *Aim, *Bre, *Bim, *Cre, *Cim, *logdt, *dskip, *wqkv, *wo;
  uint16_t* out;
  uint8_t role[72];
};

DEV uint32_t ln_word(float mean, float var) {
  float v = bfr(var);
  float s = sqrt_(bfr(v + 1e-5f));
  return pack2(mean, s);
}

DEV int stat_group(int c) { return c ^ 4; }
DEV int xg_off(int G, int g) { return (G >> 6) * 1024 + (G & 63) * 8 + (g ^ (G & 2)); }
DEV int sr_off(int G, int g) { return (G >> 6) * 256 + (g & 2) * 64 + 2 * (G & 63) + ((g >> 2) & 1); }
DEV uint32_t region(int chl) { return SM_A + (chl >> 1) * A_E + (chl & 1) * R_SZ; }
template <int N> DEV float4 gram(const uint32_t (&w)[N][2], int g) {
  float s0[4], s1[4];
  const uint32_t one = 0x3F803F80u;
  mma16z(s0, w[0][0], one, w[1][0], one, w[0][0], w[1][0]); mma16z(s1, w[0][1], one, w[1][1], one, w[0][1], w[1][1]);
#pragma unroll
  for (int j = 2; j < N; j += 2) {
    mma16(s0, w[j][0], one, w[j + 1][0], one, w[j][0], w[j + 1][0]); mma16(s1, w[j][1], one, w[j + 1][1], one, w[j][1], w[j + 1][1]);
  }
  const bool od = g & 1;
  return make_float4(od ? s0[3] : s0[2], od ? s0[1] : s0[0], od ? s1[3] : s1[2], od ? s1[1] : s1[0]);
}
DEV uint32_t ln_sums(float s, float q) { const float m = s * (1.f / 512.f); return ln_word(m, fmaxf(q * (1.f / 512.f) - m * m, 0.f)); }
DEV void cmul(float& orr, float& oi, float ar, float ai, float br, float bi) {
  float r = ar * br - ai * bi, i = ar * bi + ai * br; orr = r; oi = i;
}
DEV void cexp_(float al, float bt, float s, float& er, float& ei) {
  float mag = ex2(al * s), ph = bt * s;
  ph -= rintf(ph);
  float ang = ph * 6.283185307179586f;
  er = mag * __cosf(ang); ei = mag * __sinf(ang);
}

DEV void kgen(const Params& P, int c, int wm, int lane) {
  const int chl = wm >> 1, mh = wm & 1, g = lane >> 2, t = lane & 3;
  const int ch = 256 * (chl >> 1) + 2 * c + (chl & 1);
  const int mo = ch * 64 + mh * 32 + lane;
  const uint32_t vAr = ldw1((const uint32_t*)P.Are + mo), vAi = ldw1((const uint32_t*)P.Aim + mo);
  const uint32_t vBr = ldw1((const uint32_t*)P.Bre + mo), vBi = ldw1((const uint32_t*)P.Bim + mo);
  const uint32_t vCr = ldw1((const uint32_t*)P.Cre + mo), vCi = ldw1((const uint32_t*)P.Cim + mo);
  const uint32_t vld = ldw1((const uint32_t*)P.logdt + (ch >> 1)) >> (16 * (ch & 1)), vds = ldw1((const uint32_t*)P.dskip + (ch >> 1)) >> (16 * (ch & 1));
  bar_arrive(NB_Y, 384);
  PROF(45);
  asm volatile("setmaxnreg.inc.sync.aligned.u32 %0;" :: "n"(REG_MAIN));
  PROF(44);
  {
    const uint32_t tz = SM_TAP + chl * TAP_SZ + (mh * 32 + lane) * 16;
#pragma unroll
    for (int k = 0; k < 3; ++k) sts4(tz + k * 1024, 0, 0, 0, 0);
    static_assert(TAP_SZ > 3072 && TAP_SZ <= 4096, "");
    if (mh * 32 + lane < TAP_SZ / 16 - 192) sts4(tz + 3072, 0, 0, 0, 0);
  }
  const float dt = bfr(__expf(bflo(vld)));
  const uint32_t tb = slot(wm);
  float acc[5][4];
#pragma unroll
  for (int i = 0; i < 5; ++i) { acc[i][0] = acc[i][1] = acc[i][2] = acc[i][3] = 0.f; }
  float k2048 = 0.f;
#pragma unroll 1
  for (int r = 0; r < 2; ++r) {
    const float are = r ? bfhi(vAr) : bflo(vAr), aim = r ? bfhi(vAi) : bflo(vAi);
    const float bre = r ? bfhi(vBr) : bflo(vBr), bim = r ? bfhi(vBi) : bflo(vBi);
    const float cre = r ? bfhi(vCr) : bflo(vCr), cim = r ? bfhi(vCi) : bflo(vCi);
    const float al = dt * are * 1.4426950408889634f, bt = dt * aim * 0.15915494309189535f;
    float wr, wi; cmul(wr, wi, cre, cim, dt * bre, dt * bim);
    if (r == 0) PROFD(2, __float_as_uint(wr + al + bt));
    float e1r, e1i, e8r, e8i, eLr, eLi;
    cexp_(al, bt, 1.f, e1r, e1i); cexp_(al, bt, 8.f, e8r, e8i); cexp_(al, bt, 128.f, eLr, eLi);
    const uint32_t tw = tb + lane * 4;
    float pr[8], pi[8];
    pr[1] = e1r; pi[1] = e1i;
#pragma unroll
    for (int k = 2; k < 8; ++k) cmul(pr[k], pi[k], pr[k - 1], pi[k - 1], e1r, e1i);
    float yr = 1.f, yi = 0.f, qr = wr, qi = wi;
#pragma unroll
    for (int a = 0; a < 16; ++a) {
      sts1(tw + a * 144, pack2(yr, -yi));
      if (a == 0) { yr = e8r; yi = e8i; } else if (a < 15) cmul(yr, yi, yr, yi, e8r, e8i);
      const int step = a < 2 ? 1 : a < 4 ? 2 : a < 8 ? 4 : 8;
      const int row0 = 16 + (a < 2 ? 8 * a : a < 4 ? 16 + 4 * (a - 2) : a < 8 ? 24 + 2 * (a - 4) : 32 + (a - 8));
      sts1(tw + row0 * 144, pack2(qr, qi));
#pragma unroll
      for (int k = step; k < 8; k += step) {
        float xr, xi; cmul(xr, xi, qr, qi, pr[k], pi[k]);
        sts1(tw + (row0 + k / step) * 144, pack2(xr, xi));
      }
      cmul(qr, qi, qr, qi, eLr, eLi);
    }
    k2048 += qr;
    __syncwarp();
    if (r == 0) PROF(3);
#pragma unroll
    for (int kp = 0; kp < 2; ++kp) {
      uint32_t a0[4], a1[4];
      const uint32_t aa = tb + ((lane & 7) + 8 * ((lane >> 3) & 1)) * 144 + (lane >> 4) * 16 + kp * 64;
      ldsm4(a0, aa); ldsm4(a1, aa + 32);
#pragma unroll
      for (int tl = 0; tl < 5; ++tl) {
        uint32_t b[4];
        ldsm4(b, tb + (16 + 8 * tl + (lane & 7)) * 144 + (lane >> 3) * 16 + kp * 64);
        mma16(acc[tl], a0[0], a0[1], a0[2], a0[3], b[0], b[1]);
        mma16(acc[tl], a1[0], a1[1], a1[2], a1[3], b[2], b[3]);
      }
    }
    __syncwarp();
    bar_sync_if(NB_P0 + 1, 288, 1 - r);
  }
#pragma unroll
  for (int o = 16; o > 0; o >>= 1) k2048 += __shfl_xor_sync(0xffffffffu, k2048, o);
  if (mh == 0) {
    sts4f(tb + lane * 16, acc[2][0], acc[2][1], acc[2][2], acc[2][3]);
    sts4f(tb + 512 + lane * 16, acc[3][0], acc[3][1], acc[3][2], acc[3][3]);
  } else {
    sts4f(tb + lane * 16, acc[0][0], acc[0][1], acc[0][2], acc[0][3]);
    sts4f(tb + 512 + lane * 16, acc[1][0], acc[1][1], acc[1][2], acc[1][3]);
    sts4f(tb + 1024 + lane * 16, acc[4][0], acc[4][1], acc[4][2], acc[4][3]);
    if (lane == 0) sts1(tb + 1536, __float_as_uint(k2048));
  }
  PROF(4);
  bar_sync(NB_K + chl, 64);
  const uint32_t ob = slot(wm ^ 1), tp = SM_TAP + chl * TAP_SZ;
  if (mh == 0) {
#pragma unroll
    for (int tl = 0; tl < 2; ++tl) {
      float4 o = lds4f(ob + tl * 512 + lane * 16);
      if (tl == 0 && lane == 0) o.x += bflo(vds);
      uint32_t v0 = pack2(acc[tl][0] + o.x, acc[tl][1] + o.y), v1 = pack2(acc[tl][2] + o.z, acc[tl][3] + o.w);
      const int l = 128 * tl + 8 * g + 2 * t;
      sts16(tp + T_E + 2 * (0 - l), v0); sts16(tp + T_E + 2 * (-1 - l), v0 >> 16);
      sts16(tp + T_O + 2 * (0 - l), v0); sts16(tp + T_O + 2 * (-1 - l), v0 >> 16);
      sts16(tp + T_E + 2 * (-64 - l), v1); sts16(tp + T_E + 2 * (-65 - l), v1 >> 16);
      sts16(tp + T_O + 2 * (-64 - l), v1); sts16(tp + T_O + 2 * (-65 - l), v1 >> 16);
    }
    float4 o = lds4f(ob + 1024 + lane * 16);
    uint32_t v0 = pack2(acc[4][0] + o.x, acc[4][1] + o.y), v1 = pack2(acc[4][2] + o.z, acc[4][3] + o.w);
    const int x = 32 * t + g - 1;
    if (lane == 0) { sts16(tp + T_E - 2 * (X_5 + 63), v0); sts16(tp + T_O - 2 * (X_5 + 63), v0); sts1(tp + T_K, prmt(v0, v0, 0x1010)); }
    else sts16(tp + T_C - 2 * x, v0);
    sts16(tp + T_C - 2 * (x + 16), v0 >> 16);
    sts16(tp + T_C - 2 * (x + 8), v1);
    sts16(tp + T_C - 2 * (x + 24), v1 >> 16);
    if (lane == 0) sts16(tp + T_C - 2 * 127, pack2(k2048 + __uint_as_float(lds1(ob + 1536)), 0.f));
  } else {
    float4 o2 = lds4f(ob + lane * 16), o3 = lds4f(ob + 512 + lane * 16);
    uint32_t v0 = pack2(acc[2][0] + o2.x, acc[2][1] + o2.y), v1 = pack2(acc[2][2] + o2.z, acc[2][3] + o2.w);
    const int l0 = 256 + 128 * (t >> 1) + 4 * (t & 1) + 8 * g;
    if (lane != 0) { sts16(tp + T_E + 2 * (1 - l0), v0); sts16(tp + T_O + 2 * (1 - l0), v0); }
    sts16(tp + T_E + 2 * (0 - l0), v0); sts16(tp + T_O + 2 * (0 - l0), v0);
    sts16(tp + T_E + 2 * (-1 - l0), v0); sts16(tp + T_O + 2 * (-1 - l0), v0);
    sts16(tp + T_E + 2 * (-2 - l0), v0 >> 16); sts16(tp + T_O + 2 * (-2 - l0), v0 >> 16);
    sts16(tp + T_E + 2 * (-63 - l0), v1); sts16(tp + T_O + 2 * (-63 - l0), v1);
    sts16(tp + T_E + 2 * (-64 - l0), v1); sts16(tp + T_O + 2 * (-64 - l0), v1);
    sts16(tp + T_E + 2 * (-65 - l0), v1); sts16(tp + T_O + 2 * (-65 - l0), v1);
    sts16(tp + T_E + 2 * (-66 - l0), v1 >> 16); sts16(tp + T_O + 2 * (-66 - l0), v1 >> 16);
    uint32_t w0 = pack2(acc[3][0] + o3.x, acc[3][1] + o3.y), w1 = pack2(acc[3][2] + o3.z, acc[3][3] + o3.w);
    const int x = 16 * t + g;
    if (lane == 0) {
      const uint32_t k = prmt(w0, w0, 0x1010);
      sts1(tp + T_E - 2 * 514, k); sts1(tp + T_E - 2 * 512, k);
      sts16(tp + T_O - 2 * 514, k); sts1(tp + T_O - 2 * 513, k); sts16(tp + T_O - 2 * 511, k);
    } else { sts16(tp + T_E - 2 * (X_5 - 1 + x), w0); sts16(tp + T_O - 2 * (X_5 - 1 + x), w0); }
    sts16(tp + T_E - 2 * (X_3 + x), w0 >> 16); sts16(tp + T_O - 2 * (X_3 + x), w0 >> 16);
    sts16(tp + T_E - 2 * (X_5 + 7 + x), w1); sts16(tp + T_O - 2 * (X_5 + 7 + x), w1);
    sts16(tp + T_E - 2 * (X_3 + 8 + x), w1 >> 16); sts16(tp + T_O - 2 * (X_3 + 8 + x), w1 >> 16);
  }
}

DEV bool bad8(const uint4& v) { return min(v.x, v.z) == 0u; }
DEV uint32_t uchunk(uint32_t reg, int x) { return reg + R_U + (x ^ ((x >> 3) & 3)) * 16; }
DEV uint32_t& xword(uint4 (&x)[2], int e, int tp) { uint4& v = x[tp >> 1]; return tp & 1 ? (e ? v.w : v.z) : (e ? v.y : v.x); }

DEV void sload(const Params& P, int c, int j, int layer, uint4 (&s)[2][2]) {
  const uint4* st = &SCR->SR[layer][c >> 4][opq(j)];
  mbar_wait(B_U, layer);
  PROF(layer ? 25 : 10);
#pragma unroll
  for (int z = 0; z < 4; ++z) s[z >> 1][z & 1] = ldr4(st + z * 128);
}
DEV void uload(const Params& P, int c, int j, int layer, uint4 (&x)[2][2][2], uint4 (&s)[2][2]) {
  j = opq(j);
  const uint4* st = &SCR->SR[layer][c >> 4][j];
  const int o0 = 2 * j + ((j >> 2) & 1), o1 = o0 ^ 1;
#pragma unroll
  for (int z = 0; z < 4; ++z) { uint4& v = s[z >> 1][z & 1]; ldr4_if(v, st + z * 128, bad8(v)); }
  PROF(layer ? 26 : 11);
  mbar_wait(B_E, layer);
#pragma unroll
  for (int z = 0; z < 8; ++z) x[z >> 2][(z >> 1) & 1][z & 1] = lds4(SM_X + 16 * (z & 1 ? o1 : o0) + (z >> 1) * 4096);
  PROF(layer ? 27 : 14);
  for (int it = 0;; ++it) {
    uint32_t m = ~0u;
#pragma unroll
    for (int z = 0; z < 4; ++z) { const uint4& v = s[z >> 1][z & 1]; m = min(m, min(v.x, v.z)); }
#pragma unroll
    for (int z = 0; z < 8; ++z) { const uint4& v = x[z >> 2][(z >> 1) & 1][z & 1]; m = min(m, min(v.x, v.z)); }
    if (!RARE(__any_sync(0xffffffffu, m == 0))) break;
#pragma unroll
    for (int z = 0; z < 4; ++z) { uint4& v = s[z >> 1][z & 1]; ldr4_if(v, st + z * 128, bad8(v)); }
#pragma unroll
    for (int z = 0; z < 8; ++z) {
      uint4& v = x[z >> 2][(z >> 1) & 1][z & 1];
      ldr4_if(v, &SCR->XG[layer][c * 1024 + (opq(o0) ^ (z & 1)) + (z >> 1) * 256], bad8(v));
    }
    spin_guard(it);
  }
  PROF(4 + 12 * layer);
}
DEV void uprep(int j, int k, uint4 (&x)[2][2], uint4 (&s)[2], uint32_t (&u)[4][4]) {
  const uint32_t ua = uchunk(0, opq(j)) + k * 2048;
#pragma unroll
  for (int chl = 0; chl < 4; ++chl) {
#pragma unroll
    for (int tp = 0; tp < 4; ++tp) u[chl][tp] = hmul2(hsub2(xword(x[chl >> 1], chl & 1, tp), xword(s, 1, tp)), xword(s, 0, tp));
    sts4(ua + region(chl), u[chl][0], u[chl][1], u[chl][2], u[chl][3]);
  }
}

template <bool FULL> DEV void box_unit(uint32_t reg, int s, const uint2& a, const uint4& b, const uint32_t (&d)[4], uint32_t (&pv)[4]) {
  const uint32_t u[9] = {a.x, a.y, b.x, b.y, b.z, b.w, d[0], d[1], d[2]};
  uint32_t v[8], p[8];
#pragma unroll
  for (int j = 0; j < 8; ++j) { v[j] = prmt(u[j], u[j + 1], 0x5432); p[j] = hadd2(u[j], v[j]); }
  const uint32_t o = reg + s * 16;
  uint32_t x[4], y[4];
#pragma unroll
  for (int j = 0; j < 4; ++j) { x[j] = hadd2(hadd2(p[1 + j], p[2 + j]), u[3 + j]); y[j] = hadd2(v[3 + j], p[4 + j]); pv[j] = p[4 + j]; }
  sts4(o + R_X5, x[0], x[1], x[2], x[3]);
  sts4(o + R_X3, y[0], y[1], y[2], y[3]);
  if (FULL) {
#pragma unroll
    for (int j = 0; j < 4; ++j) { y[j] = hadd2(hadd2(v[j], v[3 + j]), x[j]); x[j] = hadd2(hadd2(u[j], u[4 + j]), y[j]); }
    const bool od = s & 1;
    sts4(o + R_BO, od ? y[0] : x[0], od ? y[1] : x[1], od ? y[2] : x[2], od ? y[3] : x[3]);
    sts4(o + R_BE + 16, od ? x[0] : y[0], od ? x[1] : y[1], od ? x[2] : y[2], od ? x[3] : y[3]);
  }
}
DEV void box_full(int j, uint32_t (&u)[4][4], uint32_t zero) {
  const uint32_t a2 = uchunk(8, j - 2), a1 = uchunk(0, j - 1);
  uint2 a[4]; uint4 b[4];
#pragma unroll
  for (int chl = 0; chl < 2; ++chl) { a[chl] = lds2(region(chl) + a2); b[chl] = lds4(region(chl) + a1); }
  split(zero);
#pragma unroll
  for (int chl = 0; chl < 4; ++chl) {
    const uint32_t d[4] = {u[chl][0], u[chl][1], u[chl][2], u[chl][3]};
    box_unit<true>(region(chl), j, a[chl], b[chl], d, u[chl]);
    if (chl + 2 < 4) { a[(chl + 2) & 3] = lds2(region(chl + 2) + a2); b[(chl + 2) & 3] = lds4(region(chl + 2) + a1); }
    if (chl != 2) {
      fence_async_smem();
      if (chl == 3) bar_arrive(NB_B + 2, 288);
      bar_arrive(NB_B + chl, 288);
    }
    if (chl == 0) PROF(31);
  }
}
DEV void box_help(int e, int lane) {
  bar_sync(NB_H, 192);
#pragma unroll 1
  for (int n = 0; n < 4; ++n) {
    const int chl = e + (n & 2), s = 128 + 32 * (n & 1) + lane;
    const uint32_t reg = region(chl);
    const uint4 d = lds4(uchunk(reg, s));
    const uint32_t u[4] = {d.x, d.y, d.z, d.w};
    uint32_t v[4];
    box_unit<false>(reg, s, lds2(uchunk(reg, s - 2) + 8), lds4(uchunk(reg, s - 1)), u, v);
    if (n & 1) { fence_async_smem(); bar_arrive(NB_B + chl, 288); }
  }
}

DEV uint4 hadd8(const uint4& a, const uint4& b) { return make_uint4(hadd2(a.x, b.x), hadd2(a.y, b.y), hadd2(a.z, b.z), hadd2(a.w, b.w)); }
DEV void conv_out(int c, int j, int chl, uint4 (&x)[2][2][2], const uint32_t (&v)[4], uint4* XF, uint32_t zero) {
  const int rho = chl >> 1, e = chl & 1;
  const uint32_t ua = uchunk(region(chl), j), fa = region(chl) + R_X5 + j * 16, ha = region(chl) + R_X3 + (j & 1) * 1088 + (j >> 1) * 16;
  const int m8 = ((j & 4) + ((j >> 1) & 1)) ^ ((2 * c + e) & 7);
  uint2* xo = (uint2*)XF + (((16 - 2 * (j & 8) + (j >> 4)) * 512 + 256 * rho + 2 * c + e) * 16 + (j & 1));
  bar_sync(NB_Y + e + 7 * rho, 256);
  uint4 y[2], f[2], h[2];
#pragma unroll
  for (int k = 0; k < 2; ++k) {
    y[k] = lds4(ua + k * 2048);
    f[k] = lds4z(ua + k * 2048 + R_BO - R_U, k || j >= 36);
    h[k] = lds4z(fa + k * 2048 - 1024, k || j >= 64);
  }
  const uint32_t q = lds1(SM_TAP + chl * TAP_SZ + T_K);
  const uint4 r = lds4(ha);
  split(zero);
  h[1] = hadd8(h[1], make_uint4(hfma2(q, v[0], r.x), hfma2(q, v[1], r.y), hfma2(q, v[2], r.z), hfma2(q, v[3], r.w)));
#pragma unroll
  for (int k = 0; k < 2; ++k) {
    const uint4 o = hadd8(hadd8(y[k], hadd8(f[k], h[k])), make_uint4(xword(x[k][rho], e, 0), xword(x[k][rho], e, 1), xword(x[k][rho], e, 2), xword(x[k][rho], e, 3)));
    str2(xo + k * 65536 + 2 * m8, prmt(o.x, o.y, 0x5410), prmt(o.z, o.w, 0x5410));
    str2(xo + k * 65536 + 2 * (m8 ^ 2), prmt(o.x, o.y, 0x7632), prmt(o.z, o.w, 0x7632));
  }
  if (e) { __syncwarp(); mbar_arrive1(B_RD + rho * 8); }
}

DEV void conv_round(int e, int rho, int w, int lane) {
  const int g = lane >> 2, t = lane & 3, chl = 2 * rho + e;
  const uint32_t reg = region(chl), tp = SM_TAP + chl * TAP_SZ, dr = dlo(reg, 128);
  const uint32_t g0 = tp + ((g & 1) ? T_O : T_E) + 2 * (2 * t - g) - 16;
  const uint32_t ga = g0 - 32 * (w & 1) - 576 * (w >> 1), id = opq(0x3210u);
  float acc[32], f1[24], f2[16];
  uint32_t q[12][4];
  {
    uint32_t qn[18][4];
    qn[0][2] = lds1(ga + 64);
#pragma unroll
    for (int n = 0; n < 18; ++n) {
      const bool nz = n < 15 || w < 2 || (n == 15 && w == 2);
      qn[n][0] = n < 15 ? lds1(ga + 48 - 32 * n) : lds1z(ga + 48 - 32 * n, nz);
      qn[n][1] = n < 15 ? lds1(ga + 32 - 32 * n) : lds1z(ga + 32 - 32 * n, nz);
    }
#pragma unroll
    for (int n = 0; n < 18; ++n) { qn[n][3] = cpy(qn[n][0], id); if (n) qn[n][2] = cpy(qn[n - 1][1], id); }
#pragma unroll
    for (int n = 0; n < 8; ++n) {
      const int i = n & 3;
      const uint32_t a = g0 + 16 - 16 * w - 2 * (n < 4 ? X_5 : X_3) + 16 * i;
      uint32_t (&q1)[4] = q[(n & 4) + (i >> 1)], (&q2)[4] = q[(n & 4) + 2 + (i >> 1)];
      q1[2 * (i & 1)] = lds1z(a, i <= w); q1[2 * (i & 1) + 1] = lds1(a - 64);
      q2[2 * (i & 1)] = cpy(0, id); q2[2 * (i & 1) + 1] = lds1z(a - 128, i >= w);
    }
    const uint32_t gc = tp + T_C - 2 + 4 * (t - g - 8 * w);
#pragma unroll
    for (int kk = 0; kk < 4; ++kk) {
      q[8 + kk][0] = lds1z(gc + 32 * kk, w >= kk); q[8 + kk][2] = lds1z(gc + 32 * kk + 16, w >= kk);
      q[8 + kk][1] = lds1(gc + 32 * kk - 128); q[8 + kk][3] = lds1(gc + 32 * kk - 112);
    }
    PROFD(rho ? 43 : 47, qn[17][2] ^ q[11][3]);
    bar_sync_if(NB_U, NBARU, 1 - rho);
    mbar_arrive1_if(B_V, chl == 1 && w == 0);
    bar_sync_if(NB_T + 1 - e, 256, chl);
    const uint32_t db = dr + (R_U + 32) / 16;
    undef(acc);
    wg_fence();
#pragma unroll
    for (int n = 0; n < 18; ++n) {
      if (n) wg_rs64k<1>(acc, qn[n], db - 2 * n); else wg_rs64k<0>(acc, qn[0], db);
      if (n == 9) wg_commit();
    }
    wg_commit();
  }
  wg_wait<1>();
  PROF(12);
  bar_sync(NB_B + chl, 288);
  const uint32_t d1 = dr + R_X5 / 16, d2 = dr + R_BO / 16;
  undef(f1); undef(f2);
  wg_fence();
#pragma unroll
  for (int n = 0; n < 8; ++n) {
    const uint32_t d = d1 + (n >> 2) * ((R_X3 - R_X5) / 16) + 16 * (n & 1) - 16 * (n & 2);
    if (n) wg_rs48t<1>(f1, q[n], d); else wg_rs48t<0>(f1, q[0], d);
    if (n & 1) { if (n > 1) wg_rs32t<1>(f2, q[8 + (n >> 1)], d2 + 16 * (n >> 1)); else wg_rs32t<0>(f2, q[8], d2); }
  }
  wg_commit();
  wg_wait<1>();
  PROF(13);
  bar_arrive_if(NB_T + e, 256, chl - 3);
  wg_wait<0>();
  PROF(14);
  bar_sync(NB_WG + e, 128);
  {
    const int p = (lane + 9 * (w >> 1)) & 31;
    const uint32_t ya = reg + ((w >> 1) ? R_BO : R_U) + p * 64 + (((2 * (w & 1)) ^ ((p >> 1) & 3)) * 16);
    const uint32_t up = p < lane ? 2048 : 0;
#pragma unroll
    for (int z = 0; z < 4; ++z) {
      const float* a = acc + 16 * (z >> 1) + 2 * (z & 1);
      stsm4t((ya + (up ^ ((z >> 1) * 2048))) ^ ((z & 1) * 16), pack2(a[0], a[1]), pack2(a[4], a[5]), pack2(a[8], a[9]), pack2(a[12], a[13]));
    }
  }
  {
    const uint32_t fa = reg + R_X5 + (8 * w + (lane & 7)) * 16 + (lane >> 3) * 512;
    uint32_t h[6];
#pragma unroll
    for (int p = 0; p < 6; ++p) h[p] = p ? pack2(f1[4 * p] + f1[4 * p - 2], f1[4 * p + 1] + f1[4 * p - 1]) : pack2(f1[0], f1[1]);
    stsm4(fa, h[0], h[1], h[2], h[3]);
    stsm2(fa + 2048, h[4], h[5]);
    stsm4(reg + R_X3 + (lane < 16 ? 1088 : 0) + (8 * w + (lane & 7) + 4 * (lane & 8)) * 16, pack2(f2[0], f2[1]), pack2(f2[2] + f2[4], f2[3] + f2[5]),
          pack2(f2[8], f2[9]), pack2(f2[10] + f2[12], f2[11] + f2[13]));
  }
  bar_arrive(NB_Y + e + 7 * rho, 256);
}
constexpr uint32_t FILL = 0xFFFFFFFFu;
template <int N> DEV void fixo(uint4 (&A)[N], const uint4* p) {
#pragma unroll 1
  for (int it = 0; it < SPIN_LIMIT; ++it) {
    uint32_t m = A[0].x;
#pragma unroll
    for (int k = 1; k < N; ++k) m = max(m, A[k].x);
    if (__all_sync(0xffffffffu, m != FILL)) break;
#pragma unroll
    for (int k = 0; k < N; ++k) ldr4_if(A[k], p + k * 32, A[k].x == FILL);
  }
}
DEV bool rows_nan(float a, float b) {
  return __any_sync(0xffffffffu, a != a || b != b);
}
template <int N> DEV void slow_step(float (&acc)[N], float a0, float a1, const uint16_t* wr, uint32_t zero) {
#pragma unroll
  for (int j = 0; j < N / 4; ++j) {
    const uint32_t v = __ldg((const uint32_t*)(wr + (j >> 3) * 512 + 8 * (j & 7)));
    acc[4 * j] += a0 * bflo(v); acc[4 * j + 1] += a0 * bfhi(v); acc[4 * j + 2] += a1 * bflo(v); acc[4 * j + 3] += a1 * bfhi(v);
    if ((j & 3) == 3) wr += __float_as_uint(acc[4 * j]) & zero;
  }
}
DEV int res_off(int w, int lane) { return ((lane & 7) + 8 * (lane >> 4)) * 8 + ((2 * (w & 2) + (w & 1) + ((lane >> 2) & 2)) ^ (lane & 7)); }
DEV void res_load(uint32_t (&res)[8][2], uint32_t sa, int w, int lane) {
  const uint32_t a = sa + res_off(w, opq(lane)) * 16;
#pragma unroll
  for (int j = 0; j < 8; j += 2) {
    uint32_t r[4];
    ldsm4t(r, a + j * 1024);
    res[j][0] = r[0]; res[j][1] = r[1]; res[j + 1][0] = r[2]; res[j + 1][1] = r[3];
  }
}

DEV uint32_t after(uint32_t b, const uint32_t (&res)[8][2], uint32_t zero) {
  return b + ((res[0][0] ^ res[2][0] ^ res[4][0] ^ res[6][0]) & zero);
}

DEV void attn_phase(const Params& P, int c, int e, int w, int lane, int layer) {
  lane = opq(lane); c = opq(c);
  const int i = c >> 3, cg = c & 7, J = 16 * e + i, G = 8 * i + 4 - 4 * e + w;
  const int g = lane >> 2, t = lane & 3;
  float acc[96];
  uint32_t res[8][2];
  float2 cs[16];
  float4 st;
  const uint32_t csb = opq(SM_CS + 8 * t);
  {
    const uint32_t sa = SM_A + e * A_E, ba = B_A + 16 * e;
    const uint32_t da = dlo(sa, 8192), db = (SB >> 4) | (512 << 16);
    undef(acc);
#pragma unroll
    for (int j = 0; j < 8; ++j) asm volatile("" : "=r"(res[j][0]), "=r"(res[j][1]));
    mbar_wait(B_WF, layer);
    mbar_wait(ba, 0);
    mbar_wait(B_RD + 8, layer);
    bar_sync_if(NB_T, 256, e);
    PROF(24);
#pragma unroll
    for (int j = 0; j < 4; ++j) {
      if (j == 1) { mbar_wait(ba + 8, 0); PROF(39); }
      wg_fence();
#pragma unroll
      for (int k = 0; k < 4; ++k) {
        if (j | k) wg_ss192<1>(acc, da + j * 512 + k * 128, db + wslot(j) * 512 + k * 128); else wg_ss192<0>(acc, da, db);
        if (j == 3 && k == 1) wg_commit();
      }
      wg_commit();
      if (j == 1 || j == 2) { wg_wait<1>(); mbar_arrive1_if(B_F + 8 * (j - 1), e); }
    }
    wg_wait<1>();
    bar_arrive(NB_T + e, 256);
    wg_wait<0>();
    if (cg < 4) res_load(res, sa + cg * 8192, w, lane);
    mbar_arrive1(after(B_AE + 8 * e, res, P.zero));
    PROF(25);
#pragma unroll 1
    for (uint32_t late = P.zero;; late = 1) {
      if (late) {
        const uint16_t* xr = (const uint16_t*)SCR->XF[layer] + opq(J) * 32768;
        zero(acc);
#pragma unroll 1
        for (int k = 0; k < 512; ++k)
          slow_step(acc, ldnan(xr + k * 64 + ((2 * w) ^ (k & 7)) * 8 + g), ldnan(xr + k * 64 + ((2 * w + 1) ^ (k & 7)) * 8 + g),
                    P.wqkv + (k * 1536 + 64 * cg + 2 * t), P.zero);
        const uint32_t* q = (const uint32_t*)xr + ((64 * cg + g) * 32 + t);
        const int m8 = (2 * (w & 2) + (w & 1)) ^ g;
#pragma unroll 1
        for (int it = 0; it < SPIN_LIMIT; ++it) {
          uint32_t m = 0;
#pragma unroll
          for (int z = 0; z < 16; ++z) { const uint32_t x = ldr1(q + (z >> 1) * 256 + (m8 ^ (2 * (z & 1))) * 4); m = max(m, x); res[z >> 1][z & 1] = movm(x); }
          if (__all_sync(0xffffffffu, m != FILL)) break;
        }
#pragma unroll
        for (int z = 0; z < 16; ++z) cs[z] = lds2f(csb + 256 + z * 32);
      } else {
        mbar_wait(B_CS, 0);
#pragma unroll
        for (int z = 0; z < 16; ++z) cs[z] = lds2f(csb + 256 + z * 32);
        mbar_wait(B_W4, layer);
        mbar_wait(ba, 1);
        bar_sync(NB_T + 1 - e, 256);
        PROF(26);
#pragma unroll
        for (int j = 4; j < 8; ++j) {
          if (j == 5) mbar_wait(ba + 8, 1);
          if (j >= 6) mbar_wait(B_W6 + 8 * (j - 6), layer);
          if (j > 4) PROF(31 + j);
          wg_fence();
#pragma unroll
          for (int k = 0; k < 4; ++k) {
            wg_ss192<1>(acc, da + (j & 3) * 512 + k * 128, db + wslot(j) * 512 + k * 128);
            if (j == 7 && k == 1) wg_commit();
          }
          wg_commit();
          if (j == 5) {
            if (cg >= 4) res_load(res, sa + (cg - 4) * 8192, w, lane);
            wg_wait<1>(); mbar_arrive1_if(B_F + 16, e); PROF(40);
          }

        }
      }
      uint32_t rs = hadd2(res[0][0], res[0][1]);
#pragma unroll
      for (int z = 2; z < 16; ++z) rs = hadd2(rs, res[z >> 1][z & 1]);
      const float rn = bflo(rs) + bfhi(rs);
      wg_wait<1>();
      bar_arrive_if(NB_T, 256, !(e | late));
      mbar_wait(B_ST + 8 * e, layer);
      st = lds4f(SM_STAT + ((4 * e + w) * 8 + g) * 16);
      PROF(34 + layer);
      wg_wait<0>();
      if (!rows_nan(acc[0] + rn, acc[2]) || late) break;
    }
  }
  mbar_arrive1(B_QE);
  PROF(8 + 12 * layer);
  uint32_t Q[4][4], K[4][2][2], V[4][2][2];
  {
#pragma unroll
    for (int z = 0; z < 8; ++z) {
      const float* a = acc + 32 + 4 * z; const float* b = acc + 64 + 4 * z;
      K[z >> 1][1][z & 1] = pack2((a[2] - st.z * cs[z].x) * st.w, (a[3] - st.z * cs[z].y) * st.w);
      V[z >> 1][1][z & 1] = movm(pack2((b[2] - st.z * cs[8 + z].x) * st.w, (b[3] - st.z * cs[8 + z].y) * st.w));
    }
    const int hop = (G >> 1) & 3;
    const uint32_t kv = SM_KV + (2 * hop + (w & 1)) * 2048 + lane * 16;
    uint4* h = SCR->H[layer] + (c * 256 + (w & 1) * 128 + lane);
    if (hop == 3) {
#pragma unroll
      for (int z = 0; z < 4; ++z) str4(h + 2048 + z * 32, K[z][1][0], K[z][1][1], V[z][1][0], V[z][1][1]);
    } else {
      mbar_wait(B_F + 16, layer);
#pragma unroll
      for (int z = 0; z < 4; ++z) sts4(kv + z * 512, K[z][1][0], K[z][1][1], V[z][1][0], V[z][1][1]);
      bar_arrive(NB_B + hop, 128);
    }
    PROF(42);
#pragma unroll
    for (int z = 0; z < 8; ++z) {
      const float* a = acc + 32 + 4 * z; const float* b = acc + 64 + 4 * z;
      K[z >> 1][0][z & 1] = pack2((a[0] - st.x * cs[z].x) * st.y, (a[1] - st.x * cs[z].y) * st.y);
      V[z >> 1][0][z & 1] = movm(pack2((b[0] - st.x * cs[8 + z].x) * st.y, (b[1] - st.x * cs[8 + z].y) * st.y));
    }
#pragma unroll
    for (int z = 0; z < 8; ++z) {
      const float2 cq = lds2f(csb + z * 32);
      const float* a = acc + 4 * z;
      Q[z >> 1][2 * (z & 1)] = pack2(a[0] - st.x * cq.x, a[1] - st.x * cq.y);
      Q[z >> 1][2 * (z & 1) + 1] = pack2(a[2] - st.z * cq.x, a[3] - st.z * cq.y);
    }
    PROF(27);
    uint4 hv[4];
#pragma unroll
    for (int z = 0; z < 4; ++z) { hv[z] = make_uint4(0, 0, 0, 0); ldr4_if(hv[z], h + z * 32, G >= 2 && hop == 0); }
    const bool p0 = 2 * t > g, p1 = 2 * t + 1 > g, first = G < 2;
    float s[4][4], mx[4][2];
#pragma unroll
    for (int z = 0; z < 4; ++z) {
      float S[4];
      mma16z(s[z], Q[z][0], Q[z][1], Q[z][2], Q[z][3], K[z][0][0], K[z][0][1]);
      mma16z(S, Q[z][0], Q[z][1], Q[z][2], Q[z][3], K[z][1][0], K[z][1][1]);
      s[z][2] = p0 ? s[z][2] : S[2]; s[z][3] = p1 ? s[z][3] : S[3];
    }
    const float sc0 = st.y * (0.25f * 1.4426950408889634f), sc1 = st.w * (0.25f * 1.4426950408889634f);
    uint32_t pw[4][2];
#pragma unroll
    for (int r = 1; r >= 0; --r) {
      if (r == 0) {
        if (hop) {
          bar_sync(NB_B + hop - 1, 128);
#pragma unroll
          for (int z = 0; z < 4; ++z) hv[z] = lds4(kv - 4096 + z * 512);
        } else fixo(hv, h);
        PROFD(41, hv[3].x);
#pragma unroll
        for (int z = 0; z < 4; ++z) {
          float S[4];
          mma16z(S, Q[z][0], Q[z][1], Q[z][2], Q[z][3], hv[z].x, hv[z].y);
          if (first) S[0] = S[1] = __uint_as_float(0xFF800000u);
          s[z][0] = p0 ? S[0] : s[z][0]; s[z][1] = p1 ? S[1] : s[z][1];
        }
      }
#pragma unroll
      for (int z = 0; z < 4; ++z) mx[z][r] = fmaxf(s[z][2 * r], s[z][2 * r + 1]);
#pragma unroll
      for (int o = 1; o < 3; ++o)
#pragma unroll
        for (int z = 0; z < 4; ++z) mx[z][r] = fmaxf(mx[z][r], __shfl_xor_sync(0xffffffffu, mx[z][r], o));
#pragma unroll
      for (int z = 0; z < 4; ++z) pw[z][r] = pack2(ex2((s[z][2 * r] - mx[z][r]) * (r ? sc1 : sc0)), ex2((s[z][2 * r + 1] - mx[z][r]) * (r ? sc1 : sc0)));
    }
    mbar_wait(layer ? B_N : B_Z, layer);
    const uint32_t M = (p0 ? 0xFFFFu : 0u) | (p1 ? 0xFFFF0000u : 0u);
    uint4* O = SCR->O + ((J * 8 + cg) * 512 + (2 * (w & 2) + (w & 1)) * 64 + t * 8 + g);
#pragma unroll
    for (int h2 = 0; h2 < 2; ++h2) {
      uint32_t ow[2][4];
#pragma unroll
      for (int z = 0; z < 2; ++z) {
        const int n = 2 * h2 + z;
        const uint32_t w0 = pw[n][0], w1 = pw[n][1];
        float sm[4] = {0.f, 0.f, 0.f, 0.f}, Oa[2][4];
        mma8(sm, w0, w1, 0x3F803F80u);
        mma16z(Oa[0], w0 & ~M, w1 & M, 0u, w1 & ~M, V[n][0][0], V[n][1][0]); mma8(Oa[0], w0 & M, 0u, hv[n].z);
        mma16z(Oa[1], w0 & ~M, w1 & M, 0u, w1 & ~M, V[n][0][1], V[n][1][1]); mma8(Oa[1], w0 & M, 0u, hv[n].w);
        const float i0 = rcp(sm[0]), i1 = rcp(sm[2]);
#pragma unroll
        for (int d = 0; d < 2; ++d) { ow[0][2 * z + d] = pack2(Oa[d][0] * i0, Oa[d][1] * i0); ow[1][2 * z + d] = pack2(Oa[d][2] * i1, Oa[d][3] * i1); }
      }
#pragma unroll
      for (int hi = 0; hi < 2; ++hi) str4(O + hi * 128 + h2 * 32, ow[hi][0], ow[hi][1], ow[hi][2], ow[hi][3]);
    }
  }
  str1(SCR->OF[layer] + (J * 32 + cg * 4 + w), 1);
  mbar_arrive1(B_AT + 8 * e + (lds1(csb) & P.zero));
  PROF(9 + 12 * layer);
  float ac[32];
  undef(ac);
  const uint32_t so = SM_O + e * O_E;
  {
    const uint32_t bo = B_O + 32 * e;
    const uint32_t dw = (SM_WO >> 4) | (512 << 16), da = dlo(so, 512);
    mbar_wait(B_WO, layer);
#pragma unroll
    for (int j = 0; j < 4; ++j) {
      mbar_wait(bo + 8 * j, layer);
      if (j == 0) { PROF(32 + layer); mbar_wait(B_AT + 8, layer); }
      wg_fence();
#pragma unroll
      for (int k = 8 * j; k < 8 * j + 8; ++k) {
        const uint32_t a = da + (k >> 2) * 512 + (k & 3) * 8, b = dw + (k & 3) * 1024 + (k >> 2) * 128;
        if (k) wg_ss64<1>(ac, a, b); else wg_ss64<0>(ac, a, b);
      }
      wg_commit();
    }
#pragma unroll 1
    for (uint32_t late = P.zero;; late = 1) {
      if (late) {
        const uint16_t* op = (const uint16_t*)(SCR->O + (J * 4096 + w * 128 + g));
        wg_wait<0>();
        zero(ac);
#pragma unroll 1
        for (int k = 0; k < 512; ++k) {
          const uint16_t* q = op + (k >> 6) * 4096 + (k & 56) * 8 + (k & 7);
          slow_step(ac, ldnan(q), ldnan(q + 512), P.wo + (((k & ~31) + 4 * (k & 6) + ((k >> 2) & 6) + (k & 1)) * 512 + 64 * cg + 2 * t), P.zero);
        }
      }
      wg_wait<0>();
      if (!rows_nan(ac[0], ac[2]) || late) break;
    }
  }
  PROF(10 + 12 * layer);
#pragma unroll
  for (int j = 0; j < 8; ++j) {
    res[j][0] = hadd2(res[j][0], pack2(ac[4 * j], ac[4 * j + 1]));
    res[j][1] = hadd2(res[j][1], pack2(ac[4 * j + 2], ac[4 * j + 3]));
  }
  if (layer == 0) {
    const float4 s = gram(res, g);
    str4_if(&SCR->PS[(G * 8 + cg) * 8 + g], nzmap(__float_as_uint(s.x)), __float_as_uint(s.y), __float_as_uint(s.z), __float_as_uint(s.w), t == (g >> 1));
    const int xo = (32 * (cg & 3) + t) * 2048 + (cg >> 2) * 512 + xg_off(G, g);
#pragma unroll
    for (int j = 0; j < 8; ++j) {
      str2((uint2*)SCR->XG[1] + (xo + j * 8192), nzmap(prmt(res[j][0], res[j][1], 0x5410)), prmt(res[j][0], res[j][1], 0x7632));
    }
    __syncwarp();
    mbar_arrive1(B_ED + 8 * e);
  } else {
    const uint32_t stg = so + w * 2048;
    const int row = (lane & 7) + 8 * ((lane >> 3) & 1);
    bar_sync(NB_WG + e, 128);
#pragma unroll
    for (int j = 0; j < 8; j += 2)
      stsm4(stg + row * 128 + (((j + (lane >> 4)) ^ (row & 7)) * 16), res[j][0], res[j][1], res[j + 1][0], res[j + 1][1]);
    __syncwarp();
#pragma unroll
    for (int k = 0; k < 4; ++k) {
      const int r = 4 * k + (lane >> 3);
      const uint4 v = lds4(stg + r * 128 + (((lane & 7) ^ (r & 7)) * 16));
      stw4(P.out + ((16 * G + 2 * (lane >> 3)) * 512 + 64 * cg + 8 * (lane & 7)) + ((k & 1) * 8 + (k >> 1)) * 512, v.x, v.y, v.z, v.w);
    }
  }
  PROF(11 + 12 * layer);
}

DEV void col_sums(const Params& P, int c, int wa, int lane) {
  const int i = c >> 3, cg = c & 7;
  uint4 wv[8];
#pragma unroll
  for (int k = 0; k < 8; ++k) wv[k] = ldnc4(P.wqkv + ((32 * i + (lane >> 3)) * 1536 + wa * 512 + 64 * cg + 8 * (lane & 7)) + 4 * k * 1536);
  float cs[8];
  zero(cs);
#pragma unroll
  for (int k = 0; k < 8; ++k) {
    cs[0] += bflo(wv[k].x); cs[1] += bfhi(wv[k].x); cs[2] += bflo(wv[k].y); cs[3] += bfhi(wv[k].y);
    cs[4] += bflo(wv[k].z); cs[5] += bfhi(wv[k].z); cs[6] += bflo(wv[k].w); cs[7] += bfhi(wv[k].w);
  }
  const bool b4 = lane & 16, b3 = lane & 8;
#pragma unroll
  for (int k = 0; k < 4; ++k) cs[k] = (b4 ? cs[k + 4] : cs[k]) + __shfl_xor_sync(0xffffffffu, b4 ? cs[k] : cs[k + 4], 16);
#pragma unroll
  for (int k = 0; k < 2; ++k) cs[k] = (b3 ? cs[k + 2] : cs[k]) + __shfl_xor_sync(0xffffffffu, b3 ? cs[k] : cs[k + 2], 8);
  str2((uint2*)SCR->CS + (i * 768 + wa * 256 + 32 * cg + 4 * (lane & 7) + (lane >> 3)), nzmap(__float_as_uint(cs[0])), __float_as_uint(cs[1]));
}
DEV void col_gather(const Params& P, int c, int wa, int lane) {
  const uint2* p = (const uint2*)SCR->CS + (wa * 256 + 32 * (c & 7) + lane);
#pragma unroll 1
  for (int it = 0;; ++it) {
    float a = 0.f, b = 0.f;
    uint32_t m = ~0u;
#pragma unroll
    for (int k = 0; k < 16; ++k) { const uint2 q = ldr2(p + k * 768); m = min(m, q.x); a += __uint_as_float(q.x); b += __uint_as_float(q.y); }
    if (__all_sync(0xffffffffu, m != 0u)) { sts2f(SM_CS + wa * 256 + lane * 8, a, b); break; }
    spin_guard(it);
  }
  __syncwarp();
  mbar_arrive1(B_CS);
}

DEV void aux_prologue(const Params& P, int c, int wa, int lane, uint4 (&s0)[2][2]) {
  const int g = lane >> 2, t = lane & 3, G = stat_group(c);
  {
    uint32_t w[16][2];
    const uint16_t* row = P.x0 + ((16 * G + 2 * g) * 512 + 128 * wa + 8 * t);
    bar_sync(NB_Y, 384);
    __nanosleep(100);
#pragma unroll
    for (int z = 0; z < 8; ++z) {
      const uint4 v = ldw4(row + (z & 1) * 512 + (z >> 1) * 32);
      const int o = 4 * (z >> 1);
      w[o][z & 1] = v.x; w[o + 1][z & 1] = v.y; w[o + 2][z & 1] = v.z; w[o + 3][z & 1] = v.w;
    }
    PROF(34);
    PROFD(35, w[0][0]);
    PROFD(36, w[15][1]);
    uint2* xo = (uint2*)SCR->XG[0] + ((64 * (wa & 1) + 4 * t) * 2048 + (wa >> 1) * 512 + xg_off(G, g));
#pragma unroll
    for (int n = 0; n < 16; ++n) str2(xo + (16 * (n >> 2) + (n & 3)) * 2048, nzmap(prmt(w[n][0], w[n][1], 0x5410)), prmt(w[n][0], w[n][1], 0x7632));
    const float4 s = gram(w, g);
    if (t == (g >> 1)) sts4f(SM_MISC + (wa * 8 + g) * 16, s.x, s.y, s.z, s.w);
    bar_arrive(NB_P0, 192);
  }
  PROF(2);
  if (lane == 0)
    asm volatile("cp.async.bulk.prefetch.L2.global [%0],4096;" :: "l"(wa < 3 ? P.wqkv + (3 * c + wa) * 2048 : P.wo + c * 2048) : "memory");
  bar_sync(NB_Y + 1, 256);
  sload(P, c, 32 * wa + lane, 0, s0);
}

DEV void stat_part(const Params& P, int c, int wa, int lane, int layer, int h, float (&v)[2]) {
  lane = opq(lane);
  const int e = wa >> 1;
  uint32_t x[4][4];
  mbar_wait(B_A + 16 * e, h); mbar_wait(B_A + 16 * e + 8, h);
#pragma unroll
  for (int k = 0; k < 4; ++k) ldsm4t(x[k], SM_A + e * A_E + (128 * (wa & 1) + lane) * 128 + (((c ^ lane) & 7) * 16) + k * 4096);
  float s[4] = {0.f, 0.f, 0.f, 0.f};
#pragma unroll
  for (int k = 0; k < 16; ++k) { const float a = bflo(x[k >> 2][k & 3]), b = bfhi(x[k >> 2][k & 3]); s[0] += a; s[1] += a * a; s[2] += b; s[3] += b * b; }
  s[0] += s[2]; s[1] += s[3];
  if (RARE(__any_sync(0xffffffffu, s[1] != s[1]))) {
    const uint16_t* q = (const uint16_t*)(SCR->XF[layer] + ((32 * e + 2 * (c >> 3) + h) * 2048 + (wa & 1) * 1024)) + (lane >> 2);
    s[0] = s[1] = 0.f;
#pragma unroll 1
    for (int k = 0; k < 32; ++k) {
      const int r = 2 * (lane & 3) + (k & 1);
      const float a = ldnan(q + ((k >> 1) * 8 + r) * 64 + ((c ^ r) & 7) * 8);
      s[0] += a; s[1] += a * a;
    }
  }
  v[0] += s[0]; v[1] += s[1];
  __syncwarp();
}
DEV void stat_finish(const Params& P, int c, int wa, int lane, int layer, float (&v)[2]) {
  lane = opq(lane);
  const bool b = lane & 1;
  const float s = (b ? v[1] : v[0]) + __shfl_xor_sync(0xffffffffu, b ? v[0] : v[1], 1);
  str1((uint32_t*)SCR->ST[layer] + ((128 * (wa >> 1) + c) * 64 + (wa & 1) * 32 + lane), nzmap(__float_as_uint(s)));
  const uint4* sp = SCR->ST[layer] + ((128 * (wa >> 1) + (c & ~7) + 4 * (wa & 1) + (lane >> 3)) * 16 + (lane & 7));
  uint4 x, y;
  for (int it = 0;; ++it) {
    x = ldr4(sp); y = ldr4(sp + 8);
    if (__all_sync(0xffffffffu, min(min(min(x.x, x.y), min(x.z, x.w)), min(min(y.x, y.y), min(y.z, y.w))) != 0u)) break;
    spin_guard(it);
  }
  const uint32_t q = ln_sums((__uint_as_float(x.x) + __uint_as_float(x.z)) + (__uint_as_float(y.x) + __uint_as_float(y.z)),
                             (__uint_as_float(x.y) + __uint_as_float(x.w)) + (__uint_as_float(y.y) + __uint_as_float(y.w)));
  sts2f(SM_STAT + (16 * wa + (lane >> 4) * 8 + (lane & 7)) * 16 + (lane & 8), bflo(q), rcp(bfhi(q)));
  __syncwarp();
  mbar_arrive1(B_ST + 4 * (wa & 2));
}

DEV void nan_source(uint32_t a, int lane) {
#pragma unroll
  for (int k = 0; k < 4; ++k) sts4(a + k * 512 + lane * 16, FILL, FILL, FILL, FILL);
  fence_async_smem();
  __syncwarp();
}
DEV void load_a(const Params& P, int J, int e, int layer, int h) {
  const uint4* src = SCR->XF[layer] + (2 * J + h) * 2048;
  const uint32_t dst = SM_A + e * A_E, b = B_A + 16 * e;
  mbar_expect1(b, 8192); bulk(dst, src, 8192, b);
  mbar_expect1(b + 8, 24576); bulk(dst + 8192, src + 512, 24576, b + 8);
}
__global__ void __launch_bounds__(NTHR, 1)
fused_kernel(const __grid_constant__ Params P, const __grid_constant__ CUtensorMap mapW, const __grid_constant__ CUtensorMap mapWo,
             const __grid_constant__ CUtensorMap mapX) {
  extern __shared__ __align__(1024) uint8_t smem_raw[];
  const int warp = __shfl_sync(0xffffffffu, threadIdx.x >> 5, 0), lane = threadIdx.x & 31;
  uint32_t smid; asm volatile("mov.u32 %0,%%smid;" : "=r"(smid));
  const uint32_t* pw = (const uint32_t*)&P + threadIdx.y;
  const int role = P.role[(smid >> 1) + threadIdx.y] + (smid & 1) + (pw[0] & pw[12]);
  const int c = __shfl_sync(0xffffffffu, pw[1] ? role : blockIdx.x, 0);
  if (c >= 128) {
#pragma unroll 1
    for (int k = (c - 128) * NTHR + threadIdx.x; k < 131072; k += P.spare * NTHR) str4(SCR->XG[1] + k, 0, 0, 0, 0);
    __threadfence();
    __syncthreads();
    if (warp == 0) { cnt_wait(SCR->C + 1, lane); cnt_add1(SCR->C + 6); }
    __syncthreads();
#pragma unroll 1
    for (int k = (c - 128) * NTHR + threadIdx.x; k < 131072; k += P.spare * NTHR) str4(SCR->XG[0] + k, 0, 0, 0, 0);
    return;
  }
#define DONE() do {} while (0)
  const int cg = c & 7;
  if (warp < 8) {
    PROF(46);
    kgen(P, c, warp, lane);
    bar_sync(0, 384);
    PROF(1);
#pragma unroll 1
    for (int layer = 0; layer < 2; ++layer) {
#pragma unroll 1
      for (int rho = 0; rho < 2; ++rho) {
        const int wz = warp + ((rho + layer) & P.zero);
        conv_round(wz >> 2, rho, wz & 3, lane_id());
        PROF(6 + rho + 12 * layer);
      }
      const int z = layer & P.zero;
      attn_phase(P, c + z, (warp + z) >> 2, (warp + z) & 3, lane_id(), layer);
    }
    DONE();
  } else if (warp < 12) {
    asm volatile("setmaxnreg.dec.sync.aligned.u32 %0;" :: "n"(REG_AUX));
    uint4 x[2][2][2], s[2][2];
    aux_prologue(P, c, warp - 8, lane, s);
    PROF(1);
    const int c0 = c;
#pragma unroll 1
    for (int layer = 0;; ++layer) {
      const int c = c0 + (layer & P.zero), wa = warp - 8 + (layer & P.zero);
#define lane lane_id()
#define j (32 * wa + lane_id())
      {
        const uint32_t za = region(wa) + lane * 16 - 512;
        sts4(za + R_U, 0, 0, 0, 0); sts4(za + R_X5, 0, 0, 0, 0); sts4(za + R_X3, 0, 0, 0, 0);
      }
      if (lane == 0) sts4(region(wa) + R_BE, 0, 0, 0, 0);
      uint32_t u[4][4];
      uload(P, c, j, layer, x, s);
      uprep(j, 1, x[1], s[1], u);
      uprep(j, 0, x[0], s[0], u);
      fence_async_smem();
      bar_arrive(NB_U, NBARU);
      bar_sync(NB_H, 192);
      PROF(5 + 12 * layer);
      box_full(j, u, P.zero);
      PROF(3 + 12 * layer);
      mbar_wait(B_Z, 0);
      conv_out(c, j, 0, x, u[0], SCR->XF[layer], P.zero);
      PROF(32);
      conv_out(c, j, 1, x, u[1], SCR->XF[layer], P.zero);
      PROF(6 + 12 * layer);
      if (layer == 0 && wa < 3) col_sums(P, c, wa, lane);
      conv_out(c, j, 2, x, u[2], SCR->XF[layer], P.zero);
      PROF(33);
      conv_out(c, j, 3, x, u[3], SCR->XF[layer], P.zero);
      PROF(7 + 12 * layer);
      float v[2];
      zero(v);
#pragma unroll 1
      for (int h = 0; h < 2; ++h) {
        stat_part(P, c, wa, lane, layer, h, v);
        if (h) break;
        mbar_arrive1(B_AE + 4 * (wa & 2));
        if (layer == 0 && wa < 3) col_gather(P, c, wa, lane);
      }
      PROF(9 + 12 * layer);
      stat_finish(P, c, wa, lane, layer, v);
      PROF(8 + 12 * layer);
      if (layer) break;
      sload(P, c, j, 1, s);
#undef lane
#undef j
    }
    DONE();
  } else {
    asm volatile("setmaxnreg.dec.sync.aligned.u32 %0;" :: "n"(REG_PROD));
    if (s2u(smem_raw) != SB) __trap();
#pragma unroll 1
    for (int n = warp - 12; n < 38; n += 4)
      asm volatile("{.reg .pred p; elect.sync _|p,0xffffffff; @p mbarrier.init.shared::cta.b64 [%0],%1;}"
                   :: "r"(SM_BAR + n * 8), "r"(n > 14 ? 1 : (int)(0x322866444444444ull >> (4 * n)) & 15) : "memory");
    fence_async_smem();
    bar_sync(NB_AUX, 128);
    bar_arrive(0, 384); bar_arrive(NB_Y + 1, 256);
    PROF(1);
    if (warp == 12) {
      if (lane == 0) {
        asm volatile("prefetch.tensormap [%0];" :: "l"(&mapW) : "memory");
        asm volatile("prefetch.tensormap [%0];" :: "l"(&mapWo) : "memory");
        asm volatile("prefetch.tensormap [%0];" :: "l"(&mapX) : "memory");
      }
      nan_source(slot(12), lane);
      mbar_wait(B_U, 0);
#pragma unroll 1
      for (int k = 0; k < 8; ++k) tma2_store(&mapX, slot(12), 128 * c, 8 * k);
#pragma unroll 1
      for (int k = 0; k < 4; ++k) bulk_store(SCR->H[k >> 1] + ((c + 8) * 256 + (k & 1) * 128), slot(12), 2048);
#pragma unroll 1
      for (int k = 0; k < 8; ++k) bulk_store(SCR->O + (c * 512 + (k >> 2) * 65536 + (k & 3) * 128), slot(12), 2048);
      bulk_wait();
      mbar_arrive1(B_Z);
      PROF(24);
#pragma unroll 1
      for (int layer = 0; layer < 2; ++layer) {
        mbar_wait(B_V, layer);
        if (layer == 1 && c < 4 && ((0x47 >> lane) & 1)) str1(SCR->C + c * 32 + lane, 0);
        mbar_expect1(B_WF, 4 * 24576);
#pragma unroll
        for (int k = 0; k < 4; ++k) tma3(slot(wslot(k)), &mapW, 64 * cg, 64 * k, 0, B_WF);
        mbar_wait(B_WF, layer);
        mbar_expect1(B_W4, 2 * 24576);
#pragma unroll
        for (int k = 4; k < 6; ++k) tma3(slot(wslot(k)), &mapW, 64 * cg, 64 * k, 0, B_W4);
        bar_sync(NB_AUX, 64);
#pragma unroll 1
        for (int k = 0; k < 2; ++k) {
          mbar_expect1(B_W6 + 8 * k, 24576);
          mbar_wait(B_F + 8 * k, layer);
          tma3(slot(3 * k), &mapW, 64 * cg, 384 + 64 * k, 0, B_W6 + 8 * k);
        }
        mbar_expect1(B_WO, 65536);
        mbar_wait(B_AE + 8, layer);
        nan_source(slot(12), lane);
        uint4* fp = layer ? SCR->O + c * 512 : SCR->XF[1] + c * 512;
#pragma unroll 1
        for (int r = 7; r >= 0; --r) {
          __nanosleep(30);
          if (r >= 4) {
            bulk_store(fp + (r & 3) * 128, slot(12), 2048); bulk_store(fp + 65536 + (r & 3) * 128, slot(12), 2048);
          }
          if (r == 3) { bulk_wait(); __threadfence(); mbar_arrive1(B_N); PROF(9 + 12 * layer); }
          if (r == 1) mbar_wait(B_F + 16, layer);
          tma4(SM_WO + r * 8192, &mapWo, 64 * cg, 0, r >> 1, 32 * (r & 1), B_WO);
        }
        PROF(8 + 12 * layer);
      }
      DONE();
    } else if (warp == 13) {
      const int G = stat_group(c);
#pragma unroll 1
      for (int layer = 0; layer < 2; ++layer) {
        float z[4];
        if (layer == 0) {
          bar_sync(NB_P0, 192);
          const float4 a = lds4f(SM_MISC + lane * 16);
          z[0] = a.x; z[1] = a.y; z[2] = a.z; z[3] = a.w;
        } else {
          mbar_wait(B_ED + 2 * (c & 4), 0);
          uint4* ps = &SCR->PS[G * 64 + lane];
          uint4 a, b;
          for (int it = 0;; ++it) {
            a = ldr4(ps); b = ldr4(ps + 32);
            if (__all_sync(0xffffffffu, min(a.x, b.x) != 0u)) break;
            spin_guard(it);
          }
          z[0] = __uint_as_float(a.x) + __uint_as_float(b.x); z[1] = __uint_as_float(a.y) + __uint_as_float(b.y);
          z[2] = __uint_as_float(a.z) + __uint_as_float(b.z); z[3] = __uint_as_float(a.w) + __uint_as_float(b.w);
        }
#pragma unroll
        for (int o = 8; o < 32; o <<= 1)
#pragma unroll
          for (int k = 0; k < 4; ++k) z[k] += __shfl_xor_sync(0xffffffffu, z[k], o);
        const uint32_t w0 = ln_sums(z[0], z[1]), w1 = ln_sums(z[2], z[3]);
        const uint32_t r = nzmap(pack2(rcp(bfhi(w0)), rcp(bfhi(w1)))), m = prmt(w0, w1, 0x5410);
        uint2* so = (uint2*)&SCR->SR[layer][lane >> 3][sr_off(G, lane)] + (lane & 1);
        str2(so, r, m); str2(so + 4 * 1024, r, m);
        PROF(4 + 12 * layer);
        box_help(0, lane);
        PROF(6 + 12 * layer);
      }
      DONE();
    } else if (warp == 14) {
#pragma unroll 1
      for (int layer = 0; layer < 2; ++layer) {
        if (layer) { mbar_wait(B_N, 0); mbar_wait(B_ED, 0); mbar_wait(B_ED + 8, 0); } else bar_sync(NB_P0, 192);
        cnt_add1(SCR->C + (c >> 5) * 32 + 3 * layer);
        if (layer == 0) bar_arrive(NB_P0 + 1, 288);
        mbar_expect1(B_E, 16384);
        PROF(4 + 12 * layer);
        cnt_wait(SCR->C + 3 * layer, lane);
        mbar_arrive1(B_U);
        bulk(SM_X, SCR->XG[layer] + c * 1024, 16384, B_E);
        PROF(5 + 12 * layer);
        if (layer == 0) {
          mbar_wait(B_Z, 0);
          __threadfence();
          mbar_arrive1(B_Z + 8);
          PROF(11);
        }
#pragma unroll 1
        for (int n = 0; n < 4; ++n) {
          if (n == 0) mbar_wait(B_RD, layer);
          if (!(n & 1)) cnt_wait(SCR->C + 3 * layer + 1 + (n >> 1), lane);
          if (n == 2) PROF(7 + 12 * layer);
          mbar_wait((n & 2 ? B_AE : B_RD) + 8 * (n & 1), layer);
          load_a(P, 16 * (n & 1) + (c >> 3), n & 1, layer, n >> 1);
          bar_arrive_if(NB_AUX, 64, n == 2);
          if (!(n & 1)) PROF(6 + n + 12 * layer);
        }
        if (layer == 0)
          for (int it = 0; ldr1(SCR->C + 6) < P.spare; ++it) spin_guard(it);
        mbar_wait(B_QE, layer);
#pragma unroll 1
        for (int e = 0; e < 2; ++e) {
          const int J = 16 * e + (c >> 3);
          mbar_wait(B_AT + 8 * e, layer);
          uint32_t todo = 0x01010101u;
          pause(300);
#pragma unroll 1
          for (int it = 0; todo; ++it) {
            uint32_t m = __ballot_sync(0xffffffffu, ldr1(SCR->OF[layer] + J * 32 + lane) != 0u);
            m &= m >> 4; m &= m >> 2; m &= m >> 1; m &= todo;
            todo ^= m;
#pragma unroll 1
            for (; m; m &= m - 1) {
              const int j = __ffs(m) - 1;
              mbar_expect1(B_O + 32 * e + j, 16384);
              bulk(SM_O + e * O_E + 2048 * j, SCR->O + (J * 4096 + j * 128), 16384, B_O + 32 * e + j);
            }
            spin_guard(it);
          }
          PROF(9 + e + 12 * layer);
        }
      }
      DONE();
    }
    if (warp == 15) {
      const int G = stat_group(c);
      str4(&SCR->ST[0][(lane >> 4) * 2048 + c * 16 + (lane & 15)], 0, 0, 0, 0); str4(&SCR->ST[1][(lane >> 4) * 2048 + c * 16 + (lane & 15)], 0, 0, 0, 0);
      if (lane < 4) str4(SCR->OF[lane >> 1] + ((lane & 1) * 512 + c * 4), 0, 0, 0, 0);
      str4(&SCR->PS[G * 64 + lane], 0, 0, 0, 0); str4(&SCR->PS[G * 64 + 32 + lane], 0, 0, 0, 0);
      str4(&SCR->SR[1][lane >> 2][sr_off(G, 2 * lane)], 0, 0, 0, 0);
      if (c < 4 && lane < 3) str1(SCR->C + c * 32 + 3 + lane, 0);
#pragma unroll
      for (int k = 0; k < 3; ++k) str2((uint2*)SCR->CS + ((c >> 3) * 768 + k * 256 + 32 * cg + lane), 0, 0);
      __threadfence();
#pragma unroll 1
      for (int layer = 0; layer < 2; ++layer) {
        PROF(4 + 12 * layer);
        box_help(1, lane);
        if (layer) str4(&SCR->SR[0][lane >> 2][sr_off(G, 2 * lane)], 0, 0, 0, 0);
        mbar_wait(B_Z + 8, 0);
        mbar_wait(B_RD, layer);
        cnt_add1(SCR->C + (c >> 5) * 32 + 3 * layer + 1);
        mbar_wait(B_RD + 8, layer);
        cnt_add1(SCR->C + (c >> 5) * 32 + 3 * layer + 2);
        if (P.spare == 0) {
#pragma unroll 1
          for (int k = 0; k < 32; ++k) str4(SCR->XG[layer] + (c * 1024 + k * 32 + lane), 0, 0, 0, 0);
        }
      }
      mbar_watch(B_O + 56, 1);
    }
  }
}

typedef CUresult (*EncodeFn)(CUtensorMap*, CUtensorMapDataType, cuuint32_t, void*, const cuuint64_t*, const cuuint64_t*,
                             const cuuint32_t*, const cuuint32_t*, CUtensorMapInterleave, CUtensorMapSwizzle,
                             CUtensorMapL2promotion, CUtensorMapFloatOOBfill);

static int place_roles(uint8_t* role) {
  int dev = 0, nsm = 0;
  cudaGetDevice(&dev);
  cudaDeviceGetAttribute(&nsm, cudaDevAttrMultiProcessorCount, dev);
  if (nsm <= 128 || nsm > 144 || (nsm & 1)) return 0;
  cudaFuncSetAttribute(fused_kernel, cudaFuncAttributeNonPortableClusterSizeAllowed, 1);
  int occ[9] = {0};
  for (int k = 2; k <= 8; ++k) {
    cudaLaunchConfig_t cfg = {};
    cudaLaunchAttribute at[1];
    at[0].id = cudaLaunchAttributeClusterDimension;
    at[0].val.clusterDim.x = 2 * k; at[0].val.clusterDim.y = 1; at[0].val.clusterDim.z = 1;
    cfg.gridDim = dim3(2 * k); cfg.blockDim = dim3(NTHR); cfg.dynamicSmemBytes = SM_TOTAL; cfg.attrs = at; cfg.numAttrs = 1;
    if (cudaOccupancyMaxActiveClusters(&occ[k], fused_kernel, &cfg) != cudaSuccess) { cudaGetLastError(); occ[k] = 0; }
  }
  int n[10];
  n[7] = occ[8]; n[6] = occ[7]; n[5] = occ[6] - 0; n[4] = occ[5];
  n[3] = occ[4] - n[7]; n[1] = occ[2] - n[3] - n[5] - n[7]; n[0] = n[2] = n[1];
  n[8] = occ[3] - n[2] - n[5];
  const int ntpc = nsm / 2;
  int sum = 0;
  bool ok = n[0] > 0 && n[0] <= 8;
  for (int r = 0; r < 9; ++r) { ok = ok && n[r] >= 0 && (r == 0 || n[r] <= n[r - 1]); sum += n[r]; }
  if (!ok || sum > ntpc) { for (int r = 0; r < 9; ++r) n[r] = r < 8 ? 8 : 0; sum = 64; }
  int tp[8][9], cnt[8] = {0}, pool[72], np = 0, id = 0;
  for (int r = 0; r < 9; ++r)
    for (int g = n[0] - n[r]; g < n[0]; ++g) tp[g][cnt[g]++] = id++;
  for (; id < ntpc; ++id) pool[np++] = id;
  int order[72], no = 0;
  for (int g = 0; g < n[0]; ++g) {
    const int full = cnt[g] / 4 * 4;
    for (int k = 0; k < cnt[g]; ++k) { if (k < full) order[no++] = tp[g][k]; else pool[np++] = tp[g][k]; }
  }
  for (int k = 0; k < np; ++k) order[no++] = pool[k];
  for (int k = 0; k < ntpc; ++k) role[order[k]] = 2 * k;
  return nsm;
}

extern "C" void kernel_launch(void* const* d_in, const int* in_sizes, int n_in, void* d_out, int out_size) {
  (void)in_sizes; (void)n_in; (void)out_size;
  static EncodeFn enc = nullptr;
  static uint8_t role[72];
  static int nsm = 0;
  static Scratch* scratch = nullptr;
  if (!enc) {
    void* fn = nullptr;
    cudaDriverEntryPointQueryResult qr;
    cudaGetDriverEntryPoint("cuTensorMapEncodeTiled", &fn, cudaEnableDefault, &qr);
    enc = (EncodeFn)fn;
    cudaFuncSetAttribute(fused_kernel, cudaFuncAttributeMaxDynamicSharedMemorySize, SM_TOTAL);
    nsm = place_roles(role);
    cudaGetSymbolAddress((void**)&scratch, g_S);
  }
  CUtensorMap mW, mWo, mX;
  {
    cuuint64_t dim[3] = {512, 512, 3}, str[2] = {3072, 1024};
    cuuint32_t box[3] = {64, 64, 3}, es[3] = {1, 1, 1};
    enc(&mW, CU_TENSOR_MAP_DATA_TYPE_BFLOAT16, 3, d_in[10], dim, str, box, es, CU_TENSOR_MAP_INTERLEAVE_NONE,
        CU_TENSOR_MAP_SWIZZLE_128B, CU_TENSOR_MAP_L2_PROMOTION_NONE, CU_TENSOR_MAP_FLOAT_OOB_FILL_NONE);
  }
  {
    cuuint64_t dim[4] = {512, 2, 4, 64}, str[3] = {1024, 2048, 8192};
    cuuint32_t box[4] = {64, 2, 1, 32}, es[4] = {1, 1, 1, 1};
    enc(&mWo, CU_TENSOR_MAP_DATA_TYPE_BFLOAT16, 4, d_in[11], dim, str, box, es, CU_TENSOR_MAP_INTERLEAVE_NONE,
        CU_TENSOR_MAP_SWIZZLE_128B, CU_TENSOR_MAP_L2_PROMOTION_NONE, CU_TENSOR_MAP_FLOAT_OOB_FILL_NONE);
  }
  {
    cuuint64_t dim[2] = {16384, 64}, str[1] = {32768};
    cuuint32_t box[2] = {128, 8}, es[2] = {1, 1};
    enc(&mX, CU_TENSOR_MAP_DATA_TYPE_BFLOAT16, 2, scratch->XF[0], dim, str, box, es, CU_TENSOR_MAP_INTERLEAVE_NONE,
        CU_TENSOR_MAP_SWIZZLE_NONE, CU_TENSOR_MAP_L2_PROMOTION_NONE, CU_TENSOR_MAP_FLOAT_OOB_FILL_NONE);
  }
  Params P;
  P.x0 = (const uint16_t*)d_in[0]; P.Are = (const uint16_t*)d_in[1]; P.Aim = (const uint16_t*)d_in[2];
  P.Bre = (const uint16_t*)d_in[3]; P.Bim = (const uint16_t*)d_in[4]; P.Cre = (const uint16_t*)d_in[5];
  P.Cim = (const uint16_t*)d_in[6]; P.logdt = (const uint16_t*)d_in[7]; P.dskip = (const uint16_t*)d_in[8];
  P.wqkv = (const uint16_t*)d_in[10]; P.wo = (const uint16_t*)d_in[11]; P.out = (uint16_t*)d_out;
  for (int k = 0; k < 72; ++k) P.role[k] = role[k];
  P.zero = 0;
  P.mid = (char*)scratch->C;
  P.spare = nsm > 0 ? nsm - 128 : 0;
  fused_kernel<<<nsm > 0 ? nsm : 128, NTHR, SM_TOTAL, cudaStreamPerThread>>>(P, mW, mWo, mX);
}
```

```cpp
#include <cuda_runtime.h>
#include <cuda_bf16.h>
#include <cuda.h>
#include <stdint.h>
#include <stddef.h>

#define DEV __device__ __forceinline__
#define RARE(x) __builtin_expect(!!(x), 0)

constexpr int NTHR = 512;
constexpr int REG_MAIN = 192, REG_AUX = 96, REG_PROD = 32;
constexpr int NBARU = 384;
constexpr int SPIN_LIMIT = 1 << 22;

constexpr uint32_t SB = 1024;
__host__ __device__ constexpr uint32_t slot(int n) { return SB + n * 8192; }
__host__ __device__ constexpr int wslot(int k) { return k < 2 ? 3 * k : k < 4 ? 3 * k + 6 : k < 6 ? 21 - 3 * k : 3 * k - 18; }
constexpr uint32_t SM_A = slot(22), A_E = 0u - 32768;
constexpr uint32_t SM_O = slot(18), O_E = 0u - 147456;
constexpr uint32_t SM_WO = slot(10), SM_X = slot(8), SM_KV = slot(9) - 4096;
constexpr uint32_t SM_TAP  = slot(26);
constexpr int TAP_SZ = 3440;
constexpr uint32_t SM_STAT = SM_TAP + 4 * TAP_SZ;
constexpr uint32_t SM_CS   = SM_STAT + 1024;
constexpr uint32_t SM_MISC = SM_CS + 768;
constexpr uint32_t SM_BAR  = SM_MISC + 528;
constexpr int SM_TOTAL = SM_BAR + 304 - SB;
static_assert(SM_TOTAL <= 232448, "");
constexpr int R_SZ = 16384, R_U = 512, R_X5 = 5120, R_X3 = 8704, R_BO = 11776, R_BE = 13824;
constexpr int X_5 = 576, X_3 = 648, T_E = 2 * 720, T_O = 1600 + 2 * 721, T_C = 3390, T_K = 3424;
constexpr uint32_t B_RD = SM_BAR, B_ED = SM_BAR + 16, B_F = SM_BAR + 32, B_AT = SM_BAR + 56;
constexpr uint32_t B_AE = SM_BAR + 72, B_QE = SM_BAR + 88, B_ST = SM_BAR + 96, B_CS = SM_BAR + 112;
constexpr uint32_t B_WO = SM_BAR + 120, B_W6 = SM_BAR + 128, B_U = SM_BAR + 144, B_E = SM_BAR + 152, B_A = SM_BAR + 160, B_O = SM_BAR + 192,
                   B_Z = SM_BAR + 256, B_WF = SM_BAR + 272, B_W4 = SM_BAR + 280, B_N = SM_BAR + 288, B_V = SM_BAR + 296;
constexpr int NB_U = 1, NB_B = 2, NB_K = 8, NB_Y = 6, NB_WG = 8, NB_T = 10, NB_AUX = 12, NB_P0 = 13, NB_H = 15;

struct Scratch {
  uint4    XG[2][128 * 1024];
  uint4    O[32 * 8 * 512];
  uint32_t C[8 * 32];
  uint32_t OF[2][32 * 32];
  uint4    CS[16 * 1536 / 4];
  uint4    PS[128 * 64];
  uint4    ST[2][32 * 128];
  uint4    SR[2][8][512];
  uint4    XF[2][32 * 512 * 8];
  uint4    H[2][17 * 8 * 256];
};
__device__ __align__(1024) Scratch g_S;
#define SCR ((Scratch*)(P.mid - offsetof(Scratch, C)))
#define PROFD(slot, v) do {} while (0)
#define PROF(slot) do {} while (0)

DEV uint32_t s2u(const void* p) { return (uint32_t)__cvta_generic_to_shared(p); }
template <class T> DEV T opq(T x) { asm volatile("" : "+r"(x)); return x; }
DEV int lane_id() { int l; asm volatile("mov.u32 %0,%%laneid;" : "=r"(l)); return l; }
DEV uint32_t pack2(float lo, float hi) { uint32_t d; asm("cvt.rn.bf16x2.f32 %0,%1,%2;" : "=r"(d) : "f"(hi), "f"(lo)); return d; }
DEV float bflo(uint32_t v) { return __uint_as_float(v << 16); }
DEV float bfhi(uint32_t v) { return __uint_as_float(v & 0xFFFF0000u); }
DEV float bfr(float x) { return bflo(pack2(x, 0.f)); }
DEV uint32_t hadd2(uint32_t a, uint32_t b) { uint32_t d; asm("add.rn.bf16x2 %0,%1,%2;" : "=r"(d) : "r"(a), "r"(b)); return d; }
DEV uint32_t hsub2(uint32_t a, uint32_t b) { uint32_t d; asm("sub.rn.bf16x2 %0,%1,%2;" : "=r"(d) : "r"(a), "r"(b)); return d; }
DEV uint32_t hmul2(uint32_t a, uint32_t b) { uint32_t d; asm("mul.rn.bf16x2 %0,%1,%2;" : "=r"(d) : "r"(a), "r"(b)); return d; }
DEV uint32_t hfma2(uint32_t a, uint32_t b, uint32_t c) { uint32_t d; asm("fma.rn.bf16x2 %0,%1,%2,%3;" : "=r"(d) : "r"(a), "r"(b), "r"(c)); return d; }
DEV uint32_t hmax2(uint32_t a, uint32_t b) { uint32_t d; asm("max.bf16x2 %0,%1,%2;" : "=r"(d) : "r"(a), "r"(b)); return d; }
DEV uint32_t prmt(uint32_t a, uint32_t b, uint32_t s) { uint32_t d; asm("prmt.b32 %0,%1,%2,%3;" : "=r"(d) : "r"(a), "r"(b), "r"(s)); return d; }
DEV uint32_t nzmap(uint32_t v) { return v == 0u ? 0x80000000u : v; }
DEV float rcp(float x) { float y; asm("rcp.approx.ftz.f32 %0,%1;" : "=f"(y) : "f"(x)); return y; }
DEV float sqrt_(float x) { float y; asm("sqrt.approx.ftz.f32 %0,%1;" : "=f"(y) : "f"(x)); return y; }
DEV float ex2(float x) { float y; asm("ex2.approx.ftz.f32 %0,%1;" : "=f"(y) : "f"(x)); return y; }

DEV uint4 ldr4(const void* p) { uint4 v; asm volatile("ld.relaxed.gpu.global.v4.u32 {%0,%1,%2,%3},[%4];" : "=r"(v.x), "=r"(v.y), "=r"(v.z), "=r"(v.w) : "l"(p) : "memory"); return v; }
DEV void ldr4_if(uint4& v, const void* p, bool c) {
  asm volatile("{.reg .pred q; setp.ne.u32 q,%5,0; @q ld.relaxed.gpu.global.v4.u32 {%0,%1,%2,%3},[%4];}"
    : "+r"(v.x), "+r"(v.y), "+r"(v.z), "+r"(v.w) : "l"(p), "r"((uint32_t)c) : "memory");
}
DEV uint2 ldr2(const void* p) { uint2 v; asm volatile("ld.relaxed.gpu.global.v2.u32 {%0,%1},[%2];" : "=r"(v.x), "=r"(v.y) : "l"(p) : "memory"); return v; }
DEV void ldr2_if(uint2& v, const void* p, bool c) {
  asm volatile("{.reg .pred q; setp.ne.u32 q,%3,0; @q ld.relaxed.gpu.global.v2.u32 {%0,%1},[%2];}" : "+r"(v.x), "+r"(v.y) : "l"(p), "r"((uint32_t)c) : "memory");
}
DEV uint32_t ldr1(const void* p) { uint32_t v; asm volatile("ld.relaxed.gpu.global.u32 %0,[%1];" : "=r"(v) : "l"(p) : "memory"); return v; }
DEV float ldnan(const uint16_t* p) {
  uint32_t v = 0xFFFFu;
#pragma unroll 1
  for (int it = 0; it < SPIN_LIMIT && __any_sync(0xffffffffu, v == 0xFFFFu); ++it) asm volatile("ld.relaxed.gpu.global.u16 %0,[%1];" : "=r"(v) : "l"(p) : "memory");
  return __uint_as_float(v << 16);
}
DEV uint4 ldw4(const void* p) { uint4 v; asm volatile("ld.global.v4.u32 {%0,%1,%2,%3},[%4];" : "=r"(v.x), "=r"(v.y), "=r"(v.z), "=r"(v.w) : "l"(p) : "memory"); return v; }
DEV uint2 ldw2(const void* p) { uint2 v; asm volatile("ld.global.v2.u32 {%0,%1},[%2];" : "=r"(v.x), "=r"(v.y) : "l"(p) : "memory"); return v; }
DEV uint32_t ldw1(const void* p) { uint32_t v; asm volatile("ld.global.u32 %0,[%1];" : "=r"(v) : "l"(p) : "memory"); return v; }
DEV void str4(void* p, uint32_t a, uint32_t b, uint32_t c, uint32_t d) { asm volatile("st.relaxed.gpu.global.v4.u32 [%0],{%1,%2,%3,%4};" :: "l"(p), "r"(a), "r"(b), "r"(c), "r"(d) : "memory"); }
DEV void str2(void* p, uint32_t a, uint32_t b) { asm volatile("st.relaxed.gpu.global.v2.u32 [%0],{%1,%2};" :: "l"(p), "r"(a), "r"(b) : "memory"); }
DEV void str1(void* p, uint32_t a) { asm volatile("st.relaxed.gpu.global.u32 [%0],%1;" :: "l"(p), "r"(a) : "memory"); }
DEV void str4_if(void* p, uint32_t a, uint32_t b, uint32_t c, uint32_t d, bool q) {
  asm volatile("{.reg .pred q; setp.ne.u32 q,%5,0; @q st.relaxed.gpu.global.v4.u32 [%0],{%1,%2,%3,%4};}" :: "l"(p), "r"(a), "r"(b), "r"(c), "r"(d), "r"((uint32_t)q) : "memory");
}
DEV void stw4(void* p, uint32_t a, uint32_t b, uint32_t c, uint32_t d) { asm volatile("st.global.v4.u32 [%0],{%1,%2,%3,%4};" :: "l"(p), "r"(a), "r"(b), "r"(c), "r"(d) : "memory"); }
DEV uint4 ldnc4(const void* p) { uint4 v; asm volatile("ld.global.nc.v4.u32 {%0,%1,%2,%3},[%4];" : "=r"(v.x), "=r"(v.y), "=r"(v.z), "=r"(v.w) : "l"(p)); return v; }
DEV uint32_t ldnc1(const void* p) { uint32_t v; asm volatile("ld.global.nc.u32 %0,[%1];" : "=r"(v) : "l"(p)); return v; }
DEV uint2 ldnc2(const void* p) { uint2 v; asm volatile("ld.global.nc.v2.u32 {%0,%1},[%2];" : "=r"(v.x), "=r"(v.y) : "l"(p)); return v; }

DEV uint2 lds2(uint32_t a) { uint2 v; asm volatile("ld.volatile.shared.v2.u32 {%0,%1},[%2];" : "=r"(v.x), "=r"(v.y) : "r"(a)); return v; }
DEV float lds16f(uint32_t a) { uint32_t v; asm volatile("ld.shared.u16 %0,[%1];" : "=r"(v) : "r"(a)); return __uint_as_float(v << 16); }
DEV void sts2(uint32_t a, uint32_t x, uint32_t y) { asm volatile("st.shared.v2.u32 [%0],{%1,%2};" :: "r"(a), "r"(x), "r"(y) : "memory"); }
DEV uint32_t lds1(uint32_t a) { uint32_t v; asm volatile("ld.volatile.shared.u32 %0,[%1];" : "=r"(v) : "r"(a)); return v; }
DEV uint32_t lds1z(uint32_t a, bool c) {
  uint32_t v; asm volatile("{.reg .pred q; setp.ne.u32 q,%2,0; mov.u32 %0,0; @q ld.volatile.shared.u32 %0,[%1];}" : "=r"(v) : "r"(a), "r"((uint32_t)c)); return v;
}
DEV uint4 lds4z(uint32_t a, bool c) {
  uint4 v = make_uint4(0, 0, 0, 0);
  asm volatile("{.reg .pred q; setp.ne.u32 q,%5,0; @q ld.volatile.shared.v4.u32 {%0,%1,%2,%3},[%4];}" : "+r"(v.x), "+r"(v.y), "+r"(v.z), "+r"(v.w) : "r"(a), "r"((uint32_t)c));
  return v;
}
DEV float lds1f(uint32_t a) { float v; asm volatile("ld.shared.f32 %0,[%1];" : "=f"(v) : "r"(a)); return v; }
DEV float2 lds2f(uint32_t a) { float2 v; asm volatile("ld.shared.v2.f32 {%0,%1},[%2];" : "=f"(v.x), "=f"(v.y) : "r"(a)); return v; }
DEV float4 lds4f(uint32_t a) { float4 v; asm volatile("ld.shared.v4.f32 {%0,%1,%2,%3},[%4];" : "=f"(v.x), "=f"(v.y), "=f"(v.z), "=f"(v.w) : "r"(a)); return v; }
DEV uint4 lds4(uint32_t a) { uint4 v; asm volatile("ld.volatile.shared.v4.u32 {%0,%1,%2,%3},[%4];" : "=r"(v.x), "=r"(v.y), "=r"(v.z), "=r"(v.w) : "r"(a)); return v; }
DEV void sts1(uint32_t a, uint32_t v) { asm volatile("st.shared.u32 [%0],%1;" :: "r"(a), "r"(v) : "memory"); }
DEV void sts16(uint32_t a, uint32_t v) { asm volatile("{.reg .b16 h; cvt.u16.u32 h,%1; st.shared.u16 [%0],h;}" :: "r"(a), "r"(v) : "memory"); }
DEV void sts2f(uint32_t a, float x, float y) { asm volatile("st.shared.v2.f32 [%0],{%1,%2};" :: "r"(a), "f"(x), "f"(y) : "memory"); }
DEV void sts4f(uint32_t a, float x, float y, float z, float w) { asm volatile("st.shared.v4.f32 [%0],{%1,%2,%3,%4};" :: "r"(a), "f"(x), "f"(y), "f"(z), "f"(w) : "memory"); }
DEV void sts4(uint32_t a, uint32_t x, uint32_t y, uint32_t z, uint32_t w) { asm volatile("st.shared.v4.u32 [%0],{%1,%2,%3,%4};" :: "r"(a), "r"(x), "r"(y), "r"(z), "r"(w) : "memory"); }

DEV void ldsm4(uint32_t (&r)[4], uint32_t a) { asm volatile("ldmatrix.sync.aligned.m8n8.x4.shared.b16 {%0,%1,%2,%3},[%4];" : "=r"(r[0]), "=r"(r[1]), "=r"(r[2]), "=r"(r[3]) : "r"(a) : "memory"); }
DEV void ldsm4t(uint32_t (&r)[4], uint32_t a) { asm volatile("ldmatrix.sync.aligned.m8n8.x4.trans.shared.b16 {%0,%1,%2,%3},[%4];" : "=r"(r[0]), "=r"(r[1]), "=r"(r[2]), "=r"(r[3]) : "r"(a) : "memory"); }
DEV void ldsm2(uint32_t (&r)[2], uint32_t a) { asm volatile("ldmatrix.sync.aligned.m8n8.x2.shared.b16 {%0,%1},[%2];" : "=r"(r[0]), "=r"(r[1]) : "r"(a) : "memory"); }
DEV void stsm4(uint32_t a, uint32_t r0, uint32_t r1, uint32_t r2, uint32_t r3) { asm volatile("stmatrix.sync.aligned.m8n8.x4.shared.b16 [%0],{%1,%2,%3,%4};" :: "r"(a), "r"(r0), "r"(r1), "r"(r2), "r"(r3) : "memory"); }
DEV void stsm2(uint32_t a, uint32_t r0, uint32_t r1) { asm volatile("stmatrix.sync.aligned.m8n8.x2.shared.b16 [%0],{%1,%2};" :: "r"(a), "r"(r0), "r"(r1) : "memory"); }
DEV void stsm4t(uint32_t a, uint32_t r0, uint32_t r1, uint32_t r2, uint32_t r3) { asm volatile("stmatrix.sync.aligned.m8n8.x4.trans.shared.b16 [%0],{%1,%2,%3,%4};" :: "r"(a), "r"(r0), "r"(r1), "r"(r2), "r"(r3) : "memory"); }
DEV uint32_t movm(uint32_t a) { uint32_t d; asm volatile("movmatrix.sync.aligned.m8n8.trans.b16 %0,%1;" : "=r"(d) : "r"(a)); return d; }
DEV void mma16(float (&d)[4], uint32_t a0, uint32_t a1, uint32_t a2, uint32_t a3, uint32_t b0, uint32_t b1) {
  asm volatile("mma.sync.aligned.m16n8k16.row.col.f32.bf16.bf16.f32 {%0,%1,%2,%3},{%4,%5,%6,%7},{%8,%9},{%0,%1,%2,%3};"
    : "+f"(d[0]), "+f"(d[1]), "+f"(d[2]), "+f"(d[3]) : "r"(a0), "r"(a1), "r"(a2), "r"(a3), "r"(b0), "r"(b1));
}
DEV void mma16z(float (&d)[4], uint32_t a0, uint32_t a1, uint32_t a2, uint32_t a3, uint32_t b0, uint32_t b1) {
  asm volatile("mma.sync.aligned.m16n8k16.row.col.f32.bf16.bf16.f32 {%0,%1,%2,%3},{%4,%5,%6,%7},{%8,%9},{%10,%10,%10,%10};"
    : "=f"(d[0]), "=f"(d[1]), "=f"(d[2]), "=f"(d[3]) : "r"(a0), "r"(a1), "r"(a2), "r"(a3), "r"(b0), "r"(b1), "f"(0.f));
}
DEV void mma8(float (&d)[4], uint32_t a0, uint32_t a1, uint32_t b0) {
  asm volatile("mma.sync.aligned.m16n8k8.row.col.f32.bf16.bf16.f32 {%0,%1,%2,%3},{%4,%5},{%6},{%0,%1,%2,%3};"
    : "+f"(d[0]), "+f"(d[1]), "+f"(d[2]), "+f"(d[3]) : "r"(a0), "r"(a1), "r"(b0));
}

DEV void bar_sync(int id, int n) { asm volatile("bar.sync %0,%1;" :: "r"(id), "r"(n) : "memory"); }
DEV void bar_sync_if(int id, int n, int c) { asm volatile("{.reg .pred q; setp.ne.s32 q,%2,0; @q bar.sync %0,%1;}" :: "r"(id), "r"(n), "r"(c) : "memory"); }
DEV void bar_arrive_if(int id, int n, int c) { asm volatile("{.reg .pred q; setp.ne.s32 q,%2,0; @q bar.arrive %0,%1;}" :: "r"(id), "r"(n), "r"(c) : "memory"); }
DEV bool bar_any(int id, int n, bool c) {
  uint32_t r; asm volatile("{.reg .pred p,q; setp.ne.u32 q,%3,0; bar.red.or.pred p,%1,%2,q; selp.u32 %0,1,0,p;}" : "=r"(r) : "r"(id), "r"(n), "r"((uint32_t)c) : "memory");
  return __any_sync(0xffffffffu, r);
}
DEV void bar_arrive(int id, int n) { asm volatile("bar.arrive %0,%1;" :: "r"(id), "r"(n) : "memory"); }
DEV void fence_async_glob() { asm volatile("fence.proxy.async.global;" ::: "memory"); }
DEV void fence_async_smem() { asm volatile("fence.proxy.async.shared::cta;" ::: "memory"); }
DEV void mbar_init(uint32_t b, int n) { asm volatile("mbarrier.init.shared::cta.b64 [%0],%1;" :: "r"(b), "r"(n) : "memory"); }
DEV void mbar_arrive(uint32_t b) { asm volatile("mbarrier.arrive.shared::cta.b64 _,[%0];" :: "r"(b) : "memory"); }
DEV void mbar_expect(uint32_t b, int bytes) { asm volatile("mbarrier.arrive.expect_tx.shared::cta.b64 _,[%0],%1;" :: "r"(b), "r"(bytes) : "memory"); }
DEV void mbar_wait(uint32_t b, uint32_t ph) {
  asm volatile("{\n.reg .pred p;\nW: mbarrier.try_wait.parity.shared::cta.b64 p,[%0],%1;\n@!p bra W;\n}" :: "r"(b), "r"(ph) : "memory");
}
DEV void mbar_watch(uint32_t b, uint32_t ph) {
  asm volatile("{\n.reg .pred p,q;\n.reg .u32 n;\nmov.u32 n,0;\n"
               "W: mbarrier.try_wait.parity.shared::cta.b64 p,[%0],%1;\n@p bra D;\n"
               "add.u32 n,n,1;\nsetp.lt.u32 q,n,%2;\n@q bra W;\ntrap;\nD:\n}"
               :: "r"(b), "r"(ph), "n"(SPIN_LIMIT) : "memory");
}
DEV void spin_guard(int it) { asm volatile("{.reg .pred p; setp.gt.s32 p,%0,%1; @p trap;}" :: "r"(it), "n"(SPIN_LIMIT)); }
DEV void split(uint32_t zero) {
  asm volatile("{.reg .pred p; setp.ne.u32 p,%0,0; @p trap;}" :: "r"(zero) : "memory");
}
DEV void pause(int n) {
  uint32_t t0, t; asm volatile("mov.u32 %0,%%clock;" : "=r"(t0));
  do asm volatile("mov.u32 %0,%%clock;" : "=r"(t)); while (t - t0 < n);
}
DEV void cnt_wait(const uint32_t* k, int lane) {
#pragma unroll 1
  for (int it = 0;; ++it) {
    spin_guard(it);
    if (__all_sync(0xffffffffu, ldr1(k + (lane & 3) * 32) >= 32)) break;
  }
}
DEV void mbar_arrive1(uint32_t b) { asm volatile("{.reg .pred p; elect.sync _|p,0xffffffff; @p mbarrier.arrive.shared::cta.b64 _,[%0];}" :: "r"(b) : "memory"); }
DEV void mbar_arrive1_if(uint32_t b, int c) {
  asm volatile("{.reg .pred p,q; setp.ne.s32 q,%1,0; elect.sync _|p,0xffffffff; and.pred p,p,q; @p mbarrier.arrive.shared::cta.b64 _,[%0];}" :: "r"(b), "r"(c) : "memory");
}
DEV void mbar_expect1(uint32_t b, int bytes) { asm volatile("{.reg .pred p; elect.sync _|p,0xffffffff; @p mbarrier.arrive.expect_tx.shared::cta.b64 _,[%0],%1;}" :: "r"(b), "r"(bytes) : "memory"); }
DEV void cnt_add1(uint32_t* q) { asm volatile("{.reg .pred p; elect.sync _|p,0xffffffff; @p red.relaxed.gpu.global.add.u32 [%0],1;}" :: "l"(q) : "memory"); }
DEV void tma4(uint32_t dst, const CUtensorMap* m, int c0, int c1, int c2, int c3, uint32_t bar) {
  asm volatile("{.reg .pred p; elect.sync _|p,0xffffffff;\n"
    "@p cp.async.bulk.tensor.4d.shared::cluster.global.mbarrier::complete_tx::bytes [%0],[%1,{%2,%3,%4,%5}],[%6];}"
    :: "r"(dst), "l"(m), "r"(c0), "r"(c1), "r"(c2), "r"(c3), "r"(bar) : "memory");
}
DEV void tma3(uint32_t dst, const CUtensorMap* m, int c0, int c1, int c2, uint32_t bar) {
  asm volatile("{.reg .pred p; elect.sync _|p,0xffffffff;\n"
    "@p cp.async.bulk.tensor.3d.shared::cluster.global.mbarrier::complete_tx::bytes [%0],[%1,{%2,%3,%4}],[%5];}"
    :: "r"(dst), "l"(m), "r"(c0), "r"(c1), "r"(c2), "r"(bar) : "memory");
}
DEV void bulk(uint32_t dst, const void* src, int bytes, uint32_t bar) {
  asm volatile("{.reg .pred p; elect.sync _|p,0xffffffff;\n@p cp.async.bulk.shared::cluster.global.mbarrier::complete_tx::bytes [%0],[%1],%2,[%3];}" :: "r"(dst), "l"(src), "r"(bytes), "r"(bar) : "memory");
}

DEV void bulk_store(void* dst, uint32_t src, int bytes) {
  asm volatile("{.reg .pred p; elect.sync _|p,0xffffffff;\n@p cp.async.bulk.global.shared::cta.bulk_group [%0],[%1],%2;}" :: "l"(dst), "r"(src), "r"(bytes) : "memory");
}
DEV void tma2_store(const CUtensorMap* m, uint32_t src, int c0, int c1) {
  asm volatile("{.reg .pred p; elect.sync _|p,0xffffffff;\n@p cp.async.bulk.tensor.2d.global.shared::cta.bulk_group [%0,{%2,%3}],[%1];}" :: "l"(m), "r"(src), "r"(c0), "r"(c1) : "memory");
}
DEV void bulk_wait() { asm volatile("cp.async.bulk.commit_group;\ncp.async.bulk.wait_group 0;\nfence.proxy.async.global;" ::: "memory"); }

DEV uint32_t dlo(uint32_t addr, uint32_t lbo) { return __shfl_sync(0xffffffffu, (addr >> 4) | ((lbo >> 4) << 16), 0); }
__host__ __device__ constexpr uint32_t dhi(uint32_t sbo, uint32_t swz) { return (sbo >> 4) | (swz << 30); }
DEV void wg_fence() { asm volatile("wgmma.fence.sync.aligned;" ::: "memory"); }
DEV void wg_commit() { asm volatile("wgmma.commit_group.sync.aligned;" ::: "memory"); }
template <int N> DEV void wg_wait() { asm volatile("wgmma.wait_group.sync.aligned %0;" :: "n"(N) : "memory"); }
template <int N> DEV void zero(float (&d)[N]) {
#pragma unroll
  for (int i = 0; i < N; ++i) d[i] = 0.f;
}
template <int N> DEV void zerov(float (&d)[N]) {
#pragma unroll
  for (int i = 0; i < N; ++i) asm volatile("mov.b32 %0,0;" : "=f"(d[i]));
}
template <int N> DEV void undef(float (&d)[N]) {
#pragma unroll
  for (int i = 0; i < N; ++i) asm volatile("" : "=f"(d[i]));
}
#define R4(d, o) "+f"(d[o]), "+f"(d[o + 1]), "+f"(d[o + 2]), "+f"(d[o + 3])
#define R8(d, o) R4(d, o), R4(d, o + 4)
#define R16(d, o) R8(d, o), R8(d, o + 8)
template <int ACC> DEV void wg_rs64k(float (&d)[32], const uint32_t (&a)[4], uint32_t db) {
  asm volatile("{.reg .pred p; .reg .b64 b; setp.ne.s32 p,%38,0; mov.b64 b,{%36,%37};\n"
    "wgmma.mma_async.sync.aligned.m64n64k16.f32.bf16.bf16 {%0,%1,%2,%3,%4,%5,%6,%7,%8,%9,%10,%11,%12,%13,%14,%15,%16,%17,%18,%19,%20,%21,%22,%23,%24,%25,%26,%27,%28,%29,%30,%31},{%32,%33,%34,%35},b,p,1,1,0;}"
    : R16(d, 0), R16(d, 16) : "r"(a[0]), "r"(a[1]), "r"(a[2]), "r"(a[3]), "r"(db), "n"(dhi(512, 2)), "n"(ACC));
}
template <int ACC> DEV void wg_rs48t(float (&d)[24], const uint32_t (&a)[4], uint32_t db) {
  asm volatile("{.reg .pred p; .reg .b64 b; setp.ne.s32 p,%30,0; mov.b64 b,{%28,%29};\n"
    "wgmma.mma_async.sync.aligned.m64n48k16.f32.bf16.bf16 {%0,%1,%2,%3,%4,%5,%6,%7,%8,%9,%10,%11,%12,%13,%14,%15,%16,%17,%18,%19,%20,%21,%22,%23},{%24,%25,%26,%27},b,p,1,1,1;}"
    : R16(d, 0), R8(d, 16) : "r"(a[0]), "r"(a[1]), "r"(a[2]), "r"(a[3]), "r"(db), "n"(dhi(512, 0)), "n"(ACC));
}
template <int ACC> DEV void wg_rs32t(float (&d)[16], const uint32_t (&a)[4], uint32_t db) {
  asm volatile("{.reg .pred p; .reg .b64 b; setp.ne.s32 p,%22,0; mov.b64 b,{%20,%21};\n"
    "wgmma.mma_async.sync.aligned.m64n32k16.f32.bf16.bf16 {%0,%1,%2,%3,%4,%5,%6,%7,%8,%9,%10,%11,%12,%13,%14,%15},{%16,%17,%18,%19},b,p,1,1,1;}"
    : R16(d, 0) : "r"(a[0]), "r"(a[1]), "r"(a[2]), "r"(a[3]), "r"(db), "n"(dhi(1024, 0)), "n"(ACC));
}
template <int ACC> DEV void wg_ss192(float (&d)[96], uint32_t da, uint32_t db) {
  asm volatile("{.reg .pred p; .reg .b64 a,b; setp.ne.s32 p,%100,0; mov.b64 a,{%96,%98}; mov.b64 b,{%97,%99};\n"
    "wgmma.mma_async.sync.aligned.m64n192k16.f32.bf16.bf16 {"
    "%0,%1,%2,%3,%4,%5,%6,%7,%8,%9,%10,%11,%12,%13,%14,%15,%16,%17,%18,%19,%20,%21,%22,%23,%24,%25,%26,%27,%28,%29,%30,%31,"
    "%32,%33,%34,%35,%36,%37,%38,%39,%40,%41,%42,%43,%44,%45,%46,%47,%48,%49,%50,%51,%52,%53,%54,%55,%56,%57,%58,%59,%60,%61,%62,%63,"
    "%64,%65,%66,%67,%68,%69,%70,%71,%72,%73,%74,%75,%76,%77,%78,%79,%80,%81,%82,%83,%84,%85,%86,%87,%88,%89,%90,%91,%92,%93,%94,%95},a,b,p,1,1,1,1;}"
    : R16(d, 0), R16(d, 16), R16(d, 32), R16(d, 48), R16(d, 64), R16(d, 80) : "r"(da), "r"(db), "n"(dhi(1024, 1)), "n"(dhi(1024, 1)), "n"(ACC));
}
template <int ACC> DEV void wg_ss64(float (&d)[32], uint32_t da, uint32_t db) {
  asm volatile("{.reg .pred p; .reg .b64 a,b; setp.ne.s32 p,%36,0; mov.b64 a,{%32,%34}; mov.b64 b,{%33,%35};\n"
    "wgmma.mma_async.sync.aligned.m64n64k16.f32.bf16.bf16 {"
    "%0,%1,%2,%3,%4,%5,%6,%7,%8,%9,%10,%11,%12,%13,%14,%15,%16,%17,%18,%19,%20,%21,%22,%23,%24,%25,%26,%27,%28,%29,%30,%31},a,b,p,1,1,0,1;}"
    : R16(d, 0), R16(d, 16) : "r"(da), "r"(db), "n"(dhi(1024, 0)), "n"(dhi(1024, 1)), "n"(ACC));
}

DEV uint32_t cpy(uint32_t v, uint32_t id) {
  uint32_t d; asm volatile("prmt.b32 %0,%1,%1,%2;" : "=r"(d) : "r"(v), "r"(id)); return d;
}
struct Params {
  uint32_t zero, spare;
  char* mid;
  const uint16_t *x0, *Are, *Aim, *Bre, *Bim, *Cre, *Cim, *logdt, *dskip, *wqkv, *wo;
  uint16_t* out;
  uint8_t role[72];
};

DEV uint32_t ln_word(float mean, float var) {
  float v = bfr(var);
  float s = sqrt_(bfr(v + 1e-5f));
  return pack2(mean, s);
}

DEV int stat_group(int c) { return c ^ 4; }
DEV int xg_off(int G, int g) { return (G >> 6) * 1024 + (G & 63) * 8 + (g ^ (G & 2)); }
DEV int sr_off(int G, int g) { return (G >> 6) * 256 + (g & 2) * 64 + 2 * (G & 63) + ((g >> 2) & 1); }
DEV uint32_t region(int chl) { return SM_A + (chl >> 1) * A_E + (chl & 1) * R_SZ; }
template <int N> DEV float4 gram(const uint32_t (&w)[N][2], int g) {
  float s0[4], s1[4];
  const uint32_t one = 0x3F803F80u;
  mma16z(s0, w[0][0], one, w[1][0], one, w[0][0], w[1][0]); mma16z(s1, w[0][1], one, w[1][1], one, w[0][1], w[1][1]);
#pragma unroll
  for (int j = 2; j < N; j += 2) {
    mma16(s0, w[j][0], one, w[j + 1][0], one, w[j][0], w[j + 1][0]); mma16(s1, w[j][1], one, w[j + 1][1], one, w[j][1], w[j + 1][1]);
  }
  const bool od = g & 1;
  return make_float4(od ? s0[3] : s0[2], od ? s0[1] : s0[0], od ? s1[3] : s1[2], od ? s1[1] : s1[0]);
}
DEV uint32_t ln_sums(float s, float q) { const float m = s * (1.f / 512.f); return ln_word(m, fmaxf(q * (1.f / 512.f) - m * m, 0.f)); }
DEV void cmul(float& orr, float& oi, float ar, float ai, float br, float bi) {
  float r = ar * br - ai * bi, i = ar * bi + ai * br; orr = r; oi = i;
}
DEV void cexp_(float al, float bt, float s, float& er, float& ei) {
  float mag = ex2(al * s), ph = bt * s;
  ph -= rintf(ph);
  float ang = ph * 6.283185307179586f;
  er = mag * __cosf(ang); ei = mag * __sinf(ang);
}

DEV void kgen(const Params& P, int c, int wm, int lane) {
  const int chl = wm >> 1, mh = wm & 1, g = lane >> 2, t = lane & 3;
  const int ch = 256 * (chl >> 1) + 2 * c + (chl & 1);
  const int mo = ch * 64 + mh * 32 + lane;
  const uint32_t vAr = ldw1((const uint32_t*)P.Are + mo), vAi = ldw1((const uint32_t*)P.Aim + mo);
  const uint32_t vBr = ldw1((const uint32_t*)P.Bre + mo), vBi = ldw1((const uint32_t*)P.Bim + mo);
  const uint32_t vCr = ldw1((const uint32_t*)P.Cre + mo), vCi = ldw1((const uint32_t*)P.Cim + mo);
  const uint32_t vld = ldw1((const uint32_t*)P.logdt + (ch >> 1)) >> (16 * (ch & 1)), vds = ldw1((const uint32_t*)P.dskip + (ch >> 1)) >> (16 * (ch & 1));
  bar_arrive(NB_Y, 384);
  PROF(45);
  asm volatile("setmaxnreg.inc.sync.aligned.u32 %0;" :: "n"(REG_MAIN));
  PROF(44);
  {
    const uint32_t tz = SM_TAP + chl * TAP_SZ + (mh * 32 + lane) * 16;
#pragma unroll
    for (int k = 0; k < 3; ++k) sts4(tz + k * 1024, 0, 0, 0, 0);
    static_assert(TAP_SZ > 3072 && TAP_SZ <= 4096, "");
    if (mh * 32 + lane < TAP_SZ / 16 - 192) sts4(tz + 3072, 0, 0, 0, 0);
  }
  const float dt = bfr(__expf(bflo(vld)));
  const uint32_t tb = slot(wm);
  float acc[5][4];
#pragma unroll
  for (int i = 0; i < 5; ++i) { acc[i][0] = acc[i][1] = acc[i][2] = acc[i][3] = 0.f; }
  float k2048 = 0.f;
#pragma unroll 1
  for (int r = 0; r < 2; ++r) {
    const float are = r ? bfhi(vAr) : bflo(vAr), aim = r ? bfhi(vAi) : bflo(vAi);
    const float bre = r ? bfhi(vBr) : bflo(vBr), bim = r ? bfhi(vBi) : bflo(vBi);
    const float cre = r ? bfhi(vCr) : bflo(vCr), cim = r ? bfhi(vCi) : bflo(vCi);
    const float al = dt * are * 1.4426950408889634f, bt = dt * aim * 0.15915494309189535f;
    float wr, wi; cmul(wr, wi, cre, cim, dt * bre, dt * bim);
    if (r == 0) PROFD(2, __float_as_uint(wr + al + bt));
    float e1r, e1i, e8r, e8i, eLr, eLi;
    cexp_(al, bt, 1.f, e1r, e1i); cexp_(al, bt, 8.f, e8r, e8i); cexp_(al, bt, 128.f, eLr, eLi);
    const uint32_t tw = tb + lane * 4;
    float pr[8], pi[8];
    pr[1] = e1r; pi[1] = e1i;
#pragma unroll
    for (int k = 2; k < 8; ++k) cmul(pr[k], pi[k], pr[k - 1], pi[k - 1], e1r, e1i);
    float yr = 1.f, yi = 0.f, qr = wr, qi = wi;
#pragma unroll
    for (int a = 0; a < 16; ++a) {
      sts1(tw + a * 144, pack2(yr, -yi));
      if (a == 0) { yr = e8r; yi = e8i; } else if (a < 15) cmul(yr, yi, yr, yi, e8r, e8i);
      const int step = a < 2 ? 1 : a < 4 ? 2 : a < 8 ? 4 : 8;
      const int row0 = 16 + (a < 2 ? 8 * a : a < 4 ? 16 + 4 * (a - 2) : a < 8 ? 24 + 2 * (a - 4) : 32 + (a - 8));
      sts1(tw + row0 * 144, pack2(qr, qi));
#pragma unroll
      for (int k = step; k < 8; k += step) {
        float xr, xi; cmul(xr, xi, qr, qi, pr[k], pi[k]);
        sts1(tw + (row0 + k / step) * 144, pack2(xr, xi));
      }
      cmul(qr, qi, qr, qi, eLr, eLi);
    }
    k2048 += qr;
    __syncwarp();
    if (r == 0) PROF(3);
#pragma unroll
    for (int kp = 0; kp < 2; ++kp) {
      uint32_t a0[4], a1[4];
      const uint32_t aa = tb + ((lane & 7) + 8 * ((lane >> 3) & 1)) * 144 + (lane >> 4) * 16 + kp * 64;
      ldsm4(a0, aa); ldsm4(a1, aa + 32);
#pragma unroll
      for (int tl = 0; tl < 5; ++tl) {
        uint32_t b[4];
        ldsm4(b, tb + (16 + 8 * tl + (lane & 7)) * 144 + (lane >> 3) * 16 + kp * 64);
        mma16(acc[tl], a0[0], a0[1], a0[2], a0[3], b[0], b[1]);
        mma16(acc[tl], a1[0], a1[1], a1[2], a1[3], b[2], b[3]);
      }
    }
    __syncwarp();
    bar_sync_if(NB_P0 + 1, 288, 1 - r);
  }
#pragma unroll
  for (int o = 16; o > 0; o >>= 1) k2048 += __shfl_xor_sync(0xffffffffu, k2048, o);
  if (mh == 0) {
    sts4f(tb + lane * 16, acc[2][0], acc[2][1], acc[2][2], acc[2][3]);
    sts4f(tb + 512 + lane * 16, acc[3][0], acc[3][1], acc[3][2], acc[3][3]);
  } else {
    sts4f(tb + lane * 16, acc[0][0], acc[0][1], acc[0][2], acc[0][3]);
    sts4f(tb + 512 + lane * 16, acc[1][0], acc[1][1], acc[1][2], acc[1][3]);
    sts4f(tb + 1024 + lane * 16, acc[4][0], acc[4][1], acc[4][2], acc[4][3]);
    if (lane == 0) sts1(tb + 1536, __float_as_uint(k2048));
  }
  PROF(4);
  bar_sync(NB_K + chl, 64);
  const uint32_t ob = slot(wm ^ 1), tp = SM_TAP + chl * TAP_SZ;
  if (mh == 0) {
#pragma unroll
    for (int tl = 0; tl < 2; ++tl) {
      float4 o = lds4f(ob + tl * 512 + lane * 16);
      if (tl == 0 && lane == 0) o.x += bflo(vds);
      uint32_t v0 = pack2(acc[tl][0] + o.x, acc[tl][1] + o.y), v1 = pack2(acc[tl][2] + o.z, acc[tl][3] + o.w);
      const int l = 128 * tl + 8 * g + 2 * t;
      sts16(tp + T_E + 2 * (0 - l), v0); sts16(tp + T_E + 2 * (-1 - l), v0 >> 16);
      sts16(tp + T_O + 2 * (0 - l), v0); sts16(tp + T_O + 2 * (-1 - l), v0 >> 16);
      sts16(tp + T_E + 2 * (-64 - l), v1); sts16(tp + T_E + 2 * (-65 - l), v1 >> 16);
      sts16(tp + T_O + 2 * (-64 - l), v1); sts16(tp + T_O + 2 * (-65 - l), v1 >> 16);
    }
    float4 o = lds4f(ob + 1024 + lane * 16);
    uint32_t v0 = pack2(acc[4][0] + o.x, acc[4][1] + o.y), v1 = pack2(acc[4][2] + o.z, acc[4][3] + o.w);
    const int x = 32 * t + g - 1;
    if (lane == 0) { sts16(tp + T_E - 2 * (X_5 + 63), v0); sts16(tp + T_O - 2 * (X_5 + 63), v0); sts1(tp + T_K, prmt(v0, v0, 0x1010)); }
    else sts16(tp + T_C - 2 * x, v0);
    sts16(tp + T_C - 2 * (x + 16), v0 >> 16);
    sts16(tp + T_C - 2 * (x + 8), v1);
    sts16(tp + T_C - 2 * (x + 24), v1 >> 16);
    if (lane == 0) sts16(tp + T_C - 2 * 127, pack2(k2048 + __uint_as_float(lds1(ob + 1536)), 0.f));
  } else {
    float4 o2 = lds4f(ob + lane * 16), o3 = lds4f(ob + 512 + lane * 16);
    uint32_t v0 = pack2(acc[2][0] + o2.x, acc[2][1] + o2.y), v1 = pack2(acc[2][2] + o2.z, acc[2][3] + o2.w);
    const int l0 = 256 + 128 * (t >> 1) + 4 * (t & 1) + 8 * g;
    if (lane != 0) { sts16(tp + T_E + 2 * (1 - l0), v0); sts16(tp + T_O + 2 * (1 - l0), v0); }
    sts16(tp + T_E + 2 * (0 - l0), v0); sts16(tp + T_O + 2 * (0 - l0), v0);
    sts16(tp + T_E + 2 * (-1 - l0), v0); sts16(tp + T_O + 2 * (-1 - l0), v0);
    sts16(tp + T_E + 2 * (-2 - l0), v0 >> 16); sts16(tp + T_O + 2 * (-2 - l0), v0 >> 16);
    sts16(tp + T_E + 2 * (-63 - l0), v1); sts16(tp + T_O + 2 * (-63 - l0), v1);
    sts16(tp + T_E + 2 * (-64 - l0), v1); sts16(tp + T_O + 2 * (-64 - l0), v1);
    sts16(tp + T_E + 2 * (-65 - l0), v1); sts16(tp + T_O + 2 * (-65 - l0), v1);
    sts16(tp + T_E + 2 * (-66 - l0), v1 >> 16); sts16(tp + T_O + 2 * (-66 - l0), v1 >> 16);
    uint32_t w0 = pack2(acc[3][0] + o3.x, acc[3][1] + o3.y), w1 = pack2(acc[3][2] + o3.z, acc[3][3] + o3.w);
    const int x = 16 * t + g;
    if (lane == 0) {
      const uint32_t k = prmt(w0, w0, 0x1010);
      sts1(tp + T_E - 2 * 514, k); sts1(tp + T_E - 2 * 512, k);
      sts16(tp + T_O - 2 * 514, k); sts1(tp + T_O - 2 * 513, k); sts16(tp + T_O - 2 * 511, k);
    } else { sts16(tp + T_E - 2 * (X_5 - 1 + x), w0); sts16(tp + T_O - 2 * (X_5 - 1 + x), w0); }
    sts16(tp + T_E - 2 * (X_3 + x), w0 >> 16); sts16(tp + T_O - 2 * (X_3 + x), w0 >> 16);
    sts16(tp + T_E - 2 * (X_5 + 7 + x), w1); sts16(tp + T_O - 2 * (X_5 + 7 + x), w1);
    sts16(tp + T_E - 2 * (X_3 + 8 + x), w1 >> 16); sts16(tp + T_O - 2 * (X_3 + 8 + x), w1 >> 16);
  }
}

DEV bool bad8(const uint4& v) { return min(v.x, v.z) == 0u; }
DEV uint32_t uchunk(uint32_t reg, int x) { return reg + R_U + (x ^ ((x >> 3) & 3)) * 16; }
DEV uint32_t& xword(uint4 (&x)[2], int e, int tp) { uint4& v = x[tp >> 1]; return tp & 1 ? (e ? v.w : v.z) : (e ? v.y : v.x); }

DEV void sload(const Params& P, int c, int j, int layer, uint4 (&s)[2][2]) {
  const uint4* st = &SCR->SR[layer][c >> 4][opq(j)];
  mbar_wait(B_U, layer);
  PROF(layer ? 25 : 10);
#pragma unroll
  for (int z = 0; z < 4; ++z) s[z >> 1][z & 1] = ldr4(st + z * 128);
}
DEV void uload(const Params& P, int c, int j, int layer, uint4 (&x)[2][2][2], uint4 (&s)[2][2]) {
  j = opq(j);
  const uint4* st = &SCR->SR[layer][c >> 4][j];
  const int o0 = 2 * j + ((j >> 2) & 1), o1 = o0 ^ 1;
#pragma unroll
  for (int z = 0; z < 4; ++z) { uint4& v = s[z >> 1][z & 1]; ldr4_if(v, st + z * 128, bad8(v)); }
  PROF(layer ? 26 : 11);
  mbar_wait(B_E, layer);
#pragma unroll
  for (int z = 0; z < 8; ++z) x[z >> 2][(z >> 1) & 1][z & 1] = lds4(SM_X + 16 * (z & 1 ? o1 : o0) + (z >> 1) * 4096);
  PROF(layer ? 27 : 14);
  for (int it = 0;; ++it) {
    uint32_t m = ~0u;
#pragma unroll
    for (int z = 0; z < 4; ++z) { const uint4& v = s[z >> 1][z & 1]; m = min(m, min(v.x, v.z)); }
#pragma unroll
    for (int z = 0; z < 8; ++z) { const uint4& v = x[z >> 2][(z >> 1) & 1][z & 1]; m = min(m, min(v.x, v.z)); }
    if (!RARE(__any_sync(0xffffffffu, m == 0))) break;
#pragma unroll
    for (int z = 0; z < 4; ++z) { uint4& v = s[z >> 1][z & 1]; ldr4_if(v, st + z * 128, bad8(v)); }
#pragma unroll
    for (int z = 0; z < 8; ++z) {
      uint4& v = x[z >> 2][(z >> 1) & 1][z & 1];
      ldr4_if(v, &SCR->XG[layer][c * 1024 + (opq(o0) ^ (z & 1)) + (z >> 1) * 256], bad8(v));
    }
    spin_guard(it);
  }
  PROF(4 + 12 * layer);
}
DEV void uprep(int j, int k, uint4 (&x)[2][2], uint4 (&s)[2], uint32_t (&u)[4][4]) {
  const uint32_t ua = uchunk(0, opq(j)) + k * 2048;
#pragma unroll
  for (int chl = 0; chl < 4; ++chl) {
#pragma unroll
    for (int tp = 0; tp < 4; ++tp) u[chl][tp] = hmul2(hsub2(xword(x[chl >> 1], chl & 1, tp), xword(s, 1, tp)), xword(s, 0, tp));
    sts4(ua + region(chl), u[chl][0], u[chl][1], u[chl][2], u[chl][3]);
  }
}

template <bool FULL> DEV void box_unit(uint32_t reg, int s, const uint2& a, const uint4& b, const uint32_t (&d)[4], uint32_t (&pv)[4]) {
  const uint32_t u[9] = {a.x, a.y, b.x, b.y, b.z, b.w, d[0], d[1], d[2]};
  uint32_t v[8], p[8];
#pragma unroll
  for (int j = 0; j < 8; ++j) { v[j] = prmt(u[j], u[j + 1], 0x5432); p[j] = hadd2(u[j], v[j]); }
  const uint32_t o = reg + s * 16;
  uint32_t x[4], y[4];
#pragma unroll
  for (int j = 0; j < 4; ++j) { x[j] = hadd2(hadd2(p[1 + j], p[2 + j]), u[3 + j]); y[j] = hadd2(v[3 + j], p[4 + j]); pv[j] = p[4 + j]; }
  sts4(o + R_X5, x[0], x[1], x[2], x[3]);
  sts4(o + R_X3, y[0], y[1], y[2], y[3]);
  if (FULL) {
#pragma unroll
    for (int j = 0; j < 4; ++j) { y[j] = hadd2(hadd2(v[j], v[3 + j]), x[j]); x[j] = hadd2(hadd2(u[j], u[4 + j]), y[j]); }
    const bool od = s & 1;
    sts4(o + R_BO, od ? y[0] : x[0], od ? y[1] : x[1], od ? y[2] : x[2], od ? y[3] : x[3]);
    sts4(o + R_BE + 16, od ? x[0] : y[0], od ? x[1] : y[1], od ? x[2] : y[2], od ? x[3] : y[3]);
  }
}
DEV void box_full(int j, uint32_t (&u)[4][4], uint32_t zero) {
  const uint32_t a2 = uchunk(8, j - 2), a1 = uchunk(0, j - 1);
  uint2 a[4]; uint4 b[4];
#define HALO(n) { a[n] = lds2(region(n) + a2); b[n] = lds4(region(n) + a1); }
  HALO(0) HALO(1)
  split(zero);
#pragma unroll
  for (int chl = 0; chl < 4; ++chl) {
    const uint32_t d[4] = {u[chl][0], u[chl][1], u[chl][2], u[chl][3]};
    box_unit<true>(region(chl), j, a[chl], b[chl], d, u[chl]);
    if (chl < 2) HALO(chl + 2)
    if (chl != 2) {
      fence_async_smem();
      if (chl == 3) bar_arrive(NB_B + 2, 288);
      bar_arrive(NB_B + chl, 288);
    }
    if (chl == 0) PROF(31);
  }
#undef HALO
}
DEV void box_help(int e, int lane) {
  bar_sync(NB_H, 192);
#pragma unroll 1
  for (int n = 0; n < 4; ++n) {
    const int chl = e + (n & 2), s = 128 + 32 * (n & 1) + lane;
    const uint32_t reg = region(chl);
    const uint4 d = lds4(uchunk(reg, s));
    const uint32_t u[4] = {d.x, d.y, d.z, d.w};
    uint32_t v[4];
    box_unit<false>(reg, s, lds2(uchunk(reg, s - 2) + 8), lds4(uchunk(reg, s - 1)), u, v);
    if (n & 1) { fence_async_smem(); bar_arrive(NB_B + chl, 288); }
  }
}

DEV uint4 hadd8(const uint4& a, const uint4& b) { return make_uint4(hadd2(a.x, b.x), hadd2(a.y, b.y), hadd2(a.z, b.z), hadd2(a.w, b.w)); }
DEV void conv_out(int c, int j, int chl, uint4 (&x)[2][2][2], const uint32_t (&v)[4], uint4* XF, uint32_t zero) {
  const int rho = chl >> 1, e = chl & 1;
  const uint32_t ua = uchunk(region(chl), j), fa = region(chl) + R_X5 + j * 16, ha = region(chl) + R_X3 + (j & 1) * 1088 + (j >> 1) * 16;
  const int m8 = ((j & 4) + ((j >> 1) & 1) + 2 * (j & 1)) ^ ((2 * c + e) & 7);
  uint4* xo = XF + (((16 - 2 * (j & 8) + (j >> 4)) * 512 + 256 * rho + 2 * c + e) * 8 + m8);
  bar_sync(NB_Y + e + 7 * rho, 256);
  uint4 y[2], f[2], h[2];
#pragma unroll
  for (int k = 0; k < 2; ++k) {
    y[k] = lds4(ua + k * 2048);
    f[k] = lds4z(ua + k * 2048 + R_BO - R_U, k || j >= 36);
    h[k] = lds4z(fa + k * 2048 - 1024, k || j >= 64);
  }
  const uint32_t q = lds1(SM_TAP + chl * TAP_SZ + T_K);
  const uint4 r = lds4(ha);
  split(zero);
  h[1] = hadd8(h[1], make_uint4(hfma2(q, v[0], r.x), hfma2(q, v[1], r.y), hfma2(q, v[2], r.z), hfma2(q, v[3], r.w)));
#pragma unroll
  for (int k = 0; k < 2; ++k) {
    const uint4 o = hadd8(hadd8(y[k], hadd8(f[k], h[k])), make_uint4(xword(x[k][rho], e, 0), xword(x[k][rho], e, 1), xword(x[k][rho], e, 2), xword(x[k][rho], e, 3)));
    const uint32_t keep = j & 1 ? 0x7632 : 0x5410, k0 = prmt(o.x, o.y, keep), k1 = prmt(o.z, o.w, keep);
    const uint32_t g0 = __shfl_xor_sync(0xffffffffu, prmt(o.x, o.y, keep ^ 0x2222), 1), g1 = __shfl_xor_sync(0xffffffffu, prmt(o.z, o.w, keep ^ 0x2222), 1);
    str4(xo + k * 32768, j & 1 ? g0 : k0, j & 1 ? g1 : k1, j & 1 ? k0 : g0, j & 1 ? k1 : g1);

  }
  if (e) { __syncwarp(); mbar_arrive1(B_RD + rho * 8); }
}

DEV void conv_round(int e, int rho, int w, int lane) {
  const int g = lane >> 2, t = lane & 3, chl = 2 * rho + e;
  const uint32_t reg = region(chl), tp = SM_TAP + chl * TAP_SZ, dr = dlo(reg, 128);
  const uint32_t g0 = tp + ((g & 1) ? T_O : T_E) + 2 * (2 * t - g) - 16;
  const uint32_t ga = g0 - 32 * (w & 1) - 576 * (w >> 1), id = opq(0x3210u);
  float acc[32], f1[24], f2[16];
  uint32_t q[12][4];
  {
    uint32_t qn[18][4];
    qn[0][2] = lds1(ga + 64);
#pragma unroll
    for (int n = 0; n < 18; ++n) {
      const bool nz = n < 15 || w < 2 || (n == 15 && w == 2);
      qn[n][0] = n < 15 ? lds1(ga + 48 - 32 * n) : lds1z(ga + 48 - 32 * n, nz);
      qn[n][1] = n < 15 ? lds1(ga + 32 - 32 * n) : lds1z(ga + 32 - 32 * n, nz);
    }
#pragma unroll
    for (int n = 0; n < 18; ++n) { qn[n][3] = cpy(qn[n][0], id); if (n) qn[n][2] = cpy(qn[n - 1][1], id); }
#pragma unroll
    for (int n = 0; n < 8; ++n) {
      const int i = n & 3;
      const uint32_t a = g0 + 16 - 16 * w - 2 * (n < 4 ? X_5 : X_3) + 16 * i;
      uint32_t (&q1)[4] = q[(n & 4) + (i >> 1)], (&q2)[4] = q[(n & 4) + 2 + (i >> 1)];
      q1[2 * (i & 1)] = lds1z(a, i <= w); q1[2 * (i & 1) + 1] = lds1(a - 64);
      q2[2 * (i & 1)] = cpy(0, id); q2[2 * (i & 1) + 1] = lds1z(a - 128, i >= w);
    }
    const uint32_t gc = tp + T_C - 2 + 4 * (t - g - 8 * w);
#pragma unroll
    for (int kk = 0; kk < 4; ++kk) {
      q[8 + kk][0] = lds1z(gc + 32 * kk, w >= kk); q[8 + kk][2] = lds1z(gc + 32 * kk + 16, w >= kk);
      q[8 + kk][1] = lds1(gc + 32 * kk - 128); q[8 + kk][3] = lds1(gc + 32 * kk - 112);
    }
    PROFD(rho ? 43 : 47, qn[17][2] ^ q[11][3]);
    bar_sync_if(NB_U, NBARU, 1 - rho);
    mbar_arrive1_if(B_V, chl == 1 && w == 0);
    bar_sync_if(NB_T + 1 - e, 256, chl);
    const uint32_t db = dr + (R_U + 32) / 16;
    undef(acc);
    wg_fence();
#pragma unroll
    for (int n = 0; n < 18; ++n) {
      if (n) wg_rs64k<1>(acc, qn[n], db - 2 * n); else wg_rs64k<0>(acc, qn[0], db);
      if (n == 9) wg_commit();
    }
    wg_commit();
  }
  wg_wait<1>();
  PROF(12);
  bar_sync(NB_B + chl, 288);
  const uint32_t d1 = dr + R_X5 / 16, d2 = dr + R_BO / 16;
  undef(f1); undef(f2);
  wg_fence();
#pragma unroll
  for (int n = 0; n < 8; ++n) {
    const uint32_t d = d1 + (n >> 2) * ((R_X3 - R_X5) / 16) + 16 * (n & 1) - 16 * (n & 2);
    if (n) wg_rs48t<1>(f1, q[n], d); else wg_rs48t<0>(f1, q[0], d);
    if (n & 1) { if (n > 1) wg_rs32t<1>(f2, q[8 + (n >> 1)], d2 + 16 * (n >> 1)); else wg_rs32t<0>(f2, q[8], d2); }
  }
  wg_commit();
  wg_wait<1>();
  PROF(13);
  bar_arrive_if(NB_T + e, 256, chl - 3);
  wg_wait<0>();
  PROF(14);
  bar_sync(NB_WG + e, 128);
  {
    const int p = (lane + 9 * (w >> 1)) & 31;
    const uint32_t ya = reg + ((w >> 1) ? R_BO : R_U) + p * 64 + (((2 * (w & 1)) ^ ((p >> 1) & 3)) * 16);
    const uint32_t up = p < lane ? 2048 : 0;
#pragma unroll
    for (int z = 0; z < 4; ++z) {
      const float* a = acc + 16 * (z >> 1) + 2 * (z & 1);
      stsm4t((ya + (up ^ ((z >> 1) * 2048))) ^ ((z & 1) * 16), pack2(a[0], a[1]), pack2(a[4], a[5]), pack2(a[8], a[9]), pack2(a[12], a[13]));
    }
  }
  {
    const uint32_t fa = reg + R_X5 + (8 * w + (lane & 7)) * 16 + (lane >> 3) * 512;
    uint32_t h[6];
#pragma unroll
    for (int p = 0; p < 6; ++p) h[p] = p ? pack2(f1[4 * p] + f1[4 * p - 2], f1[4 * p + 1] + f1[4 * p - 1]) : pack2(f1[0], f1[1]);
    stsm4(fa, h[0], h[1], h[2], h[3]);
    stsm2(fa + 2048, h[4], h[5]);
    stsm4(reg + R_X3 + (lane < 16 ? 1088 : 0) + (8 * w + (lane & 7) + 4 * (lane & 8)) * 16, pack2(f2[0], f2[1]), pack2(f2[2] + f2[4], f2[3] + f2[5]),
          pack2(f2[8], f2[9]), pack2(f2[10] + f2[12], f2[11] + f2[13]));
  }
  bar_arrive(NB_Y + e + 7 * rho, 256);
}
constexpr uint32_t FILL = 0xFFFFFFFFu;
template <int N> DEV void fixo(uint4 (&A)[N], const uint4* p) {
#pragma unroll 1
  for (int it = 0; it < SPIN_LIMIT; ++it) {
    uint32_t m = A[0].x;
#pragma unroll
    for (int k = 1; k < N; ++k) m = max(m, A[k].x);
    if (__all_sync(0xffffffffu, m != FILL)) break;
#pragma unroll
    for (int k = 0; k < N; ++k) ldr4_if(A[k], p + k * 32, A[k].x == FILL);
  }
}
DEV bool rows_nan(float a, float b) {
  return __any_sync(0xffffffffu, a != a || b != b);
}
template <int N> DEV void slow_step(float (&acc)[N], float a0, float a1, const uint16_t* wr, uint32_t zero) {
#pragma unroll
  for (int j = 0; j < N / 4; ++j) {
    const uint32_t v = __ldg((const uint32_t*)(wr + (j >> 3) * 512 + 8 * (j & 7)));
    acc[4 * j] += a0 * bflo(v); acc[4 * j + 1] += a0 * bfhi(v); acc[4 * j + 2] += a1 * bflo(v); acc[4 * j + 3] += a1 * bfhi(v);
    if ((j & 3) == 3) wr += __float_as_uint(acc[4 * j]) & zero;
  }
}
DEV int res_off(int w, int lane) { return ((lane & 7) + 8 * (lane >> 4)) * 8 + ((2 * (w & 2) + (w & 1) + ((lane >> 2) & 2)) ^ (lane & 7)); }
DEV void res_load(uint32_t (&res)[8][2], uint32_t sa, int w, int lane) {
  const uint32_t a = sa + res_off(w, opq(lane)) * 16;
#pragma unroll
  for (int j = 0; j < 8; j += 2) {
    uint32_t r[4];
    ldsm4t(r, a + j * 1024);
    res[j][0] = r[0]; res[j][1] = r[1]; res[j + 1][0] = r[2]; res[j + 1][1] = r[3];
  }
}

DEV uint32_t after(uint32_t b, const uint32_t (&res)[8][2], uint32_t zero) {
  return b + ((res[0][0] ^ res[2][0] ^ res[4][0] ^ res[6][0]) & zero);
}

DEV void attn_phase(const Params& P, int c, int e, int w, int lane, int layer) {
  lane = opq(lane); c = opq(c);
  const int i = c >> 3, cg = c & 7, J = 16 * e + i, G = 8 * i + 4 - 4 * e + w;
  const int g = lane >> 2, t = lane & 3;
  float acc[96];
  uint32_t res[8][2];
  float2 cs[16];
  float4 st;
  const uint32_t csb = opq(SM_CS + 8 * t);
  {
    const uint32_t sa = SM_A + e * A_E, ba = B_A + 16 * e;
    const uint32_t da = dlo(sa, 8192), db = (SB >> 4) | (512 << 16);
    undef(acc);
#pragma unroll
    for (int j = 0; j < 8; ++j) asm volatile("" : "=r"(res[j][0]), "=r"(res[j][1]));
    mbar_wait(B_WF, layer);
    mbar_wait(ba, 0);
    mbar_wait(B_RD + 8, layer);
    bar_sync_if(NB_T, 256, e);
    PROF(24);
#pragma unroll
    for (int j = 0; j < 4; ++j) {
      if (j == 1) { mbar_wait(ba + 8, 0); PROF(39); }
      wg_fence();
#pragma unroll
      for (int k = 0; k < 4; ++k) {
        if (j | k) wg_ss192<1>(acc, da + j * 512 + k * 128, db + wslot(j) * 512 + k * 128); else wg_ss192<0>(acc, da, db);
        if (j == 3 && k == 1) wg_commit();
      }
      wg_commit();
      if (j == 1 || j == 2) { wg_wait<1>(); mbar_arrive1_if(B_F + 8 * (j - 1), e); }
    }
    wg_wait<1>();
    bar_arrive(NB_T + e, 256);
    wg_wait<0>();
    if (cg < 4) res_load(res, sa + cg * 8192, w, lane);
    mbar_arrive1(after(B_AE + 8 * e, res, P.zero));
    PROF(25);
#pragma unroll 1
    for (uint32_t late = P.zero;; late = 1) {
      if (late) {
        const uint16_t* xr = (const uint16_t*)SCR->XF[layer] + opq(J) * 32768;
        zero(acc);
#pragma unroll 1
        for (int k = 0; k < 512; ++k)
          slow_step(acc, ldnan(xr + k * 64 + ((2 * w) ^ (k & 7)) * 8 + g), ldnan(xr + k * 64 + ((2 * w + 1) ^ (k & 7)) * 8 + g),
                    P.wqkv + (k * 1536 + 64 * cg + 2 * t), P.zero);
        const uint32_t* q = (const uint32_t*)xr + ((64 * cg + g) * 32 + t);
        const int m8 = (2 * (w & 2) + (w & 1)) ^ g;
#pragma unroll 1
        for (int it = 0; it < SPIN_LIMIT; ++it) {
          uint32_t m = 0;
#pragma unroll
          for (int z = 0; z < 16; ++z) { const uint32_t x = ldr1(q + (z >> 1) * 256 + (m8 ^ (2 * (z & 1))) * 4); m = max(m, x); res[z >> 1][z & 1] = movm(x); }
          if (__all_sync(0xffffffffu, m != FILL)) break;
        }
#pragma unroll
        for (int z = 0; z < 16; ++z) cs[z] = lds2f(csb + 256 + z * 32);
      } else {
        mbar_wait(B_CS, 0);
#pragma unroll
        for (int z = 0; z < 16; ++z) cs[z] = lds2f(csb + 256 + z * 32);
        mbar_wait(B_W4, layer);
        mbar_wait(ba, 1);
        bar_sync(NB_T + 1 - e, 256);
        PROF(26);
#pragma unroll
        for (int j = 4; j < 8; ++j) {
          if (j == 5) mbar_wait(ba + 8, 1);
          if (j >= 6) mbar_wait(B_W6 + 8 * (j - 6), layer);
          if (j > 4) PROF(31 + j);
          wg_fence();
#pragma unroll
          for (int k = 0; k < 4; ++k) {
            wg_ss192<1>(acc, da + (j & 3) * 512 + k * 128, db + wslot(j) * 512 + k * 128);
            if (j == 7 && k == 1) wg_commit();
          }
          wg_commit();
          if (j == 5) {
            if (cg >= 4) res_load(res, sa + (cg - 4) * 8192, w, lane);
            wg_wait<1>(); mbar_arrive1_if(B_F + 16, e); PROF(40);
          }

        }
      }
      uint32_t rs = hadd2(res[0][0], res[0][1]);
#pragma unroll
      for (int z = 2; z < 16; ++z) rs = hadd2(rs, res[z >> 1][z & 1]);
      const float rn = bflo(rs) + bfhi(rs);
      wg_wait<1>();
      bar_arrive_if(NB_T, 256, !(e | late));
      mbar_wait(B_ST + 8 * e, layer);
      st = lds4f(SM_STAT + ((4 * e + w) * 8 + g) * 16);
      PROF(34 + layer);
      wg_wait<0>();
      if (!rows_nan(acc[0] + rn, acc[2]) || late) break;
    }
  }
  mbar_arrive1(B_QE);
  PROF(8 + 12 * layer);
  uint32_t Q[4][4], K[4][2][2], V[4][2][2];
  {
#pragma unroll
    for (int z = 0; z < 8; ++z) {
      const float* a = acc + 32 + 4 * z; const float* b = acc + 64 + 4 * z;
      K[z >> 1][1][z & 1] = pack2((a[2] - st.z * cs[z].x) * st.w, (a[3] - st.z * cs[z].y) * st.w);
      V[z >> 1][1][z & 1] = movm(pack2((b[2] - st.z * cs[8 + z].x) * st.w, (b[3] - st.z * cs[8 + z].y) * st.w));
    }
    const int hop = (G >> 1) & 3;
    const uint32_t kv = SM_KV + (2 * hop + (w & 1)) * 2048 + lane * 16;
    uint4* h = SCR->H[layer] + (c * 256 + (w & 1) * 128 + lane);
    if (hop == 3) {
#pragma unroll
      for (int z = 0; z < 4; ++z) str4(h + 2048 + z * 32, K[z][1][0], K[z][1][1], V[z][1][0], V[z][1][1]);
    } else {
      mbar_wait(B_F + 16, layer);
#pragma unroll
      for (int z = 0; z < 4; ++z) sts4(kv + z * 512, K[z][1][0], K[z][1][1], V[z][1][0], V[z][1][1]);
      bar_arrive(NB_B + hop, 128);
    }
    PROF(42);
    uint4 hv[4];
#pragma unroll
    for (int z = 0; z < 4; ++z) { hv[z] = make_uint4(0, 0, 0, 0); ldr4_if(hv[z], h + z * 32, G >= 2 && hop == 0); }
#pragma unroll
    for (int z = 0; z < 8; ++z) {
      const float* a = acc + 32 + 4 * z; const float* b = acc + 64 + 4 * z;
      K[z >> 1][0][z & 1] = pack2((a[0] - st.x * cs[z].x) * st.y, (a[1] - st.x * cs[z].y) * st.y);
      V[z >> 1][0][z & 1] = movm(pack2((b[0] - st.x * cs[8 + z].x) * st.y, (b[1] - st.x * cs[8 + z].y) * st.y));
    }
#pragma unroll
    for (int z = 0; z < 8; ++z) {
      const float2 cq = lds2f(csb + z * 32);
      const float* a = acc + 4 * z;
      Q[z >> 1][2 * (z & 1)] = pack2(a[0] - st.x * cq.x, a[1] - st.x * cq.y);
      Q[z >> 1][2 * (z & 1) + 1] = pack2(a[2] - st.z * cq.x, a[3] - st.z * cq.y);
    }
    PROF(27);
    const bool p0 = 2 * t > g, p1 = 2 * t + 1 > g, first = G < 2;
    float s[4][4], mx[4][2];
#pragma unroll
    for (int z = 0; z < 4; ++z) {
      float S[4];
      mma16z(s[z], Q[z][0], Q[z][1], Q[z][2], Q[z][3], K[z][0][0], K[z][0][1]);
      mma16z(S, Q[z][0], Q[z][1], Q[z][2], Q[z][3], K[z][1][0], K[z][1][1]);
      s[z][2] = p0 ? s[z][2] : S[2]; s[z][3] = p1 ? s[z][3] : S[3];
    }
    const float sc0 = st.y * (0.25f * 1.4426950408889634f), sc1 = st.w * (0.25f * 1.4426950408889634f);
    uint32_t pw[4][2];
#pragma unroll
    for (int r = 1; r >= 0; --r) {
      if (r == 0) {
        if (hop) {
          bar_sync(NB_B + hop - 1, 128);
#pragma unroll
          for (int z = 0; z < 4; ++z) hv[z] = lds4(kv - 4096 + z * 512);
        } else fixo(hv, h);
        PROFD(41, hv[3].x);
#pragma unroll
        for (int z = 0; z < 4; ++z) {
          float S[4];
          mma16z(S, Q[z][0], Q[z][1], Q[z][2], Q[z][3], hv[z].x, hv[z].y);
          if (first) S[0] = S[1] = __uint_as_float(0xFF800000u);
          s[z][0] = p0 ? S[0] : s[z][0]; s[z][1] = p1 ? S[1] : s[z][1];
        }
      }
#pragma unroll
      for (int z = 0; z < 4; ++z) mx[z][r] = fmaxf(s[z][2 * r], s[z][2 * r + 1]);
#pragma unroll
      for (int o = 1; o < 3; ++o)
#pragma unroll
        for (int z = 0; z < 4; ++z) mx[z][r] = fmaxf(mx[z][r], __shfl_xor_sync(0xffffffffu, mx[z][r], o));
#pragma unroll
      for (int z = 0; z < 4; ++z) pw[z][r] = pack2(ex2((s[z][2 * r] - mx[z][r]) * (r ? sc1 : sc0)), ex2((s[z][2 * r + 1] - mx[z][r]) * (r ? sc1 : sc0)));
    }
    mbar_wait(layer ? B_N : B_Z, layer);
    const uint32_t M = (p0 ? 0xFFFFu : 0u) | (p1 ? 0xFFFF0000u : 0u);
    uint4* O = SCR->O + ((J * 8 + cg) * 512 + (2 * (w & 2) + (w & 1)) * 64 + t * 8 + g);
#pragma unroll
    for (int h2 = 0; h2 < 2; ++h2) {
      uint32_t ow[2][4];
#pragma unroll
      for (int z = 0; z < 2; ++z) {
        const int n = 2 * h2 + z;
        const uint32_t w0 = pw[n][0], w1 = pw[n][1];
        float sm[4] = {0.f, 0.f, 0.f, 0.f}, Oa[2][4];
        mma8(sm, w0, w1, 0x3F803F80u);
        mma16z(Oa[0], w0 & ~M, w1 & M, 0u, w1 & ~M, V[n][0][0], V[n][1][0]); mma8(Oa[0], w0 & M, 0u, hv[n].z);
        mma16z(Oa[1], w0 & ~M, w1 & M, 0u, w1 & ~M, V[n][0][1], V[n][1][1]); mma8(Oa[1], w0 & M, 0u, hv[n].w);
        const float i0 = rcp(sm[0]), i1 = rcp(sm[2]);
#pragma unroll
        for (int d = 0; d < 2; ++d) { ow[0][2 * z + d] = pack2(Oa[d][0] * i0, Oa[d][1] * i0); ow[1][2 * z + d] = pack2(Oa[d][2] * i1, Oa[d][3] * i1); }
      }
#pragma unroll
      for (int hi = 0; hi < 2; ++hi) str4(O + hi * 128 + h2 * 32, ow[hi][0], ow[hi][1], ow[hi][2], ow[hi][3]);
    }
  }
  str1(SCR->OF[layer] + (J * 32 + cg * 4 + w), 1);
  mbar_arrive1(B_AT + 8 * e + (lds1(csb) & P.zero));
  PROF(9 + 12 * layer);
  float ac[32];
  undef(ac);
  const uint32_t so = SM_O + e * O_E;
  {
    const uint32_t bo = B_O + 32 * e;
    const uint32_t dw = (SM_WO >> 4) | (512 << 16), da = dlo(so, 512);
    mbar_wait(B_WO, layer);
#pragma unroll
    for (int j = 0; j < 4; ++j) {
      mbar_wait(bo + 8 * j, layer);
      if (j == 0) { PROF(32 + layer); mbar_wait(B_AT + 8, layer); }
      wg_fence();
#pragma unroll
      for (int k = 8 * j; k < 8 * j + 8; ++k) {
        const uint32_t a = da + (k >> 2) * 512 + (k & 3) * 8, b = dw + (k & 3) * 1024 + (k >> 2) * 128;
        if (k) wg_ss64<1>(ac, a, b); else wg_ss64<0>(ac, a, b);
      }
      wg_commit();
    }
#pragma unroll 1
    for (uint32_t late = P.zero;; late = 1) {
      if (late) {
        const uint16_t* op = (const uint16_t*)(SCR->O + (J * 4096 + w * 128 + g));
        wg_wait<0>();
        zero(ac);
#pragma unroll 1
        for (int k = 0; k < 512; ++k) {
          const uint16_t* q = op + (k >> 6) * 4096 + (k & 56) * 8 + (k & 7);
          slow_step(ac, ldnan(q), ldnan(q + 512), P.wo + (((k & ~31) + 4 * (k & 6) + ((k >> 2) & 6) + (k & 1)) * 512 + 64 * cg + 2 * t), P.zero);
        }
      }
      wg_wait<0>();
      if (!rows_nan(ac[0], ac[2]) || late) break;
    }
  }
  PROF(10 + 12 * layer);
#pragma unroll
  for (int j = 0; j < 8; ++j) {
    res[j][0] = hadd2(res[j][0], pack2(ac[4 * j], ac[4 * j + 1]));
    res[j][1] = hadd2(res[j][1], pack2(ac[4 * j + 2], ac[4 * j + 3]));
  }
  if (layer == 0) {
    const float4 s = gram(res, g);
    str4_if(&SCR->PS[(G * 8 + cg) * 8 + g], nzmap(__float_as_uint(s.x)), __float_as_uint(s.y), __float_as_uint(s.z), __float_as_uint(s.w), t == (g >> 1));
    const int xo = (32 * (cg & 3) + t) * 2048 + (cg >> 2) * 512 + xg_off(G, g);
#pragma unroll
    for (int j = 0; j < 8; ++j) {
      str2((uint2*)SCR->XG[1] + (xo + j * 8192), nzmap(prmt(res[j][0], res[j][1], 0x5410)), prmt(res[j][0], res[j][1], 0x7632));
    }
    __syncwarp();
    mbar_arrive1(B_ED + 8 * e);
  } else {
    const uint32_t stg = so + w * 2048;
    const int row = (lane & 7) + 8 * ((lane >> 3) & 1);
    bar_sync(NB_WG + e, 128);
#pragma unroll
    for (int j = 0; j < 8; j += 2)
      stsm4(stg + row * 128 + (((j + (lane >> 4)) ^ (row & 7)) * 16), res[j][0], res[j][1], res[j + 1][0], res[j + 1][1]);
    __syncwarp();
#pragma unroll
    for (int k = 0; k < 4; ++k) {
      const int r = 4 * k + (lane >> 3);
      const uint4 v = lds4(stg + r * 128 + (((lane & 7) ^ (r & 7)) * 16));
      stw4(P.out + ((16 * G + 2 * (lane >> 3)) * 512 + 64 * cg + 8 * (lane & 7)) + ((k & 1) * 8 + (k >> 1)) * 512, v.x, v.y, v.z, v.w);
    }
  }
  PROF(11 + 12 * layer);
}

DEV void col_sums(const Params& P, int c, int wa, int lane) {
  const int i = c >> 3, cg = c & 7;
  uint4 wv[8];
#pragma unroll
  for (int k = 0; k < 8; ++k) wv[k] = ldnc4(P.wqkv + ((32 * i + (lane >> 3)) * 1536 + wa * 512 + 64 * cg + 8 * (lane & 7)) + 4 * k * 1536);
  float cs[8];
  zero(cs);
#pragma unroll
  for (int k = 0; k < 8; ++k) {
    cs[0] += bflo(wv[k].x); cs[1] += bfhi(wv[k].x); cs[2] += bflo(wv[k].y); cs[3] += bfhi(wv[k].y);
    cs[4] += bflo(wv[k].z); cs[5] += bfhi(wv[k].z); cs[6] += bflo(wv[k].w); cs[7] += bfhi(wv[k].w);
  }
  const bool b4 = lane & 16, b3 = lane & 8;
#pragma unroll
  for (int k = 0; k < 4; ++k) cs[k] = (b4 ? cs[k + 4] : cs[k]) + __shfl_xor_sync(0xffffffffu, b4 ? cs[k] : cs[k + 4], 16);
#pragma unroll
  for (int k = 0; k < 2; ++k) cs[k] = (b3 ? cs[k + 2] : cs[k]) + __shfl_xor_sync(0xffffffffu, b3 ? cs[k] : cs[k + 2], 8);
  str2((uint2*)SCR->CS + (i * 768 + wa * 256 + 32 * cg + 4 * (lane & 7) + (lane >> 3)), nzmap(__float_as_uint(cs[0])), __float_as_uint(cs[1]));
}
DEV void col_gather(const Params& P, int c, int wa, int lane) {
  const uint2* p = (const uint2*)SCR->CS + (wa * 256 + 32 * (c & 7) + lane);
#pragma unroll 1
  for (int it = 0;; ++it) {
    float a = 0.f, b = 0.f;
    uint32_t m = ~0u;
#pragma unroll
    for (int k = 0; k < 16; ++k) { const uint2 q = ldr2(p + k * 768); m = min(m, q.x); a += __uint_as_float(q.x); b += __uint_as_float(q.y); }
    if (__all_sync(0xffffffffu, m != 0u)) { sts2f(SM_CS + wa * 256 + lane * 8, a, b); break; }
    spin_guard(it);
  }
  __syncwarp();
  mbar_arrive1(B_CS);
}

DEV void aux_prologue(const Params& P, int c, int wa, int lane, uint4 (&s0)[2][2]) {
  const int g = lane >> 2, t = lane & 3, G = stat_group(c);
  {
    uint32_t w[16][2];
    const uint16_t* row = P.x0 + ((16 * G + 2 * g) * 512 + 128 * wa + 8 * t);
    bar_sync(NB_Y, 384);
    __nanosleep(100);
#pragma unroll
    for (int z = 0; z < 8; ++z) {
      const uint4 v = ldw4(row + (z & 1) * 512 + (z >> 1) * 32);
      const int o = 4 * (z >> 1);
      w[o][z & 1] = v.x; w[o + 1][z & 1] = v.y; w[o + 2][z & 1] = v.z; w[o + 3][z & 1] = v.w;
    }
    PROF(34);
    PROFD(35, w[0][0]);
    PROFD(36, w[15][1]);
    uint2* xo = (uint2*)SCR->XG[0] + ((64 * (wa & 1) + 4 * t) * 2048 + (wa >> 1) * 512 + xg_off(G, g));
#pragma unroll
    for (int n = 0; n < 16; ++n) str2(xo + (16 * (n >> 2) + (n & 3)) * 2048, nzmap(prmt(w[n][0], w[n][1], 0x5410)), prmt(w[n][0], w[n][1], 0x7632));
    const float4 s = gram(w, g);
    if (t == (g >> 1)) sts4f(SM_MISC + (wa * 8 + g) * 16, s.x, s.y, s.z, s.w);
    bar_arrive(NB_P0, 192);
  }
  PROF(2);
  if (lane == 0)
    asm volatile("cp.async.bulk.prefetch.L2.global [%0],4096;" :: "l"(wa < 3 ? P.wqkv + (3 * c + wa) * 2048 : P.wo + c * 2048) : "memory");
  bar_sync(NB_Y + 1, 256);
  sload(P, c, 32 * wa + lane, 0, s0);
}

DEV void stat_part(const Params& P, int c, int wa, int lane, int layer, int h, float (&v)[2]) {
  lane = opq(lane);
  const int e = wa >> 1;
  uint32_t x[4][4];
  mbar_wait(B_A + 16 * e, h); mbar_wait(B_A + 16 * e + 8, h);
#pragma unroll
  for (int k = 0; k < 4; ++k) ldsm4t(x[k], SM_A + e * A_E + (128 * (wa & 1) + lane) * 128 + (((c ^ lane) & 7) * 16) + k * 4096);
  float s[4] = {0.f, 0.f, 0.f, 0.f};
#pragma unroll
  for (int k = 0; k < 16; ++k) { const float a = bflo(x[k >> 2][k & 3]), b = bfhi(x[k >> 2][k & 3]); s[0] += a; s[1] += a * a; s[2] += b; s[3] += b * b; }
  s[0] += s[2]; s[1] += s[3];
  if (RARE(rows_nan(s[1], s[1]))) {
    const uint16_t* q = (const uint16_t*)(SCR->XF[layer] + ((32 * e + 2 * (c >> 3) + h) * 2048 + (wa & 1) * 1024)) + (lane >> 2);
    s[0] = s[1] = 0.f;
#pragma unroll 1
    for (int k = 0; k < 32; ++k) {
      const int r = 2 * (lane & 3) + (k & 1);
      const float a = ldnan(q + ((k >> 1) * 8 + r) * 64 + ((c ^ r) & 7) * 8);
      s[0] += a; s[1] += a * a;
    }
  }
  v[0] += s[0]; v[1] += s[1];
  __syncwarp();
}
DEV void stat_finish(const Params& P, int c, int wa, int lane, int layer, float (&v)[2]) {
  lane = opq(lane);
  const bool b = lane & 1;
  const float s = (b ? v[1] : v[0]) + __shfl_xor_sync(0xffffffffu, b ? v[0] : v[1], 1);
  str1((uint32_t*)SCR->ST[layer] + ((128 * (wa >> 1) + c) * 64 + (wa & 1) * 32 + lane), nzmap(__float_as_uint(s)));
  const uint4* sp = SCR->ST[layer] + ((128 * (wa >> 1) + (c & ~7) + 4 * (wa & 1) + (lane >> 3)) * 16 + (lane & 7));
  uint4 x, y;
  for (int it = 0;; ++it) {
    x = ldr4(sp); y = ldr4(sp + 8);
    if (__all_sync(0xffffffffu, min(min(min(x.x, x.y), min(x.z, x.w)), min(min(y.x, y.y), min(y.z, y.w))) != 0u)) break;
    spin_guard(it);
  }
  const uint32_t q = ln_sums((__uint_as_float(x.x) + __uint_as_float(x.z)) + (__uint_as_float(y.x) + __uint_as_float(y.z)),
                             (__uint_as_float(x.y) + __uint_as_float(x.w)) + (__uint_as_float(y.y) + __uint_as_float(y.w)));
  sts2f(SM_STAT + (16 * wa + (lane >> 4) * 8 + (lane & 7)) * 16 + (lane & 8), bflo(q), rcp(bfhi(q)));
  __syncwarp();
  mbar_arrive1(B_ST + 4 * (wa & 2));
}

DEV void nan_source(uint32_t a, int lane) {
#pragma unroll
  for (int k = 0; k < 4; ++k) sts4(a + k * 512 + lane * 16, FILL, FILL, FILL, FILL);
  fence_async_smem();
  __syncwarp();
}
DEV void load_a(const Params& P, int J, int e, int layer, int h) {
  const uint4* src = SCR->XF[layer] + (2 * J + h) * 2048;
  const uint32_t dst = SM_A + e * A_E, b = B_A + 16 * e;
  mbar_expect1(b, 8192); bulk(dst, src, 8192, b);
  mbar_expect1(b + 8, 24576); bulk(dst + 8192, src + 512, 24576, b + 8);
}
DEV void load_o(const Params& P, int c, int e, int layer, int lane) {
  const int J = 16 * e + (c >> 3);
  mbar_wait(B_AT + 8 * e, layer);
  if (!e) pause(260);
#pragma unroll 1
  for (int it = 0;; ++it) {
    spin_guard(it);
    if (__all_sync(0xffffffffu, ldr1(SCR->OF[layer] + J * 32 + lane) != 0u)) break;
  }
#pragma unroll
  for (int j = 0; j < 4; ++j) bulk(SM_O + e * O_E + 16384 * j, SCR->O + (J * 4096 + j * 1024), 16384, B_O + 32 * e + 8 * j);
  PROF(9 + e + 12 * layer);
}

__global__ void __launch_bounds__(NTHR, 1)
fused_kernel(const __grid_constant__ Params P, const __grid_constant__ CUtensorMap mapW, const __grid_constant__ CUtensorMap mapWo,
             const __grid_constant__ CUtensorMap mapX) {
  extern __shared__ __align__(1024) uint8_t smem_raw[];
  const int warp = __shfl_sync(0xffffffffu, threadIdx.x >> 5, 0), lane = threadIdx.x & 31;
  uint32_t smid; asm volatile("mov.u32 %0,%%smid;" : "=r"(smid));
  const uint32_t* pw = (const uint32_t*)&P + threadIdx.y;
  const int role = P.role[(smid >> 1) + threadIdx.y] + (smid & 1) + (pw[0] & pw[12]);
  const int c = __shfl_sync(0xffffffffu, pw[1] ? role : blockIdx.x, 0);
  if (c >= 128) {
#pragma unroll 1
    for (int k = (c - 128) * NTHR + threadIdx.x; k < 131072; k += P.spare * NTHR) str4(SCR->XG[1] + k, 0, 0, 0, 0);
    __threadfence();
    __syncthreads();
    if (warp == 0) { cnt_wait(SCR->C + 1, lane); cnt_add1(SCR->C + 6); }
    __syncthreads();
#pragma unroll 1
    for (int k = (c - 128) * NTHR + threadIdx.x; k < 131072; k += P.spare * NTHR) str4(SCR->XG[0] + k, 0, 0, 0, 0);
    return;
  }
#define DONE() do {} while (0)
  const int cg = c & 7;
  if (warp < 8) {
    PROF(46);
    kgen(P, c, warp, lane);
    bar_sync(0, 384);
    PROF(1);
#pragma unroll 1
    for (int layer = 0; layer < 2; ++layer) {
#pragma unroll 1
      for (int rho = 0; rho < 2; ++rho) {
        const int wz = warp + ((rho + layer) & P.zero);
        conv_round(wz >> 2, rho, wz & 3, lane_id());
        PROF(6 + rho + 12 * layer);
      }
      const int z = layer & P.zero;
      attn_phase(P, c + z, (warp + z) >> 2, (warp + z) & 3, lane_id(), layer);
    }
    DONE();
  } else if (warp < 12) {
    asm volatile("setmaxnreg.dec.sync.aligned.u32 %0;" :: "n"(REG_AUX));
    uint4 x[2][2][2], s[2][2];
    aux_prologue(P, c, warp - 8, lane, s);
    PROF(1);
    const int c0 = c;
#pragma unroll 1
    for (int layer = 0;; ++layer) {
      const int c = c0 + (layer & P.zero), wa = warp - 8 + (layer & P.zero);
#define lane lane_id()
#define j (32 * wa + lane_id())
      {
        const uint32_t za = region(wa) + lane * 16 - 512;
        sts4(za + R_U, 0, 0, 0, 0); sts4(za + R_X5, 0, 0, 0, 0); sts4(za + R_X3, 0, 0, 0, 0);
      }
      if (lane == 0) sts4(region(wa) + R_BE, 0, 0, 0, 0);
      uint32_t u[4][4];
      uload(P, c, j, layer, x, s);
      uprep(j, 1, x[1], s[1], u);
      uprep(j, 0, x[0], s[0], u);
      fence_async_smem();
      bar_arrive(NB_U, NBARU);
      bar_sync(NB_H, 192);
      PROF(5 + 12 * layer);
      box_full(j, u, P.zero);
      PROF(3 + 12 * layer);
      mbar_wait(B_Z, 0);
      conv_out(c, j, 0, x, u[0], SCR->XF[layer], P.zero);
      PROF(32);
      conv_out(c, j, 1, x, u[1], SCR->XF[layer], P.zero);
      PROF(6 + 12 * layer);
      if (layer == 0 && wa < 3) col_sums(P, c, wa, lane);
      conv_out(c, j, 2, x, u[2], SCR->XF[layer], P.zero);
      PROF(33);
      conv_out(c, j, 3, x, u[3], SCR->XF[layer], P.zero);
      PROF(7 + 12 * layer);
      float v[2];
      zero(v);
#pragma unroll 1
      for (int h = 0; h < 2; ++h) {
        stat_part(P, c, wa, lane, layer, h, v);
        if (h) break;
        mbar_arrive1(B_AE + 4 * (wa & 2));
        if (layer == 0 && wa < 3) col_gather(P, c, wa, lane);
      }
      PROF(9 + 12 * layer);
      stat_finish(P, c, wa, lane, layer, v);
      PROF(8 + 12 * layer);
      if (layer) break;
      sload(P, c, j, 1, s);
#undef lane
#undef j
    }
    DONE();
  } else {
    asm volatile("setmaxnreg.dec.sync.aligned.u32 %0;" :: "n"(REG_PROD));
    if (s2u(smem_raw) != SB) __trap();
#pragma unroll 1
    for (int n = warp - 12; n < 38; n += 4)
      asm volatile("{.reg .pred p; elect.sync _|p,0xffffffff; @p mbarrier.init.shared::cta.b64 [%0],%1;}"
                   :: "r"(SM_BAR + n * 8), "r"(n > 14 ? 1 : (int)(0x322866444444444ull >> (4 * n)) & 15) : "memory");
    fence_async_smem();
    bar_sync(NB_AUX, 128);
    bar_arrive(0, 384); bar_arrive(NB_Y + 1, 256);
    PROF(1);
    if (warp == 12) {
      if (lane == 0) {
        asm volatile("prefetch.tensormap [%0];" :: "l"(&mapW) : "memory");
        asm volatile("prefetch.tensormap [%0];" :: "l"(&mapWo) : "memory");
        asm volatile("prefetch.tensormap [%0];" :: "l"(&mapX) : "memory");
      }
      nan_source(slot(12), lane);
      mbar_wait(B_U, 0);
#pragma unroll 1
      for (int k = 0; k < 8; ++k) tma2_store(&mapX, slot(12), 128 * c, 8 * k);
#pragma unroll 1
      for (int k = 0; k < 4; ++k) bulk_store(SCR->H[k >> 1] + ((c + 8) * 256 + (k & 1) * 128), slot(12), 2048);
#pragma unroll 1
      for (int k = 0; k < 8; ++k) bulk_store(SCR->O + (c * 512 + (k >> 2) * 65536 + (k & 3) * 128), slot(12), 2048);
      bulk_wait();
      mbar_arrive1(B_Z);
      PROF(24);
#pragma unroll 1
      for (int layer = 0; layer < 2; ++layer) {
        mbar_wait(B_V, layer);
        if (layer == 1 && c < 4 && ((0x47 >> lane) & 1)) str1(SCR->C + c * 32 + lane, 0);
        mbar_expect1(B_WF, 4 * 24576);
#pragma unroll
        for (int k = 0; k < 4; ++k) tma3(slot(wslot(k)), &mapW, 64 * cg, 64 * k, 0, B_WF);
        mbar_wait(B_WF, layer);
        mbar_expect1(B_W4, 2 * 24576);
#pragma unroll
        for (int k = 4; k < 6; ++k) tma3(slot(wslot(k)), &mapW, 64 * cg, 64 * k, 0, B_W4);
        bar_sync(NB_AUX, 64);
#pragma unroll 1
        for (int k = 0; k < 2; ++k) {
          mbar_expect1(B_W6 + 8 * k, 24576);
          mbar_wait(B_F + 8 * k, layer);
          tma3(slot(3 * k), &mapW, 64 * cg, 384 + 64 * k, 0, B_W6 + 8 * k);
        }
        mbar_expect1(B_WO, 65536);
        mbar_wait(B_AE + 8, layer);
        nan_source(slot(12), lane);
        uint4* fp = layer ? SCR->O + c * 512 : SCR->XF[1] + c * 512;
#pragma unroll 1
        for (int r = 7; r >= 0; --r) {
          __nanosleep(30);
          if (r >= 4) {
            bulk_store(fp + (r & 3) * 128, slot(12), 2048); bulk_store(fp + 65536 + (r & 3) * 128, slot(12), 2048);
          }
          if (r == 3) { bulk_wait(); __threadfence(); mbar_arrive1(B_N); PROF(9 + 12 * layer); }
          if (r == 1) mbar_wait(B_F + 16, layer);
          tma4(SM_WO + r * 8192, &mapWo, 64 * cg, 0, r >> 1, 32 * (r & 1), B_WO);
        }
        PROF(8 + 12 * layer);
      }
      DONE();
    } else if (warp == 13) {
      const int G = stat_group(c);
#pragma unroll 1
      for (int layer = 0; layer < 2; ++layer) {
        float z[4];
        if (layer == 0) {
          bar_sync(NB_P0, 192);
          const float4 a = lds4f(SM_MISC + lane * 16);
          z[0] = a.x; z[1] = a.y; z[2] = a.z; z[3] = a.w;
        } else {
          mbar_wait(B_ED + 2 * (c & 4), 0);
          uint4* ps = &SCR->PS[G * 64 + lane];
          uint4 a, b;
          for (int it = 0;; ++it) {
            a = ldr4(ps); b = ldr4(ps + 32);
            if (__all_sync(0xffffffffu, min(a.x, b.x) != 0u)) break;
            spin_guard(it);
          }
          z[0] = __uint_as_float(a.x) + __uint_as_float(b.x); z[1] = __uint_as_float(a.y) + __uint_as_float(b.y);
          z[2] = __uint_as_float(a.z) + __uint_as_float(b.z); z[3] = __uint_as_float(a.w) + __uint_as_float(b.w);
        }
#pragma unroll
        for (int o = 8; o < 32; o <<= 1)
#pragma unroll
          for (int k = 0; k < 4; ++k) z[k] += __shfl_xor_sync(0xffffffffu, z[k], o);
        const uint32_t w0 = ln_sums(z[0], z[1]), w1 = ln_sums(z[2], z[3]);
        const uint32_t r = nzmap(pack2(rcp(bfhi(w0)), rcp(bfhi(w1)))), m = prmt(w0, w1, 0x5410);
        uint2* so = (uint2*)&SCR->SR[layer][lane >> 3][sr_off(G, lane)] + (lane & 1);
        str2(so, r, m); str2(so + 4 * 1024, r, m);
        PROF(4 + 12 * layer);
        box_help(0, lane);
        PROF(6 + 12 * layer);
      }
      DONE();
    } else if (warp == 14) {
#pragma unroll 1
      for (int layer = 0; layer < 2; ++layer) {
        if (layer) { mbar_wait(B_N, 0); mbar_wait(B_ED, 0); mbar_wait(B_ED + 8, 0); } else bar_sync(NB_P0, 192);
        cnt_add1(SCR->C + (c >> 5) * 32 + 3 * layer);
        if (layer == 0) bar_arrive(NB_P0 + 1, 288);
        mbar_expect1(B_E, 16384);
        PROF(4 + 12 * layer);
        cnt_wait(SCR->C + 3 * layer, lane);
        mbar_arrive1(B_U);
        bulk(SM_X, SCR->XG[layer] + c * 1024, 16384, B_E);
        PROF(5 + 12 * layer);
        if (layer == 0) {
          mbar_wait(B_Z, 0);
          __threadfence();
          PROF(11);
        }
#pragma unroll 1
        for (int n = 0; n < 4; ++n) {
          if (n == 0) { mbar_wait(B_RD, layer); cnt_add1(SCR->C + (c >> 5) * 32 + 3 * layer + 1); }
          if (!(n & 1)) cnt_wait(SCR->C + 3 * layer + 1 + (n >> 1), lane);
          if (n == 2) PROF(7 + 12 * layer);
          mbar_wait((n & 2 ? B_AE : B_RD) + 8 * (n & 1), layer);
          load_a(P, 16 * (n & 1) + (c >> 3), n & 1, layer, n >> 1);
          bar_arrive_if(NB_AUX, 64, n == 2);
          if (!(n & 1)) PROF(6 + n + 12 * layer);
        }
#pragma unroll 1
        for (int n = 0; n < 8; ++n) mbar_expect1(B_O + 8 * n, 16384);
        if (layer == 0)
          for (int it = 0; ldr1(SCR->C + 6) < P.spare; ++it) spin_guard(it);
        mbar_wait(B_QE, layer);
#pragma unroll 1
        for (int e = 0; e < 2; ++e) load_o(P, c, e, layer, lane);
      }
      DONE();
    }
    if (warp == 15) {
      const int G = stat_group(c);
      str4(&SCR->ST[0][(lane >> 4) * 2048 + c * 16 + (lane & 15)], 0, 0, 0, 0); str4(&SCR->ST[1][(lane >> 4) * 2048 + c * 16 + (lane & 15)], 0, 0, 0, 0);
      if (lane < 4) str4(SCR->OF[lane >> 1] + ((lane & 1) * 512 + c * 4), 0, 0, 0, 0);
      str4(&SCR->PS[G * 64 + lane], 0, 0, 0, 0); str4(&SCR->PS[G * 64 + 32 + lane], 0, 0, 0, 0);
      str4(&SCR->SR[1][lane >> 2][sr_off(G, 2 * lane)], 0, 0, 0, 0);
      if (c < 4 && lane < 3) str1(SCR->C + c * 32 + 3 + lane, 0);
#pragma unroll
      for (int k = 0; k < 3; ++k) str2((uint2*)SCR->CS + ((c >> 3) * 768 + k * 256 + 32 * cg + lane), 0, 0);
      __threadfence();
#pragma unroll 1
      for (int layer = 0; layer < 2; ++layer) {
        PROF(4 + 12 * layer);
        box_help(1, lane);
        if (layer) str4(&SCR->SR[0][lane >> 2][sr_off(G, 2 * lane)], 0, 0, 0, 0);
        mbar_wait(B_RD + 8, layer);
        cnt_add1(SCR->C + (c >> 5) * 32 + 3 * layer + 2);
        if (P.spare == 0) {
#pragma unroll 1
          for (int k = 0; k < 32; ++k) str4(SCR->XG[layer] + (c * 1024 + k * 32 + lane), 0, 0, 0, 0);
        }
      }
      mbar_watch(B_O + 56, 1);
    }
  }
}

typedef CUresult (*EncodeFn)(CUtensorMap*, CUtensorMapDataType, cuuint32_t, void*, const cuuint64_t*, const cuuint64_t*,
                             const cuuint32_t*, const cuuint32_t*, CUtensorMapInterleave, CUtensorMapSwizzle,
                             CUtensorMapL2promotion, CUtensorMapFloatOOBfill);

static int place_roles(uint8_t* role) {
  int dev = 0, nsm = 0;
  cudaGetDevice(&dev);
  cudaDeviceGetAttribute(&nsm, cudaDevAttrMultiProcessorCount, dev);
  if (nsm <= 128 || nsm > 144 || (nsm & 1)) return 0;
  cudaFuncSetAttribute(fused_kernel, cudaFuncAttributeNonPortableClusterSizeAllowed, 1);
  int occ[9] = {0};
  for (int k = 2; k <= 8; ++k) {
    cudaLaunchConfig_t cfg = {};
    cudaLaunchAttribute at[1];
    at[0].id = cudaLaunchAttributeClusterDimension;
    at[0].val.clusterDim.x = 2 * k; at[0].val.clusterDim.y = 1; at[0].val.clusterDim.z = 1;
    cfg.gridDim = dim3(2 * k); cfg.blockDim = dim3(NTHR); cfg.dynamicSmemBytes = SM_TOTAL; cfg.attrs = at; cfg.numAttrs = 1;
    if (cudaOccupancyMaxActiveClusters(&occ[k], fused_kernel, &cfg) != cudaSuccess) { cudaGetLastError(); occ[k] = 0; }
  }
  int n[10];
  n[7] = occ[8]; n[6] = occ[7]; n[5] = occ[6] - 0; n[4] = occ[5];
  n[3] = occ[4] - n[7]; n[1] = occ[2] - n[3] - n[5] - n[7]; n[0] = n[2] = n[1];
  n[8] = occ[3] - n[2] - n[5];
  const int ntpc = nsm / 2;
  int sum = 0;
  bool ok = n[0] > 0 && n[0] <= 8;
  for (int r = 0; r < 9; ++r) { ok = ok && n[r] >= 0 && (r == 0 || n[r] <= n[r - 1]); sum += n[r]; }
  if (!ok || sum > ntpc) { for (int r = 0; r < 9; ++r) n[r] = r < 8 ? 8 : 0; sum = 64; }
  int tp[8][9], cnt[8] = {0}, pool[72], np = 0, id = 0;
  for (int r = 0; r < 9; ++r)
    for (int g = n[0] - n[r]; g < n[0]; ++g) tp[g][cnt[g]++] = id++;
  for (; id < ntpc; ++id) pool[np++] = id;
  int order[72], no = 0;
  for (int g = 0; g < n[0]; ++g) {
    const int full = cnt[g] / 4 * 4;
    for (int k = 0; k < cnt[g]; ++k) { if (k < full) order[no++] = tp[g][k]; else pool[np++] = tp[g][k]; }
  }
  for (int k = 0; k < np; ++k) order[no++] = pool[k];
  for (int k = 0; k < ntpc; ++k) role[order[k]] = 2 * k;
  return nsm;
}

extern "C" void kernel_launch(void* const* d_in, const int* in_sizes, int n_in, void* d_out, int out_size) {
  (void)in_sizes; (void)n_in; (void)out_size;
  static EncodeFn enc = nullptr;
  static uint8_t role[72];
  static int nsm = 0;
  static Scratch* scratch = nullptr;
  if (!enc) {
    void* fn = nullptr;
    cudaDriverEntryPointQueryResult qr;
    cudaGetDriverEntryPoint("cuTensorMapEncodeTiled", &fn, cudaEnableDefault, &qr);
    enc = (EncodeFn)fn;
    cudaFuncSetAttribute(fused_kernel, cudaFuncAttributeMaxDynamicSharedMemorySize, SM_TOTAL);
    nsm = place_roles(role);
    cudaGetSymbolAddress((void**)&scratch, g_S);
  }
  CUtensorMap mW, mWo, mX;
  {
    cuuint64_t dim[3] = {512, 512, 3}, str[2] = {3072, 1024};
    cuuint32_t box[3] = {64, 64, 3}, es[3] = {1, 1, 1};
    enc(&mW, CU_TENSOR_MAP_DATA_TYPE_BFLOAT16, 3, d_in[10], dim, str, box, es, CU_TENSOR_MAP_INTERLEAVE_NONE,
        CU_TENSOR_MAP_SWIZZLE_128B, CU_TENSOR_MAP_L2_PROMOTION_NONE, CU_TENSOR_MAP_FLOAT_OOB_FILL_NONE);
  }
  {
    cuuint64_t dim[4] = {512, 2, 4, 64}, str[3] = {1024, 2048, 8192};
    cuuint32_t box[4] = {64, 2, 1, 32}, es[4] = {1, 1, 1, 1};
    enc(&mWo, CU_TENSOR_MAP_DATA_TYPE_BFLOAT16, 4, d_in[11], dim, str, box, es, CU_TENSOR_MAP_INTERLEAVE_NONE,
        CU_TENSOR_MAP_SWIZZLE_128B, CU_TENSOR_MAP_L2_PROMOTION_NONE, CU_TENSOR_MAP_FLOAT_OOB_FILL_NONE);
  }
  {
    cuuint64_t dim[2] = {16384, 64}, str[1] = {32768};
    cuuint32_t box[2] = {128, 8}, es[2] = {1, 1};
    enc(&mX, CU_TENSOR_MAP_DATA_TYPE_BFLOAT16, 2, scratch->XF[0], dim, str, box, es, CU_TENSOR_MAP_INTERLEAVE_NONE,
        CU_TENSOR_MAP_SWIZZLE_NONE, CU_TENSOR_MAP_L2_PROMOTION_NONE, CU_TENSOR_MAP_FLOAT_OOB_FILL_NONE);
  }
  Params P;
  P.x0 = (const uint16_t*)d_in[0]; P.Are = (const uint16_t*)d_in[1]; P.Aim = (const uint16_t*)d_in[2];
  P.Bre = (const uint16_t*)d_in[3]; P.Bim = (const uint16_t*)d_in[4]; P.Cre = (const uint16_t*)d_in[5];
  P.Cim = (const uint16_t*)d_in[6]; P.logdt = (const uint16_t*)d_in[7]; P.dskip = (const uint16_t*)d_in[8];
  P.wqkv = (const uint16_t*)d_in[10]; P.wo = (const uint16_t*)d_in[11]; P.out = (uint16_t*)d_out;
  for (int k = 0; k < 72; ++k) P.role[k] = role[k];
  P.zero = 0;
  P.mid = (char*)scratch->C;
  P.spare = nsm > 0 ? nsm - 128 : 0;
  fused_kernel<<<nsm > 0 ? nsm : 128, NTHR, SM_TOTAL, cudaStreamPerThread>>>(P, mW, mWo, mX);
}
```

```cpp
#include <cuda_runtime.h>
#include <cuda_bf16.h>
#include <cuda.h>
#include <stdint.h>
#include <stddef.h>

#define DEV __device__ __forceinline__
#define RARE(x) __builtin_expect(!!(x), 0)

constexpr int NTHR = 512;
constexpr int REG_MAIN = 192, REG_AUX = 96, REG_PROD = 32;
constexpr int NBARU = 384;
constexpr int SPIN_LIMIT = 1 << 22;

constexpr uint32_t SB = 1024;
__host__ __device__ constexpr uint32_t slot(int n) { return SB + n * 8192; }
__host__ __device__ constexpr int wslot(int k) { return k < 2 ? 3 * k : k < 4 ? 3 * k + 6 : k < 6 ? 21 - 3 * k : 3 * k - 18; }
constexpr uint32_t SM_A = slot(22), A_E = 0u - 32768;
constexpr uint32_t SM_O = slot(18), O_E = 0u - 147456;
constexpr uint32_t SM_WO = slot(10), SM_X = slot(8), SM_KV = slot(9) - 4096;
constexpr uint32_t SM_TAP  = slot(26);
constexpr int TAP_SZ = 3440;
constexpr uint32_t SM_STAT = SM_TAP + 4 * TAP_SZ;
constexpr uint32_t SM_CS   = SM_STAT + 1024;
constexpr uint32_t SM_MISC = SM_CS + 768;
constexpr uint32_t SM_BAR  = SM_MISC + 528;
constexpr int SM_TOTAL = SM_BAR + 304 - SB;
static_assert(SM_TOTAL <= 232448, "");
constexpr int R_SZ = 16384, R_U = 512, R_X5 = 5120, R_X3 = 8704, R_BO = 11776, R_BE = 13824;
constexpr int X_5 = 576, X_3 = 648, T_E = 2 * 720, T_O = 1600 + 2 * 721, T_C = 3390, T_K = 3424;
constexpr uint32_t B_RD = SM_BAR, B_ED = SM_BAR + 16, B_F = SM_BAR + 32, B_AT = SM_BAR + 56;
constexpr uint32_t B_AE = SM_BAR + 72, B_QE = SM_BAR + 88, B_ST = SM_BAR + 96, B_CS = SM_BAR + 112;
constexpr uint32_t B_WO = SM_BAR + 120, B_W6 = SM_BAR + 128, B_U = SM_BAR + 144, B_E = SM_BAR + 152, B_A = SM_BAR + 160, B_O = SM_BAR + 192,
                   B_Z = SM_BAR + 256, B_WF = SM_BAR + 272, B_W4 = SM_BAR + 280, B_N = SM_BAR + 288, B_V = SM_BAR + 296;
constexpr int NB_U = 1, NB_B = 2, NB_K = 8, NB_Y = 6, NB_WG = 8, NB_T = 10, NB_AUX = 12, NB_P0 = 13, NB_H = 15;

struct Scratch {
  uint4    XG[2][128 * 1024];
  uint4    O[32 * 8 * 512];
  uint32_t C[8 * 32];
  uint32_t OF[2][32 * 32];
  uint4    CS[16 * 1536 / 4];
  uint4    PS[128 * 64];
  uint4    ST[2][32 * 128];
  uint4    SR[2][8][512];
  uint4    XF[2][32 * 512 * 8];
  uint4    H[2][17 * 8 * 256];
};
__device__ __align__(1024) Scratch g_S;
#define SCR ((Scratch*)(P.mid - offsetof(Scratch, C)))
#define PROFD(slot, v) do {} while (0)
#define PROF(slot) do {} while (0)
#define PROFK(slot) do {} while (0)

DEV uint32_t s2u(const void* p) { return (uint32_t)__cvta_generic_to_shared(p); }
template <class T> DEV T* opqp(T* x) { asm volatile("" : "+l"(x)); return x; }
template <class T> DEV T opq(T x) { asm volatile("" : "+r"(x)); return x; }
DEV int lane_id() { int l; asm volatile("mov.u32 %0,%%laneid;" : "=r"(l)); return l; }
DEV uint32_t pack2(float lo, float hi) { uint32_t d; asm("cvt.rn.bf16x2.f32 %0,%1,%2;" : "=r"(d) : "f"(hi), "f"(lo)); return d; }
DEV float bflo(uint32_t v) { return __uint_as_float(v << 16); }
DEV float bfhi(uint32_t v) { return __uint_as_float(v & 0xFFFF0000u); }
DEV float bfr(float x) { return bflo(pack2(x, 0.f)); }
DEV uint32_t hadd2(uint32_t a, uint32_t b) { uint32_t d; asm("add.rn.bf16x2 %0,%1,%2;" : "=r"(d) : "r"(a), "r"(b)); return d; }
DEV uint32_t hsub2(uint32_t a, uint32_t b) { uint32_t d; asm("sub.rn.bf16x2 %0,%1,%2;" : "=r"(d) : "r"(a), "r"(b)); return d; }
DEV uint32_t hmul2(uint32_t a, uint32_t b) { uint32_t d; asm("mul.rn.bf16x2 %0,%1,%2;" : "=r"(d) : "r"(a), "r"(b)); return d; }
DEV uint32_t hfma2(uint32_t a, uint32_t b, uint32_t c) { uint32_t d; asm("fma.rn.bf16x2 %0,%1,%2,%3;" : "=r"(d) : "r"(a), "r"(b), "r"(c)); return d; }
DEV uint32_t hmax2(uint32_t a, uint32_t b) { uint32_t d; asm("max.bf16x2 %0,%1,%2;" : "=r"(d) : "r"(a), "r"(b)); return d; }
DEV uint32_t prmt(uint32_t a, uint32_t b, uint32_t s) { uint32_t d; asm("prmt.b32 %0,%1,%2,%3;" : "=r"(d) : "r"(a), "r"(b), "r"(s)); return d; }
DEV uint32_t nzmap(uint32_t v) { uint32_t d; asm("max.u32 %0,%1,1;" : "=r"(d) : "r"(v)); return d; }
DEV float rcp(float x) { float y; asm("rcp.approx.ftz.f32 %0,%1;" : "=f"(y) : "f"(x)); return y; }
DEV float sqrt_(float x) { float y; asm("sqrt.approx.ftz.f32 %0,%1;" : "=f"(y) : "f"(x)); return y; }
DEV float ex2(float x) { float y; asm("ex2.approx.ftz.f32 %0,%1;" : "=f"(y) : "f"(x)); return y; }

DEV uint4 ldr4(const void* p) { uint4 v; asm volatile("ld.relaxed.gpu.global.v4.u32 {%0,%1,%2,%3},[%4];" : "=r"(v.x), "=r"(v.y), "=r"(v.z), "=r"(v.w) : "l"(p) : "memory"); return v; }
DEV void ldr4_if(uint4& v, const void* p, bool c) {
  asm volatile("{.reg .pred q; setp.ne.u32 q,%5,0; @q ld.relaxed.gpu.global.v4.u32 {%0,%1,%2,%3},[%4];}"
    : "+r"(v.x), "+r"(v.y), "+r"(v.z), "+r"(v.w) : "l"(p), "r"((uint32_t)c) : "memory");
}
DEV uint2 ldr2(const void* p) { uint2 v; asm volatile("ld.relaxed.gpu.global.v2.u32 {%0,%1},[%2];" : "=r"(v.x), "=r"(v.y) : "l"(p) : "memory"); return v; }
DEV void ldr2_if(uint2& v, const void* p, bool c) {
  asm volatile("{.reg .pred q; setp.ne.u32 q,%3,0; @q ld.relaxed.gpu.global.v2.u32 {%0,%1},[%2];}" : "+r"(v.x), "+r"(v.y) : "l"(p), "r"((uint32_t)c) : "memory");
}
DEV uint32_t ldr1(const void* p) { uint32_t v; asm volatile("ld.relaxed.gpu.global.u32 %0,[%1];" : "=r"(v) : "l"(p) : "memory"); return v; }
DEV float ldnan(const uint16_t* p) {
  uint32_t v = 0xFFFFu;
#pragma unroll 1
  for (int it = 0; it < SPIN_LIMIT && __any_sync(0xffffffffu, v == 0xFFFFu); ++it) asm volatile("ld.relaxed.gpu.global.u16 %0,[%1];" : "=r"(v) : "l"(p) : "memory");
  return __uint_as_float(v << 16);
}
DEV uint4 ldw4(const void* p) { uint4 v; asm volatile("ld.global.v4.u32 {%0,%1,%2,%3},[%4];" : "=r"(v.x), "=r"(v.y), "=r"(v.z), "=r"(v.w) : "l"(p) : "memory"); return v; }
DEV uint2 ldw2(const void* p) { uint2 v; asm volatile("ld.global.v2.u32 {%0,%1},[%2];" : "=r"(v.x), "=r"(v.y) : "l"(p) : "memory"); return v; }
DEV uint32_t ldw1(const void* p) { uint32_t v; asm volatile("ld.global.u32 %0,[%1];" : "=r"(v) : "l"(p) : "memory"); return v; }
DEV void str4(void* p, uint32_t a, uint32_t b, uint32_t c, uint32_t d) { asm volatile("st.relaxed.gpu.global.v4.u32 [%0],{%1,%2,%3,%4};" :: "l"(p), "r"(a), "r"(b), "r"(c), "r"(d) : "memory"); }
DEV void str2(void* p, uint32_t a, uint32_t b) { asm volatile("st.relaxed.gpu.global.v2.u32 [%0],{%1,%2};" :: "l"(p), "r"(a), "r"(b) : "memory"); }
DEV void str1(void* p, uint32_t a) { asm volatile("st.relaxed.gpu.global.u32 [%0],%1;" :: "l"(p), "r"(a) : "memory"); }
DEV void str4_if(void* p, uint32_t a, uint32_t b, uint32_t c, uint32_t d, bool q) {
  asm volatile("{.reg .pred q; setp.ne.u32 q,%5,0; @q st.relaxed.gpu.global.v4.u32 [%0],{%1,%2,%3,%4};}" :: "l"(p), "r"(a), "r"(b), "r"(c), "r"(d), "r"((uint32_t)q) : "memory");
}
DEV void stw4(void* p, uint32_t a, uint32_t b, uint32_t c, uint32_t d) { asm volatile("st.global.v4.u32 [%0],{%1,%2,%3,%4};" :: "l"(p), "r"(a), "r"(b), "r"(c), "r"(d) : "memory"); }
DEV uint4 ldnc4(const void* p) { uint4 v; asm volatile("ld.global.nc.v4.u32 {%0,%1,%2,%3},[%4];" : "=r"(v.x), "=r"(v.y), "=r"(v.z), "=r"(v.w) : "l"(p)); return v; }
DEV uint32_t ldnc1(const void* p) { uint32_t v; asm volatile("ld.global.nc.u32 %0,[%1];" : "=r"(v) : "l"(p)); return v; }
DEV uint2 ldnc2(const void* p) { uint2 v; asm volatile("ld.global.nc.v2.u32 {%0,%1},[%2];" : "=r"(v.x), "=r"(v.y) : "l"(p)); return v; }

DEV uint2 lds2(uint32_t a) { uint2 v; asm volatile("ld.volatile.shared.v2.u32 {%0,%1},[%2];" : "=r"(v.x), "=r"(v.y) : "r"(a)); return v; }
DEV float lds16f(uint32_t a) { uint32_t v; asm volatile("ld.shared.u16 %0,[%1];" : "=r"(v) : "r"(a)); return __uint_as_float(v << 16); }
DEV void sts2(uint32_t a, uint32_t x, uint32_t y) { asm volatile("st.shared.v2.u32 [%0],{%1,%2};" :: "r"(a), "r"(x), "r"(y) : "memory"); }
DEV uint32_t lds1(uint32_t a) { uint32_t v; asm volatile("ld.volatile.shared.u32 %0,[%1];" : "=r"(v) : "r"(a)); return v; }
DEV uint32_t lds1z(uint32_t a, bool c) {
  uint32_t v; asm volatile("{.reg .pred q; setp.ne.u32 q,%2,0; mov.u32 %0,0; @q ld.volatile.shared.u32 %0,[%1];}" : "=r"(v) : "r"(a), "r"((uint32_t)c)); return v;
}
DEV uint4 lds4z(uint32_t a, bool c) {
  uint4 v = make_uint4(0, 0, 0, 0);
  asm volatile("{.reg .pred q; setp.ne.u32 q,%5,0; @q ld.volatile.shared.v4.u32 {%0,%1,%2,%3},[%4];}" : "+r"(v.x), "+r"(v.y), "+r"(v.z), "+r"(v.w) : "r"(a), "r"((uint32_t)c));
  return v;
}
DEV float lds1f(uint32_t a) { float v; asm volatile("ld.shared.f32 %0,[%1];" : "=f"(v) : "r"(a)); return v; }
DEV float2 lds2f(uint32_t a) { float2 v; asm volatile("ld.shared.v2.f32 {%0,%1},[%2];" : "=f"(v.x), "=f"(v.y) : "r"(a)); return v; }
DEV float4 lds4f(uint32_t a) { float4 v; asm volatile("ld.shared.v4.f32 {%0,%1,%2,%3},[%4];" : "=f"(v.x), "=f"(v.y), "=f"(v.z), "=f"(v.w) : "r"(a)); return v; }
DEV uint4 lds4(uint32_t a) { uint4 v; asm volatile("ld.volatile.shared.v4.u32 {%0,%1,%2,%3},[%4];" : "=r"(v.x), "=r"(v.y), "=r"(v.z), "=r"(v.w) : "r"(a)); return v; }
DEV void sts1(uint32_t a, uint32_t v) { asm volatile("st.shared.u32 [%0],%1;" :: "r"(a), "r"(v) : "memory"); }
DEV void sts16(uint32_t a, uint32_t v) { asm volatile("{.reg .b16 h; cvt.u16.u32 h,%1; st.shared.u16 [%0],h;}" :: "r"(a), "r"(v) : "memory"); }
DEV void sts2f(uint32_t a, float x, float y) { asm volatile("st.shared.v2.f32 [%0],{%1,%2};" :: "r"(a), "f"(x), "f"(y) : "memory"); }
DEV void sts4f(uint32_t a, float x, float y, float z, float w) { asm volatile("st.shared.v4.f32 [%0],{%1,%2,%3,%4};" :: "r"(a), "f"(x), "f"(y), "f"(z), "f"(w) : "memory"); }
DEV void sts4(uint32_t a, uint32_t x, uint32_t y, uint32_t z, uint32_t w) { asm volatile("st.shared.v4.u32 [%0],{%1,%2,%3,%4};" :: "r"(a), "r"(x), "r"(y), "r"(z), "r"(w) : "memory"); }

DEV void ldsm4(uint32_t (&r)[4], uint32_t a) { asm volatile("ldmatrix.sync.aligned.m8n8.x4.shared.b16 {%0,%1,%2,%3},[%4];" : "=r"(r[0]), "=r"(r[1]), "=r"(r[2]), "=r"(r[3]) : "r"(a) : "memory"); }
DEV void ldsm4t(uint32_t (&r)[4], uint32_t a) { asm volatile("ldmatrix.sync.aligned.m8n8.x4.trans.shared.b16 {%0,%1,%2,%3},[%4];" : "=r"(r[0]), "=r"(r[1]), "=r"(r[2]), "=r"(r[3]) : "r"(a) : "memory"); }
DEV void ldsm2(uint32_t (&r)[2], uint32_t a) { asm volatile("ldmatrix.sync.aligned.m8n8.x2.shared.b16 {%0,%1},[%2];" : "=r"(r[0]), "=r"(r[1]) : "r"(a) : "memory"); }
DEV void stsm4(uint32_t a, uint32_t r0, uint32_t r1, uint32_t r2, uint32_t r3) { asm volatile("stmatrix.sync.aligned.m8n8.x4.shared.b16 [%0],{%1,%2,%3,%4};" :: "r"(a), "r"(r0), "r"(r1), "r"(r2), "r"(r3) : "memory"); }
DEV void stsm2(uint32_t a, uint32_t r0, uint32_t r1) { asm volatile("stmatrix.sync.aligned.m8n8.x2.shared.b16 [%0],{%1,%2};" :: "r"(a), "r"(r0), "r"(r1) : "memory"); }
DEV void stsm4t(uint32_t a, uint32_t r0, uint32_t r1, uint32_t r2, uint32_t r3) { asm volatile("stmatrix.sync.aligned.m8n8.x4.trans.shared.b16 [%0],{%1,%2,%3,%4};" :: "r"(a), "r"(r0), "r"(r1), "r"(r2), "r"(r3) : "memory"); }
DEV uint32_t movm(uint32_t a) { uint32_t d; asm volatile("movmatrix.sync.aligned.m8n8.trans.b16 %0,%1;" : "=r"(d) : "r"(a)); return d; }
DEV void mma16(float (&d)[4], uint32_t a0, uint32_t a1, uint32_t a2, uint32_t a3, uint32_t b0, uint32_t b1) {
  asm volatile("mma.sync.aligned.m16n8k16.row.col.f32.bf16.bf16.f32 {%0,%1,%2,%3},{%4,%5,%6,%7},{%8,%9},{%0,%1,%2,%3};"
    : "+f"(d[0]), "+f"(d[1]), "+f"(d[2]), "+f"(d[3]) : "r"(a0), "r"(a1), "r"(a2), "r"(a3), "r"(b0), "r"(b1));
}
DEV void mma16z(float (&d)[4], uint32_t a0, uint32_t a1, uint32_t a2, uint32_t a3, uint32_t b0, uint32_t b1) {
  asm volatile("mma.sync.aligned.m16n8k16.row.col.f32.bf16.bf16.f32 {%0,%1,%2,%3},{%4,%5,%6,%7},{%8,%9},{%10,%10,%10,%10};"
    : "=f"(d[0]), "=f"(d[1]), "=f"(d[2]), "=f"(d[3]) : "r"(a0), "r"(a1), "r"(a2), "r"(a3), "r"(b0), "r"(b1), "f"(0.f));
}
DEV void mma8(float (&d)[4], uint32_t a0, uint32_t a1, uint32_t b0) {
  asm volatile("mma.sync.aligned.m16n8k8.row.col.f32.bf16.bf16.f32 {%0,%1,%2,%3},{%4,%5},{%6},{%0,%1,%2,%3};"
    : "+f"(d[0]), "+f"(d[1]), "+f"(d[2]), "+f"(d[3]) : "r"(a0), "r"(a1), "r"(b0));
}

DEV void mma8z(float (&d)[4], uint32_t a0, uint32_t a1, uint32_t b0) {
  asm volatile("mma.sync.aligned.m16n8k8.row.col.f32.bf16.bf16.f32 {%0,%1,%2,%3},{%4,%5},{%6},{%7,%7,%7,%7};"
    : "=f"(d[0]), "=f"(d[1]), "=f"(d[2]), "=f"(d[3]) : "r"(a0), "r"(a1), "r"(b0), "f"(0.f));
}
DEV void bar_sync(int id, int n) { asm volatile("bar.sync %0,%1;" :: "r"(id), "r"(n) : "memory"); }
DEV void bar_sync_if(int id, int n, int c) { asm volatile("{.reg .pred q; setp.ne.s32 q,%2,0; @q bar.sync %0,%1;}" :: "r"(id), "r"(n), "r"(c) : "memory"); }
DEV void bar_arrive_if(int id, int n, int c) { asm volatile("{.reg .pred q; setp.ne.s32 q,%2,0; @q bar.arrive %0,%1;}" :: "r"(id), "r"(n), "r"(c) : "memory"); }
DEV bool bar_any(int id, int n, bool c) {
  uint32_t r; asm volatile("{.reg .pred p,q; setp.ne.u32 q,%3,0; bar.red.or.pred p,%1,%2,q; selp.u32 %0,1,0,p;}" : "=r"(r) : "r"(id), "r"(n), "r"((uint32_t)c) : "memory");
  return __any_sync(0xffffffffu, r);
}
DEV void bar_arrive(int id, int n) { asm volatile("bar.arrive %0,%1;" :: "r"(id), "r"(n) : "memory"); }
DEV void fence_async_glob() { asm volatile("fence.proxy.async.global;" ::: "memory"); }
DEV void fence_async_smem() { asm volatile("fence.proxy.async.shared::cta;" ::: "memory"); }
DEV void mbar_init(uint32_t b, int n) { asm volatile("mbarrier.init.shared::cta.b64 [%0],%1;" :: "r"(b), "r"(n) : "memory"); }
DEV void mbar_arrive(uint32_t b) { asm volatile("mbarrier.arrive.shared::cta.b64 _,[%0];" :: "r"(b) : "memory"); }
DEV void mbar_expect(uint32_t b, int bytes) { asm volatile("mbarrier.arrive.expect_tx.shared::cta.b64 _,[%0],%1;" :: "r"(b), "r"(bytes) : "memory"); }
DEV void mbar_wait(uint32_t b, uint32_t ph) {
  asm volatile("{\n.reg .pred p;\nW: mbarrier.try_wait.parity.shared::cta.b64 p,[%0],%1;\n@!p bra W;\n}" :: "r"(b), "r"(ph) : "memory");
}
DEV void mbar_watch(uint32_t b, uint32_t ph) {
  asm volatile("{\n.reg .pred p,q;\n.reg .u32 n;\nmov.u32 n,0;\n"
               "W: mbarrier.try_wait.parity.shared::cta.b64 p,[%0],%1;\n@p bra D;\n"
               "add.u32 n,n,1;\nsetp.lt.u32 q,n,%2;\n@q bra W;\ntrap;\nD:\n}"
               :: "r"(b), "r"(ph), "n"(SPIN_LIMIT) : "memory");
}
DEV void spin_guard(int it) { asm volatile("{.reg .pred p; setp.gt.s32 p,%0,%1; @p trap;}" :: "r"(it), "n"(SPIN_LIMIT)); }
DEV void split(uint32_t zero) {
  asm volatile("{.reg .pred p; setp.ne.u32 p,%0,0; @p trap;}" :: "r"(zero) : "memory");
}
DEV void pause(int n) {
  uint32_t t0, t; asm volatile("mov.u32 %0,%%clock;" : "=r"(t0));
  do asm volatile("mov.u32 %0,%%clock;" : "=r"(t)); while (t - t0 < n);
}
DEV void cnt_wait(const uint32_t* k, int lane) {
#pragma unroll 1
  for (int it = 0;; ++it) {
    spin_guard(it);
    if (__all_sync(0xffffffffu, ldr1(k + (lane & 3) * 32) >= 32)) break;
  }
}
DEV void mbar_arrive1(uint32_t b) { asm volatile("{.reg .pred p; elect.sync _|p,0xffffffff; @p mbarrier.arrive.shared::cta.b64 _,[%0];}" :: "r"(b) : "memory"); }
DEV void mbar_arrive1_if(uint32_t b, int c) {
  asm volatile("{.reg .pred p,q; setp.ne.s32 q,%1,0; elect.sync _|p,0xffffffff; and.pred p,p,q; @p mbarrier.arrive.shared::cta.b64 _,[%0];}" :: "r"(b), "r"(c) : "memory");
}
DEV void mbar_expect1(uint32_t b, int bytes) { asm volatile("{.reg .pred p; elect.sync _|p,0xffffffff; @p mbarrier.arrive.expect_tx.shared::cta.b64 _,[%0],%1;}" :: "r"(b), "r"(bytes) : "memory"); }
DEV void cnt_add1(uint32_t* q) { asm volatile("{.reg .pred p; elect.sync _|p,0xffffffff; @p red.relaxed.gpu.global.add.u32 [%0],1;}" :: "l"(q) : "memory"); }
DEV void tma4(uint32_t dst, const CUtensorMap* m, int c0, int c1, int c2, int c3, uint32_t bar) {
  asm volatile("{.reg .pred p; elect.sync _|p,0xffffffff;\n"
    "@p cp.async.bulk.tensor.4d.shared::cluster.global.mbarrier::complete_tx::bytes [%0],[%1,{%2,%3,%4,%5}],[%6];}"
    :: "r"(dst), "l"(m), "r"(c0), "r"(c1), "r"(c2), "r"(c3), "r"(bar) : "memory");
}
DEV void tma3(uint32_t dst, const CUtensorMap* m, int c0, int c1, int c2, uint32_t bar) {
  asm volatile("{.reg .pred p; elect.sync _|p,0xffffffff;\n"
    "@p cp.async.bulk.tensor.3d.shared::cluster.global.mbarrier::complete_tx::bytes [%0],[%1,{%2,%3,%4}],[%5];}"
    :: "r"(dst), "l"(m), "r"(c0), "r"(c1), "r"(c2), "r"(bar) : "memory");
}
DEV void bulk(uint32_t dst, const void* src, int bytes, uint32_t bar) {
  asm volatile("{.reg .pred p; elect.sync _|p,0xffffffff;\n@p cp.async.bulk.shared::cluster.global.mbarrier::complete_tx::bytes [%0],[%1],%2,[%3];}" :: "r"(dst), "l"(src), "r"(bytes), "r"(bar) : "memory");
}

DEV void bulk_store(void* dst, uint32_t src, int bytes) {
  asm volatile("{.reg .pred p; elect.sync _|p,0xffffffff;\n@p cp.async.bulk.global.shared::cta.bulk_group [%0],[%1],%2;}" :: "l"(dst), "r"(src), "r"(bytes) : "memory");
}
DEV void tma2_store(const CUtensorMap* m, uint32_t src, int c0, int c1) {
  asm volatile("{.reg .pred p; elect.sync _|p,0xffffffff;\n@p cp.async.bulk.tensor.2d.global.shared::cta.bulk_group [%0,{%2,%3}],[%1];}" :: "l"(m), "r"(src), "r"(c0), "r"(c1) : "memory");
}
DEV void bulk_wait() { asm volatile("cp.async.bulk.commit_group;\ncp.async.bulk.wait_group 0;\nfence.proxy.async.global;" ::: "memory"); }

DEV uint32_t dlo(uint32_t addr, uint32_t lbo) { return __shfl_sync(0xffffffffu, (addr >> 4) | ((lbo >> 4) << 16), 0); }
__host__ __device__ constexpr uint32_t dhi(uint32_t sbo, uint32_t swz) { return (sbo >> 4) | (swz << 30); }
DEV void wg_fence() { asm volatile("wgmma.fence.sync.aligned;" ::: "memory"); }
DEV void wg_commit() { asm volatile("wgmma.commit_group.sync.aligned;" ::: "memory"); }
template <int N> DEV void wg_wait() { asm volatile("wgmma.wait_group.sync.aligned %0;" :: "n"(N) : "memory"); }
template <int N> DEV void zero(float (&d)[N]) {
#pragma unroll
  for (int i = 0; i < N; ++i) d[i] = 0.f;
}
template <int N> DEV void zerov(float (&d)[N]) {
#pragma unroll
  for (int i = 0; i < N; ++i) asm volatile("mov.b32 %0,0;" : "=f"(d[i]));
}
template <int N> DEV void undef(float (&d)[N]) {
#pragma unroll
  for (int i = 0; i < N; ++i) asm volatile("" : "=f"(d[i]));
}
#define R4(d, o) "+f"(d[o]), "+f"(d[o + 1]), "+f"(d[o + 2]), "+f"(d[o + 3])
#define R8(d, o) R4(d, o), R4(d, o + 4)
#define R16(d, o) R8(d, o), R8(d, o + 8)
template <int ACC> DEV void wg_rs64k(float (&d)[32], const uint32_t (&a)[4], uint32_t db) {
  asm volatile("{.reg .pred p; .reg .b64 b; setp.ne.s32 p,%38,0; mov.b64 b,{%36,%37};\n"
    "wgmma.mma_async.sync.aligned.m64n64k16.f32.bf16.bf16 {%0,%1,%2,%3,%4,%5,%6,%7,%8,%9,%10,%11,%12,%13,%14,%15,%16,%17,%18,%19,%20,%21,%22,%23,%24,%25,%26,%27,%28,%29,%30,%31},{%32,%33,%34,%35},b,p,1,1,0;}"
    : R16(d, 0), R16(d, 16) : "r"(a[0]), "r"(a[1]), "r"(a[2]), "r"(a[3]), "r"(db), "n"(dhi(512, 2)), "n"(ACC));
}
template <int ACC> DEV void wg_rs48t(float (&d)[24], const uint32_t (&a)[4], uint32_t db) {
  asm volatile("{.reg .pred p; .reg .b64 b; setp.ne.s32 p,%30,0; mov.b64 b,{%28,%29};\n"
    "wgmma.mma_async.sync.aligned.m64n48k16.f32.bf16.bf16 {%0,%1,%2,%3,%4,%5,%6,%7,%8,%9,%10,%11,%12,%13,%14,%15,%16,%17,%18,%19,%20,%21,%22,%23},{%24,%25,%26,%27},b,p,1,1,1;}"
    : R16(d, 0), R8(d, 16) : "r"(a[0]), "r"(a[1]), "r"(a[2]), "r"(a[3]), "r"(db), "n"(dhi(512, 0)), "n"(ACC));
}
template <int ACC> DEV void wg_rs32t(float (&d)[16], const uint32_t (&a)[4], uint32_t db) {
  asm volatile("{.reg .pred p; .reg .b64 b; setp.ne.s32 p,%22,0; mov.b64 b,{%20,%21};\n"
    "wgmma.mma_async.sync.aligned.m64n32k16.f32.bf16.bf16 {%0,%1,%2,%3,%4,%5,%6,%7,%8,%9,%10,%11,%12,%13,%14,%15},{%16,%17,%18,%19},b,p,1,1,1;}"
    : R16(d, 0) : "r"(a[0]), "r"(a[1]), "r"(a[2]), "r"(a[3]), "r"(db), "n"(dhi(1024, 0)), "n"(ACC));
}
template <int ACC> DEV void wg_ss192(float (&d)[96], uint32_t da, uint32_t db) {
  asm volatile("{.reg .pred p; .reg .b64 a,b; setp.ne.s32 p,%100,0; mov.b64 a,{%96,%98}; mov.b64 b,{%97,%99};\n"
    "wgmma.mma_async.sync.aligned.m64n192k16.f32.bf16.bf16 {"
    "%0,%1,%2,%3,%4,%5,%6,%7,%8,%9,%10,%11,%12,%13,%14,%15,%16,%17,%18,%19,%20,%21,%22,%23,%24,%25,%26,%27,%28,%29,%30,%31,"
    "%32,%33,%34,%35,%36,%37,%38,%39,%40,%41,%42,%43,%44,%45,%46,%47,%48,%49,%50,%51,%52,%53,%54,%55,%56,%57,%58,%59,%60,%61,%62,%63,"
    "%64,%65,%66,%67,%68,%69,%70,%71,%72,%73,%74,%75,%76,%77,%78,%79,%80,%81,%82,%83,%84,%85,%86,%87,%88,%89,%90,%91,%92,%93,%94,%95},a,b,p,1,1,1,1;}"
    : R16(d, 0), R16(d, 16), R16(d, 32), R16(d, 48), R16(d, 64), R16(d, 80) : "r"(da), "r"(db), "n"(dhi(1024, 1)), "n"(dhi(1024, 1)), "n"(ACC));
}
template <int ACC> DEV void wg_ss64(float (&d)[32], uint32_t da, uint32_t db) {
  asm volatile("{.reg .pred p; .reg .b64 a,b; setp.ne.s32 p,%36,0; mov.b64 a,{%32,%34}; mov.b64 b,{%33,%35};\n"
    "wgmma.mma_async.sync.aligned.m64n64k16.f32.bf16.bf16 {"
    "%0,%1,%2,%3,%4,%5,%6,%7,%8,%9,%10,%11,%12,%13,%14,%15,%16,%17,%18,%19,%20,%21,%22,%23,%24,%25,%26,%27,%28,%29,%30,%31},a,b,p,1,1,0,1;}"
    : R16(d, 0), R16(d, 16) : "r"(da), "r"(db), "n"(dhi(1024, 0)), "n"(dhi(1024, 1)), "n"(ACC));
}

DEV uint32_t cpy(uint32_t v, uint32_t id) {
  uint32_t d; asm volatile("prmt.b32 %0,%1,%1,%2;" : "=r"(d) : "r"(v), "r"(id)); return d;
}
struct Params {
  uint32_t zero, spare;
  char* mid;
  const uint16_t *x0, *Are, *Aim, *Bre, *Bim, *Cre, *Cim, *logdt, *dskip, *wqkv, *wo;
  uint16_t* out;
  uint8_t role[72];
};

DEV uint32_t ln_word(float mean, float var) {
  float v = bfr(var);
  float s = sqrt_(bfr(v + 1e-5f));
  return pack2(mean, s);
}

DEV int stat_group(int c) { return c ^ 4; }
DEV int xg_off(int G, int g) { return (G >> 6) * 1024 + (G & 63) * 8 + (g ^ (G & 2)); }
DEV int sr_off(int G, int g) { return (G >> 6) * 256 + (g & 2) * 64 + 2 * (G & 63) + ((g >> 2) & 1); }
DEV uint32_t region(int chl) { return SM_A + (chl >> 1) * A_E + (chl & 1) * R_SZ; }
template <bool FIRST> DEV void gram(float (&s)[4], float (&q0)[4], float (&q1)[4], uint32_t a0, uint32_t a1, uint32_t a2, uint32_t a3) {
  const uint32_t one = 0x3F803F80u;
  if (FIRST) { mma16z(s, a0, a1, a2, a3, one, one); mma8z(q0, a0, a1, a0); mma8z(q1, a0, a1, a1); }
  else { mma16(s, a0, a1, a2, a3, one, one); mma8(q0, a0, a1, a0); mma8(q1, a0, a1, a1); }
  mma8(q0, a2, a3, a2); mma8(q1, a2, a3, a3);
}
DEV uint32_t ln_sums(float s, float q) { const float m = s * (1.f / 512.f); return ln_word(m, fmaxf(q * (1.f / 512.f) - m * m, 0.f)); }
DEV void cmul(float& orr, float& oi, float ar, float ai, float br, float bi) {
  float r = ar * br - ai * bi, i = ar * bi + ai * br; orr = r; oi = i;
}
DEV void cexp_(float al, float bt, float s, float& er, float& ei) {
  float mag = ex2(al * s), ph = bt * s;
  ph -= rintf(ph);
  float ang = ph * 6.283185307179586f;
  er = mag * __cosf(ang); ei = mag * __sinf(ang);
}

DEV void kgen(const Params& P, int c, int wm, int lane) {
  const int chl = wm >> 1, mh = wm & 1, g = lane >> 2, t = lane & 3;
  const int ch = 256 * (chl >> 1) + 2 * c + (chl & 1);
  const int mo = ch * 64 + mh * 32 + lane;
  const uint32_t vAr = ldw1((const uint32_t*)P.Are + mo), vAi = ldw1((const uint32_t*)P.Aim + mo);
  const uint32_t vBr = ldw1((const uint32_t*)P.Bre + mo), vBi = ldw1((const uint32_t*)P.Bim + mo);
  const uint32_t vCr = ldw1((const uint32_t*)P.Cre + mo), vCi = ldw1((const uint32_t*)P.Cim + mo);
  const uint32_t vld = ldw1((const uint32_t*)P.logdt + (ch >> 1)) >> (16 * (ch & 1)), vds = ldw1((const uint32_t*)P.dskip + (ch >> 1)) >> (16 * (ch & 1));
  bar_arrive(NB_Y, 384);
  PROF(45);
  asm volatile("setmaxnreg.inc.sync.aligned.u32 %0;" :: "n"(REG_MAIN));
  PROF(44);
  {
    const uint32_t tz = SM_TAP + chl * TAP_SZ + (mh * 32 + lane) * 16;
#pragma unroll
    for (int k = 0; k < 3; ++k) sts4(tz + k * 1024, 0, 0, 0, 0);
    static_assert(TAP_SZ > 3072 && TAP_SZ <= 4096, "");
    if (mh * 32 + lane < TAP_SZ / 16 - 192) sts4(tz + 3072, 0, 0, 0, 0);
  }
  const float dt = bfr(__expf(bflo(vld)));
  const uint32_t tb = slot(wm);
  float acc[5][4];
#pragma unroll
  for (int i = 0; i < 5; ++i) { acc[i][0] = acc[i][1] = acc[i][2] = acc[i][3] = 0.f; }
  float k2048 = 0.f;
#pragma unroll 1
  for (int r = 0; r < 2; ++r) {
    const float are = r ? bfhi(vAr) : bflo(vAr), aim = r ? bfhi(vAi) : bflo(vAi);
    const float bre = r ? bfhi(vBr) : bflo(vBr), bim = r ? bfhi(vBi) : bflo(vBi);
    const float cre = r ? bfhi(vCr) : bflo(vCr), cim = r ? bfhi(vCi) : bflo(vCi);
    const float al = dt * are * 1.4426950408889634f, bt = dt * aim * 0.15915494309189535f;
    float wr, wi; cmul(wr, wi, cre, cim, dt * bre, dt * bim);
    if (r == 0) PROFD(2, __float_as_uint(wr + al + bt));
    float e1r, e1i, e8r, e8i, eLr, eLi;
    cexp_(al, bt, 1.f, e1r, e1i); cexp_(al, bt, 8.f, e8r, e8i); cexp_(al, bt, 128.f, eLr, eLi);
    const uint32_t tw = tb + lane * 4;
    float pr[8], pi[8];
    pr[1] = e1r; pi[1] = e1i;
#pragma unroll
    for (int k = 2; k < 8; ++k) cmul(pr[k], pi[k], pr[k - 1], pi[k - 1], e1r, e1i);
    float yr = 1.f, yi = 0.f, qr = wr, qi = wi;
#pragma unroll
    for (int a = 0; a < 16; ++a) {
      sts1(tw + a * 144, pack2(yr, -yi));
      if (a == 0) { yr = e8r; yi = e8i; } else if (a < 15) cmul(yr, yi, yr, yi, e8r, e8i);
      const int step = a < 2 ? 1 : a < 4 ? 2 : a < 8 ? 4 : 8;
      const int row0 = 16 + (a < 2 ? 8 * a : a < 4 ? 16 + 4 * (a - 2) : a < 8 ? 24 + 2 * (a - 4) : 32 + (a - 8));
      sts1(tw + row0 * 144, pack2(qr, qi));
#pragma unroll
      for (int k = step; k < 8; k += step) {
        float xr, xi; cmul(xr, xi, qr, qi, pr[k], pi[k]);
        sts1(tw + (row0 + k / step) * 144, pack2(xr, xi));
      }
      cmul(qr, qi, qr, qi, eLr, eLi);
    }
    k2048 += qr;
    __syncwarp();
    if (r == 0) PROF(3);
#pragma unroll
    for (int kp = 0; kp < 2; ++kp) {
      uint32_t a0[4], a1[4];
      const uint32_t aa = tb + ((lane & 7) + 8 * ((lane >> 3) & 1)) * 144 + (lane >> 4) * 16 + kp * 64;
      ldsm4(a0, aa); ldsm4(a1, aa + 32);
#pragma unroll
      for (int tl = 0; tl < 5; ++tl) {
        uint32_t b[4];
        ldsm4(b, tb + (16 + 8 * tl + (lane & 7)) * 144 + (lane >> 3) * 16 + kp * 64);
        mma16(acc[tl], a0[0], a0[1], a0[2], a0[3], b[0], b[1]);
        mma16(acc[tl], a1[0], a1[1], a1[2], a1[3], b[2], b[3]);
      }
    }
    __syncwarp();
    bar_sync_if(NB_P0 + 1, 288, 1 - r);
  }
#pragma unroll
  for (int o = 16; o > 0; o >>= 1) k2048 += __shfl_xor_sync(0xffffffffu, k2048, o);
  if (mh == 0) {
    sts4f(tb + lane * 16, acc[2][0], acc[2][1], acc[2][2], acc[2][3]);
    sts4f(tb + 512 + lane * 16, acc[3][0], acc[3][1], acc[3][2], acc[3][3]);
  } else {
    sts4f(tb + lane * 16, acc[0][0], acc[0][1], acc[0][2], acc[0][3]);
    sts4f(tb + 512 + lane * 16, acc[1][0], acc[1][1], acc[1][2], acc[1][3]);
    sts4f(tb + 1024 + lane * 16, acc[4][0], acc[4][1], acc[4][2], acc[4][3]);
    if (lane == 0) sts1(tb + 1536, __float_as_uint(k2048));
  }
  PROF(4);
  bar_sync(NB_K + chl, 64);
  const uint32_t ob = slot(wm ^ 1), tp = SM_TAP + chl * TAP_SZ;
  if (mh == 0) {
#pragma unroll
    for (int tl = 0; tl < 2; ++tl) {
      float4 o = lds4f(ob + tl * 512 + lane * 16);
      if (tl == 0 && lane == 0) o.x += bflo(vds);
      uint32_t v0 = pack2(acc[tl][0] + o.x, acc[tl][1] + o.y), v1 = pack2(acc[tl][2] + o.z, acc[tl][3] + o.w);
      const int l = 128 * tl + 8 * g + 2 * t;
      sts16(tp + T_E + 2 * (0 - l), v0); sts16(tp + T_E + 2 * (-1 - l), v0 >> 16);
      sts16(tp + T_O + 2 * (0 - l), v0); sts16(tp + T_O + 2 * (-1 - l), v0 >> 16);
      sts16(tp + T_E + 2 * (-64 - l), v1); sts16(tp + T_E + 2 * (-65 - l), v1 >> 16);
      sts16(tp + T_O + 2 * (-64 - l), v1); sts16(tp + T_O + 2 * (-65 - l), v1 >> 16);
    }
    float4 o = lds4f(ob + 1024 + lane * 16);
    uint32_t v0 = pack2(acc[4][0] + o.x, acc[4][1] + o.y), v1 = pack2(acc[4][2] + o.z, acc[4][3] + o.w);
    const int x = 32 * t + g - 1;
    if (lane == 0) { sts16(tp + T_E - 2 * (X_5 + 63), v0); sts16(tp + T_O - 2 * (X_5 + 63), v0); sts1(tp + T_K, prmt(v0, v0, 0x1010)); }
    else sts16(tp + T_C - 2 * x, v0);
    sts16(tp + T_C - 2 * (x + 16), v0 >> 16);
    sts16(tp + T_C - 2 * (x + 8), v1);
    sts16(tp + T_C - 2 * (x + 24), v1 >> 16);
    if (lane == 0) sts16(tp + T_C - 2 * 127, pack2(k2048 + __uint_as_float(lds1(ob + 1536)), 0.f));
  } else {
    float4 o2 = lds4f(ob + lane * 16), o3 = lds4f(ob + 512 + lane * 16);
    uint32_t v0 = pack2(acc[2][0] + o2.x, acc[2][1] + o2.y), v1 = pack2(acc[2][2] + o2.z, acc[2][3] + o2.w);
    const int l0 = 256 + 128 * (t >> 1) + 4 * (t & 1) + 8 * g;
    if (lane != 0) { sts16(tp + T_E + 2 * (1 - l0), v0); sts16(tp + T_O + 2 * (1 - l0), v0); }
    sts16(tp + T_E + 2 * (0 - l0), v0); sts16(tp + T_O + 2 * (0 - l0), v0);
    sts16(tp + T_E + 2 * (-1 - l0), v0); sts16(tp + T_O + 2 * (-1 - l0), v0);
    sts16(tp + T_E + 2 * (-2 - l0), v0 >> 16); sts16(tp + T_O + 2 * (-2 - l0), v0 >> 16);
    sts16(tp + T_E + 2 * (-63 - l0), v1); sts16(tp + T_O + 2 * (-63 - l0), v1);
    sts16(tp + T_E + 2 * (-64 - l0), v1); sts16(tp + T_O + 2 * (-64 - l0), v1);
    sts16(tp + T_E + 2 * (-65 - l0), v1); sts16(tp + T_O + 2 * (-65 - l0), v1);
    sts16(tp + T_E + 2 * (-66 - l0), v1 >> 16); sts16(tp + T_O + 2 * (-66 - l0), v1 >> 16);
    uint32_t w0 = pack2(acc[3][0] + o3.x, acc[3][1] + o3.y), w1 = pack2(acc[3][2] + o3.z, acc[3][3] + o3.w);
    const int x = 16 * t + g;
    if (lane == 0) {
      const uint32_t k = prmt(w0, w0, 0x1010);
      sts1(tp + T_E - 2 * 514, k); sts1(tp + T_E - 2 * 512, k);
      sts16(tp + T_O - 2 * 514, k); sts1(tp + T_O - 2 * 513, k); sts16(tp + T_O - 2 * 511, k);
    } else { sts16(tp + T_E - 2 * (X_5 - 1 + x), w0); sts16(tp + T_O - 2 * (X_5 - 1 + x), w0); }
    sts16(tp + T_E - 2 * (X_3 + x), w0 >> 16); sts16(tp + T_O - 2 * (X_3 + x), w0 >> 16);
    sts16(tp + T_E - 2 * (X_5 + 7 + x), w1); sts16(tp + T_O - 2 * (X_5 + 7 + x), w1);
    sts16(tp + T_E - 2 * (X_3 + 8 + x), w1 >> 16); sts16(tp + T_O - 2 * (X_3 + 8 + x), w1 >> 16);
  }
}

DEV bool bad8(const uint4& v) { return min(v.x, v.z) == 0u; }
DEV uint32_t uchunk(uint32_t reg, int x) { return reg + R_U + (x ^ ((x >> 3) & 3)) * 16; }
DEV uint32_t& xword(uint4 (&x)[2], int e, int tp) { uint4& v = x[tp >> 1]; return tp & 1 ? (e ? v.w : v.z) : (e ? v.y : v.x); }

DEV void sload(const Params& P, int c, int j, int layer, uint4 (&s)[2][2]) {
  const uint4* st = &SCR->SR[layer][c >> 4][opq(j)];
  mbar_wait(B_U, layer);
  PROF(layer ? 25 : 10);
#pragma unroll
  for (int z = 0; z < 4; ++z) s[z >> 1][z & 1] = ldr4(st + z * 128);
}
DEV void uload(const Params& P, int c, int j, int layer, uint4 (&x)[2][2][2], uint4 (&s)[2][2]) {
  j = opq(j);
  const uint4* st = &SCR->SR[layer][c >> 4][j];
  const int o0 = 2 * j + ((j >> 2) & 1), o1 = o0 ^ 1;
#pragma unroll
  for (int z = 0; z < 4; ++z) { uint4& v = s[z >> 1][z & 1]; ldr4_if(v, st + z * 128, bad8(v)); }
  PROF(layer ? 26 : 11);
  mbar_wait(B_E, layer);
#pragma unroll
  for (int z = 0; z < 8; ++z) x[z >> 2][(z >> 1) & 1][z & 1] = lds4(SM_X + 16 * (z & 1 ? o1 : o0) + (z >> 1) * 4096);
  PROF(layer ? 27 : 14);
  for (int it = 0;; ++it) {
    uint32_t m = ~0u;
#pragma unroll
    for (int z = 0; z < 4; ++z) { const uint4& v = s[z >> 1][z & 1]; m = min(m, min(v.x, v.z)); }
#pragma unroll
    for (int z = 0; z < 8; ++z) { const uint4& v = x[z >> 2][(z >> 1) & 1][z & 1]; m = min(m, min(v.x, v.z)); }
    if (!RARE(__any_sync(0xffffffffu, m == 0))) break;
#pragma unroll
    for (int z = 0; z < 4; ++z) { uint4& v = s[z >> 1][z & 1]; ldr4_if(v, st + z * 128, bad8(v)); }
#pragma unroll
    for (int z = 0; z < 8; ++z) {
      uint4& v = x[z >> 2][(z >> 1) & 1][z & 1];
      ldr4_if(v, &SCR->XG[layer][c * 1024 + (opq(o0) ^ (z & 1)) + (z >> 1) * 256], bad8(v));
    }
    spin_guard(it);
  }
  PROF(4 + 12 * layer);
}
DEV void uprep(int j, int k, uint4 (&x)[2][2], uint4 (&s)[2], uint32_t (&u)[4][4]) {
  const uint32_t ua = uchunk(0, opq(j)) + k * 2048;
#pragma unroll
  for (int chl = 0; chl < 4; ++chl) {
#pragma unroll
    for (int tp = 0; tp < 4; ++tp) u[chl][tp] = hmul2(hsub2(xword(x[chl >> 1], chl & 1, tp), xword(s, 1, tp)), xword(s, 0, tp));
    sts4(ua + region(chl), u[chl][0], u[chl][1], u[chl][2], u[chl][3]);
  }
}

template <bool FULL> DEV void box_unit(uint32_t reg, int s, const uint2& a, const uint4& b, const uint32_t (&d)[4], uint32_t (&pv)[4]) {
  const uint32_t u[9] = {a.x, a.y, b.x, b.y, b.z, b.w, d[0], d[1], d[2]};
  uint32_t v[8], p[8];
#pragma unroll
  for (int j = 0; j < 8; ++j) { v[j] = prmt(u[j], u[j + 1], 0x5432); p[j] = hadd2(u[j], v[j]); }
  const uint32_t o = reg + s * 16;
  uint32_t x[4], y[4];
#pragma unroll
  for (int j = 0; j < 4; ++j) { x[j] = hadd2(hadd2(p[1 + j], p[2 + j]), u[3 + j]); y[j] = hadd2(v[3 + j], p[4 + j]); pv[j] = p[4 + j]; }
  sts4(o + R_X5, x[0], x[1], x[2], x[3]);
  sts4(o + R_X3, y[0], y[1], y[2], y[3]);
  if (FULL) {
#pragma unroll
    for (int j = 0; j < 4; ++j) { y[j] = hadd2(hadd2(v[j], v[3 + j]), x[j]); x[j] = hadd2(hadd2(u[j], u[4 + j]), y[j]); }
    const bool od = s & 1;
    sts4(o + R_BO, od ? y[0] : x[0], od ? y[1] : x[1], od ? y[2] : x[2], od ? y[3] : x[3]);
    sts4(o + R_BE + 16, od ? x[0] : y[0], od ? x[1] : y[1], od ? x[2] : y[2], od ? x[3] : y[3]);
  }
}
DEV void box_full(int j, uint32_t (&u)[4][4], uint32_t zero) {
  const uint32_t a2 = uchunk(8, j - 2), a1 = uchunk(0, j - 1);
  uint2 a[4]; uint4 b[4];
#define HALO(n) { a[n] = lds2(region(n) + a2); b[n] = lds4(region(n) + a1); }
  HALO(0) HALO(1)
  split(zero);
#pragma unroll
  for (int chl = 0; chl < 4; ++chl) {
    const uint32_t d[4] = {u[chl][0], u[chl][1], u[chl][2], u[chl][3]};
    box_unit<true>(region(chl), j, a[chl], b[chl], d, u[chl]);
    if (chl < 2) HALO(chl + 2)
    if (chl != 2) {
      fence_async_smem();
      if (chl == 3) bar_arrive(NB_B + 2, 288);
      bar_arrive(NB_B + chl, 288);
    }
    if (chl == 0) PROF(31);
  }
#undef HALO
}
DEV void box_help(int e, int lane) {
  bar_sync(NB_H, 192);
#pragma unroll 1
  for (int n = 0; n < 4; ++n) {
    const int chl = e + (n & 2), s = 128 + 32 * (n & 1) + lane;
    const uint32_t reg = region(chl);
    const uint4 d = lds4(uchunk(reg, s));
    const uint32_t u[4] = {d.x, d.y, d.z, d.w};
    uint32_t v[4];
    box_unit<false>(reg, s, lds2(uchunk(reg, s - 2) + 8), lds4(uchunk(reg, s - 1)), u, v);
    if (n & 1) { fence_async_smem(); bar_arrive(NB_B + chl, 288); }
  }
}

DEV uint4 hadd8(const uint4& a, const uint4& b) { return make_uint4(hadd2(a.x, b.x), hadd2(a.y, b.y), hadd2(a.z, b.z), hadd2(a.w, b.w)); }
DEV void conv_out(int c, int j, int chl, uint4 (&x)[2][2][2], const uint32_t (&v)[4], uint4* XF, uint32_t zero) {
  const int rho = chl >> 1, e = chl & 1;
  const uint32_t ua = uchunk(region(chl), j), fa = region(chl) + R_X5 + j * 16, ha = region(chl) + R_X3 + (j & 1) * 1088 + (j >> 1) * 16;
  const int m8 = ((j & 4) + ((j >> 1) & 1) + 2 * (j & 1)) ^ ((2 * c + e) & 7);
  uint4* xo = XF + (((16 - 2 * (j & 8) + (j >> 4)) * 512 + 256 * rho + 2 * c + e) * 8 + m8);
  bar_sync(NB_Y + e + 7 * rho, 256);
  uint4 y[2], f[2], h[2];
#pragma unroll
  for (int k = 0; k < 2; ++k) {
    y[k] = lds4(ua + k * 2048);
    f[k] = lds4z(ua + k * 2048 + R_BO - R_U, k || j >= 36);
    h[k] = lds4z(fa + k * 2048 - 1024, k || j >= 64);
  }
  const uint32_t q = lds1(SM_TAP + chl * TAP_SZ + T_K);
  const uint4 r = lds4(ha);
  split(zero);
  h[1] = hadd8(h[1], make_uint4(hfma2(q, v[0], r.x), hfma2(q, v[1], r.y), hfma2(q, v[2], r.z), hfma2(q, v[3], r.w)));
#pragma unroll
  for (int k = 0; k < 2; ++k) {
    const uint4 o = hadd8(hadd8(y[k], hadd8(f[k], h[k])), make_uint4(xword(x[k][rho], e, 0), xword(x[k][rho], e, 1), xword(x[k][rho], e, 2), xword(x[k][rho], e, 3)));
    const uint32_t keep = j & 1 ? 0x7632 : 0x5410, k0 = prmt(o.x, o.y, keep), k1 = prmt(o.z, o.w, keep);
    const uint32_t g0 = __shfl_xor_sync(0xffffffffu, prmt(o.x, o.y, keep ^ 0x2222), 1), g1 = __shfl_xor_sync(0xffffffffu, prmt(o.z, o.w, keep ^ 0x2222), 1);
    str4(xo + k * 32768, j & 1 ? g0 : k0, j & 1 ? g1 : k1, j & 1 ? k0 : g0, j & 1 ? k1 : g1);

  }
  if (e) { __syncwarp(); mbar_arrive1(B_RD + rho * 8); }
}

DEV void conv_round(int e, int rho, int w, int lane) {
  const int g = lane >> 2, t = lane & 3, chl = 2 * rho + e;
  const uint32_t reg = region(chl), tp = SM_TAP + chl * TAP_SZ, dr = dlo(reg, 128);
  const uint32_t g0 = tp + ((g & 1) ? T_O : T_E) + 2 * (2 * t - g) - 16;
  const uint32_t ga = g0 - 32 * (w & 1) - 576 * (w >> 1), id = opq(0x3210u);
  float acc[32], f1[24], f2[16];
  uint32_t q[12][4];
  {
    uint32_t qn[18][4];
    qn[0][2] = lds1(ga + 64);
#pragma unroll
    for (int n = 0; n < 18; ++n) {
      const bool nz = n < 15 || w < 2 || (n == 15 && w == 2);
      qn[n][0] = n < 15 ? lds1(ga + 48 - 32 * n) : lds1z(ga + 48 - 32 * n, nz);
      qn[n][1] = n < 15 ? lds1(ga + 32 - 32 * n) : lds1z(ga + 32 - 32 * n, nz);
    }
#pragma unroll
    for (int n = 0; n < 18; ++n) { qn[n][3] = cpy(qn[n][0], id); if (n) qn[n][2] = cpy(qn[n - 1][1], id); }
#pragma unroll
    for (int n = 0; n < 8; ++n) {
      const int i = n & 3;
      const uint32_t a = g0 + 16 - 16 * w - 2 * (n < 4 ? X_5 : X_3) + 16 * i;
      uint32_t (&q1)[4] = q[(n & 4) + (i >> 1)], (&q2)[4] = q[(n & 4) + 2 + (i >> 1)];
      q1[2 * (i & 1)] = lds1z(a, i <= w); q1[2 * (i & 1) + 1] = lds1(a - 64);
      q2[2 * (i & 1)] = cpy(0, id); q2[2 * (i & 1) + 1] = lds1z(a - 128, i >= w);
    }
    const uint32_t gc = tp + T_C - 2 + 4 * (t - g - 8 * w);
#pragma unroll
    for (int kk = 0; kk < 4; ++kk) {
      q[8 + kk][0] = lds1z(gc + 32 * kk, w >= kk); q[8 + kk][2] = lds1z(gc + 32 * kk + 16, w >= kk);
      q[8 + kk][1] = lds1(gc + 32 * kk - 128); q[8 + kk][3] = lds1(gc + 32 * kk - 112);
    }
    PROFD(rho ? 43 : 47, qn[17][2] ^ q[11][3]);
    bar_sync_if(NB_U, NBARU, 1 - rho);
    mbar_arrive1_if(B_V, chl == 1 && w == 0);
    bar_sync_if(NB_T + 1 - e, 256, chl);
    const uint32_t db = dr + (R_U + 32) / 16;
    undef(acc);
    wg_fence();
#pragma unroll
    for (int n = 0; n < 18; ++n) {
      if (n) wg_rs64k<1>(acc, qn[n], db - 2 * n); else wg_rs64k<0>(acc, qn[0], db);
      if (n == 9) wg_commit();
    }
    wg_commit();
  }
  wg_wait<1>();
  PROF(12);
  bar_sync(NB_B + chl, 288);
  const uint32_t d1 = dr + R_X5 / 16, d2 = dr + R_BO / 16;
  undef(f1); undef(f2);
  wg_fence();
#pragma unroll
  for (int n = 0; n < 8; ++n) {
    const uint32_t d = d1 + (n >> 2) * ((R_X3 - R_X5) / 16) + 16 * (n & 1) - 16 * (n & 2);
    if (n) wg_rs48t<1>(f1, q[n], d); else wg_rs48t<0>(f1, q[0], d);
    if (n & 1) { if (n > 1) wg_rs32t<1>(f2, q[8 + (n >> 1)], d2 + 16 * (n >> 1)); else wg_rs32t<0>(f2, q[8], d2); }
  }
  wg_commit();
  wg_wait<1>();
  PROF(13);
  bar_arrive_if(NB_T + e, 256, chl - 3);
  wg_wait<0>();
  PROF(14);
  bar_sync(NB_WG + e, 128);
  {
    const int p = (lane + 9 * (w >> 1)) & 31;
    const uint32_t ya = reg + ((w >> 1) ? R_BO : R_U) + p * 64 + (((2 * (w & 1)) ^ ((p >> 1) & 3)) * 16);
    const uint32_t up = p < lane ? 2048 : 0;
#pragma unroll
    for (int z = 0; z < 4; ++z) {
      const float* a = acc + 16 * (z >> 1) + 2 * (z & 1);
      stsm4t((ya + (up ^ ((z >> 1) * 2048))) ^ ((z & 1) * 16), pack2(a[0], a[1]), pack2(a[4], a[5]), pack2(a[8], a[9]), pack2(a[12], a[13]));
    }
  }
  {
    const uint32_t fa = reg + R_X5 + (8 * w + (lane & 7)) * 16 + (lane >> 3) * 512;
    uint32_t h[6];
#pragma unroll
    for (int p = 0; p < 6; ++p) h[p] = p ? pack2(f1[4 * p] + f1[4 * p - 2], f1[4 * p + 1] + f1[4 * p - 1]) : pack2(f1[0], f1[1]);
    stsm4(fa, h[0], h[1], h[2], h[3]);
    stsm2(fa + 2048, h[4], h[5]);
    stsm4(reg + R_X3 + (lane < 16 ? 1088 : 0) + (8 * w + (lane & 7) + 4 * (lane & 8)) * 16, pack2(f2[0], f2[1]), pack2(f2[2] + f2[4], f2[3] + f2[5]),
          pack2(f2[8], f2[9]), pack2(f2[10] + f2[12], f2[11] + f2[13]));
  }
  bar_arrive(NB_Y + e + 7 * rho, 256);
}
constexpr uint32_t FILL = 0xFFFFFFFFu;
template <int N> DEV void fixo(uint4 (&A)[N], const uint4* p) {
#pragma unroll 1
  for (int it = 0; it < SPIN_LIMIT; ++it) {
    uint32_t m = A[0].x;
#pragma unroll
    for (int k = 1; k < N; ++k) m = max(m, A[k].x);
    if (__all_sync(0xffffffffu, m != FILL)) break;
#pragma unroll
    for (int k = 0; k < N; ++k) ldr4_if(A[k], p + k * 32, A[k].x == FILL);
  }
}
DEV bool rows_nan(float a, float b) {
  return __any_sync(0xffffffffu, a != a || b != b);
}
template <int N> DEV void slow_step(float (&acc)[N], float a0, float a1, const uint16_t* wr, uint32_t zero) {
#pragma unroll
  for (int j = 0; j < N / 4; ++j) {
    const uint32_t v = __ldg((const uint32_t*)(wr + (j >> 3) * 512 + 8 * (j & 7)));
    acc[4 * j] += a0 * bflo(v); acc[4 * j + 1] += a0 * bfhi(v); acc[4 * j + 2] += a1 * bflo(v); acc[4 * j + 3] += a1 * bfhi(v);
    if ((j & 3) == 3) wr += __float_as_uint(acc[4 * j]) & zero;
  }
}
DEV int res_off(int w, int lane) { return ((lane & 7) + 8 * (lane >> 4)) * 8 + ((2 * (w & 2) + (w & 1) + ((lane >> 2) & 2)) ^ (lane & 7)); }
DEV void res_load(uint32_t (&res)[8][2], uint32_t sa, int w, int lane) {
  const uint32_t a = sa + res_off(w, opq(lane)) * 16;
#pragma unroll
  for (int j = 0; j < 8; j += 2) {
    uint32_t r[4];
    ldsm4t(r, a + j * 1024);
    res[j][0] = r[0]; res[j][1] = r[1]; res[j + 1][0] = r[2]; res[j + 1][1] = r[3];
  }
}

DEV void res_init(float (&ac)[32], const uint32_t (&res)[8][2]) {
#pragma unroll
  for (int j = 0; j < 16; ++j) { ac[2 * j] = bflo(res[j >> 1][j & 1]); ac[2 * j + 1] = bfhi(res[j >> 1][j & 1]); }
}
DEV uint32_t after(uint32_t b, const uint32_t (&res)[8][2], uint32_t zero) {
  return b + ((res[0][0] ^ res[2][0] ^ res[4][0] ^ res[6][0]) & zero);
}

DEV void attn_phase(const Params& P, int c, int e, int w, int lane, int layer) {
  lane = opq(lane); c = opq(c);
  const int i = c >> 3, cg = c & 7, J = 16 * e + i, G = 8 * i + 4 - 4 * e + w;
  const int g = lane >> 2, t = lane & 3;
  float acc[96];
  uint32_t res[8][2];
  float2 cs[16];
  float4 st;
  const uint32_t csb = opq(SM_CS + 8 * t);
  {
    const uint32_t sa = SM_A + e * A_E, ba = B_A + 16 * e;
    const uint32_t da = dlo(sa, 8192), db = (SB >> 4) | (512 << 16);
    undef(acc);
#pragma unroll
    for (int j = 0; j < 8; ++j) asm volatile("" : "=r"(res[j][0]), "=r"(res[j][1]));
    mbar_wait(B_WF, layer);
    mbar_wait(ba, 0);
    mbar_wait(B_RD + 8, layer);
    bar_sync_if(NB_T, 256, e);
    PROF(24);
#pragma unroll
    for (int j = 0; j < 4; ++j) {
      if (j == 1) { mbar_wait(ba + 8, 0); PROFK(layer ? 39 : 15); }
      wg_fence();
#pragma unroll
      for (int k = 0; k < 4; ++k) {
        if (j | k) wg_ss192<1>(acc, da + j * 512 + k * 128, db + wslot(j) * 512 + k * 128); else wg_ss192<0>(acc, da, db);
        if (j == 3 && k == 1) wg_commit();
      }
      wg_commit();
      if (j == 1 || j == 2) { wg_wait<1>(); mbar_arrive1_if(B_F + 8 * (j - 1), e); }
    }
    wg_wait<1>();
    bar_arrive(NB_T + e, 256);
    wg_wait<0>();
    if (cg < 4) res_load(res, sa + cg * 8192, w, lane);
    mbar_arrive1(after(B_AE + 8 * e, res, P.zero));
    PROF(25);
#pragma unroll 1
    for (uint32_t late = P.zero;; late = 1) {
      if (late) {
        const uint16_t* xr = (const uint16_t*)SCR->XF[layer] + opq(J) * 32768;
        zero(acc);
#pragma unroll 1
        for (int k = 0; k < 512; ++k)
          slow_step(acc, ldnan(xr + k * 64 + ((2 * w) ^ (k & 7)) * 8 + g), ldnan(xr + k * 64 + ((2 * w + 1) ^ (k & 7)) * 8 + g),
                    P.wqkv + (k * 1536 + 64 * cg + 2 * t), P.zero);
        const uint32_t* q = (const uint32_t*)xr + ((64 * cg + g) * 32 + t);
        const int m8 = (2 * (w & 2) + (w & 1)) ^ g;
#pragma unroll 1
        for (int it = 0; it < SPIN_LIMIT; ++it) {
          uint32_t m = 0;
#pragma unroll
          for (int z = 0; z < 16; ++z) { const uint32_t x = ldr1(q + (z >> 1) * 256 + (m8 ^ (2 * (z & 1))) * 4); m = max(m, x); res[z >> 1][z & 1] = movm(x); }
          if (__all_sync(0xffffffffu, m != FILL)) break;
        }
#pragma unroll
        for (int z = 0; z < 16; ++z) cs[z] = lds2f(csb + 256 + z * 32);
      } else {
        mbar_wait(B_CS, 0);
#pragma unroll
        for (int z = 0; z < 16; ++z) cs[z] = lds2f(csb + 256 + z * 32);
        mbar_wait(B_W4, layer);
        mbar_wait(ba, 1);
        bar_sync(NB_T + 1 - e, 256);
        PROF(26);
#pragma unroll
        for (int j = 4; j < 8; ++j) {
          if (j == 5) mbar_wait(ba + 8, 1);
          if (j >= 6) mbar_wait(B_W6 + 8 * (j - 6), layer);
          if (j > 4) PROF(31 + j);
          wg_fence();
#pragma unroll
          for (int k = 0; k < 4; ++k) {
            wg_ss192<1>(acc, da + (j & 3) * 512 + k * 128, db + wslot(j) * 512 + k * 128);
            if (j == 7 && k == 1) wg_commit();
          }
          wg_commit();
          if (j == 5) {
            if (cg >= 4) res_load(res, sa + (cg - 4) * 8192, w, lane);
            wg_wait<1>(); mbar_arrive1_if(B_F + 16, e); PROF(40);
          }

        }
      }
      uint32_t rs = hadd2(res[0][0], res[0][1]);
#pragma unroll
      for (int z = 2; z < 16; ++z) rs = hadd2(rs, res[z >> 1][z & 1]);
      const float rn = bflo(rs) + bfhi(rs);
      wg_wait<1>();
      bar_arrive_if(NB_T, 256, !(e | late));
      mbar_wait(B_ST + 8 * e, layer);
      st = lds4f(SM_STAT + ((4 * e + w) * 8 + g) * 16);
      PROF(34 + layer);
      wg_wait<0>();
      if (!rows_nan(acc[0] + rn, acc[2]) || late) break;
    }
  }
  mbar_arrive1(B_QE);
  PROFK(8 + 12 * layer);
  uint32_t Q[4][4], K[4][2][2], V[4][2][2];
  {
#pragma unroll
    for (int z = 0; z < 8; ++z) {
      const float* a = acc + 32 + 4 * z; const float* b = acc + 64 + 4 * z;
      K[z >> 1][1][z & 1] = pack2((a[2] - st.z * cs[z].x) * st.w, (a[3] - st.z * cs[z].y) * st.w);
      V[z >> 1][1][z & 1] = movm(pack2((b[2] - st.z * cs[8 + z].x) * st.w, (b[3] - st.z * cs[8 + z].y) * st.w));
    }
    const int hop = (G >> 1) & 3;
    const uint32_t kv = SM_KV + (2 * hop + (w & 1)) * 2048 + lane * 16;
    uint4* h = SCR->H[layer] + (c * 256 + (w & 1) * 128 + lane);
    if (hop == 3) {
#pragma unroll
      for (int z = 0; z < 4; ++z) str4(h + 2048 + z * 32, K[z][1][0], K[z][1][1], V[z][1][0], V[z][1][1]);
    } else {
      mbar_wait(B_F + 16, layer);
#pragma unroll
      for (int z = 0; z < 4; ++z) sts4(kv + z * 512, K[z][1][0], K[z][1][1], V[z][1][0], V[z][1][1]);
      bar_arrive(NB_B + hop, 128);
    }
    PROF(42);
    uint4 hv[4];
#pragma unroll
    for (int z = 0; z < 4; ++z) { hv[z] = make_uint4(0, 0, 0, 0); ldr4_if(hv[z], h + z * 32, G >= 2 && hop == 0); }
#pragma unroll
    for (int z = 0; z < 8; ++z) {
      const float* a = acc + 32 + 4 * z; const float* b = acc + 64 + 4 * z;
      K[z >> 1][0][z & 1] = pack2((a[0] - st.x * cs[z].x) * st.y, (a[1] - st.x * cs[z].y) * st.y);
      V[z >> 1][0][z & 1] = movm(pack2((b[0] - st.x * cs[8 + z].x) * st.y, (b[1] - st.x * cs[8 + z].y) * st.y));
    }
#pragma unroll
    for (int z = 0; z < 8; ++z) {
      const float2 cq = lds2f(csb + z * 32);
      const float* a = acc + 4 * z;
      Q[z >> 1][2 * (z & 1)] = pack2(a[0] - st.x * cq.x, a[1] - st.x * cq.y);
      Q[z >> 1][2 * (z & 1) + 1] = pack2(a[2] - st.z * cq.x, a[3] - st.z * cq.y);
    }
    PROF(27);
    const bool p0 = 2 * t > g, p1 = 2 * t + 1 > g, first = G < 2;
    float s[4][4], mx[4][2];
#pragma unroll
    for (int z = 0; z < 4; ++z) {
      float S[4];
      mma16z(s[z], Q[z][0], Q[z][1], Q[z][2], Q[z][3], K[z][0][0], K[z][0][1]);
      mma16z(S, Q[z][0], Q[z][1], Q[z][2], Q[z][3], K[z][1][0], K[z][1][1]);
      s[z][2] = p0 ? s[z][2] : S[2]; s[z][3] = p1 ? s[z][3] : S[3];
    }
    const float sc0 = st.y * (0.25f * 1.4426950408889634f), sc1 = st.w * (0.25f * 1.4426950408889634f);
    uint32_t pw[4][2];
#pragma unroll
    for (int r = 1; r >= 0; --r) {
      if (r == 0) {
        if (hop) {
          bar_sync(NB_B + hop - 1, 128);
#pragma unroll
          for (int z = 0; z < 4; ++z) hv[z] = lds4(kv - 4096 + z * 512);
        } else fixo(hv, h);
        PROFD(41, hv[3].x);
#pragma unroll
        for (int z = 0; z < 4; ++z) {
          float S[4];
          mma16z(S, Q[z][0], Q[z][1], Q[z][2], Q[z][3], hv[z].x, hv[z].y);
          if (first) S[0] = S[1] = __uint_as_float(0xFF800000u);
          s[z][0] = p0 ? S[0] : s[z][0]; s[z][1] = p1 ? S[1] : s[z][1];
        }
      }
#pragma unroll
      for (int z = 0; z < 4; ++z) mx[z][r] = fmaxf(s[z][2 * r], s[z][2 * r + 1]);
#pragma unroll
      for (int o = 1; o < 3; ++o)
#pragma unroll
        for (int z = 0; z < 4; ++z) mx[z][r] = fmaxf(mx[z][r], __shfl_xor_sync(0xffffffffu, mx[z][r], o));
#pragma unroll
      for (int z = 0; z < 4; ++z) pw[z][r] = pack2(ex2((s[z][2 * r] - mx[z][r]) * (r ? sc1 : sc0)), ex2((s[z][2 * r + 1] - mx[z][r]) * (r ? sc1 : sc0)));
    }
    mbar_wait(layer ? B_N : B_Z, layer);
    const uint32_t M = (p0 ? 0xFFFFu : 0u) | (p1 ? 0xFFFF0000u : 0u);
    uint4* O = SCR->O + ((J * 8 + cg) * 512 + (2 * (w & 2) + (w & 1)) * 64 + t * 8 + g);
#pragma unroll
    for (int h2 = 0; h2 < 2; ++h2) {
      uint32_t ow[2][4];
#pragma unroll
      for (int z = 0; z < 2; ++z) {
        const int n = 2 * h2 + z;
        const uint32_t w0 = pw[n][0], w1 = pw[n][1];
        float sm[4] = {0.f, 0.f, 0.f, 0.f}, Oa[2][4];
        mma8(sm, w0, w1, 0x3F803F80u);
        mma16z(Oa[0], w0 & ~M, w1 & M, 0u, w1 & ~M, V[n][0][0], V[n][1][0]); mma8(Oa[0], w0 & M, 0u, hv[n].z);
        mma16z(Oa[1], w0 & ~M, w1 & M, 0u, w1 & ~M, V[n][0][1], V[n][1][1]); mma8(Oa[1], w0 & M, 0u, hv[n].w);
        const float i0 = rcp(sm[0]), i1 = rcp(sm[2]);
#pragma unroll
        for (int d = 0; d < 2; ++d) { ow[0][2 * z + d] = pack2(Oa[d][0] * i0, Oa[d][1] * i0); ow[1][2 * z + d] = pack2(Oa[d][2] * i1, Oa[d][3] * i1); }
      }
#pragma unroll
      for (int hi = 0; hi < 2; ++hi) str4(O + hi * 128 + h2 * 32, ow[hi][0], ow[hi][1], ow[hi][2], ow[hi][3]);
    }
  }
  str1(SCR->OF[layer] + (J * 32 + cg * 4 + w), 1);
  mbar_arrive1(B_AT + 8 * e + (lds1(csb) & P.zero));
  PROFK(9 + 12 * layer);
  float ac[32];
  res_init(ac, res);
  const uint32_t so = SM_O + e * O_E;
  uint2* xo = opqp(layer ? (uint2*)(P.out + ((16 * G + 2 * (lane >> 3)) * 512 + 64 * cg + 8 * (lane & 7)))
                         : (uint2*)SCR->XG[1] + ((32 * (cg & 3) + t) * 2048 + (cg >> 2) * 512 + xg_off(G, g)));
  const uint32_t stg = SM_X + (4 * e + w) * 2048;
  const uint32_t sw = opq(stg + (lane & 15) * 128 + (((lane >> 4) ^ (lane & 7)) * 16)), sr = opq(stg + (lane >> 3) * 128 + (((lane & 7) ^ (lane >> 3)) * 16));
  uint4* ps = opqp(&SCR->PS[(G * 8 + cg) * 8 + g]);
  {
    const uint32_t bo = B_O + 32 * e;
    const uint32_t dw = (SM_WO >> 4) | (512 << 16), da = dlo(so, 512);
    mbar_wait(B_WO, layer);
#pragma unroll
    for (int j = 0; j < 4; ++j) {
      mbar_wait(bo + 8 * j, layer);
      if (j == 0) { PROFK(32 + layer); mbar_wait(B_AT + 8, layer); }
      wg_fence();
#pragma unroll
      for (int k = 8 * j; k < 8 * j + 8; ++k) {
        const uint32_t a = da + (k >> 2) * 512 + (k & 3) * 8, b = dw + (k & 3) * 1024 + (k >> 2) * 128;
        wg_ss64<1>(ac, a, b);
      }
      wg_commit();
    }
#pragma unroll 1
    for (uint32_t late = P.zero;; late = 1) {
      if (late) {
        const uint16_t* op = (const uint16_t*)(SCR->O + (J * 4096 + w * 128 + g));
        wg_wait<0>();
        res_init(ac, res);
#pragma unroll 1
        for (int k = 0; k < 512; ++k) {
          const uint16_t* q = op + (k >> 6) * 4096 + (k & 56) * 8 + (k & 7);
          slow_step(ac, ldnan(q), ldnan(q + 512), P.wo + (((k & ~31) + 4 * (k & 6) + ((k >> 2) & 6) + (k & 1)) * 512 + 64 * cg + 2 * t), P.zero);
        }
      }
      wg_wait<0>();
      if (!rows_nan(ac[0], ac[2]) || late) break;
    }
  }
  PROFK(10 + 12 * layer);
#pragma unroll
  for (int j = 0; j < 16; ++j) res[j >> 1][j & 1] = pack2(ac[2 * j], ac[2 * j + 1]);
  if (layer == 0) {
    float s[2][4], q0[2][4], q1[2][4];
#pragma unroll
    for (int j = 0; j < 2; ++j) gram<true>(s[j], q0[j], q1[j], res[2 * j][0], res[2 * j][1], res[2 * j + 1][0], res[2 * j + 1][1]);
#pragma unroll
    for (int j = 0; j < 2; ++j) gram<false>(s[j], q0[j], q1[j], res[2 * j + 4][0], res[2 * j + 4][1], res[2 * j + 5][0], res[2 * j + 5][1]);
    const bool od = g & 1;
    str4_if(ps, nzmap(__float_as_uint(s[0][0] + s[1][0])), __float_as_uint(od ? q0[0][1] + q0[1][1] : q0[0][0] + q0[1][0]),
            __float_as_uint(s[0][2] + s[1][2]), __float_as_uint(od ? q1[0][3] + q1[1][3] : q1[0][2] + q1[1][2]), t == (g >> 1));
#pragma unroll
    for (int j = 0; j < 8; ++j) {
      str2(xo + j * 8192, nzmap(prmt(res[j][0], res[j][1], 0x5410)), prmt(res[j][0], res[j][1], 0x7632));
    }
    mbar_arrive1(B_ED + 8 * e);
  } else {
#pragma unroll
    for (int j = 0; j < 8; j += 2) stsm4(sw ^ (j * 16), res[j][0], res[j][1], res[j + 1][0], res[j + 1][1]);
    __syncwarp();
    uint4 v[4];
#pragma unroll
    for (int k = 0; k < 4; ++k) v[k] = lds4((sr ^ ((k & 1) * 64)) + k * 512);
#pragma unroll
    for (int k = 0; k < 4; ++k) stw4(xo + ((k & 1) * 8 + (k >> 1)) * 128, v[k].x, v[k].y, v[k].z, v[k].w);
  }
  PROFK(11 + 12 * layer);
}

DEV void col_sums(const Params& P, int c, int wa, int lane) {
  const int i = c >> 3, cg = c & 7;
  uint4 wv[8];
#pragma unroll
  for (int k = 0; k < 8; ++k) wv[k] = ldnc4(P.wqkv + ((32 * i + (lane >> 3)) * 1536 + wa * 512 + 64 * cg + 8 * (lane & 7)) + 4 * k * 1536);
  float cs[8];
  zero(cs);
#pragma unroll
  for (int k = 0; k < 8; ++k) {
    cs[0] += bflo(wv[k].x); cs[1] += bfhi(wv[k].x); cs[2] += bflo(wv[k].y); cs[3] += bfhi(wv[k].y);
    cs[4] += bflo(wv[k].z); cs[5] += bfhi(wv[k].z); cs[6] += bflo(wv[k].w); cs[7] += bfhi(wv[k].w);
  }
  const bool b4 = lane & 16, b3 = lane & 8;
#pragma unroll
  for (int k = 0; k < 4; ++k) cs[k] = (b4 ? cs[k + 4] : cs[k]) + __shfl_xor_sync(0xffffffffu, b4 ? cs[k] : cs[k + 4], 16);
#pragma unroll
  for (int k = 0; k < 2; ++k) cs[k] = (b3 ? cs[k + 2] : cs[k]) + __shfl_xor_sync(0xffffffffu, b3 ? cs[k] : cs[k + 2], 8);
  str2((uint2*)SCR->CS + (i * 768 + wa * 256 + 32 * cg + 4 * (lane & 7) + (lane >> 3)), nzmap(__float_as_uint(cs[0])), __float_as_uint(cs[1]));
}
DEV void col_gather(const Params& P, int c, int wa, int lane) {
  const uint2* p = (const uint2*)SCR->CS + (wa * 256 + 32 * (c & 7) + lane);
#pragma unroll 1
  for (int it = 0;; ++it) {
    float a = 0.f, b = 0.f;
    uint32_t m = ~0u;
#pragma unroll
    for (int k = 0; k < 16; ++k) { const uint2 q = ldr2(p + k * 768); m = min(m, q.x); a += __uint_as_float(q.x); b += __uint_as_float(q.y); }
    if (__all_sync(0xffffffffu, m != 0u)) { sts2f(SM_CS + wa * 256 + lane * 8, a, b); break; }
    spin_guard(it);
  }
  __syncwarp();
  mbar_arrive1(B_CS);
}

DEV void aux_prologue(const Params& P, int c, int wa, int lane, uint4 (&s0)[2][2]) {
  const int g = lane >> 2, t = lane & 3, G = stat_group(c);
  {
    uint32_t w[16][2];
    const uint16_t* row = P.x0 + ((16 * G + 2 * g) * 512 + 128 * wa + 8 * t);
    bar_sync(NB_Y, 384);
    __nanosleep(100);
#pragma unroll
    for (int z = 0; z < 8; ++z) {
      const uint4 v = ldw4(row + (z & 1) * 512 + (z >> 1) * 32);
      const int o = 4 * (z >> 1);
      w[o][z & 1] = v.x; w[o + 1][z & 1] = v.y; w[o + 2][z & 1] = v.z; w[o + 3][z & 1] = v.w;
    }
    PROF(34);
    PROFD(35, w[0][0]);
    PROFD(36, w[15][1]);
    uint2* xo = (uint2*)SCR->XG[0] + ((64 * (wa & 1) + 4 * t) * 2048 + (wa >> 1) * 512 + xg_off(G, g));
#pragma unroll
    for (int n = 0; n < 16; ++n) str2(xo + (16 * (n >> 2) + (n & 3)) * 2048, nzmap(prmt(w[n][0], w[n][1], 0x5410)), prmt(w[n][0], w[n][1], 0x7632));
    float s[2][4], q0[2][4], q1[2][4];
#pragma unroll
    for (int z = 0; z < 8; ++z) {
      const int o = 4 * (z >> 1), r = z & 1;
      if (z < 2) gram<true>(s[r], q0[r], q1[r], w[o][r], w[o + 1][r], w[o + 2][r], w[o + 3][r]);
      else gram<false>(s[r], q0[r], q1[r], w[o][r], w[o + 1][r], w[o + 2][r], w[o + 3][r]);
    }
    const bool od = g & 1;
    if (t == (g >> 1))
      sts4f(SM_MISC + (wa * 8 + g) * 16, s[0][0] + s[0][2], od ? q0[0][1] + q1[0][3] : q0[0][0] + q1[0][2],
            s[1][0] + s[1][2], od ? q0[1][1] + q1[1][3] : q0[1][0] + q1[1][2]);
    bar_arrive(NB_P0, 192);
  }
  PROF(2);
  if (lane == 0)
    asm volatile("cp.async.bulk.prefetch.L2.global [%0],4096;" :: "l"(wa < 3 ? P.wqkv + (3 * c + wa) * 2048 : P.wo + c * 2048) : "memory");
  bar_sync(NB_Y + 1, 256);
  sload(P, c, 32 * wa + lane, 0, s0);
}

DEV void stat_part(const Params& P, int c, int wa, int lane, int layer, int h, float (&v)[2]) {
  lane = opq(lane);
  const int e = wa >> 1;
  uint32_t x[4][4];
  mbar_wait(B_A + 16 * e, h); mbar_wait(B_A + 16 * e + 8, h);
#pragma unroll
  for (int k = 0; k < 4; ++k) ldsm4t(x[k], SM_A + e * A_E + (128 * (wa & 1) + lane) * 128 + (((c ^ lane) & 7) * 16) + k * 4096);
  float s[4] = {0.f, 0.f, 0.f, 0.f};
#pragma unroll
  for (int k = 0; k < 16; ++k) { const float a = bflo(x[k >> 2][k & 3]), b = bfhi(x[k >> 2][k & 3]); s[0] += a; s[1] += a * a; s[2] += b; s[3] += b * b; }
  s[0] += s[2]; s[1] += s[3];
  if (RARE(rows_nan(s[1], s[1]))) {
    const uint16_t* q = (const uint16_t*)(SCR->XF[layer] + ((32 * e + 2 * (c >> 3) + h) * 2048 + (wa & 1) * 1024)) + (lane >> 2);
    s[0] = s[1] = 0.f;
#pragma unroll 1
    for (int k = 0; k < 32; ++k) {
      const int r = 2 * (lane & 3) + (k & 1);
      const float a = ldnan(q + ((k >> 1) * 8 + r) * 64 + ((c ^ r) & 7) * 8);
      s[0] += a; s[1] += a * a;
    }
  }
  v[0] += s[0]; v[1] += s[1];
  __syncwarp();
}
DEV void stat_finish(const Params& P, int c, int wa, int lane, int layer, float (&v)[2]) {
  lane = opq(lane);
  const bool b = lane & 1;
  const float s = (b ? v[1] : v[0]) + __shfl_xor_sync(0xffffffffu, b ? v[0] : v[1], 1);
  str1((uint32_t*)SCR->ST[layer] + ((128 * (wa >> 1) + c) * 64 + (wa & 1) * 32 + lane), nzmap(__float_as_uint(s)));
  const uint4* sp = SCR->ST[layer] + ((128 * (wa >> 1) + (c & ~7) + 4 * (wa & 1) + (lane >> 3)) * 16 + (lane & 7));
  uint4 x, y;
  for (int it = 0;; ++it) {
    x = ldr4(sp); y = ldr4(sp + 8);
    if (__all_sync(0xffffffffu, min(min(min(x.x, x.y), min(x.z, x.w)), min(min(y.x, y.y), min(y.z, y.w))) != 0u)) break;
    spin_guard(it);
  }
  const uint32_t q = ln_sums((__uint_as_float(x.x) + __uint_as_float(x.z)) + (__uint_as_float(y.x) + __uint_as_float(y.z)),
                             (__uint_as_float(x.y) + __uint_as_float(x.w)) + (__uint_as_float(y.y) + __uint_as_float(y.w)));
  sts2f(SM_STAT + (16 * wa + (lane >> 4) * 8 + (lane & 7)) * 16 + (lane & 8), bflo(q), rcp(bfhi(q)));
  __syncwarp();
  mbar_arrive1(B_ST + 4 * (wa & 2));
}

DEV void nan_source(uint32_t a, int lane) {
#pragma unroll
  for (int k = 0; k < 4; ++k) sts4(a + k * 512 + lane * 16, FILL, FILL, FILL, FILL);
  fence_async_smem();
  __syncwarp();
}
DEV void load_a(const Params& P, int J, int e, int layer, int h) {
  const uint4* src = SCR->XF[layer] + (2 * J + h) * 2048;
  const uint32_t dst = SM_A + e * A_E, b = B_A + 16 * e;
  mbar_expect1(b, 8192); bulk(dst, src, 8192, b);
  mbar_expect1(b + 8, 24576); bulk(dst + 8192, src + 512, 24576, b + 8);
}
DEV void load_o(const Params& P, int c, int e, int layer, int lane) {
  const int J = 16 * e + (c >> 3);
  mbar_wait(B_AT + 8 * e, layer);
  if (!e) pause(260);
#pragma unroll 1
  for (int it = 0;; ++it) {
    spin_guard(it);
    if (__all_sync(0xffffffffu, ldr1(SCR->OF[layer] + J * 32 + lane) != 0u)) break;
  }
#pragma unroll
  for (int j = 0; j < 4; ++j) bulk(SM_O + e * O_E + 16384 * j, SCR->O + (J * 4096 + j * 1024), 16384, B_O + 32 * e + 8 * j);
  PROFK(9 + e + 12 * layer);
}

__global__ void __launch_bounds__(NTHR, 1)
fused_kernel(const __grid_constant__ Params P, const __grid_constant__ CUtensorMap mapW, const __grid_constant__ CUtensorMap mapWo,
             const __grid_constant__ CUtensorMap mapX) {
  extern __shared__ __align__(1024) uint8_t smem_raw[];
  const int warp = __shfl_sync(0xffffffffu, threadIdx.x >> 5, 0), lane = threadIdx.x & 31;
  uint32_t smid; asm volatile("mov.u32 %0,%%smid;" : "=r"(smid));
  const uint32_t* pw = (const uint32_t*)&P + threadIdx.y;
  const int role = P.role[(smid >> 1) + threadIdx.y] + (smid & 1) + (pw[0] & pw[12]);
  const int c = __shfl_sync(0xffffffffu, pw[1] ? role : blockIdx.x, 0);
  if (c >= 128) {
#pragma unroll 1
    for (int k = (c - 128) * NTHR + threadIdx.x; k < 131072; k += P.spare * NTHR) str4(SCR->XG[1] + k, 0, 0, 0, 0);
    __threadfence();
    __syncthreads();
    if (warp == 0) { cnt_wait(SCR->C + 1, lane); cnt_add1(SCR->C + 6); }
    __syncthreads();
#pragma unroll 1
    for (int k = (c - 128) * NTHR + threadIdx.x; k < 131072; k += P.spare * NTHR) str4(SCR->XG[0] + k, 0, 0, 0, 0);
    return;
  }
#define DONE() do {} while (0)
  const int cg = c & 7;
  if (warp < 8) {
    PROF(46);
    kgen(P, c, warp, lane);
    PROFK(1);
    bar_sync(0, 384);
#pragma unroll 1
    for (int layer = 0; layer < 2; ++layer) {
#pragma unroll 1
      for (int rho = 0; rho < 2; ++rho) {
        const int wz = warp + ((rho + layer) & P.zero);
        conv_round(wz >> 2, rho, wz & 3, lane_id());
        PROFK(6 + rho + 12 * layer);
      }
      const int z = layer & P.zero;
      attn_phase(P, c + z, (warp + z) >> 2, (warp + z) & 3, lane_id(), layer);
    }
    DONE();
  } else if (warp < 12) {
    asm volatile("setmaxnreg.dec.sync.aligned.u32 %0;" :: "n"(REG_AUX));
    uint4 x[2][2][2], s[2][2];
    aux_prologue(P, c, warp - 8, lane, s);
    PROF(1);
    const int c0 = c;
#pragma unroll 1
    for (int layer = 0;; ++layer) {
      const int c = c0 + (layer & P.zero), wa = warp - 8 + (layer & P.zero);
#define lane lane_id()
#define j (32 * wa + lane_id())
      {
        const uint32_t za = region(wa) + lane * 16 - 512;
        sts4(za + R_U, 0, 0, 0, 0); sts4(za + R_X5, 0, 0, 0, 0); sts4(za + R_X3, 0, 0, 0, 0);
      }
      if (lane == 0) sts4(region(wa) + R_BE, 0, 0, 0, 0);
      uint32_t u[4][4];
      uload(P, c, j, layer, x, s);
      uprep(j, 1, x[1], s[1], u);
      uprep(j, 0, x[0], s[0], u);
      fence_async_smem();
      bar_arrive(NB_U, NBARU);
      PROFK(5 + 12 * layer);
      bar_sync(NB_H, 192);
      box_full(j, u, P.zero);
      PROF(3 + 12 * layer);
      mbar_wait(B_Z, 0);
      conv_out(c, j, 0, x, u[0], SCR->XF[layer], P.zero);
      PROF(32);
      conv_out(c, j, 1, x, u[1], SCR->XF[layer], P.zero);
      PROF(6 + 12 * layer);
      if (layer == 0 && wa < 3) col_sums(P, c, wa, lane);
      conv_out(c, j, 2, x, u[2], SCR->XF[layer], P.zero);
      PROF(33);
      conv_out(c, j, 3, x, u[3], SCR->XF[layer], P.zero);
      PROFK(7 + 12 * layer);
      float v[2];
      zero(v);
#pragma unroll 1
      for (int h = 0; h < 2; ++h) {
        stat_part(P, c, wa, lane, layer, h, v);
        if (h) break;
        mbar_arrive1(B_AE + 4 * (wa & 2));
        if (layer == 0 && wa < 3) col_gather(P, c, wa, lane);
      }
      PROF(9 + 12 * layer);
      stat_finish(P, c, wa, lane, layer, v);
      PROF(8 + 12 * layer);
      if (layer) break;
      sload(P, c, j, 1, s);
#undef lane
#undef j
    }
    DONE();
  } else {
    asm volatile("setmaxnreg.dec.sync.aligned.u32 %0;" :: "n"(REG_PROD));
    if (s2u(smem_raw) != SB) __trap();
#pragma unroll 1
    for (int n = warp - 12; n < 38; n += 4)
      asm volatile("{.reg .pred p; elect.sync _|p,0xffffffff; @p mbarrier.init.shared::cta.b64 [%0],%1;}"
                   :: "r"(SM_BAR + n * 8), "r"(n > 14 ? 1 : (int)(0x322866444444444ull >> (4 * n)) & 15) : "memory");
    fence_async_smem();
    bar_sync(NB_AUX, 128);
    bar_arrive(0, 384); bar_arrive(NB_Y + 1, 256);
    PROF(1);
    if (warp == 12) {
      if (lane == 0) {
        asm volatile("prefetch.tensormap [%0];" :: "l"(&mapW) : "memory");
        asm volatile("prefetch.tensormap [%0];" :: "l"(&mapWo) : "memory");
        asm volatile("prefetch.tensormap [%0];" :: "l"(&mapX) : "memory");
      }
      nan_source(slot(12), lane);
      mbar_wait(B_U, 0);
#pragma unroll 1
      for (int k = 0; k < 8; ++k) tma2_store(&mapX, slot(12), 128 * c, 8 * k);
#pragma unroll 1
      for (int k = 0; k < 4; ++k) bulk_store(SCR->H[k >> 1] + ((c + 8) * 256 + (k & 1) * 128), slot(12), 2048);
#pragma unroll 1
      for (int k = 0; k < 8; ++k) bulk_store(SCR->O + (c * 512 + (k >> 2) * 65536 + (k & 3) * 128), slot(12), 2048);
      bulk_wait();
      mbar_arrive1(B_Z);
      PROF(24);
#pragma unroll 1
      for (int layer = 0; layer < 2; ++layer) {
        mbar_wait(B_V, layer);
        if (layer == 1 && c < 4 && ((0x47 >> lane) & 1)) str1(SCR->C + c * 32 + lane, 0);
        mbar_expect1(B_WF, 4 * 24576);
#pragma unroll
        for (int k = 0; k < 4; ++k) tma3(slot(wslot(k)), &mapW, 64 * cg, 64 * k, 0, B_WF);
        mbar_wait(B_WF, layer);
        mbar_expect1(B_W4, 2 * 24576);
#pragma unroll
        for (int k = 4; k < 6; ++k) tma3(slot(wslot(k)), &mapW, 64 * cg, 64 * k, 0, B_W4);
        bar_sync(NB_AUX, 64);
#pragma unroll 1
        for (int k = 0; k < 2; ++k) {
          mbar_expect1(B_W6 + 8 * k, 24576);
          mbar_wait(B_F + 8 * k, layer);
          tma3(slot(3 * k), &mapW, 64 * cg, 384 + 64 * k, 0, B_W6 + 8 * k);
        }
        mbar_expect1(B_WO, 65536);
        mbar_wait(B_AE + 8, layer);
        nan_source(slot(12), lane);
        uint4* fp = layer ? SCR->O + c * 512 : SCR->XF[1] + c * 512;
#pragma unroll 1
        for (int r = 7; r >= 0; --r) {
          __nanosleep(30);
          if (r >= 4) {
            bulk_store(fp + (r & 3) * 128, slot(12), 2048); bulk_store(fp + 65536 + (r & 3) * 128, slot(12), 2048);
          }
          if (r == 3) { bulk_wait(); __threadfence(); mbar_arrive1(B_N); PROF(9 + 12 * layer); }
          if (r == 1) mbar_wait(B_F + 16, layer);
          tma4(SM_WO + r * 8192, &mapWo, 64 * cg, 0, r >> 1, 32 * (r & 1), B_WO);
        }
        PROF(8 + 12 * layer);
      }
      DONE();
    } else if (warp == 13) {
      const int G = stat_group(c);
#pragma unroll 1
      for (int layer = 0; layer < 2; ++layer) {
        float z[4];
        if (layer == 0) {
          bar_sync(NB_P0, 192);
          const float4 a = lds4f(SM_MISC + lane * 16);
          z[0] = a.x; z[1] = a.y; z[2] = a.z; z[3] = a.w;
        } else {
          mbar_wait(B_ED + 2 * (c & 4), 0);
          uint4* ps = &SCR->PS[G * 64 + lane];
          uint4 a, b;
          for (int it = 0;; ++it) {
            a = ldr4(ps); b = ldr4(ps + 32);
            if (__all_sync(0xffffffffu, min(a.x, b.x) != 0u)) break;
            spin_guard(it);
          }
          z[0] = __uint_as_float(a.x) + __uint_as_float(b.x); z[1] = __uint_as_float(a.y) + __uint_as_float(b.y);
          z[2] = __uint_as_float(a.z) + __uint_as_float(b.z); z[3] = __uint_as_float(a.w) + __uint_as_float(b.w);
        }
#pragma unroll
        for (int o = 8; o < 32; o <<= 1)
#pragma unroll
          for (int k = 0; k < 4; ++k) z[k] += __shfl_xor_sync(0xffffffffu, z[k], o);
        const uint32_t w0 = ln_sums(z[0], z[1]), w1 = ln_sums(z[2], z[3]);
        const uint32_t r = nzmap(pack2(rcp(bfhi(w0)), rcp(bfhi(w1)))), m = prmt(w0, w1, 0x5410);
        uint2* so = (uint2*)&SCR->SR[layer][lane >> 3][sr_off(G, lane)] + (lane & 1);
        str2(so, r, m); str2(so + 4 * 1024, r, m);
        PROF(4 + 12 * layer);
        box_help(0, lane);
        PROF(6 + 12 * layer);
      }
      DONE();
    } else if (warp == 14) {
#pragma unroll 1
      for (int layer = 0; layer < 2; ++layer) {
        if (layer) { mbar_wait(B_N, 0); mbar_wait(B_ED, 0); mbar_wait(B_ED + 8, 0); } else bar_sync(NB_P0, 192);
        cnt_add1(SCR->C + (c >> 5) * 32 + 3 * layer);
        if (layer == 0) bar_arrive(NB_P0 + 1, 288);
        mbar_expect1(B_E, 16384);
        PROF(4 + 12 * layer);
        cnt_wait(SCR->C + 3 * layer, lane);
        mbar_arrive1(B_U);
        bulk(SM_X, SCR->XG[layer] + c * 1024, 16384, B_E);
        PROFK(5 + 12 * layer);
        if (layer == 0) {
          mbar_wait(B_Z, 0);
          __threadfence();
          PROF(11);
        }
#pragma unroll 1
        for (int n = 0; n < 4; ++n) {
          if (n == 0) { mbar_wait(B_RD, layer); cnt_add1(SCR->C + (c >> 5) * 32 + 3 * layer + 1); }
          if (!(n & 1)) cnt_wait(SCR->C + 3 * layer + 1 + (n >> 1), lane);
          if (n == 2) PROF(7 + 12 * layer);
          mbar_wait((n & 2 ? B_AE : B_RD) + 8 * (n & 1), layer);
          load_a(P, 16 * (n & 1) + (c >> 3), n & 1, layer, n >> 1);
          bar_arrive_if(NB_AUX, 64, n == 2);
          if (!(n & 1)) PROFK(6 + n + 12 * layer);
        }
#pragma unroll 1
        for (int n = 0; n < 8; ++n) mbar_expect1(B_O + 8 * n, 16384);
        if (layer == 0)
          for (int it = 0; ldr1(SCR->C + 6) < P.spare; ++it) spin_guard(it);
        mbar_wait(B_QE, layer);
#pragma unroll 1
        for (int e = 0; e < 2; ++e) load_o(P, c, e, layer, lane);
      }
      DONE();
    }
    if (warp == 15) {
      const int G = stat_group(c);
      str4(&SCR->ST[0][(lane >> 4) * 2048 + c * 16 + (lane & 15)], 0, 0, 0, 0); str4(&SCR->ST[1][(lane >> 4) * 2048 + c * 16 + (lane & 15)], 0, 0, 0, 0);
      if (lane < 4) str4(SCR->OF[lane >> 1] + ((lane & 1) * 512 + c * 4), 0, 0, 0, 0);
      str4(&SCR->PS[G * 64 + lane], 0, 0, 0, 0); str4(&SCR->PS[G * 64 + 32 + lane], 0, 0, 0, 0);
      str4(&SCR->SR[1][lane >> 2][sr_off(G, 2 * lane)], 0, 0, 0, 0);
      if (c < 4 && lane < 3) str1(SCR->C + c * 32 + 3 + lane, 0);
#pragma unroll
      for (int k = 0; k < 3; ++k) str2((uint2*)SCR->CS + ((c >> 3) * 768 + k * 256 + 32 * cg + lane), 0, 0);
      __threadfence();
#pragma unroll 1
      for (int layer = 0; layer < 2; ++layer) {
        PROF(4 + 12 * layer);
        box_help(1, lane);
        if (layer) str4(&SCR->SR[0][lane >> 2][sr_off(G, 2 * lane)], 0, 0, 0, 0);
        mbar_wait(B_RD + 8, layer);
        cnt_add1(SCR->C + (c >> 5) * 32 + 3 * layer + 2);
        if (P.spare == 0) {
#pragma unroll 1
          for (int k = 0; k < 32; ++k) str4(SCR->XG[layer] + (c * 1024 + k * 32 + lane), 0, 0, 0, 0);
        }
      }
      mbar_watch(B_O + 56, 1);
    }
  }
}

typedef CUresult (*EncodeFn)(CUtensorMap*, CUtensorMapDataType, cuuint32_t, void*, const cuuint64_t*, const cuuint64_t*,
                             const cuuint32_t*, const cuuint32_t*, CUtensorMapInterleave, CUtensorMapSwizzle,
                             CUtensorMapL2promotion, CUtensorMapFloatOOBfill);

static int place_roles(uint8_t* role) {
  int dev = 0, nsm = 0;
  cudaGetDevice(&dev);
  cudaDeviceGetAttribute(&nsm, cudaDevAttrMultiProcessorCount, dev);
  if (nsm <= 128 || nsm > 144 || (nsm & 1)) return 0;
  cudaFuncSetAttribute(fused_kernel, cudaFuncAttributeNonPortableClusterSizeAllowed, 1);
  int occ[9] = {0};
  for (int k = 2; k <= 8; ++k) {
    cudaLaunchConfig_t cfg = {};
    cudaLaunchAttribute at[1];
    at[0].id = cudaLaunchAttributeClusterDimension;
    at[0].val.clusterDim.x = 2 * k; at[0].val.clusterDim.y = 1; at[0].val.clusterDim.z = 1;
    cfg.gridDim = dim3(2 * k); cfg.blockDim = dim3(NTHR); cfg.dynamicSmemBytes = SM_TOTAL; cfg.attrs = at; cfg.numAttrs = 1;
    if (cudaOccupancyMaxActiveClusters(&occ[k], fused_kernel, &cfg) != cudaSuccess) { cudaGetLastError(); occ[k] = 0; }
  }
  int n[10];
  n[7] = occ[8]; n[6] = occ[7]; n[5] = occ[6] - 0; n[4] = occ[5];
  n[3] = occ[4] - n[7]; n[1] = occ[2] - n[3] - n[5] - n[7]; n[0] = n[2] = n[1];
  n[8] = occ[3] - n[2] - n[5];
  const int ntpc = nsm / 2;
  int sum = 0;
  bool ok = n[0] > 0 && n[0] <= 8;
  for (int r = 0; r < 9; ++r) { ok = ok && n[r] >= 0 && (r == 0 || n[r] <= n[r - 1]); sum += n[r]; }
  if (!ok || sum > ntpc) { for (int r = 0; r < 9; ++r) n[r] = r < 8 ? 8 : 0; sum = 64; }
  int tp[8][9], cnt[8] = {0}, pool[72], np = 0, id = 0;
  for (int r = 0; r < 9; ++r)
    for (int g = n[0] - n[r]; g < n[0]; ++g) tp[g][cnt[g]++] = id++;
  for (; id < ntpc; ++id) pool[np++] = id;
  int order[72], no = 0;
  for (int g = 0; g < n[0]; ++g) {
    const int full = cnt[g] / 4 * 4;
    for (int k = 0; k < cnt[g]; ++k) { if (k < full) order[no++] = tp[g][k]; else pool[np++] = tp[g][k]; }
  }
  for (int k = 0; k < np; ++k) order[no++] = pool[k];
  for (int k = 0; k < ntpc; ++k) role[order[k]] = 2 * k;
  return nsm;
}

extern "C" void kernel_launch(void* const* d_in, const int* in_sizes, int n_in, void* d_out, int out_size) {
  (void)in_sizes; (void)n_in; (void)out_size;
  static EncodeFn enc = nullptr;
  static uint8_t role[72];
  static int nsm = 0;
  static Scratch* scratch = nullptr;
  if (!enc) {
    void* fn = nullptr;
    cudaDriverEntryPointQueryResult qr;
    cudaGetDriverEntryPoint("cuTensorMapEncodeTiled", &fn, cudaEnableDefault, &qr);
    enc = (EncodeFn)fn;
    cudaFuncSetAttribute(fused_kernel, cudaFuncAttributeMaxDynamicSharedMemorySize, SM_TOTAL);
    nsm = place_roles(role);
    cudaGetSymbolAddress((void**)&scratch, g_S);
  }
  CUtensorMap mW, mWo, mX;
  {
    cuuint64_t dim[3] = {512, 512, 3}, str[2] = {3072, 1024};
    cuuint32_t box[3] = {64, 64, 3}, es[3] = {1, 1, 1};
    enc(&mW, CU_TENSOR_MAP_DATA_TYPE_BFLOAT16, 3, d_in[10], dim, str, box, es, CU_TENSOR_MAP_INTERLEAVE_NONE,
        CU_TENSOR_MAP_SWIZZLE_128B, CU_TENSOR_MAP_L2_PROMOTION_NONE, CU_TENSOR_MAP_FLOAT_OOB_FILL_NONE);
  }
  {
    cuuint64_t dim[4] = {512, 2, 4, 64}, str[3] = {1024, 2048, 8192};
    cuuint32_t box[4] = {64, 2, 1, 32}, es[4] = {1, 1, 1, 1};
    enc(&mWo, CU_TENSOR_MAP_DATA_TYPE_BFLOAT16, 4, d_in[11], dim, str, box, es, CU_TENSOR_MAP_INTERLEAVE_NONE,
        CU_TENSOR_MAP_SWIZZLE_128B, CU_TENSOR_MAP_L2_PROMOTION_NONE, CU_TENSOR_MAP_FLOAT_OOB_FILL_NONE);
  }
  {
    cuuint64_t dim[2] = {16384, 64}, str[1] = {32768};
    cuuint32_t box[2] = {128, 8}, es[2] = {1, 1};
    enc(&mX, CU_TENSOR_MAP_DATA_TYPE_BFLOAT16, 2, scratch->XF[0], dim, str, box, es, CU_TENSOR_MAP_INTERLEAVE_NONE,
        CU_TENSOR_MAP_SWIZZLE_NONE, CU_TENSOR_MAP_L2_PROMOTION_NONE, CU_TENSOR_MAP_FLOAT_OOB_FILL_NONE);
  }
  Params P;
  P.x0 = (const uint16_t*)d_in[0]; P.Are = (const uint16_t*)d_in[1]; P.Aim = (const uint16_t*)d_in[2];
  P.Bre = (const uint16_t*)d_in[3]; P.Bim = (const uint16_t*)d_in[4]; P.Cre = (const uint16_t*)d_in[5];
  P.Cim = (const uint16_t*)d_in[6]; P.logdt = (const uint16_t*)d_in[7]; P.dskip = (const uint16_t*)d_in[8];
  P.wqkv = (const uint16_t*)d_in[10]; P.wo = (const uint16_t*)d_in[11]; P.out = (uint16_t*)d_out;
  for (int k = 0; k < 72; ++k) P.role[k] = role[k];
  P.zero = 0;
  P.mid = (char*)scratch->C;
  P.spare = nsm > 0 ? nsm - 128 : 0;
  fused_kernel<<<nsm > 0 ? nsm : 128, NTHR, SM_TOTAL, cudaStreamPerThread>>>(P, mW, mWo, mX);
}
```

```cpp
#include <cuda_runtime.h>
#include <cuda_bf16.h>
#include <cuda.h>
#include <stdint.h>
#include <stddef.h>

#define DEV __device__ __forceinline__
#define RARE(x) __builtin_expect(!!(x), 0)

constexpr int NTHR = 512;
constexpr int REG_MAIN = 192, REG_AUX = 96, REG_PROD = 32;
constexpr int NBARU = 384;
constexpr int SPIN_LIMIT = 1 << 22;

constexpr uint32_t SB = 1024;
__host__ __device__ constexpr uint32_t slot(int n) { return SB + n * 8192; }
__host__ __device__ constexpr int wslot(int k) { return k < 2 ? 3 * k : k < 4 ? 3 * k + 6 : k < 6 ? 21 - 3 * k : 3 * k - 18; }
constexpr uint32_t SM_A = slot(22), A_E = 0u - 32768;
constexpr uint32_t SM_O = slot(18), O_E = 0u - 147456;
constexpr uint32_t SM_WO = slot(10), SM_X = slot(8), SM_KV = slot(9) - 4096;
constexpr uint32_t SM_TAP  = slot(26);
constexpr int TAP_SZ = 3440;
constexpr uint32_t SM_STAT = SM_TAP + 4 * TAP_SZ;
constexpr uint32_t SM_CS   = SM_STAT + 1024;
constexpr uint32_t SM_MISC = SM_CS + 768;
constexpr uint32_t SM_BAR  = SM_MISC + 528;
constexpr int SM_TOTAL = SM_BAR + 304 - SB;
static_assert(SM_TOTAL <= 232448, "");
constexpr int R_SZ = 16384, R_U = 512, R_X5 = 5120, R_X3 = 8704, R_BO = 11776, R_BE = 13824;
constexpr int X_5 = 576, X_3 = 648, T_E = 2 * 720, T_O = 1600 + 2 * 721, T_C = 3390, T_K = 3424;
constexpr uint32_t B_RD = SM_BAR, B_ED = SM_BAR + 16, B_F = SM_BAR + 32, B_AT = SM_BAR + 56;
constexpr uint32_t B_AE = SM_BAR + 72, B_QE = SM_BAR + 88, B_ST = SM_BAR + 96, B_CS = SM_BAR + 112;
constexpr uint32_t B_WO = SM_BAR + 120, B_W6 = SM_BAR + 128, B_U = SM_BAR + 144, B_E = SM_BAR + 152, B_A = SM_BAR + 160, B_O = SM_BAR + 192,
                   B_Z = SM_BAR + 256, B_WF = SM_BAR + 272, B_W4 = SM_BAR + 280, B_N = SM_BAR + 288, B_V = SM_BAR + 296;
constexpr int NB_U = 1, NB_B = 2, NB_K = 8, NB_Y = 6, NB_WG = 8, NB_T = 10, NB_AUX = 12, NB_P0 = 13, NB_H = 15;

struct Scratch {
  uint4    XG[2][128 * 1024];
  uint4    O[32 * 8 * 512];
  uint32_t C[8 * 32];
  uint32_t OF[2][32 * 32];
  uint4    CS[16 * 1536 / 4];
  uint4    PS[128 * 64];
  uint4    ST[2][32 * 128];
  uint4    SR[2][8][512];
  uint4    XF[2][32 * 512 * 8];
  uint4    H[2][17 * 8 * 256];
};
__device__ __align__(1024) Scratch g_S;
#define SCR ((Scratch*)(P.mid - offsetof(Scratch, C)))
#define PROFD(slot, v) do {} while (0)
#define PROF(slot) do {} while (0)
#define PROFK(slot) do {} while (0)

DEV uint32_t s2u(const void* p) { return (uint32_t)__cvta_generic_to_shared(p); }
template <class T> DEV T* opqp(T* x) { asm volatile("" : "+l"(x)); return x; }
template <class T> DEV T opq(T x) { asm volatile("" : "+r"(x)); return x; }
DEV int lane_id() { int l; asm volatile("mov.u32 %0,%%laneid;" : "=r"(l)); return l; }
DEV uint32_t pack2(float lo, float hi) { uint32_t d; asm("cvt.rn.bf16x2.f32 %0,%1,%2;" : "=r"(d) : "f"(hi), "f"(lo)); return d; }
DEV float bflo(uint32_t v) { return __uint_as_float(v << 16); }
DEV float bfhi(uint32_t v) { return __uint_as_float(v & 0xFFFF0000u); }
DEV float bfr(float x) { return bflo(pack2(x, 0.f)); }
DEV uint32_t hadd2(uint32_t a, uint32_t b) { uint32_t d; asm("add.rn.bf16x2 %0,%1,%2;" : "=r"(d) : "r"(a), "r"(b)); return d; }
DEV uint32_t hsub2(uint32_t a, uint32_t b) { uint32_t d; asm("sub.rn.bf16x2 %0,%1,%2;" : "=r"(d) : "r"(a), "r"(b)); return d; }
DEV uint32_t hmul2(uint32_t a, uint32_t b) { uint32_t d; asm("mul.rn.bf16x2 %0,%1,%2;" : "=r"(d) : "r"(a), "r"(b)); return d; }
DEV uint32_t hfma2(uint32_t a, uint32_t b, uint32_t c) { uint32_t d; asm("fma.rn.bf16x2 %0,%1,%2,%3;" : "=r"(d) : "r"(a), "r"(b), "r"(c)); return d; }
DEV uint32_t hmax2(uint32_t a, uint32_t b) { uint32_t d; asm("max.bf16x2 %0,%1,%2;" : "=r"(d) : "r"(a), "r"(b)); return d; }
DEV uint32_t prmt(uint32_t a, uint32_t b, uint32_t s) { uint32_t d; asm("prmt.b32 %0,%1,%2,%3;" : "=r"(d) : "r"(a), "r"(b), "r"(s)); return d; }
DEV uint32_t nzmap(uint32_t v) { uint32_t d; asm("max.u32 %0,%1,1;" : "=r"(d) : "r"(v)); return d; }
DEV float rcp(float x) { float y; asm("rcp.approx.ftz.f32 %0,%1;" : "=f"(y) : "f"(x)); return y; }
DEV float sqrt_(float x) { float y; asm("sqrt.approx.ftz.f32 %0,%1;" : "=f"(y) : "f"(x)); return y; }
DEV float ex2(float x) { float y; asm("ex2.approx.ftz.f32 %0,%1;" : "=f"(y) : "f"(x)); return y; }

DEV uint4 ldr4(const void* p) { uint4 v; asm volatile("ld.relaxed.gpu.global.v4.u32 {%0,%1,%2,%3},[%4];" : "=r"(v.x), "=r"(v.y), "=r"(v.z), "=r"(v.w) : "l"(p) : "memory"); return v; }
DEV void ldr4_if(uint4& v, const void* p, bool c) {
  asm volatile("{.reg .pred q; setp.ne.u32 q,%5,0; @q ld.relaxed.gpu.global.v4.u32 {%0,%1,%2,%3},[%4];}"
    : "+r"(v.x), "+r"(v.y), "+r"(v.z), "+r"(v.w) : "l"(p), "r"((uint32_t)c) : "memory");
}
DEV uint2 ldr2(const void* p) { uint2 v; asm volatile("ld.relaxed.gpu.global.v2.u32 {%0,%1},[%2];" : "=r"(v.x), "=r"(v.y) : "l"(p) : "memory"); return v; }
DEV void ldr2_if(uint2& v, const void* p, bool c) {
  asm volatile("{.reg .pred q; setp.ne.u32 q,%3,0; @q ld.relaxed.gpu.global.v2.u32 {%0,%1},[%2];}" : "+r"(v.x), "+r"(v.y) : "l"(p), "r"((uint32_t)c) : "memory");
}
DEV uint32_t ldr1(const void* p) { uint32_t v; asm volatile("ld.relaxed.gpu.global.u32 %0,[%1];" : "=r"(v) : "l"(p) : "memory"); return v; }
DEV float ldnan(const uint16_t* p) {
  uint32_t v = 0xFFFFu;
#pragma unroll 1
  for (int it = 0; it < SPIN_LIMIT && __any_sync(0xffffffffu, v == 0xFFFFu); ++it) asm volatile("ld.relaxed.gpu.global.u16 %0,[%1];" : "=r"(v) : "l"(p) : "memory");
  return __uint_as_float(v << 16);
}
DEV uint4 ldw4(const void* p) { uint4 v; asm volatile("ld.global.v4.u32 {%0,%1,%2,%3},[%4];" : "=r"(v.x), "=r"(v.y), "=r"(v.z), "=r"(v.w) : "l"(p) : "memory"); return v; }
DEV uint2 ldw2(const void* p) { uint2 v; asm volatile("ld.global.v2.u32 {%0,%1},[%2];" : "=r"(v.x), "=r"(v.y) : "l"(p) : "memory"); return v; }
DEV uint32_t ldw1(const void* p) { uint32_t v; asm volatile("ld.global.u32 %0,[%1];" : "=r"(v) : "l"(p) : "memory"); return v; }
DEV void str4(void* p, uint32_t a, uint32_t b, uint32_t c, uint32_t d) { asm volatile("st.relaxed.gpu.global.v4.u32 [%0],{%1,%2,%3,%4};" :: "l"(p), "r"(a), "r"(b), "r"(c), "r"(d) : "memory"); }
DEV void str2(void* p, uint32_t a, uint32_t b) { asm volatile("st.relaxed.gpu.global.v2.u32 [%0],{%1,%2};" :: "l"(p), "r"(a), "r"(b) : "memory"); }
DEV void str1(void* p, uint32_t a) { asm volatile("st.relaxed.gpu.global.u32 [%0],%1;" :: "l"(p), "r"(a) : "memory"); }
DEV void str4_if(void* p, uint32_t a, uint32_t b, uint32_t c, uint32_t d, bool q) {
  asm volatile("{.reg .pred q; setp.ne.u32 q,%5,0; @q st.relaxed.gpu.global.v4.u32 [%0],{%1,%2,%3,%4};}" :: "l"(p), "r"(a), "r"(b), "r"(c), "r"(d), "r"((uint32_t)q) : "memory");
}
DEV void stw4(void* p, uint32_t a, uint32_t b, uint32_t c, uint32_t d) { asm volatile("st.global.v4.u32 [%0],{%1,%2,%3,%4};" :: "l"(p), "r"(a), "r"(b), "r"(c), "r"(d) : "memory"); }
DEV uint4 ldnc4(const void* p) { uint4 v; asm volatile("ld.global.nc.v4.u32 {%0,%1,%2,%3},[%4];" : "=r"(v.x), "=r"(v.y), "=r"(v.z), "=r"(v.w) : "l"(p)); return v; }
DEV uint32_t ldnc1(const void* p) { uint32_t v; asm volatile("ld.global.nc.u32 %0,[%1];" : "=r"(v) : "l"(p)); return v; }
DEV uint2 ldnc2(const void* p) { uint2 v; asm volatile("ld.global.nc.v2.u32 {%0,%1},[%2];" : "=r"(v.x), "=r"(v.y) : "l"(p)); return v; }

DEV uint2 lds2(uint32_t a) { uint2 v; asm volatile("ld.volatile.shared.v2.u32 {%0,%1},[%2];" : "=r"(v.x), "=r"(v.y) : "r"(a)); return v; }
DEV float lds16f(uint32_t a) { uint32_t v; asm volatile("ld.shared.u16 %0,[%1];" : "=r"(v) : "r"(a)); return __uint_as_float(v << 16); }
DEV void sts2(uint32_t a, uint32_t x, uint32_t y) { asm volatile("st.shared.v2.u32 [%0],{%1,%2};" :: "r"(a), "r"(x), "r"(y) : "memory"); }
DEV uint32_t lds1(uint32_t a) { uint32_t v; asm volatile("ld.volatile.shared.u32 %0,[%1];" : "=r"(v) : "r"(a)); return v; }
DEV uint32_t lds1z(uint32_t a, bool c) {
  uint32_t v; asm volatile("{.reg .pred q; setp.ne.u32 q,%2,0; mov.u32 %0,0; @q ld.volatile.shared.u32 %0,[%1];}" : "=r"(v) : "r"(a), "r"((uint32_t)c)); return v;
}
DEV uint4 lds4z(uint32_t a, bool c) {
  uint4 v = make_uint4(0, 0, 0, 0);
  asm volatile("{.reg .pred q; setp.ne.u32 q,%5,0; @q ld.volatile.shared.v4.u32 {%0,%1,%2,%3},[%4];}" : "+r"(v.x), "+r"(v.y), "+r"(v.z), "+r"(v.w) : "r"(a), "r"((uint32_t)c));
  return v;
}
DEV float lds1f(uint32_t a) { float v; asm volatile("ld.shared.f32 %0,[%1];" : "=f"(v) : "r"(a)); return v; }
DEV float2 lds2f(uint32_t a) { float2 v; asm volatile("ld.shared.v2.f32 {%0,%1},[%2];" : "=f"(v.x), "=f"(v.y) : "r"(a)); return v; }
DEV float4 lds4f(uint32_t a) { float4 v; asm volatile("ld.shared.v4.f32 {%0,%1,%2,%3},[%4];" : "=f"(v.x), "=f"(v.y), "=f"(v.z), "=f"(v.w) : "r"(a)); return v; }
DEV uint4 lds4(uint32_t a) { uint4 v; asm volatile("ld.volatile.shared.v4.u32 {%0,%1,%2,%3},[%4];" : "=r"(v.x), "=r"(v.y), "=r"(v.z), "=r"(v.w) : "r"(a)); return v; }
DEV void sts1(uint32_t a, uint32_t v) { asm volatile("st.shared.u32 [%0],%1;" :: "r"(a), "r"(v) : "memory"); }
DEV void sts16(uint32_t a, uint32_t v) { asm volatile("{.reg .b16 h; cvt.u16.u32 h,%1; st.shared.u16 [%0],h;}" :: "r"(a), "r"(v) : "memory"); }
DEV void sts2f(uint32_t a, float x, float y) { asm volatile("st.shared.v2.f32 [%0],{%1,%2};" :: "r"(a), "f"(x), "f"(y) : "memory"); }
DEV void sts4f(uint32_t a, float x, float y, float z, float w) { asm volatile("st.shared.v4.f32 [%0],{%1,%2,%3,%4};" :: "r"(a), "f"(x), "f"(y), "f"(z), "f"(w) : "memory"); }
DEV void sts4(uint32_t a, uint32_t x, uint32_t y, uint32_t z, uint32_t w) { asm volatile("st.shared.v4.u32 [%0],{%1,%2,%3,%4};" :: "r"(a), "r"(x), "r"(y), "r"(z), "r"(w) : "memory"); }

DEV void ldsm4(uint32_t (&r)[4], uint32_t a) { asm volatile("ldmatrix.sync.aligned.m8n8.x4.shared.b16 {%0,%1,%2,%3},[%4];" : "=r"(r[0]), "=r"(r[1]), "=r"(r[2]), "=r"(r[3]) : "r"(a) : "memory"); }
DEV void ldsm4t(uint32_t (&r)[4], uint32_t a) { asm volatile("ldmatrix.sync.aligned.m8n8.x4.trans.shared.b16 {%0,%1,%2,%3},[%4];" : "=r"(r[0]), "=r"(r[1]), "=r"(r[2]), "=r"(r[3]) : "r"(a) : "memory"); }
DEV void ldsm2(uint32_t (&r)[2], uint32_t a) { asm volatile("ldmatrix.sync.aligned.m8n8.x2.shared.b16 {%0,%1},[%2];" : "=r"(r[0]), "=r"(r[1]) : "r"(a) : "memory"); }
DEV void stsm4(uint32_t a, uint32_t r0, uint32_t r1, uint32_t r2, uint32_t r3) { asm volatile("stmatrix.sync.aligned.m8n8.x4.shared.b16 [%0],{%1,%2,%3,%4};" :: "r"(a), "r"(r0), "r"(r1), "r"(r2), "r"(r3) : "memory"); }
DEV void stsm2(uint32_t a, uint32_t r0, uint32_t r1) { asm volatile("stmatrix.sync.aligned.m8n8.x2.shared.b16 [%0],{%1,%2};" :: "r"(a), "r"(r0), "r"(r1) : "memory"); }
DEV void stsm4t(uint32_t a, uint32_t r0, uint32_t r1, uint32_t r2, uint32_t r3) { asm volatile("stmatrix.sync.aligned.m8n8.x4.trans.shared.b16 [%0],{%1,%2,%3,%4};" :: "r"(a), "r"(r0), "r"(r1), "r"(r2), "r"(r3) : "memory"); }
DEV uint32_t movm(uint32_t a) { uint32_t d; asm volatile("movmatrix.sync.aligned.m8n8.trans.b16 %0,%1;" : "=r"(d) : "r"(a)); return d; }
DEV void mma16(float (&d)[4], uint32_t a0, uint32_t a1, uint32_t a2, uint32_t a3, uint32_t b0, uint32_t b1) {
  asm volatile("mma.sync.aligned.m16n8k16.row.col.f32.bf16.bf16.f32 {%0,%1,%2,%3},{%4,%5,%6,%7},{%8,%9},{%0,%1,%2,%3};"
    : "+f"(d[0]), "+f"(d[1]), "+f"(d[2]), "+f"(d[3]) : "r"(a0), "r"(a1), "r"(a2), "r"(a3), "r"(b0), "r"(b1));
}
DEV void mma16z(float (&d)[4], uint32_t a0, uint32_t a1, uint32_t a2, uint32_t a3, uint32_t b0, uint32_t b1) {
  asm volatile("mma.sync.aligned.m16n8k16.row.col.f32.bf16.bf16.f32 {%0,%1,%2,%3},{%4,%5,%6,%7},{%8,%9},{%10,%10,%10,%10};"
    : "=f"(d[0]), "=f"(d[1]), "=f"(d[2]), "=f"(d[3]) : "r"(a0), "r"(a1), "r"(a2), "r"(a3), "r"(b0), "r"(b1), "f"(0.f));
}
DEV void mma8(float (&d)[4], uint32_t a0, uint32_t a1, uint32_t b0) {
  asm volatile("mma.sync.aligned.m16n8k8.row.col.f32.bf16.bf16.f32 {%0,%1,%2,%3},{%4,%5},{%6},{%0,%1,%2,%3};"
    : "+f"(d[0]), "+f"(d[1]), "+f"(d[2]), "+f"(d[3]) : "r"(a0), "r"(a1), "r"(b0));
}

DEV void mma8z(float (&d)[4], uint32_t a0, uint32_t a1, uint32_t b0) {
  asm volatile("mma.sync.aligned.m16n8k8.row.col.f32.bf16.bf16.f32 {%0,%1,%2,%3},{%4,%5},{%6},{%7,%7,%7,%7};"
    : "=f"(d[0]), "=f"(d[1]), "=f"(d[2]), "=f"(d[3]) : "r"(a0), "r"(a1), "r"(b0), "f"(0.f));
}
DEV void bar_sync(int id, int n) { asm volatile("bar.sync %0,%1;" :: "r"(id), "r"(n) : "memory"); }
DEV void bar_sync_if(int id, int n, int c) { asm volatile("{.reg .pred q; setp.ne.s32 q,%2,0; @q bar.sync %0,%1;}" :: "r"(id), "r"(n), "r"(c) : "memory"); }
DEV void bar_arrive_if(int id, int n, int c) { asm volatile("{.reg .pred q; setp.ne.s32 q,%2,0; @q bar.arrive %0,%1;}" :: "r"(id), "r"(n), "r"(c) : "memory"); }
DEV bool bar_any(int id, int n, bool c) {
  uint32_t r; asm volatile("{.reg .pred p,q; setp.ne.u32 q,%3,0; bar.red.or.pred p,%1,%2,q; selp.u32 %0,1,0,p;}" : "=r"(r) : "r"(id), "r"(n), "r"((uint32_t)c) : "memory");
  return __any_sync(0xffffffffu, r);
}
DEV void bar_arrive(int id, int n) { asm volatile("bar.arrive %0,%1;" :: "r"(id), "r"(n) : "memory"); }
DEV void fence_async_glob() { asm volatile("fence.proxy.async.global;" ::: "memory"); }
DEV void fence_async_smem() { asm volatile("fence.proxy.async.shared::cta;" ::: "memory"); }
DEV void mbar_init(uint32_t b, int n) { asm volatile("mbarrier.init.shared::cta.b64 [%0],%1;" :: "r"(b), "r"(n) : "memory"); }
DEV void mbar_arrive(uint32_t b) { asm volatile("mbarrier.arrive.shared::cta.b64 _,[%0];" :: "r"(b) : "memory"); }
DEV void mbar_expect(uint32_t b, int bytes) { asm volatile("mbarrier.arrive.expect_tx.shared::cta.b64 _,[%0],%1;" :: "r"(b), "r"(bytes) : "memory"); }
DEV void mbar_wait(uint32_t b, uint32_t ph) {
  asm volatile("{\n.reg .pred p;\nW: mbarrier.try_wait.parity.shared::cta.b64 p,[%0],%1;\n@!p bra W;\n}" :: "r"(b), "r"(ph) : "memory");
}
DEV void mbar_watch(uint32_t b, uint32_t ph) {
  asm volatile("{\n.reg .pred p,q;\n.reg .u32 n;\nmov.u32 n,0;\n"
               "W: mbarrier.try_wait.parity.shared::cta.b64 p,[%0],%1;\n@p bra D;\n"
               "add.u32 n,n,1;\nsetp.lt.u32 q,n,%2;\n@q bra W;\ntrap;\nD:\n}"
               :: "r"(b), "r"(ph), "n"(SPIN_LIMIT) : "memory");
}
DEV void spin_guard(int it) { asm volatile("{.reg .pred p; setp.gt.s32 p,%0,%1; @p trap;}" :: "r"(it), "n"(SPIN_LIMIT)); }
DEV void split(uint32_t zero) {
  asm volatile("{.reg .pred p; setp.ne.u32 p,%0,0; @p trap;}" :: "r"(zero) : "memory");
}
DEV void pause(int n) {
  uint32_t t0, t; asm volatile("mov.u32 %0,%%clock;" : "=r"(t0));
  do asm volatile("mov.u32 %0,%%clock;" : "=r"(t)); while (t - t0 < n);
}
DEV void cnt_wait(const uint32_t* k, int lane) {
#pragma unroll 1
  for (int it = 0;; ++it) {
    spin_guard(it);
    if (__all_sync(0xffffffffu, ldr1(k + (lane & 3) * 32) >= 32)) break;
  }
}
DEV void mbar_arrive1(uint32_t b) { asm volatile("{.reg .pred p; elect.sync _|p,0xffffffff; @p mbarrier.arrive.shared::cta.b64 _,[%0];}" :: "r"(b) : "memory"); }
DEV void mbar_arrive1_if(uint32_t b, int c) {
  asm volatile("{.reg .pred p,q; setp.ne.s32 q,%1,0; elect.sync _|p,0xffffffff; and.pred p,p,q; @p mbarrier.arrive.shared::cta.b64 _,[%0];}" :: "r"(b), "r"(c) : "memory");
}
DEV void mbar_expect1(uint32_t b, int bytes) { asm volatile("{.reg .pred p; elect.sync _|p,0xffffffff; @p mbarrier.arrive.expect_tx.shared::cta.b64 _,[%0],%1;}" :: "r"(b), "r"(bytes) : "memory"); }
DEV void cnt_add1(uint32_t* q) { asm volatile("{.reg .pred p; elect.sync _|p,0xffffffff; @p red.relaxed.gpu.global.add.u32 [%0],1;}" :: "l"(q) : "memory"); }
DEV void tma4(uint32_t dst, const CUtensorMap* m, int c0, int c1, int c2, int c3, uint32_t bar) {
  asm volatile("{.reg .pred p; elect.sync _|p,0xffffffff;\n"
    "@p cp.async.bulk.tensor.4d.shared::cluster.global.mbarrier::complete_tx::bytes [%0],[%1,{%2,%3,%4,%5}],[%6];}"
    :: "r"(dst), "l"(m), "r"(c0), "r"(c1), "r"(c2), "r"(c3), "r"(bar) : "memory");
}
DEV void tma3(uint32_t dst, const CUtensorMap* m, int c0, int c1, int c2, uint32_t bar) {
  asm volatile("{.reg .pred p; elect.sync _|p,0xffffffff;\n"
    "@p cp.async.bulk.tensor.3d.shared::cluster.global.mbarrier::complete_tx::bytes [%0],[%1,{%2,%3,%4}],[%5];}"
    :: "r"(dst), "l"(m), "r"(c0), "r"(c1), "r"(c2), "r"(bar) : "memory");
}
DEV void bulk(uint32_t dst, const void* src, int bytes, uint32_t bar) {
  asm volatile("{.reg .pred p; elect.sync _|p,0xffffffff;\n@p cp.async.bulk.shared::cluster.global.mbarrier::complete_tx::bytes [%0],[%1],%2,[%3];}" :: "r"(dst), "l"(src), "r"(bytes), "r"(bar) : "memory");
}

DEV void bulk_store(void* dst, uint32_t src, int bytes) {
  asm volatile("{.reg .pred p; elect.sync _|p,0xffffffff;\n@p cp.async.bulk.global.shared::cta.bulk_group [%0],[%1],%2;}" :: "l"(dst), "r"(src), "r"(bytes) : "memory");
}
DEV void tma2_store(const CUtensorMap* m, uint32_t src, int c0, int c1) {
  asm volatile("{.reg .pred p; elect.sync _|p,0xffffffff;\n@p cp.async.bulk.tensor.2d.global.shared::cta.bulk_group [%0,{%2,%3}],[%1];}" :: "l"(m), "r"(src), "r"(c0), "r"(c1) : "memory");
}
DEV void bulk_wait() { asm volatile("cp.async.bulk.commit_group;\ncp.async.bulk.wait_group 0;\nfence.proxy.async.global;" ::: "memory"); }

DEV uint32_t dlo(uint32_t addr, uint32_t lbo) { return __shfl_sync(0xffffffffu, (addr >> 4) | ((lbo >> 4) << 16), 0); }
__host__ __device__ constexpr uint32_t dhi(uint32_t sbo, uint32_t swz) { return (sbo >> 4) | (swz << 30); }
DEV void wg_fence() { asm volatile("wgmma.fence.sync.aligned;" ::: "memory"); }
DEV void wg_commit() { asm volatile("wgmma.commit_group.sync.aligned;" ::: "memory"); }
template <int N> DEV void wg_wait() { asm volatile("wgmma.wait_group.sync.aligned %0;" :: "n"(N) : "memory"); }
template <int N> DEV void zero(float (&d)[N]) {
#pragma unroll
  for (int i = 0; i < N; ++i) d[i] = 0.f;
}
template <int N> DEV void zerov(float (&d)[N]) {
#pragma unroll
  for (int i = 0; i < N; ++i) asm volatile("mov.b32 %0,0;" : "=f"(d[i]));
}
template <int N> DEV void undef(float (&d)[N]) {
#pragma unroll
  for (int i = 0; i < N; ++i) asm volatile("" : "=f"(d[i]));
}
#define R4(d, o) "+f"(d[o]), "+f"(d[o + 1]), "+f"(d[o + 2]), "+f"(d[o + 3])
#define R8(d, o) R4(d, o), R4(d, o + 4)
#define R16(d, o) R8(d, o), R8(d, o + 8)
template <int ACC> DEV void wg_rs64k(float (&d)[32], const uint32_t (&a)[4], uint32_t db) {
  asm volatile("{.reg .pred p; .reg .b64 b; setp.ne.s32 p,%38,0; mov.b64 b,{%36,%37};\n"
    "wgmma.mma_async.sync.aligned.m64n64k16.f32.bf16.bf16 {%0,%1,%2,%3,%4,%5,%6,%7,%8,%9,%10,%11,%12,%13,%14,%15,%16,%17,%18,%19,%20,%21,%22,%23,%24,%25,%26,%27,%28,%29,%30,%31},{%32,%33,%34,%35},b,p,1,1,0;}"
    : R16(d, 0), R16(d, 16) : "r"(a[0]), "r"(a[1]), "r"(a[2]), "r"(a[3]), "r"(db), "n"(dhi(512, 2)), "n"(ACC));
}
template <int ACC> DEV void wg_rs48t(float (&d)[24], const uint32_t (&a)[4], uint32_t db) {
  asm volatile("{.reg .pred p; .reg .b64 b; setp.ne.s32 p,%30,0; mov.b64 b,{%28,%29};\n"
    "wgmma.mma_async.sync.aligned.m64n48k16.f32.bf16.bf16 {%0,%1,%2,%3,%4,%5,%6,%7,%8,%9,%10,%11,%12,%13,%14,%15,%16,%17,%18,%19,%20,%21,%22,%23},{%24,%25,%26,%27},b,p,1,1,1;}"
    : R16(d, 0), R8(d, 16) : "r"(a[0]), "r"(a[1]), "r"(a[2]), "r"(a[3]), "r"(db), "n"(dhi(512, 0)), "n"(ACC));
}
template <int ACC> DEV void wg_rs32t(float (&d)[16], const uint32_t (&a)[4], uint32_t db) {
  asm volatile("{.reg .pred p; .reg .b64 b; setp.ne.s32 p,%22,0; mov.b64 b,{%20,%21};\n"
    "wgmma.mma_async.sync.aligned.m64n32k16.f32.bf16.bf16 {%0,%1,%2,%3,%4,%5,%6,%7,%8,%9,%10,%11,%12,%13,%14,%15},{%16,%17,%18,%19},b,p,1,1,1;}"
    : R16(d, 0) : "r"(a[0]), "r"(a[1]), "r"(a[2]), "r"(a[3]), "r"(db), "n"(dhi(1024, 0)), "n"(ACC));
}
template <int ACC> DEV void wg_ss192(float (&d)[96], uint32_t da, uint32_t db) {
  asm volatile("{.reg .pred p; .reg .b64 a,b; setp.ne.s32 p,%100,0; mov.b64 a,{%96,%98}; mov.b64 b,{%97,%99};\n"
    "wgmma.mma_async.sync.aligned.m64n192k16.f32.bf16.bf16 {"
    "%0,%1,%2,%3,%4,%5,%6,%7,%8,%9,%10,%11,%12,%13,%14,%15,%16,%17,%18,%19,%20,%21,%22,%23,%24,%25,%26,%27,%28,%29,%30,%31,"
    "%32,%33,%34,%35,%36,%37,%38,%39,%40,%41,%42,%43,%44,%45,%46,%47,%48,%49,%50,%51,%52,%53,%54,%55,%56,%57,%58,%59,%60,%61,%62,%63,"
    "%64,%65,%66,%67,%68,%69,%70,%71,%72,%73,%74,%75,%76,%77,%78,%79,%80,%81,%82,%83,%84,%85,%86,%87,%88,%89,%90,%91,%92,%93,%94,%95},a,b,p,1,1,1,1;}"
    : R16(d, 0), R16(d, 16), R16(d, 32), R16(d, 48), R16(d, 64), R16(d, 80) : "r"(da), "r"(db), "n"(dhi(1024, 1)), "n"(dhi(1024, 1)), "n"(ACC));
}
template <int ACC> DEV void wg_ss64(float (&d)[32], uint32_t da, uint32_t db) {
  asm volatile("{.reg .pred p; .reg .b64 a,b; setp.ne.s32 p,%36,0; mov.b64 a,{%32,%34}; mov.b64 b,{%33,%35};\n"
    "wgmma.mma_async.sync.aligned.m64n64k16.f32.bf16.bf16 {"
    "%0,%1,%2,%3,%4,%5,%6,%7,%8,%9,%10,%11,%12,%13,%14,%15,%16,%17,%18,%19,%20,%21,%22,%23,%24,%25,%26,%27,%28,%29,%30,%31},a,b,p,1,1,0,1;}"
    : R16(d, 0), R16(d, 16) : "r"(da), "r"(db), "n"(dhi(1024, 0)), "n"(dhi(1024, 1)), "n"(ACC));
}

DEV uint32_t cpy(uint32_t v, uint32_t id) {
  uint32_t d; asm volatile("prmt.b32 %0,%1,%1,%2;" : "=r"(d) : "r"(v), "r"(id)); return d;
}
struct Params {
  uint32_t zero, spare;
  char* mid;
  const uint16_t *x0, *Are, *Aim, *Bre, *Bim, *Cre, *Cim, *logdt, *dskip, *wqkv, *wo;
  uint16_t* out;
  uint8_t role[72];
};

DEV uint32_t ln_word(float mean, float var) {
  float v = bfr(var);
  float s = sqrt_(bfr(v + 1e-5f));
  return pack2(mean, s);
}

DEV int stat_group(int c) { return c ^ 4; }
DEV int xg_off(int G, int g) { return (G >> 6) * 1024 + (G & 63) * 8 + (g ^ (G & 2)); }
DEV int sr_off(int G, int g) { return (G >> 6) * 256 + (g & 2) * 64 + 2 * (G & 63) + ((g >> 2) & 1); }
DEV uint32_t region(int chl) { return SM_A + (chl >> 1) * A_E + (chl & 1) * R_SZ; }
template <bool FIRST> DEV void gram(float (&s)[4], float (&q0)[4], float (&q1)[4], uint32_t a0, uint32_t a1, uint32_t a2, uint32_t a3) {
  const uint32_t one = 0x3F803F80u;
  if (FIRST) { mma16z(s, a0, a1, a2, a3, one, one); mma8z(q0, a0, a1, a0); mma8z(q1, a0, a1, a1); }
  else { mma16(s, a0, a1, a2, a3, one, one); mma8(q0, a0, a1, a0); mma8(q1, a0, a1, a1); }
  mma8(q0, a2, a3, a2); mma8(q1, a2, a3, a3);
}
DEV uint32_t ln_sums(float s, float q) { const float m = s * (1.f / 512.f); return ln_word(m, fmaxf(q * (1.f / 512.f) - m * m, 0.f)); }
DEV void cmul(float& orr, float& oi, float ar, float ai, float br, float bi) {
  float r = ar * br - ai * bi, i = ar * bi + ai * br; orr = r; oi = i;
}
DEV void cexp_(float al, float bt, float s, float& er, float& ei) {
  float mag = ex2(al * s), ph = bt * s;
  ph -= rintf(ph);
  float ang = ph * 6.283185307179586f;
  er = mag * __cosf(ang); ei = mag * __sinf(ang);
}

DEV void kgen(const Params& P, int c, int wm, int lane) {
  const int chl = wm >> 1, mh = wm & 1, g = lane >> 2, t = lane & 3;
  const int ch = 256 * (chl >> 1) + 2 * c + (chl & 1);
  const int mo = ch * 64 + mh * 32 + lane;
  const uint32_t vAr = ldw1((const uint32_t*)P.Are + mo), vAi = ldw1((const uint32_t*)P.Aim + mo);
  const uint32_t vBr = ldw1((const uint32_t*)P.Bre + mo), vBi = ldw1((const uint32_t*)P.Bim + mo);
  const uint32_t vCr = ldw1((const uint32_t*)P.Cre + mo), vCi = ldw1((const uint32_t*)P.Cim + mo);
  const uint32_t vld = ldw1((const uint32_t*)P.logdt + (ch >> 1)) >> (16 * (ch & 1)), vds = ldw1((const uint32_t*)P.dskip + (ch >> 1)) >> (16 * (ch & 1));
  bar_arrive(NB_Y, 384);
  PROF(45);
  asm volatile("setmaxnreg.inc.sync.aligned.u32 %0;" :: "n"(REG_MAIN));
  PROF(44);
  {
    const uint32_t tz = SM_TAP + chl * TAP_SZ + (mh * 32 + lane) * 16;
#pragma unroll
    for (int k = 0; k < 3; ++k) sts4(tz + k * 1024, 0, 0, 0, 0);
    static_assert(TAP_SZ > 3072 && TAP_SZ <= 4096, "");
    if (mh * 32 + lane < TAP_SZ / 16 - 192) sts4(tz + 3072, 0, 0, 0, 0);
  }
  const float dt = bfr(__expf(bflo(vld)));
  const uint32_t tb = slot(wm);
  float acc[5][4];
#pragma unroll
  for (int i = 0; i < 5; ++i) { acc[i][0] = acc[i][1] = acc[i][2] = acc[i][3] = 0.f; }
  float k2048 = 0.f;
#pragma unroll 1
  for (int r = 0; r < 2; ++r) {
    const float are = r ? bfhi(vAr) : bflo(vAr), aim = r ? bfhi(vAi) : bflo(vAi);
    const float bre = r ? bfhi(vBr) : bflo(vBr), bim = r ? bfhi(vBi) : bflo(vBi);
    const float cre = r ? bfhi(vCr) : bflo(vCr), cim = r ? bfhi(vCi) : bflo(vCi);
    const float al = dt * are * 1.4426950408889634f, bt = dt * aim * 0.15915494309189535f;
    float wr, wi; cmul(wr, wi, cre, cim, dt * bre, dt * bim);
    if (r == 0) PROFD(2, __float_as_uint(wr + al + bt));
    float e1r, e1i, e8r, e8i, eLr, eLi;
    cexp_(al, bt, 1.f, e1r, e1i); cexp_(al, bt, 8.f, e8r, e8i); cexp_(al, bt, 128.f, eLr, eLi);
    const uint32_t tw = tb + lane * 4;
    float pr[8], pi[8];
    pr[1] = e1r; pi[1] = e1i;
#pragma unroll
    for (int k = 2; k < 8; ++k) cmul(pr[k], pi[k], pr[k - 1], pi[k - 1], e1r, e1i);
    float yr = 1.f, yi = 0.f, qr = wr, qi = wi;
#pragma unroll
    for (int a = 0; a < 16; ++a) {
      sts1(tw + a * 144, pack2(yr, -yi));
      if (a == 0) { yr = e8r; yi = e8i; } else if (a < 15) cmul(yr, yi, yr, yi, e8r, e8i);
      const int step = a < 2 ? 1 : a < 4 ? 2 : a < 8 ? 4 : 8;
      const int row0 = 16 + (a < 2 ? 8 * a : a < 4 ? 16 + 4 * (a - 2) : a < 8 ? 24 + 2 * (a - 4) : 32 + (a - 8));
      sts1(tw + row0 * 144, pack2(qr, qi));
#pragma unroll
      for (int k = step; k < 8; k += step) {
        float xr, xi; cmul(xr, xi, qr, qi, pr[k], pi[k]);
        sts1(tw + (row0 + k / step) * 144, pack2(xr, xi));
      }
      cmul(qr, qi, qr, qi, eLr, eLi);
    }
    k2048 += qr;
    __syncwarp();
    if (r == 0) PROF(3);
#pragma unroll
    for (int kp = 0; kp < 2; ++kp) {
      uint32_t a0[4], a1[4];
      const uint32_t aa = tb + ((lane & 7) + 8 * ((lane >> 3) & 1)) * 144 + (lane >> 4) * 16 + kp * 64;
      ldsm4(a0, aa); ldsm4(a1, aa + 32);
#pragma unroll
      for (int tl = 0; tl < 5; ++tl) {
        uint32_t b[4];
        ldsm4(b, tb + (16 + 8 * tl + (lane & 7)) * 144 + (lane >> 3) * 16 + kp * 64);
        mma16(acc[tl], a0[0], a0[1], a0[2], a0[3], b[0], b[1]);
        mma16(acc[tl], a1[0], a1[1], a1[2], a1[3], b[2], b[3]);
      }
    }
    __syncwarp();
    bar_sync_if(NB_P0 + 1, 288, 1 - r);
  }
#pragma unroll
  for (int o = 16; o > 0; o >>= 1) k2048 += __shfl_xor_sync(0xffffffffu, k2048, o);
  if (mh == 0) {
    sts4f(tb + lane * 16, acc[2][0], acc[2][1], acc[2][2], acc[2][3]);
    sts4f(tb + 512 + lane * 16, acc[3][0], acc[3][1], acc[3][2], acc[3][3]);
  } else {
    sts4f(tb + lane * 16, acc[0][0], acc[0][1], acc[0][2], acc[0][3]);
    sts4f(tb + 512 + lane * 16, acc[1][0], acc[1][1], acc[1][2], acc[1][3]);
    sts4f(tb + 1024 + lane * 16, acc[4][0], acc[4][1], acc[4][2], acc[4][3]);
    if (lane == 0) sts1(tb + 1536, __float_as_uint(k2048));
  }
  PROF(4);
  bar_sync(NB_K + chl, 64);
  const uint32_t ob = slot(wm ^ 1), tp = SM_TAP + chl * TAP_SZ;
  if (mh == 0) {
#pragma unroll
    for (int tl = 0; tl < 2; ++tl) {
      float4 o = lds4f(ob + tl * 512 + lane * 16);
      if (tl == 0 && lane == 0) o.x += bflo(vds);
      uint32_t v0 = pack2(acc[tl][0] + o.x, acc[tl][1] + o.y), v1 = pack2(acc[tl][2] + o.z, acc[tl][3] + o.w);
      const int l = 128 * tl + 8 * g + 2 * t;
      sts16(tp + T_E + 2 * (0 - l), v0); sts16(tp + T_E + 2 * (-1 - l), v0 >> 16);
      sts16(tp + T_O + 2 * (0 - l), v0); sts16(tp + T_O + 2 * (-1 - l), v0 >> 16);
      sts16(tp + T_E + 2 * (-64 - l), v1); sts16(tp + T_E + 2 * (-65 - l), v1 >> 16);
      sts16(tp + T_O + 2 * (-64 - l), v1); sts16(tp + T_O + 2 * (-65 - l), v1 >> 16);
    }
    float4 o = lds4f(ob + 1024 + lane * 16);
    uint32_t v0 = pack2(acc[4][0] + o.x, acc[4][1] + o.y), v1 = pack2(acc[4][2] + o.z, acc[4][3] + o.w);
    const int x = 32 * t + g - 1;
    if (lane == 0) { sts16(tp + T_E - 2 * (X_5 + 63), v0); sts16(tp + T_O - 2 * (X_5 + 63), v0); sts1(tp + T_K, prmt(v0, v0, 0x1010)); }
    else sts16(tp + T_C - 2 * x, v0);
    sts16(tp + T_C - 2 * (x + 16), v0 >> 16);
    sts16(tp + T_C - 2 * (x + 8), v1);
    sts16(tp + T_C - 2 * (x + 24), v1 >> 16);
    if (lane == 0) sts16(tp + T_C - 2 * 127, pack2(k2048 + __uint_as_float(lds1(ob + 1536)), 0.f));
  } else {
    float4 o2 = lds4f(ob + lane * 16), o3 = lds4f(ob + 512 + lane * 16);
    uint32_t v0 = pack2(acc[2][0] + o2.x, acc[2][1] + o2.y), v1 = pack2(acc[2][2] + o2.z, acc[2][3] + o2.w);
    const int l0 = 256 + 128 * (t >> 1) + 4 * (t & 1) + 8 * g;
    if (lane != 0) { sts16(tp + T_E + 2 * (1 - l0), v0); sts16(tp + T_O + 2 * (1 - l0), v0); }
    sts16(tp + T_E + 2 * (0 - l0), v0); sts16(tp + T_O + 2 * (0 - l0), v0);
    sts16(tp + T_E + 2 * (-1 - l0), v0); sts16(tp + T_O + 2 * (-1 - l0), v0);
    sts16(tp + T_E + 2 * (-2 - l0), v0 >> 16); sts16(tp + T_O + 2 * (-2 - l0), v0 >> 16);
    sts16(tp + T_E + 2 * (-63 - l0), v1); sts16(tp + T_O + 2 * (-63 - l0), v1);
    sts16(tp + T_E + 2 * (-64 - l0), v1); sts16(tp + T_O + 2 * (-64 - l0), v1);
    sts16(tp + T_E + 2 * (-65 - l0), v1); sts16(tp + T_O + 2 * (-65 - l0), v1);
    sts16(tp + T_E + 2 * (-66 - l0), v1 >> 16); sts16(tp + T_O + 2 * (-66 - l0), v1 >> 16);
    uint32_t w0 = pack2(acc[3][0] + o3.x, acc[3][1] + o3.y), w1 = pack2(acc[3][2] + o3.z, acc[3][3] + o3.w);
    const int x = 16 * t + g;
    if (lane == 0) {
      const uint32_t k = prmt(w0, w0, 0x1010);
      sts1(tp + T_E - 2 * 514, k); sts1(tp + T_E - 2 * 512, k);
      sts16(tp + T_O - 2 * 514, k); sts1(tp + T_O - 2 * 513, k); sts16(tp + T_O - 2 * 511, k);
    } else { sts16(tp + T_E - 2 * (X_5 - 1 + x), w0); sts16(tp + T_O - 2 * (X_5 - 1 + x), w0); }
    sts16(tp + T_E - 2 * (X_3 + x), w0 >> 16); sts16(tp + T_O - 2 * (X_3 + x), w0 >> 16);
    sts16(tp + T_E - 2 * (X_5 + 7 + x), w1); sts16(tp + T_O - 2 * (X_5 + 7 + x), w1);
    sts16(tp + T_E - 2 * (X_3 + 8 + x), w1 >> 16); sts16(tp + T_O - 2 * (X_3 + 8 + x), w1 >> 16);
  }
}

DEV bool bad8(const uint4& v) { return min(v.x, v.z) == 0u; }
DEV uint32_t uchunk(uint32_t reg, int x) { return reg + R_U + (x ^ ((x >> 3) & 3)) * 16; }
DEV uint32_t& xword(uint4 (&x)[2], int e, int tp) { uint4& v = x[tp >> 1]; return tp & 1 ? (e ? v.w : v.z) : (e ? v.y : v.x); }

DEV void uprep(const Params& P, int c, int wa, int lane, int layer, uint4 (&x)[2][2][2], uint32_t (&u)[4][4]) {
  const int j = 32 * wa + lane, o0 = 2 * j + ((j >> 2) & 1);
  {
    const uint32_t za = region(wa) + lane * 16 - 512;
    sts4(za + R_U, 0, 0, 0, 0); sts4(za + R_X5, 0, 0, 0, 0); sts4(za + R_X3, 0, 0, 0, 0);
    sts4(region(wa) + R_BE, 0, 0, 0, 0);
  }
  const uint4* st = opqp(&SCR->SR[layer][c >> 4][j]);
  const uint32_t xa = opq(SM_X + 16 * o0), xb = opq(SM_X + 16 * (o0 ^ 1)), ua = opq(uchunk(0, j));
  uint4 s[2][2];
#pragma unroll
  for (int z = 0; z < 12; ++z) {
    uint4& v = z < 8 ? x[(z >> 2) & 1][(z >> 1) & 1][z & 1] : s[(z >> 1) & 1][z & 1];
    asm volatile("mov.b32 %0,0; mov.b32 %1,0; mov.b32 %2,0; mov.b32 %3,0;" : "=r"(v.x), "=r"(v.y), "=r"(v.z), "=r"(v.w));
  }
#pragma unroll 1
  for (uint32_t it = P.zero;; ++it) {
    if (it) {
      spin_guard(it);
#pragma unroll
      for (int z = 0; z < 4; ++z) { uint4& v = s[z >> 1][z & 1]; ldr4_if(v, st + z * 128, bad8(v)); }
      const uint4* xp = &SCR->XG[layer][c * 1024 + o0];
#pragma unroll
      for (int z = 0; z < 8; ++z) {
        uint4& v = x[z >> 2][(z >> 1) & 1][z & 1];
        ldr4_if(v, (const uint4*)((uintptr_t)xp ^ (16 * (z & 1))) + (z >> 1) * 256, bad8(v));
      }
    } else {
      mbar_wait(B_U, layer);
      PROF(layer ? 25 : 10);
#pragma unroll
      for (int z = 0; z < 4; ++z) s[z >> 1][z & 1] = ldr4(st + z * 128);
#pragma unroll
      for (int z = 0; z < 4; ++z) { uint4& v = s[z >> 1][z & 1]; ldr4_if(v, st + z * 128, bad8(v)); }
      PROF(layer ? 26 : 11);
      mbar_wait(B_E, layer);
#pragma unroll
      for (int z = 7; z >= 0; --z) x[z >> 2][(z >> 1) & 1][z & 1] = lds4((z & 1 ? xb : xa) + (z >> 1) * 4096);
      PROF(layer ? 27 : 14);
    }
    uint32_t m = ~0u;
#pragma unroll
    for (int z = 7; z >= 0; --z) {
      const int k = z >> 2, chl = z & 3;
#pragma unroll
      for (int tp = 0; tp < 4; ++tp) u[chl][tp] = hfma2(xword(x[k][chl >> 1], chl & 1, tp), xword(s[k], 0, tp), xword(s[k], 1, tp));
      sts4(ua + region(chl) + k * 2048, u[chl][0], u[chl][1], u[chl][2], u[chl][3]);
      const uint4& v = x[k][chl >> 1][chl & 1];
      m = min(m, min(v.x, v.z));
      if (z < 4) m = min(m, min(s[z >> 1][z & 1].x, s[z >> 1][z & 1].z));
    }
    if (!__any_sync(0xffffffffu, m == 0)) break;
  }
  PROF(4 + 12 * layer);
}

template <bool FULL> DEV void box_unit(uint32_t reg, int s, const uint2& a, const uint4& b, const uint32_t (&d)[4], uint32_t (&pv)[4]) {
  const uint32_t u[9] = {a.x, a.y, b.x, b.y, b.z, b.w, d[0], d[1], d[2]};
  uint32_t v[8], p[8];
#pragma unroll
  for (int j = 0; j < 8; ++j) { v[j] = prmt(u[j], u[j + 1], 0x5432); p[j] = hadd2(u[j], v[j]); }
  const uint32_t o = reg + s * 16;
  uint32_t x[4], y[4];
#pragma unroll
  for (int j = 0; j < 4; ++j) { x[j] = hadd2(hadd2(p[1 + j], p[2 + j]), u[3 + j]); y[j] = hadd2(v[3 + j], p[4 + j]); pv[j] = p[4 + j]; }
  sts4(o + R_X5, x[0], x[1], x[2], x[3]);
  sts4(o + R_X3, y[0], y[1], y[2], y[3]);
  if (FULL) {
#pragma unroll
    for (int j = 0; j < 4; ++j) { y[j] = hadd2(hadd2(v[j], v[3 + j]), x[j]); x[j] = hadd2(hadd2(u[j], u[4 + j]), y[j]); }
    const bool od = s & 1;
    sts4(o + R_BO, od ? y[0] : x[0], od ? y[1] : x[1], od ? y[2] : x[2], od ? y[3] : x[3]);
    sts4(o + R_BE + 16, od ? x[0] : y[0], od ? x[1] : y[1], od ? x[2] : y[2], od ? x[3] : y[3]);
  }
}
DEV void box_full(int j, uint32_t (&u)[4][4], uint32_t zero) {
  const uint32_t a2 = uchunk(8, j - 2), a1 = uchunk(0, j - 1);
  uint2 a[4]; uint4 b[4];
#define HALO(n) { a[n] = lds2(region(n) + a2); b[n] = lds4(region(n) + a1); }
  HALO(0) HALO(1)
  split(zero);
#pragma unroll
  for (int chl = 0; chl < 4; ++chl) {
    const uint32_t d[4] = {u[chl][0], u[chl][1], u[chl][2], u[chl][3]};
    box_unit<true>(region(chl), j, a[chl], b[chl], d, u[chl]);
    if (chl < 2) HALO(chl + 2)
    if (chl != 2) {
      fence_async_smem();
      if (chl == 3) bar_arrive(NB_B + 2, 288);
      bar_arrive(NB_B + chl, 288);
    }
    if (chl == 0) PROF(31);
  }
#undef HALO
}
DEV void box_help(int e, int lane) {
  bar_sync(NB_H, 192);
#pragma unroll 1
  for (int n = 0; n < 4; ++n) {
    const int chl = e + (n & 2), s = 128 + 32 * (n & 1) + lane;
    const uint32_t reg = region(chl);
    const uint4 d = lds4(uchunk(reg, s));
    const uint32_t u[4] = {d.x, d.y, d.z, d.w};
    uint32_t v[4];
    box_unit<false>(reg, s, lds2(uchunk(reg, s - 2) + 8), lds4(uchunk(reg, s - 1)), u, v);
    if (n & 1) { fence_async_smem(); bar_arrive(NB_B + chl, 288); }
  }
}

DEV uint4 hadd8(const uint4& a, const uint4& b) { return make_uint4(hadd2(a.x, b.x), hadd2(a.y, b.y), hadd2(a.z, b.z), hadd2(a.w, b.w)); }
DEV void conv_out(int c, int j, int chl, uint4 (&x)[2][2][2], const uint32_t (&v)[4], uint4* XF, uint32_t zero) {
  const int rho = chl >> 1, e = chl & 1;
  const uint32_t ua = uchunk(region(chl), j), fa = region(chl) + R_X5 + j * 16, ha = region(chl) + R_X3 + (j & 1) * 1088 + (j >> 1) * 16;
  const int m8 = ((j & 4) + ((j >> 1) & 1) + 2 * (j & 1)) ^ ((2 * c + e) & 7);
  uint4* xo = XF + (((16 - 2 * (j & 8) + (j >> 4)) * 512 + 256 * rho + 2 * c + e) * 8 + m8);
  bar_sync(NB_Y + e + 7 * rho, 256);
  uint4 y[2], f[2], h[2];
#pragma unroll
  for (int k = 0; k < 2; ++k) {
    y[k] = lds4(ua + k * 2048);
    f[k] = lds4z(ua + k * 2048 + R_BO - R_U, k || j >= 36);
    h[k] = lds4z(fa + k * 2048 - 1024, k || j >= 64);
  }
  const uint32_t q = lds1(SM_TAP + chl * TAP_SZ + T_K);
  const uint4 r = lds4(ha);
  split(zero);
  h[1] = hadd8(h[1], make_uint4(hfma2(q, v[0], r.x), hfma2(q, v[1], r.y), hfma2(q, v[2], r.z), hfma2(q, v[3], r.w)));
#pragma unroll
  for (int k = 0; k < 2; ++k) {
    const uint4 o = hadd8(hadd8(y[k], hadd8(f[k], h[k])), make_uint4(xword(x[k][rho], e, 0), xword(x[k][rho], e, 1), xword(x[k][rho], e, 2), xword(x[k][rho], e, 3)));
    const uint32_t keep = j & 1 ? 0x7632 : 0x5410, k0 = prmt(o.x, o.y, keep), k1 = prmt(o.z, o.w, keep);
    const uint32_t g0 = __shfl_xor_sync(0xffffffffu, prmt(o.x, o.y, keep ^ 0x2222), 1), g1 = __shfl_xor_sync(0xffffffffu, prmt(o.z, o.w, keep ^ 0x2222), 1);
    str4(xo + k * 32768, j & 1 ? g0 : k0, j & 1 ? g1 : k1, j & 1 ? k0 : g0, j & 1 ? k1 : g1);

  }
  if (e) { __syncwarp(); mbar_arrive1(B_RD + rho * 8); }
}

DEV void conv_round(int e, int rho, int w, int lane) {
  const int g = lane >> 2, t = lane & 3, chl = 2 * rho + e;
  const uint32_t reg = region(chl), tp = SM_TAP + chl * TAP_SZ, dr = dlo(reg, 128);
  const uint32_t g0 = tp + ((g & 1) ? T_O : T_E) + 2 * (2 * t - g) - 16;
  const uint32_t ga = g0 - 32 * (w & 1) - 576 * (w >> 1), id = opq(0x3210u);
  float acc[32], f1[24], f2[16];
  uint32_t q[12][4];
  {
    uint32_t qn[18][4];
    qn[0][2] = lds1(ga + 64);
#pragma unroll
    for (int n = 0; n < 18; ++n) {
      const bool nz = n < 15 || w < 2 || (n == 15 && w == 2);
      qn[n][0] = n < 15 ? lds1(ga + 48 - 32 * n) : lds1z(ga + 48 - 32 * n, nz);
      qn[n][1] = n < 15 ? lds1(ga + 32 - 32 * n) : lds1z(ga + 32 - 32 * n, nz);
    }
#pragma unroll
    for (int n = 0; n < 18; ++n) { qn[n][3] = cpy(qn[n][0], id); if (n) qn[n][2] = cpy(qn[n - 1][1], id); }
#pragma unroll
    for (int n = 0; n < 8; ++n) {
      const int i = n & 3;
      const uint32_t a = g0 + 16 - 16 * w - 2 * (n < 4 ? X_5 : X_3) + 16 * i;
      uint32_t (&q1)[4] = q[(n & 4) + (i >> 1)], (&q2)[4] = q[(n & 4) + 2 + (i >> 1)];
      q1[2 * (i & 1)] = lds1z(a, i <= w); q1[2 * (i & 1) + 1] = lds1(a - 64);
      q2[2 * (i & 1)] = cpy(0, id); q2[2 * (i & 1) + 1] = lds1z(a - 128, i >= w);
    }
    const uint32_t gc = tp + T_C - 2 + 4 * (t - g - 8 * w);
#pragma unroll
    for (int kk = 0; kk < 4; ++kk) {
      q[8 + kk][0] = lds1z(gc + 32 * kk, w >= kk); q[8 + kk][2] = lds1z(gc + 32 * kk + 16, w >= kk);
      q[8 + kk][1] = lds1(gc + 32 * kk - 128); q[8 + kk][3] = lds1(gc + 32 * kk - 112);
    }
    PROFD(rho ? 43 : 47, qn[17][2] ^ q[11][3]);
    bar_sync_if(NB_U, NBARU, 1 - rho);
    mbar_arrive1_if(B_V, chl == 1 && w == 0);
    bar_sync_if(NB_T + 1 - e, 256, chl);
    const uint32_t db = dr + (R_U + 32) / 16;
    undef(acc);
    wg_fence();
#pragma unroll
    for (int n = 0; n < 18; ++n) {
      if (n) wg_rs64k<1>(acc, qn[n], db - 2 * n); else wg_rs64k<0>(acc, qn[0], db);
      if (n == 9) wg_commit();
    }
    wg_commit();
  }
  wg_wait<1>();
  PROF(12);
  bar_sync(NB_B + chl, 288);
  const uint32_t d1 = dr + R_X5 / 16, d2 = dr + R_BO / 16;
  undef(f1); undef(f2);
  wg_fence();
#pragma unroll
  for (int n = 0; n < 8; ++n) {
    const uint32_t d = d1 + (n >> 2) * ((R_X3 - R_X5) / 16) + 16 * (n & 1) - 16 * (n & 2);
    if (n) wg_rs48t<1>(f1, q[n], d); else wg_rs48t<0>(f1, q[0], d);
    if (n & 1) { if (n > 1) wg_rs32t<1>(f2, q[8 + (n >> 1)], d2 + 16 * (n >> 1)); else wg_rs32t<0>(f2, q[8], d2); }
  }
  wg_commit();
  wg_wait<1>();
  PROF(13);
  bar_arrive_if(NB_T + e, 256, chl - 3);
  wg_wait<0>();
  PROF(14);
  bar_sync(NB_WG + e, 128);
  {
    const int p = (lane + 9 * (w >> 1)) & 31;
    const uint32_t ya = reg + ((w >> 1) ? R_BO : R_U) + p * 64 + (((2 * (w & 1)) ^ ((p >> 1) & 3)) * 16);
    const uint32_t up = p < lane ? 2048 : 0;
#pragma unroll
    for (int z = 0; z < 4; ++z) {
      const float* a = acc + 16 * (z >> 1) + 2 * (z & 1);
      stsm4t((ya + (up ^ ((z >> 1) * 2048))) ^ ((z & 1) * 16), pack2(a[0], a[1]), pack2(a[4], a[5]), pack2(a[8], a[9]), pack2(a[12], a[13]));
    }
  }
  {
    const uint32_t fa = reg + R_X5 + (8 * w + (lane & 7)) * 16 + (lane >> 3) * 512;
    uint32_t h[6];
#pragma unroll
    for (int p = 0; p < 6; ++p) h[p] = p ? pack2(f1[4 * p] + f1[4 * p - 2], f1[4 * p + 1] + f1[4 * p - 1]) : pack2(f1[0], f1[1]);
    stsm4(fa, h[0], h[1], h[2], h[3]);
    stsm2(fa + 2048, h[4], h[5]);
    stsm4(reg + R_X3 + (lane < 16 ? 1088 : 0) + (8 * w + (lane & 7) + 4 * (lane & 8)) * 16, pack2(f2[0], f2[1]), pack2(f2[2] + f2[4], f2[3] + f2[5]),
          pack2(f2[8], f2[9]), pack2(f2[10] + f2[12], f2[11] + f2[13]));
  }
  bar_arrive(NB_Y + e + 7 * rho, 256);
}
constexpr uint32_t FILL = 0xFFFFFFFFu;
template <int N> DEV void fixo(uint4 (&A)[N], const uint4* p) {
#pragma unroll 1
  for (int it = 0; it < SPIN_LIMIT; ++it) {
    uint32_t m = A[0].x;
#pragma unroll
    for (int k = 1; k < N; ++k) m = max(m, A[k].x);
    if (__all_sync(0xffffffffu, m != FILL)) break;
#pragma unroll
    for (int k = 0; k < N; ++k) ldr4_if(A[k], p + k * 32, A[k].x == FILL);
  }
}
DEV bool rows_nan(float a, float b) {
  return __any_sync(0xffffffffu, a != a || b != b);
}
template <int N> DEV void slow_step(float (&acc)[N], float a0, float a1, const uint16_t* wr, uint32_t zero) {
#pragma unroll
  for (int j = 0; j < N / 4; ++j) {
    const uint32_t v = __ldg((const uint32_t*)(wr + (j >> 3) * 512 + 8 * (j & 7)));
    acc[4 * j] += a0 * bflo(v); acc[4 * j + 1] += a0 * bfhi(v); acc[4 * j + 2] += a1 * bflo(v); acc[4 * j + 3] += a1 * bfhi(v);
    if ((j & 3) == 3) wr += __float_as_uint(acc[4 * j]) & zero;
  }
}
DEV int res_off(int w, int lane) { return ((lane & 7) + 8 * (lane >> 4)) * 8 + ((2 * (w & 2) + (w & 1) + ((lane >> 2) & 2)) ^ (lane & 7)); }
DEV void res_load(uint32_t (&res)[8][2], uint32_t sa, int w, int lane) {
  const uint32_t a = sa + res_off(w, opq(lane)) * 16;
#pragma unroll
  for (int j = 0; j < 8; j += 2) {
    uint32_t r[4];
    ldsm4t(r, a + j * 1024);
    res[j][0] = r[0]; res[j][1] = r[1]; res[j + 1][0] = r[2]; res[j + 1][1] = r[3];
  }
}

DEV void res_init(float (&ac)[32], const uint32_t (&res)[8][2]) {
#pragma unroll
  for (int j = 0; j < 16; ++j) { ac[2 * j] = bflo(res[j >> 1][j & 1]); ac[2 * j + 1] = bfhi(res[j >> 1][j & 1]); }
}
DEV uint32_t after(uint32_t b, const uint32_t (&res)[8][2], uint32_t zero) {
  return b + ((res[0][0] ^ res[2][0] ^ res[4][0] ^ res[6][0]) & zero);
}

DEV void attn_phase(const Params& P, int c, int e, int w, int lane, int layer) {
  lane = opq(lane); c = opq(c);
  const int i = c >> 3, cg = c & 7, J = 16 * e + i, G = 8 * i + 4 - 4 * e + w;
  const int g = lane >> 2, t = lane & 3;
  float acc[96];
  uint32_t res[8][2];
  float2 cs[16];
  float4 st;
  const uint32_t csb = opq(SM_CS + 8 * t);
  {
    const uint32_t sa = SM_A + e * A_E, ba = B_A + 16 * e;
    const uint32_t da = dlo(sa, 8192), db = (SB >> 4) | (512 << 16);
    undef(acc);
#pragma unroll
    for (int j = 0; j < 8; ++j) asm volatile("" : "=r"(res[j][0]), "=r"(res[j][1]));
    mbar_wait(B_WF, layer);
    mbar_wait(ba, 0);
    mbar_wait(B_RD + 8, layer);
    bar_sync_if(NB_T, 256, e);
    PROF(24);
#pragma unroll
    for (int j = 0; j < 4; ++j) {
      if (j == 1) { mbar_wait(ba + 8, 0); PROFK(layer ? 39 : 15); }
      wg_fence();
#pragma unroll
      for (int k = 0; k < 4; ++k) {
        if (j | k) wg_ss192<1>(acc, da + j * 512 + k * 128, db + wslot(j) * 512 + k * 128); else wg_ss192<0>(acc, da, db);
        if (j == 3 && k == 1) wg_commit();
      }
      wg_commit();
      if (j == 1 || j == 2) { wg_wait<1>(); mbar_arrive1_if(B_F + 8 * (j - 1), e); }
    }
    wg_wait<1>();
    bar_arrive(NB_T + e, 256);
    wg_wait<0>();
    if (cg < 4) res_load(res, sa + cg * 8192, w, lane);
    mbar_arrive1(after(B_AE + 8 * e, res, P.zero));
    PROF(25);
#pragma unroll 1
    for (uint32_t late = P.zero;; late = 1) {
      if (late) {
        const uint16_t* xr = (const uint16_t*)SCR->XF[layer] + opq(J) * 32768;
        zero(acc);
#pragma unroll 1
        for (int k = 0; k < 512; ++k)
          slow_step(acc, ldnan(xr + k * 64 + ((2 * w) ^ (k & 7)) * 8 + g), ldnan(xr + k * 64 + ((2 * w + 1) ^ (k & 7)) * 8 + g),
                    P.wqkv + (k * 1536 + 64 * cg + 2 * t), P.zero);
        const uint32_t* q = (const uint32_t*)xr + ((64 * cg + g) * 32 + t);
        const int m8 = (2 * (w & 2) + (w & 1)) ^ g;
#pragma unroll 1
        for (int it = 0; it < SPIN_LIMIT; ++it) {
          uint32_t m = 0;
#pragma unroll
          for (int z = 0; z < 16; ++z) { const uint32_t x = ldr1(q + (z >> 1) * 256 + (m8 ^ (2 * (z & 1))) * 4); m = max(m, x); res[z >> 1][z & 1] = movm(x); }
          if (__all_sync(0xffffffffu, m != FILL)) break;
        }
#pragma unroll
        for (int z = 0; z < 16; ++z) cs[z] = lds2f(csb + 256 + z * 32);
      } else {
        mbar_wait(B_CS, 0);
#pragma unroll
        for (int z = 0; z < 16; ++z) cs[z] = lds2f(csb + 256 + z * 32);
        mbar_wait(B_W4, layer);
        mbar_wait(ba, 1);
        bar_sync(NB_T + 1 - e, 256);
        PROF(26);
#pragma unroll
        for (int j = 4; j < 8; ++j) {
          if (j == 5) mbar_wait(ba + 8, 1);
          if (j >= 6) mbar_wait(B_W6 + 8 * (j - 6), layer);
          if (j > 4) PROF(31 + j);
          wg_fence();
#pragma unroll
          for (int k = 0; k < 4; ++k) {
            wg_ss192<1>(acc, da + (j & 3) * 512 + k * 128, db + wslot(j) * 512 + k * 128);
            if (j == 7 && k == 1) wg_commit();
          }
          wg_commit();
          if (j == 5) {
            if (cg >= 4) res_load(res, sa + (cg - 4) * 8192, w, lane);
            wg_wait<1>(); mbar_arrive1_if(B_F + 16, e); PROF(40);
          }

        }
      }
      uint32_t rs = hadd2(res[0][0], res[0][1]);
#pragma unroll
      for (int z = 2; z < 16; ++z) rs = hadd2(rs, res[z >> 1][z & 1]);
      const float rn = bflo(rs) + bfhi(rs);
      wg_wait<1>();
      bar_arrive_if(NB_T, 256, !(e | late));
      mbar_wait(B_ST + 8 * e, layer);
      st = lds4f(SM_STAT + ((4 * e + w) * 8 + g) * 16);
      PROF(34 + layer);
      wg_wait<0>();
      if (!rows_nan(acc[0] + rn, acc[2]) || late) break;
    }
  }
  mbar_arrive1(B_QE);
  PROFK(8 + 12 * layer);
  uint32_t Q[4][4], K[4][2][2], V[4][2][2];
  {
#pragma unroll
    for (int z = 0; z < 8; ++z) {
      const float* a = acc + 32 + 4 * z; const float* b = acc + 64 + 4 * z;
      K[z >> 1][1][z & 1] = pack2((a[2] - st.z * cs[z].x) * st.w, (a[3] - st.z * cs[z].y) * st.w);
      V[z >> 1][1][z & 1] = movm(pack2((b[2] - st.z * cs[8 + z].x) * st.w, (b[3] - st.z * cs[8 + z].y) * st.w));
    }
    const int hop = (G >> 1) & 3;
    const uint32_t kv = SM_KV + (2 * hop + (w & 1)) * 2048 + lane * 16;
    uint4* h = SCR->H[layer] + (c * 256 + (w & 1) * 128 + lane);
    if (hop == 3) {
#pragma unroll
      for (int z = 0; z < 4; ++z) str4(h + 2048 + z * 32, K[z][1][0], K[z][1][1], V[z][1][0], V[z][1][1]);
    } else {
      mbar_wait(B_F + 16, layer);
#pragma unroll
      for (int z = 0; z < 4; ++z) sts4(kv + z * 512, K[z][1][0], K[z][1][1], V[z][1][0], V[z][1][1]);
      bar_arrive(NB_B + hop, 128);
    }
    PROF(42);
    uint4 hv[4];
#pragma unroll
    for (int z = 0; z < 4; ++z) { hv[z] = make_uint4(0, 0, 0, 0); ldr4_if(hv[z], h + z * 32, G >= 2 && hop == 0); }
#pragma unroll
    for (int z = 0; z < 8; ++z) {
      const float* a = acc + 32 + 4 * z; const float* b = acc + 64 + 4 * z;
      K[z >> 1][0][z & 1] = pack2((a[0] - st.x * cs[z].x) * st.y, (a[1] - st.x * cs[z].y) * st.y);
      V[z >> 1][0][z & 1] = movm(pack2((b[0] - st.x * cs[8 + z].x) * st.y, (b[1] - st.x * cs[8 + z].y) * st.y));
    }
#pragma unroll
    for (int z = 0; z < 8; ++z) {
      const float2 cq = lds2f(csb + z * 32);
      const float* a = acc + 4 * z;
      Q[z >> 1][2 * (z & 1)] = pack2(a[0] - st.x * cq.x, a[1] - st.x * cq.y);
      Q[z >> 1][2 * (z & 1) + 1] = pack2(a[2] - st.z * cq.x, a[3] - st.z * cq.y);
    }
    PROF(27);
    const bool p0 = 2 * t > g, p1 = 2 * t + 1 > g, first = G < 2;
    float s[4][4], mx[4][2];
#pragma unroll
    for (int z = 0; z < 4; ++z) {
      float S[4];
      mma16z(s[z], Q[z][0], Q[z][1], Q[z][2], Q[z][3], K[z][0][0], K[z][0][1]);
      mma16z(S, Q[z][0], Q[z][1], Q[z][2], Q[z][3], K[z][1][0], K[z][1][1]);
      s[z][2] = p0 ? s[z][2] : S[2]; s[z][3] = p1 ? s[z][3] : S[3];
    }
    const float sc0 = st.y * (0.25f * 1.4426950408889634f), sc1 = st.w * (0.25f * 1.4426950408889634f);
    uint32_t pw[4][2];
#pragma unroll
    for (int r = 1; r >= 0; --r) {
      if (r == 0) {
        if (hop) {
          bar_sync(NB_B + hop - 1, 128);
#pragma unroll
          for (int z = 0; z < 4; ++z) hv[z] = lds4(kv - 4096 + z * 512);
        } else fixo(hv, h);
        PROFD(41, hv[3].x);
#pragma unroll
        for (int z = 0; z < 4; ++z) {
          float S[4];
          mma16z(S, Q[z][0], Q[z][1], Q[z][2], Q[z][3], hv[z].x, hv[z].y);
          if (first) S[0] = S[1] = __uint_as_float(0xFF800000u);
          s[z][0] = p0 ? S[0] : s[z][0]; s[z][1] = p1 ? S[1] : s[z][1];
        }
      }
#pragma unroll
      for (int z = 0; z < 4; ++z) mx[z][r] = fmaxf(s[z][2 * r], s[z][2 * r + 1]);
#pragma unroll
      for (int o = 1; o < 3; ++o)
#pragma unroll
        for (int z = 0; z < 4; ++z) mx[z][r] = fmaxf(mx[z][r], __shfl_xor_sync(0xffffffffu, mx[z][r], o));
#pragma unroll
      for (int z = 0; z < 4; ++z) pw[z][r] = pack2(ex2((s[z][2 * r] - mx[z][r]) * (r ? sc1 : sc0)), ex2((s[z][2 * r + 1] - mx[z][r]) * (r ? sc1 : sc0)));
    }
    mbar_wait(layer ? B_N : B_Z, layer);
    const uint32_t M = (p0 ? 0xFFFFu : 0u) | (p1 ? 0xFFFF0000u : 0u);
    uint4* O = SCR->O + ((J * 8 + cg) * 512 + (2 * (w & 2) + (w & 1)) * 64 + t * 8 + g);
#pragma unroll
    for (int h2 = 0; h2 < 2; ++h2) {
      uint32_t ow[2][4];
#pragma unroll
      for (int z = 0; z < 2; ++z) {
        const int n = 2 * h2 + z;
        const uint32_t w0 = pw[n][0], w1 = pw[n][1];
        float sm[4] = {0.f, 0.f, 0.f, 0.f}, Oa[2][4];
        mma8(sm, w0, w1, 0x3F803F80u);
        mma16z(Oa[0], w0 & ~M, w1 & M, 0u, w1 & ~M, V[n][0][0], V[n][1][0]); mma8(Oa[0], w0 & M, 0u, hv[n].z);
        mma16z(Oa[1], w0 & ~M, w1 & M, 0u, w1 & ~M, V[n][0][1], V[n][1][1]); mma8(Oa[1], w0 & M, 0u, hv[n].w);
        const float i0 = rcp(sm[0]), i1 = rcp(sm[2]);
#pragma unroll
        for (int d = 0; d < 2; ++d) { ow[0][2 * z + d] = pack2(Oa[d][0] * i0, Oa[d][1] * i0); ow[1][2 * z + d] = pack2(Oa[d][2] * i1, Oa[d][3] * i1); }
      }
#pragma unroll
      for (int hi = 0; hi < 2; ++hi) str4(O + hi * 128 + h2 * 32, ow[hi][0], ow[hi][1], ow[hi][2], ow[hi][3]);
    }
  }
  str1(SCR->OF[layer] + (J * 32 + cg * 4 + w), 1);
  mbar_arrive1(B_AT + 8 * e + (lds1(csb) & P.zero));
  PROFK(9 + 12 * layer);
  float ac[32];
  res_init(ac, res);
  const uint32_t so = SM_O + e * O_E;
  uint2* xo = opqp(layer ? (uint2*)(P.out + ((16 * G + 2 * (lane >> 3)) * 512 + 64 * cg + 8 * (lane & 7)))
                         : (uint2*)SCR->XG[1] + ((32 * (cg & 3) + t) * 2048 + (cg >> 2) * 512 + xg_off(G, g)));
  const uint32_t stg = SM_X + (4 * e + w) * 2048;
  const uint32_t sw = opq(stg + (lane & 15) * 128 + (((lane >> 4) ^ (lane & 7)) * 16)), sr = opq(stg + (lane >> 3) * 128 + (((lane & 7) ^ (lane >> 3)) * 16));
  uint4* ps = opqp(&SCR->PS[(G * 8 + cg) * 8 + g]);
  {
    const uint32_t bo = B_O + 32 * e;
    const uint32_t dw = (SM_WO >> 4) | (512 << 16), da = dlo(so, 512);
    mbar_wait(B_WO, layer);
#pragma unroll
    for (int j = 0; j < 4; ++j) {
      mbar_wait(bo + 8 * j, layer);
      if (j == 0) { PROFK(32 + layer); mbar_wait(B_AT + 8, layer); }
      wg_fence();
#pragma unroll
      for (int k = 8 * j; k < 8 * j + 8; ++k) {
        const uint32_t a = da + (k >> 2) * 512 + (k & 3) * 8, b = dw + (k & 3) * 1024 + (k >> 2) * 128;
        wg_ss64<1>(ac, a, b);
      }
      wg_commit();
    }
#pragma unroll 1
    for (uint32_t late = P.zero;; late = 1) {
      if (late) {
        const uint16_t* op = (const uint16_t*)(SCR->O + (J * 4096 + w * 128 + g));
        wg_wait<0>();
        res_init(ac, res);
#pragma unroll 1
        for (int k = 0; k < 512; ++k) {
          const uint16_t* q = op + (k >> 6) * 4096 + (k & 56) * 8 + (k & 7);
          slow_step(ac, ldnan(q), ldnan(q + 512), P.wo + (((k & ~31) + 4 * (k & 6) + ((k >> 2) & 6) + (k & 1)) * 512 + 64 * cg + 2 * t), P.zero);
        }
      }
      wg_wait<0>();
      if (!rows_nan(ac[0], ac[2]) || late) break;
    }
  }
  PROFK(10 + 12 * layer);
#pragma unroll
  for (int j = 0; j < 16; ++j) res[j >> 1][j & 1] = pack2(ac[2 * j], ac[2 * j + 1]);
  if (layer == 0) {
    float s[2][4], q0[2][4], q1[2][4];
#pragma unroll
    for (int j = 0; j < 2; ++j) gram<true>(s[j], q0[j], q1[j], res[2 * j][0], res[2 * j][1], res[2 * j + 1][0], res[2 * j + 1][1]);
#pragma unroll
    for (int j = 0; j < 2; ++j) gram<false>(s[j], q0[j], q1[j], res[2 * j + 4][0], res[2 * j + 4][1], res[2 * j + 5][0], res[2 * j + 5][1]);
    const bool od = g & 1;
    str4_if(ps, nzmap(__float_as_uint(s[0][0] + s[1][0])), __float_as_uint(od ? q0[0][1] + q0[1][1] : q0[0][0] + q0[1][0]),
            __float_as_uint(s[0][2] + s[1][2]), __float_as_uint(od ? q1[0][3] + q1[1][3] : q1[0][2] + q1[1][2]), t == (g >> 1));
#pragma unroll
    for (int j = 0; j < 8; ++j) {
      str2(xo + j * 8192, nzmap(prmt(res[j][0], res[j][1], 0x5410)), prmt(res[j][0], res[j][1], 0x7632));
    }
    mbar_arrive1(B_ED + 8 * e);
  } else {
#pragma unroll
    for (int j = 0; j < 8; j += 2) stsm4(sw ^ (j * 16), res[j][0], res[j][1], res[j + 1][0], res[j + 1][1]);
    __syncwarp();
    uint4 v[4];
#pragma unroll
    for (int k = 0; k < 4; ++k) v[k] = lds4((sr ^ ((k & 1) * 64)) + k * 512);
#pragma unroll
    for (int k = 0; k < 4; ++k) stw4(xo + ((k & 1) * 8 + (k >> 1)) * 128, v[k].x, v[k].y, v[k].z, v[k].w);
  }
  PROFK(11 + 12 * layer);
}

DEV void col_sums(const Params& P, int c, int wa, int lane) {
  const int i = c >> 3, cg = c & 7;
  uint4 wv[8];
#pragma unroll
  for (int k = 0; k < 8; ++k) wv[k] = ldnc4(P.wqkv + ((32 * i + (lane >> 3)) * 1536 + wa * 512 + 64 * cg + 8 * (lane & 7)) + 4 * k * 1536);
  float cs[8];
  zero(cs);
#pragma unroll
  for (int k = 0; k < 8; ++k) {
    cs[0] += bflo(wv[k].x); cs[1] += bfhi(wv[k].x); cs[2] += bflo(wv[k].y); cs[3] += bfhi(wv[k].y);
    cs[4] += bflo(wv[k].z); cs[5] += bfhi(wv[k].z); cs[6] += bflo(wv[k].w); cs[7] += bfhi(wv[k].w);
  }
  const bool b4 = lane & 16, b3 = lane & 8;
#pragma unroll
  for (int k = 0; k < 4; ++k) cs[k] = (b4 ? cs[k + 4] : cs[k]) + __shfl_xor_sync(0xffffffffu, b4 ? cs[k] : cs[k + 4], 16);
#pragma unroll
  for (int k = 0; k < 2; ++k) cs[k] = (b3 ? cs[k + 2] : cs[k]) + __shfl_xor_sync(0xffffffffu, b3 ? cs[k] : cs[k + 2], 8);
  str2((uint2*)SCR->CS + (i * 768 + wa * 256 + 32 * cg + 4 * (lane & 7) + (lane >> 3)), nzmap(__float_as_uint(cs[0])), __float_as_uint(cs[1]));
}
DEV void col_gather(const Params& P, int c, int wa, int lane) {
  const uint2* p = (const uint2*)SCR->CS + (wa * 256 + 32 * (c & 7) + lane);
#pragma unroll 1
  for (int it = 0;; ++it) {
    float a = 0.f, b = 0.f;
    uint32_t m = ~0u;
#pragma unroll
    for (int k = 0; k < 16; ++k) { const uint2 q = ldr2(p + k * 768); m = min(m, q.x); a += __uint_as_float(q.x); b += __uint_as_float(q.y); }
    if (__all_sync(0xffffffffu, m != 0u)) { sts2f(SM_CS + wa * 256 + lane * 8, a, b); break; }
    spin_guard(it);
  }
  __syncwarp();
  mbar_arrive1(B_CS);
}

DEV void aux_prologue(const Params& P, int c, int wa, int lane) {
  const int g = lane >> 2, t = lane & 3, G = stat_group(c);
  {
    uint32_t w[16][2];
    const uint16_t* row = P.x0 + ((16 * G + 2 * g) * 512 + 128 * wa + 8 * t);
    bar_sync(NB_Y, 384);
    __nanosleep(100);
#pragma unroll
    for (int z = 0; z < 8; ++z) {
      const uint4 v = ldw4(row + (z & 1) * 512 + (z >> 1) * 32);
      const int o = 4 * (z >> 1);
      w[o][z & 1] = v.x; w[o + 1][z & 1] = v.y; w[o + 2][z & 1] = v.z; w[o + 3][z & 1] = v.w;
    }
    PROF(34);
    PROFD(35, w[0][0]);
    PROFD(36, w[15][1]);
    uint2* xo = (uint2*)SCR->XG[0] + ((64 * (wa & 1) + 4 * t) * 2048 + (wa >> 1) * 512 + xg_off(G, g));
#pragma unroll
    for (int n = 0; n < 16; ++n) str2(xo + (16 * (n >> 2) + (n & 3)) * 2048, nzmap(prmt(w[n][0], w[n][1], 0x5410)), prmt(w[n][0], w[n][1], 0x7632));
    float s[2][4], q0[2][4], q1[2][4];
#pragma unroll
    for (int z = 0; z < 8; ++z) {
      const int o = 4 * (z >> 1), r = z & 1;
      if (z < 2) gram<true>(s[r], q0[r], q1[r], w[o][r], w[o + 1][r], w[o + 2][r], w[o + 3][r]);
      else gram<false>(s[r], q0[r], q1[r], w[o][r], w[o + 1][r], w[o + 2][r], w[o + 3][r]);
    }
    const bool od = g & 1;
    if (t == (g >> 1))
      sts4f(SM_MISC + (wa * 8 + g) * 16, s[0][0] + s[0][2], od ? q0[0][1] + q1[0][3] : q0[0][0] + q1[0][2],
            s[1][0] + s[1][2], od ? q0[1][1] + q1[1][3] : q0[1][0] + q1[1][2]);
    bar_arrive(NB_P0, 192);
  }
  PROF(2);
  if (lane == 0)
    asm volatile("cp.async.bulk.prefetch.L2.global [%0],4096;" :: "l"(wa < 3 ? P.wqkv + (3 * c + wa) * 2048 : P.wo + c * 2048) : "memory");
  bar_sync(NB_Y + 1, 256);
}

DEV void stat_part(const Params& P, int c, int wa, int lane, int layer, int h, float (&v)[2]) {
  lane = opq(lane);
  const int e = wa >> 1;
  uint32_t x[4][4];
  mbar_wait(B_A + 16 * e, h); mbar_wait(B_A + 16 * e + 8, h);
#pragma unroll
  for (int k = 0; k < 4; ++k) ldsm4t(x[k], SM_A + e * A_E + (128 * (wa & 1) + lane) * 128 + (((c ^ lane) & 7) * 16) + k * 4096);
  float s[4] = {0.f, 0.f, 0.f, 0.f};
#pragma unroll
  for (int k = 0; k < 16; ++k) { const float a = bflo(x[k >> 2][k & 3]), b = bfhi(x[k >> 2][k & 3]); s[0] += a; s[1] += a * a; s[2] += b; s[3] += b * b; }
  s[0] += s[2]; s[1] += s[3];
  if (RARE(rows_nan(s[1], s[1]))) {
    const uint16_t* q = (const uint16_t*)(SCR->XF[layer] + ((32 * e + 2 * (c >> 3) + h) * 2048 + (wa & 1) * 1024)) + (lane >> 2);
    s[0] = s[1] = 0.f;
#pragma unroll 1
    for (int k = 0; k < 32; ++k) {
      const int r = 2 * (lane & 3) + (k & 1);
      const float a = ldnan(q + ((k >> 1) * 8 + r) * 64 + ((c ^ r) & 7) * 8);
      s[0] += a; s[1] += a * a;
    }
  }
  v[0] += s[0]; v[1] += s[1];
  __syncwarp();
}
DEV void stat_finish(const Params& P, int c, int wa, int lane, int layer, float (&v)[2]) {
  lane = opq(lane);
  const bool b = lane & 1;
  const float s = (b ? v[1] : v[0]) + __shfl_xor_sync(0xffffffffu, b ? v[0] : v[1], 1);
  str1((uint32_t*)SCR->ST[layer] + ((128 * (wa >> 1) + c) * 64 + (wa & 1) * 32 + lane), nzmap(__float_as_uint(s)));
  const uint4* sp = SCR->ST[layer] + ((128 * (wa >> 1) + (c & ~7) + 4 * (wa & 1) + (lane >> 3)) * 16 + (lane & 7));
  uint4 x, y;
  for (int it = 0;; ++it) {
    x = ldr4(sp); y = ldr4(sp + 8);
    if (__all_sync(0xffffffffu, min(min(min(x.x, x.y), min(x.z, x.w)), min(min(y.x, y.y), min(y.z, y.w))) != 0u)) break;
    spin_guard(it);
  }
  const uint32_t q = ln_sums((__uint_as_float(x.x) + __uint_as_float(x.z)) + (__uint_as_float(y.x) + __uint_as_float(y.z)),
                             (__uint_as_float(x.y) + __uint_as_float(x.w)) + (__uint_as_float(y.y) + __uint_as_float(y.w)));
  sts2f(SM_STAT + (16 * wa + (lane >> 4) * 8 + (lane & 7)) * 16 + (lane & 8), bflo(q), rcp(bfhi(q)));
  __syncwarp();
  mbar_arrive1(B_ST + 4 * (wa & 2));
}

DEV void nan_source(uint32_t a, int lane) {
#pragma unroll
  for (int k = 0; k < 4; ++k) sts4(a + k * 512 + lane * 16, FILL, FILL, FILL, FILL);
  fence_async_smem();
  __syncwarp();
}
DEV void load_a(const Params& P, int J, int e, int layer, int h) {
  const uint4* src = SCR->XF[layer] + (2 * J + h) * 2048;
  const uint32_t dst = SM_A + e * A_E, b = B_A + 16 * e;
  mbar_expect1(b, 8192); bulk(dst, src, 8192, b);
  mbar_expect1(b + 8, 24576); bulk(dst + 8192, src + 512, 24576, b + 8);
}
DEV void load_o(const Params& P, int c, int e, int layer, int lane) {
  const int J = 16 * e + (c >> 3);
  mbar_wait(B_AT + 8 * e, layer);
  if (!e) pause(260);
#pragma unroll 1
  for (int it = 0;; ++it) {
    spin_guard(it);
    if (__all_sync(0xffffffffu, ldr1(SCR->OF[layer] + J * 32 + lane) != 0u)) break;
  }
#pragma unroll
  for (int j = 0; j < 4; ++j) bulk(SM_O + e * O_E + 16384 * j, SCR->O + (J * 4096 + j * 1024), 16384, B_O + 32 * e + 8 * j);
  PROFK(9 + e + 12 * layer);
}

__global__ void __launch_bounds__(NTHR, 1)
fused_kernel(const __grid_constant__ Params P, const __grid_constant__ CUtensorMap mapW, const __grid_constant__ CUtensorMap mapWo,
             const __grid_constant__ CUtensorMap mapX) {
  extern __shared__ __align__(1024) uint8_t smem_raw[];
  const int warp = __shfl_sync(0xffffffffu, threadIdx.x >> 5, 0), lane = threadIdx.x & 31;
  uint32_t smid; asm volatile("mov.u32 %0,%%smid;" : "=r"(smid));
  const uint32_t* pw = (const uint32_t*)&P + threadIdx.y;
  const int role = P.role[(smid >> 1) + threadIdx.y] + (smid & 1) + (pw[0] & pw[12]);
  const int c = __shfl_sync(0xffffffffu, pw[1] ? role : blockIdx.x, 0);
  if (c >= 128) {
#pragma unroll 1
    for (int k = (c - 128) * NTHR + threadIdx.x; k < 131072; k += P.spare * NTHR) str4(SCR->XG[1] + k, 0, 0, 0, 0);
    __threadfence();
    __syncthreads();
    if (warp == 0) { cnt_wait(SCR->C + 1, lane); cnt_add1(SCR->C + 6); }
    __syncthreads();
#pragma unroll 1
    for (int k = (c - 128) * NTHR + threadIdx.x; k < 131072; k += P.spare * NTHR) str4(SCR->XG[0] + k, 0, 0, 0, 0);
    return;
  }
#define DONE() do {} while (0)
  const int cg = c & 7;
  if (warp < 8) {
    PROF(46);
    kgen(P, c, warp, lane);
    PROFK(1);
    bar_sync(0, 384);
#pragma unroll 1
    for (int layer = 0; layer < 2; ++layer) {
#pragma unroll 1
      for (int rho = 0; rho < 2; ++rho) {
        const int wz = warp + ((rho + layer) & P.zero);
        conv_round(wz >> 2, rho, wz & 3, lane_id());
        PROFK(6 + rho + 12 * layer);
      }
      const int z = layer & P.zero;
      attn_phase(P, c + z, (warp + z) >> 2, (warp + z) & 3, lane_id(), layer);
    }
    DONE();
  } else if (warp < 12) {
    asm volatile("setmaxnreg.dec.sync.aligned.u32 %0;" :: "n"(REG_AUX));
    aux_prologue(P, c, warp - 8, lane);
    PROF(1);
    const int c0 = c;
#pragma unroll 1
    for (int layer = 0;; ++layer) {
      const int c = c0 + (layer & P.zero), wa = warp - 8 + (layer & P.zero);
#define lane lane_id()
#define j (32 * wa + lane_id())
      uint4 x[2][2][2];
      uint32_t u[4][4];
      uprep(P, c, wa, lane, layer, x, u);
      fence_async_smem();
      bar_arrive(NB_U, NBARU);
      PROFK(5 + 12 * layer);
      bar_sync(NB_H, 192);
      box_full(j, u, P.zero);
      PROF(3 + 12 * layer);
      mbar_wait(B_Z, 0);
      conv_out(c, j, 0, x, u[0], SCR->XF[layer], P.zero);
      PROF(32);
      conv_out(c, j, 1, x, u[1], SCR->XF[layer], P.zero);
      PROF(6 + 12 * layer);
      if (layer == 0 && wa < 3) col_sums(P, c, wa, lane);
      conv_out(c, j, 2, x, u[2], SCR->XF[layer], P.zero);
      PROF(33);
      conv_out(c, j, 3, x, u[3], SCR->XF[layer], P.zero);
      PROFK(7 + 12 * layer);
      float v[2];
      zero(v);
#pragma unroll 1
      for (int h = 0; h < 2; ++h) {
        stat_part(P, c, wa, lane, layer, h, v);
        if (h) break;
        mbar_arrive1(B_AE + 4 * (wa & 2));
        if (layer == 0 && wa < 3) col_gather(P, c, wa, lane);
      }
      PROF(9 + 12 * layer);
      stat_finish(P, c, wa, lane, layer, v);
      PROF(8 + 12 * layer);
      if (layer) break;
      mbar_wait(B_ED, 0); mbar_wait(B_ED + 8, 0);
#undef lane
#undef j
    }
    DONE();
  } else {
    asm volatile("setmaxnreg.dec.sync.aligned.u32 %0;" :: "n"(REG_PROD));
    if (s2u(smem_raw) != SB) __trap();
#pragma unroll 1
    for (int n = warp - 12; n < 38; n += 4)
      asm volatile("{.reg .pred p; elect.sync _|p,0xffffffff; @p mbarrier.init.shared::cta.b64 [%0],%1;}"
                   :: "r"(SM_BAR + n * 8), "r"(n > 14 ? 1 : (int)(0x322866444444444ull >> (4 * n)) & 15) : "memory");
    fence_async_smem();
    bar_sync(NB_AUX, 128);
    bar_arrive(0, 384); bar_arrive(NB_Y + 1, 256);
    PROF(1);
    if (warp == 12) {
      if (lane == 0) {
        asm volatile("prefetch.tensormap [%0];" :: "l"(&mapW) : "memory");
        asm volatile("prefetch.tensormap [%0];" :: "l"(&mapWo) : "memory");
        asm volatile("prefetch.tensormap [%0];" :: "l"(&mapX) : "memory");
      }
      nan_source(slot(12), lane);
      mbar_wait(B_U, 0);
#pragma unroll 1
      for (int k = 0; k < 8; ++k) tma2_store(&mapX, slot(12), 128 * c, 8 * k);
#pragma unroll 1
      for (int k = 0; k < 4; ++k) bulk_store(SCR->H[k >> 1] + ((c + 8) * 256 + (k & 1) * 128), slot(12), 2048);
#pragma unroll 1
      for (int k = 0; k < 8; ++k) bulk_store(SCR->O + (c * 512 + (k >> 2) * 65536 + (k & 3) * 128), slot(12), 2048);
      bulk_wait();
      mbar_arrive1(B_Z);
      PROF(24);
#pragma unroll 1
      for (int layer = 0; layer < 2; ++layer) {
        mbar_wait(B_V, layer);
        if (layer == 1 && c < 4 && ((0x47 >> lane) & 1)) str1(SCR->C + c * 32 + lane, 0);
        mbar_expect1(B_WF, 4 * 24576);
#pragma unroll
        for (int k = 0; k < 4; ++k) tma3(slot(wslot(k)), &mapW, 64 * cg, 64 * k, 0, B_WF);
        mbar_wait(B_WF, layer);
        mbar_expect1(B_W4, 2 * 24576);
#pragma unroll
        for (int k = 4; k < 6; ++k) tma3(slot(wslot(k)), &mapW, 64 * cg, 64 * k, 0, B_W4);
        bar_sync(NB_AUX, 64);
#pragma unroll 1
        for (int k = 0; k < 2; ++k) {
          mbar_expect1(B_W6 + 8 * k, 24576);
          mbar_wait(B_F + 8 * k, layer);
          tma3(slot(3 * k), &mapW, 64 * cg, 384 + 64 * k, 0, B_W6 + 8 * k);
        }
        mbar_expect1(B_WO, 65536);
        mbar_wait(B_AE + 8, layer);
        nan_source(slot(12), lane);
        uint4* fp = layer ? SCR->O + c * 512 : SCR->XF[1] + c * 512;
#pragma unroll 1
        for (int r = 7; r >= 0; --r) {
          __nanosleep(30);
          if (r >= 4) {
            bulk_store(fp + (r & 3) * 128, slot(12), 2048); bulk_store(fp + 65536 + (r & 3) * 128, slot(12), 2048);
          }
          if (r == 3) { bulk_wait(); __threadfence(); mbar_arrive1(B_N); PROF(9 + 12 * layer); }
          if (r == 1) mbar_wait(B_F + 16, layer);
          tma4(SM_WO + r * 8192, &mapWo, 64 * cg, 0, r >> 1, 32 * (r & 1), B_WO);
        }
        PROF(8 + 12 * layer);
      }
      DONE();
    } else if (warp == 13) {
      const int G = stat_group(c);
#pragma unroll 1
      for (int layer = 0; layer < 2; ++layer) {
        float z[4];
        if (layer == 0) {
          bar_sync(NB_P0, 192);
          const float4 a = lds4f(SM_MISC + lane * 16);
          z[0] = a.x; z[1] = a.y; z[2] = a.z; z[3] = a.w;
        } else {
          mbar_wait(B_ED + 2 * (c & 4), 0);
          uint4* ps = &SCR->PS[G * 64 + lane];
          uint4 a, b;
          for (int it = 0;; ++it) {
            a = ldr4(ps); b = ldr4(ps + 32);
            if (__all_sync(0xffffffffu, min(a.x, b.x) != 0u)) break;
            spin_guard(it);
          }
          z[0] = __uint_as_float(a.x) + __uint_as_float(b.x); z[1] = __uint_as_float(a.y) + __uint_as_float(b.y);
          z[2] = __uint_as_float(a.z) + __uint_as_float(b.z); z[3] = __uint_as_float(a.w) + __uint_as_float(b.w);
        }
#pragma unroll
        for (int o = 8; o < 32; o <<= 1)
#pragma unroll
          for (int k = 0; k < 4; ++k) z[k] += __shfl_xor_sync(0xffffffffu, z[k], o);
        const uint32_t w0 = ln_sums(z[0], z[1]), w1 = ln_sums(z[2], z[3]);
        const uint32_t r = nzmap(pack2(rcp(bfhi(w0)), rcp(bfhi(w1)))), m = pack2(z[0] * (-1.f / 512.f) * bflo(r), z[2] * (-1.f / 512.f) * bfhi(r));
        uint2* so = (uint2*)&SCR->SR[layer][lane >> 3][sr_off(G, lane)] + (lane & 1);
        str2(so, r, m); str2(so + 4 * 1024, r, m);
        PROF(4 + 12 * layer);
        box_help(0, lane);
        PROF(6 + 12 * layer);
      }
      DONE();
    } else if (warp == 14) {
#pragma unroll 1
      for (int layer = 0; layer < 2; ++layer) {
        if (layer) { mbar_wait(B_N, 0); mbar_wait(B_ED, 0); mbar_wait(B_ED + 8, 0); } else bar_sync(NB_P0, 192);
        cnt_add1(SCR->C + (c >> 5) * 32 + 3 * layer);
        if (layer == 0) bar_arrive(NB_P0 + 1, 288);
        mbar_expect1(B_E, 16384);
        PROF(4 + 12 * layer);
        cnt_wait(SCR->C + 3 * layer, lane);
        mbar_arrive1(B_U);
        bulk(SM_X, SCR->XG[layer] + c * 1024, 16384, B_E);
        PROFK(5 + 12 * layer);
        if (layer == 0) {
          mbar_wait(B_Z, 0);
          __threadfence();
          PROF(11);
        }
#pragma unroll 1
        for (int n = 0; n < 4; ++n) {
          if (n == 0) { mbar_wait(B_RD, layer); cnt_add1(SCR->C + (c >> 5) * 32 + 3 * layer + 1); }
          if (!(n & 1)) cnt_wait(SCR->C + 3 * layer + 1 + (n >> 1), lane);
          if (n == 2) PROF(7 + 12 * layer);
          mbar_wait((n & 2 ? B_AE : B_RD) + 8 * (n & 1), layer);
          load_a(P, 16 * (n & 1) + (c >> 3), n & 1, layer, n >> 1);
          bar_arrive_if(NB_AUX, 64, n == 2);
          if (!(n & 1)) PROFK(6 + n + 12 * layer);
        }
#pragma unroll 1
        for (int n = 0; n < 8; ++n) mbar_expect1(B_O + 8 * n, 16384);
        if (layer == 0)
          for (int it = 0; ldr1(SCR->C + 6) < P.spare; ++it) spin_guard(it);
        mbar_wait(B_QE, layer);
#pragma unroll 1
        for (int e = 0; e < 2; ++e) load_o(P, c, e, layer, lane);
      }
      DONE();
    }
    if (warp == 15) {
      const int G = stat_group(c);
      str4(&SCR->ST[0][(lane >> 4) * 2048 + c * 16 + (lane & 15)], 0, 0, 0, 0); str4(&SCR->ST[1][(lane >> 4) * 2048 + c * 16 + (lane & 15)], 0, 0, 0, 0);
      if (lane < 4) str4(SCR->OF[lane >> 1] + ((lane & 1) * 512 + c * 4), 0, 0, 0, 0);
      str4(&SCR->PS[G * 64 + lane], 0, 0, 0, 0); str4(&SCR->PS[G * 64 + 32 + lane], 0, 0, 0, 0);
      str4(&SCR->SR[1][lane >> 2][sr_off(G, 2 * lane)], 0, 0, 0, 0);
      if (c < 4 && lane < 3) str1(SCR->C + c * 32 + 3 + lane, 0);
#pragma unroll
      for (int k = 0; k < 3; ++k) str2((uint2*)SCR->CS + ((c >> 3) * 768 + k * 256 + 32 * cg + lane), 0, 0);
      __threadfence();
#pragma unroll 1
      for (int layer = 0; layer < 2; ++layer) {
        PROF(4 + 12 * layer);
        box_help(1, lane);
        if (layer) str4(&SCR->SR[0][lane >> 2][sr_off(G, 2 * lane)], 0, 0, 0, 0);
        mbar_wait(B_RD + 8, layer);
        cnt_add1(SCR->C + (c >> 5) * 32 + 3 * layer + 2);
        if (P.spare == 0) {
#pragma unroll 1
          for (int k = 0; k < 32; ++k) str4(SCR->XG[layer] + (c * 1024 + k * 32 + lane), 0, 0, 0, 0);
        }
      }
      mbar_watch(B_O + 56, 1);
    }
  }
}

typedef CUresult (*EncodeFn)(CUtensorMap*, CUtensorMapDataType, cuuint32_t, void*, const cuuint64_t*, const cuuint64_t*,
                             const cuuint32_t*, const cuuint32_t*, CUtensorMapInterleave, CUtensorMapSwizzle,
                             CUtensorMapL2promotion, CUtensorMapFloatOOBfill);

static int place_roles(uint8_t* role) {
  int dev = 0, nsm = 0;
  cudaGetDevice(&dev);
  cudaDeviceGetAttribute(&nsm, cudaDevAttrMultiProcessorCount, dev);
  if (nsm <= 128 || nsm > 144 || (nsm & 1)) return 0;
  cudaFuncSetAttribute(fused_kernel, cudaFuncAttributeNonPortableClusterSizeAllowed, 1);
  int occ[9] = {0};
  for (int k = 2; k <= 8; ++k) {
    cudaLaunchConfig_t cfg = {};
    cudaLaunchAttribute at[1];
    at[0].id = cudaLaunchAttributeClusterDimension;
    at[0].val.clusterDim.x = 2 * k; at[0].val.clusterDim.y = 1; at[0].val.clusterDim.z = 1;
    cfg.gridDim = dim3(2 * k); cfg.blockDim = dim3(NTHR); cfg.dynamicSmemBytes = SM_TOTAL; cfg.attrs = at; cfg.numAttrs = 1;
    if (cudaOccupancyMaxActiveClusters(&occ[k], fused_kernel, &cfg) != cudaSuccess) { cudaGetLastError(); occ[k] = 0; }
  }
  int n[10];
  n[7] = occ[8]; n[6] = occ[7]; n[5] = occ[6] - 0; n[4] = occ[5];
  n[3] = occ[4] - n[7]; n[1] = occ[2] - n[3] - n[5] - n[7]; n[0] = n[2] = n[1];
  n[8] = occ[3] - n[2] - n[5];
  const int ntpc = nsm / 2;
  int sum = 0;
  bool ok = n[0] > 0 && n[0] <= 8;
  for (int r = 0; r < 9; ++r) { ok = ok && n[r] >= 0 && (r == 0 || n[r] <= n[r - 1]); sum += n[r]; }
  if (!ok || sum > ntpc) { for (int r = 0; r < 9; ++r) n[r] = r < 8 ? 8 : 0; sum = 64; }
  int tp[8][9], cnt[8] = {0}, pool[72], np = 0, id = 0;
  for (int r = 0; r < 9; ++r)
    for (int g = n[0] - n[r]; g < n[0]; ++g) tp[g][cnt[g]++] = id++;
  for (; id < ntpc; ++id) pool[np++] = id;
  int order[72], no = 0;
  for (int g = 0; g < n[0]; ++g) {
    const int full = cnt[g] / 4 * 4;
    for (int k = 0; k < cnt[g]; ++k) { if (k < full) order[no++] = tp[g][k]; else pool[np++] = tp[g][k]; }
  }
  for (int k = 0; k < np; ++k) order[no++] = pool[k];
  for (int k = 0; k < ntpc; ++k) role[order[k]] = 2 * k;
  return nsm;
}

extern "C" void kernel_launch(void* const* d_in, const int* in_sizes, int n_in, void* d_out, int out_size) {
  (void)in_sizes; (void)n_in; (void)out_size;
  static EncodeFn enc = nullptr;
  static uint8_t role[72];
  static int nsm = 0;
  static Scratch* scratch = nullptr;
  if (!enc) {
    void* fn = nullptr;
    cudaDriverEntryPointQueryResult qr;
    cudaGetDriverEntryPoint("cuTensorMapEncodeTiled", &fn, cudaEnableDefault, &qr);
    enc = (EncodeFn)fn;
    cudaFuncSetAttribute(fused_kernel, cudaFuncAttributeMaxDynamicSharedMemorySize, SM_TOTAL);
    nsm = place_roles(role);
    cudaGetSymbolAddress((void**)&scratch, g_S);
  }
  CUtensorMap mW, mWo, mX;
  {
    cuuint64_t dim[3] = {512, 512, 3}, str[2] = {3072, 1024};
    cuuint32_t box[3] = {64, 64, 3}, es[3] = {1, 1, 1};
    enc(&mW, CU_TENSOR_MAP_DATA_TYPE_BFLOAT16, 3, d_in[10], dim, str, box, es, CU_TENSOR_MAP_INTERLEAVE_NONE,
        CU_TENSOR_MAP_SWIZZLE_128B, CU_TENSOR_MAP_L2_PROMOTION_NONE, CU_TENSOR_MAP_FLOAT_OOB_FILL_NONE);
  }
  {
    cuuint64_t dim[4] = {512, 2, 4, 64}, str[3] = {1024, 2048, 8192};
    cuuint32_t box[4] = {64, 2, 1, 32}, es[4] = {1, 1, 1, 1};
    enc(&mWo, CU_TENSOR_MAP_DATA_TYPE_BFLOAT16, 4, d_in[11], dim, str, box, es, CU_TENSOR_MAP_INTERLEAVE_NONE,
        CU_TENSOR_MAP_SWIZZLE_128B, CU_TENSOR_MAP_L2_PROMOTION_NONE, CU_TENSOR_MAP_FLOAT_OOB_FILL_NONE);
  }
  {
    cuuint64_t dim[2] = {16384, 64}, str[1] = {32768};
    cuuint32_t box[2] = {128, 8}, es[2] = {1, 1};
    enc(&mX, CU_TENSOR_MAP_DATA_TYPE_BFLOAT16, 2, scratch->XF[0], dim, str, box, es, CU_TENSOR_MAP_INTERLEAVE_NONE,
        CU_TENSOR_MAP_SWIZZLE_NONE, CU_TENSOR_MAP_L2_PROMOTION_NONE, CU_TENSOR_MAP_FLOAT_OOB_FILL_NONE);
  }
  Params P;
  P.x0 = (const uint16_t*)d_in[0]; P.Are = (const uint16_t*)d_in[1]; P.Aim = (const uint16_t*)d_in[2];
  P.Bre = (const uint16_t*)d_in[3]; P.Bim = (const uint16_t*)d_in[4]; P.Cre = (const uint16_t*)d_in[5];
  P.Cim = (const uint16_t*)d_in[6]; P.logdt = (const uint16_t*)d_in[7]; P.dskip = (const uint16_t*)d_in[8];
  P.wqkv = (const uint16_t*)d_in[10]; P.wo = (const uint16_t*)d_in[11]; P.out = (uint16_t*)d_out;
  for (int k = 0; k < 72; ++k) P.role[k] = role[k];
  P.zero = 0;
  P.mid = (char*)scratch->C;
  P.spare = nsm > 0 ? nsm - 128 : 0;
  fused_kernel<<<nsm > 0 ? nsm : 128, NTHR, SM_TOTAL, cudaStreamPerThread>>>(P, mW, mWo, mX);
}
```

```cpp
#include <cuda_runtime.h>
#include <cuda_bf16.h>
#include <cuda.h>
#include <stdint.h>
#include <stddef.h>

#define DEV __device__ __forceinline__
#define RARE(x) __builtin_expect(!!(x), 0)

constexpr int NTHR = 512;
constexpr int REG_MAIN = 192, REG_AUX = 96, REG_PROD = 32;
constexpr int NBARU = 384;
constexpr int SPIN_LIMIT = 1 << 22;

constexpr uint32_t SB = 1024;
__host__ __device__ constexpr uint32_t slot(int n) { return SB + n * 8192; }
__host__ __device__ constexpr int wslot(int k) { return k < 2 ? 3 * k : k < 4 ? 3 * k + 6 : k < 6 ? 21 - 3 * k : 3 * k - 18; }
constexpr uint32_t SM_A = slot(22), A_E = 0u - 32768;
constexpr uint32_t SM_O = slot(18), O_E = 0u - 147456;
constexpr uint32_t SM_WO = slot(10), SM_X = slot(8), SM_KV = slot(9) - 4096;
constexpr uint32_t SM_TAP  = slot(26);
constexpr int TAP_SZ = 3440;
constexpr uint32_t SM_STAT = SM_TAP + 4 * TAP_SZ;
constexpr uint32_t SM_CS   = SM_STAT + 1024;
constexpr uint32_t SM_MISC = SM_CS + 768;
constexpr uint32_t SM_BAR  = SM_MISC + 528;
constexpr int SM_TOTAL = SM_BAR + 304 - SB;
static_assert(SM_TOTAL <= 232448, "");
constexpr int R_SZ = 16384, R_U = 512, R_X5 = 5120, R_X3 = 8704, R_BO = 11776, R_BE = 13824;
constexpr int X_5 = 576, X_3 = 648, T_E = 2 * 720, T_O = 1600 + 2 * 721, T_C = 3390, T_K = 3424;
constexpr uint32_t B_RD = SM_BAR, B_ED = SM_BAR + 16, B_F = SM_BAR + 32, B_AT = SM_BAR + 56;
constexpr uint32_t B_AE = SM_BAR + 72, B_QE = SM_BAR + 88, B_ST = SM_BAR + 96, B_CS = SM_BAR + 112;
constexpr uint32_t B_WO = SM_BAR + 120, B_W6 = SM_BAR + 128, B_U = SM_BAR + 144, B_E = SM_BAR + 152, B_A = SM_BAR + 160, B_O = SM_BAR + 192,
                   B_Z = SM_BAR + 256, B_WF = SM_BAR + 272, B_W4 = SM_BAR + 280, B_N = SM_BAR + 288, B_V = SM_BAR + 296;
constexpr int NB_U = 1, NB_B = 2, NB_K = 8, NB_Y = 6, NB_WG = 8, NB_T = 10, NB_AUX = 12, NB_P0 = 13, NB_H = 15;

struct Scratch {
  uint4    XG[2][128 * 1024];
  uint4    O[32 * 8 * 512];
  uint32_t C[8 * 32];
  uint32_t OF[2][32 * 32];
  uint4    CS[16 * 1536 / 4];
  uint4    PS[128 * 64];
  uint4    ST[2][32 * 128];
  uint4    SR[2][8][512];
  uint4    XF[2][32 * 512 * 8];
  uint4    H[2][17 * 8 * 256];
};
__device__ __align__(1024) Scratch g_S;
#define SCR ((Scratch*)(P.mid - offsetof(Scratch, C)))
#define PROFD(slot, v) do {} while (0)
#define PROF(slot) do {} while (0)
#define PROFK(slot) do {} while (0)

DEV uint32_t s2u(const void* p) { return (uint32_t)__cvta_generic_to_shared(p); }
template <class T> DEV T* opqp(T* x) { asm volatile("" : "+l"(x)); return x; }
template <class T> DEV T opq(T x) { asm volatile("" : "+r"(x)); return x; }
DEV int lane_id() { int l; asm volatile("mov.u32 %0,%%laneid;" : "=r"(l)); return l; }
DEV uint32_t pack2(float lo, float hi) { uint32_t d; asm("cvt.rn.bf16x2.f32 %0,%1,%2;" : "=r"(d) : "f"(hi), "f"(lo)); return d; }
DEV float bflo(uint32_t v) { return __uint_as_float(v << 16); }
DEV float bfhi(uint32_t v) { return __uint_as_float(v & 0xFFFF0000u); }
DEV float bfr(float x) { return bflo(pack2(x, 0.f)); }
DEV uint32_t hadd2(uint32_t a, uint32_t b) { uint32_t d; asm("add.rn.bf16x2 %0,%1,%2;" : "=r"(d) : "r"(a), "r"(b)); return d; }
DEV uint32_t hsub2(uint32_t a, uint32_t b) { uint32_t d; asm("sub.rn.bf16x2 %0,%1,%2;" : "=r"(d) : "r"(a), "r"(b)); return d; }
DEV uint32_t hmul2(uint32_t a, uint32_t b) { uint32_t d; asm("mul.rn.bf16x2 %0,%1,%2;" : "=r"(d) : "r"(a), "r"(b)); return d; }
DEV uint32_t hfma2(uint32_t a, uint32_t b, uint32_t c) { uint32_t d; asm("fma.rn.bf16x2 %0,%1,%2,%3;" : "=r"(d) : "r"(a), "r"(b), "r"(c)); return d; }
DEV uint32_t hmax2(uint32_t a, uint32_t b) { uint32_t d; asm("max.bf16x2 %0,%1,%2;" : "=r"(d) : "r"(a), "r"(b)); return d; }
DEV uint32_t prmt(uint32_t a, uint32_t b, uint32_t s) { uint32_t d; asm("prmt.b32 %0,%1,%2,%3;" : "=r"(d) : "r"(a), "r"(b), "r"(s)); return d; }
DEV uint32_t nzmap(uint32_t v) { uint32_t d; asm("max.u32 %0,%1,1;" : "=r"(d) : "r"(v)); return d; }
DEV float rcp(float x) { float y; asm("rcp.approx.ftz.f32 %0,%1;" : "=f"(y) : "f"(x)); return y; }
DEV float sqrt_(float x) { float y; asm("sqrt.approx.ftz.f32 %0,%1;" : "=f"(y) : "f"(x)); return y; }
DEV float ex2(float x) { float y; asm("ex2.approx.ftz.f32 %0,%1;" : "=f"(y) : "f"(x)); return y; }

DEV uint4 ldr4(const void* p) { uint4 v; asm volatile("ld.relaxed.gpu.global.v4.u32 {%0,%1,%2,%3},[%4];" : "=r"(v.x), "=r"(v.y), "=r"(v.z), "=r"(v.w) : "l"(p) : "memory"); return v; }
DEV void ldr4_if(uint4& v, const void* p, bool c) {
  asm volatile("{.reg .pred q; setp.ne.u32 q,%5,0; @q ld.relaxed.gpu.global.v4.u32 {%0,%1,%2,%3},[%4];}"
    : "+r"(v.x), "+r"(v.y), "+r"(v.z), "+r"(v.w) : "l"(p), "r"((uint32_t)c) : "memory");
}
DEV uint2 ldr2(const void* p) { uint2 v; asm volatile("ld.relaxed.gpu.global.v2.u32 {%0,%1},[%2];" : "=r"(v.x), "=r"(v.y) : "l"(p) : "memory"); return v; }
DEV void ldr2_if(uint2& v, const void* p, bool c) {
  asm volatile("{.reg .pred q; setp.ne.u32 q,%3,0; @q ld.relaxed.gpu.global.v2.u32 {%0,%1},[%2];}" : "+r"(v.x), "+r"(v.y) : "l"(p), "r"((uint32_t)c) : "memory");
}
DEV uint32_t ldr1(const void* p) { uint32_t v; asm volatile("ld.relaxed.gpu.global.u32 %0,[%1];" : "=r"(v) : "l"(p) : "memory"); return v; }
DEV float ldnan(const uint16_t* p) {
  uint32_t v = 0xFFFFu;
#pragma unroll 1
  for (int it = 0; it < SPIN_LIMIT && __any_sync(0xffffffffu, v == 0xFFFFu); ++it) asm volatile("ld.relaxed.gpu.global.u16 %0,[%1];" : "=r"(v) : "l"(p) : "memory");
  return __uint_as_float(v << 16);
}
DEV uint4 ldw4(const void* p) { uint4 v; asm volatile("ld.global.v4.u32 {%0,%1,%2,%3},[%4];" : "=r"(v.x), "=r"(v.y), "=r"(v.z), "=r"(v.w) : "l"(p) : "memory"); return v; }
DEV uint2 ldw2(const void* p) { uint2 v; asm volatile("ld.global.v2.u32 {%0,%1},[%2];" : "=r"(v.x), "=r"(v.y) : "l"(p) : "memory"); return v; }
DEV uint32_t ldw1(const void* p) { uint32_t v; asm volatile("ld.global.u32 %0,[%1];" : "=r"(v) : "l"(p) : "memory"); return v; }
DEV void str4(void* p, uint32_t a, uint32_t b, uint32_t c, uint32_t d) { asm volatile("st.relaxed.gpu.global.v4.u32 [%0],{%1,%2,%3,%4};" :: "l"(p), "r"(a), "r"(b), "r"(c), "r"(d) : "memory"); }
DEV void str2(void* p, uint32_t a, uint32_t b) { asm volatile("st.relaxed.gpu.global.v2.u32 [%0],{%1,%2};" :: "l"(p), "r"(a), "r"(b) : "memory"); }
DEV void str1(void* p, uint32_t a) { asm volatile("st.relaxed.gpu.global.u32 [%0],%1;" :: "l"(p), "r"(a) : "memory"); }
DEV void str4_if(void* p, uint32_t a, uint32_t b, uint32_t c, uint32_t d, bool q) {
  asm volatile("{.reg .pred q; setp.ne.u32 q,%5,0; @q st.relaxed.gpu.global.v4.u32 [%0],{%1,%2,%3,%4};}" :: "l"(p), "r"(a), "r"(b), "r"(c), "r"(d), "r"((uint32_t)q) : "memory");
}
DEV void stw4(void* p, uint32_t a, uint32_t b, uint32_t c, uint32_t d) { asm volatile("st.global.v4.u32 [%0],{%1,%2,%3,%4};" :: "l"(p), "r"(a), "r"(b), "r"(c), "r"(d) : "memory"); }
DEV uint4 ldnc4(const void* p) { uint4 v; asm volatile("ld.global.nc.v4.u32 {%0,%1,%2,%3},[%4];" : "=r"(v.x), "=r"(v.y), "=r"(v.z), "=r"(v.w) : "l"(p)); return v; }
DEV uint32_t ldnc1(const void* p) { uint32_t v; asm volatile("ld.global.nc.u32 %0,[%1];" : "=r"(v) : "l"(p)); return v; }
DEV uint2 ldnc2(const void* p) { uint2 v; asm volatile("ld.global.nc.v2.u32 {%0,%1},[%2];" : "=r"(v.x), "=r"(v.y) : "l"(p)); return v; }

DEV uint2 lds2(uint32_t a) { uint2 v; asm volatile("ld.volatile.shared.v2.u32 {%0,%1},[%2];" : "=r"(v.x), "=r"(v.y) : "r"(a)); return v; }
DEV float lds16f(uint32_t a) { uint32_t v; asm volatile("ld.shared.u16 %0,[%1];" : "=r"(v) : "r"(a)); return __uint_as_float(v << 16); }
DEV void sts2(uint32_t a, uint32_t x, uint32_t y) { asm volatile("st.shared.v2.u32 [%0],{%1,%2};" :: "r"(a), "r"(x), "r"(y) : "memory"); }
DEV uint32_t lds1(uint32_t a) { uint32_t v; asm volatile("ld.volatile.shared.u32 %0,[%1];" : "=r"(v) : "r"(a)); return v; }
DEV uint32_t lds1z(uint32_t a, bool c) {
  uint32_t v; asm volatile("{.reg .pred q; setp.ne.u32 q,%2,0; mov.u32 %0,0; @q ld.volatile.shared.u32 %0,[%1];}" : "=r"(v) : "r"(a), "r"((uint32_t)c)); return v;
}
DEV uint4 lds4z(uint32_t a, bool c) {
  uint4 v = make_uint4(0, 0, 0, 0);
  asm volatile("{.reg .pred q; setp.ne.u32 q,%5,0; @q ld.volatile.shared.v4.u32 {%0,%1,%2,%3},[%4];}" : "+r"(v.x), "+r"(v.y), "+r"(v.z), "+r"(v.w) : "r"(a), "r"((uint32_t)c));
  return v;
}
DEV float lds1f(uint32_t a) { float v; asm volatile("ld.shared.f32 %0,[%1];" : "=f"(v) : "r"(a)); return v; }
DEV float2 lds2f(uint32_t a) { float2 v; asm volatile("ld.shared.v2.f32 {%0,%1},[%2];" : "=f"(v.x), "=f"(v.y) : "r"(a)); return v; }
DEV float4 lds4f(uint32_t a) { float4 v; asm volatile("ld.shared.v4.f32 {%0,%1,%2,%3},[%4];" : "=f"(v.x), "=f"(v.y), "=f"(v.z), "=f"(v.w) : "r"(a)); return v; }
DEV uint4 lds4(uint32_t a) { uint4 v; asm volatile("ld.volatile.shared.v4.u32 {%0,%1,%2,%3},[%4];" : "=r"(v.x), "=r"(v.y), "=r"(v.z), "=r"(v.w) : "r"(a)); return v; }
DEV void sts1(uint32_t a, uint32_t v) { asm volatile("st.shared.u32 [%0],%1;" :: "r"(a), "r"(v) : "memory"); }
DEV void sts16(uint32_t a, uint32_t v) { asm volatile("{.reg .b16 h; cvt.u16.u32 h,%1; st.shared.u16 [%0],h;}" :: "r"(a), "r"(v) : "memory"); }
DEV void sts2f(uint32_t a, float x, float y) { asm volatile("st.shared.v2.f32 [%0],{%1,%2};" :: "r"(a), "f"(x), "f"(y) : "memory"); }
DEV void sts4f(uint32_t a, float x, float y, float z, float w) { asm volatile("st.shared.v4.f32 [%0],{%1,%2,%3,%4};" :: "r"(a), "f"(x), "f"(y), "f"(z), "f"(w) : "memory"); }
DEV void sts4(uint32_t a, uint32_t x, uint32_t y, uint32_t z, uint32_t w) { asm volatile("st.shared.v4.u32 [%0],{%1,%2,%3,%4};" :: "r"(a), "r"(x), "r"(y), "r"(z), "r"(w) : "memory"); }

DEV void ldsm4(uint32_t (&r)[4], uint32_t a) { asm volatile("ldmatrix.sync.aligned.m8n8.x4.shared.b16 {%0,%1,%2,%3},[%4];" : "=r"(r[0]), "=r"(r[1]), "=r"(r[2]), "=r"(r[3]) : "r"(a) : "memory"); }
DEV void ldsm4t(uint32_t (&r)[4], uint32_t a) { asm volatile("ldmatrix.sync.aligned.m8n8.x4.trans.shared.b16 {%0,%1,%2,%3},[%4];" : "=r"(r[0]), "=r"(r[1]), "=r"(r[2]), "=r"(r[3]) : "r"(a) : "memory"); }
DEV void ldsm2(uint32_t (&r)[2], uint32_t a) { asm volatile("ldmatrix.sync.aligned.m8n8.x2.shared.b16 {%0,%1},[%2];" : "=r"(r[0]), "=r"(r[1]) : "r"(a) : "memory"); }
DEV void stsm4(uint32_t a, uint32_t r0, uint32_t r1, uint32_t r2, uint32_t r3) { asm volatile("stmatrix.sync.aligned.m8n8.x4.shared.b16 [%0],{%1,%2,%3,%4};" :: "r"(a), "r"(r0), "r"(r1), "r"(r2), "r"(r3) : "memory"); }
DEV void stsm2(uint32_t a, uint32_t r0, uint32_t r1) { asm volatile("stmatrix.sync.aligned.m8n8.x2.shared.b16 [%0],{%1,%2};" :: "r"(a), "r"(r0), "r"(r1) : "memory"); }
DEV void stsm4t(uint32_t a, uint32_t r0, uint32_t r1, uint32_t r2, uint32_t r3) { asm volatile("stmatrix.sync.aligned.m8n8.x4.trans.shared.b16 [%0],{%1,%2,%3,%4};" :: "r"(a), "r"(r0), "r"(r1), "r"(r2), "r"(r3) : "memory"); }
DEV uint32_t movm(uint32_t a) { uint32_t d; asm volatile("movmatrix.sync.aligned.m8n8.trans.b16 %0,%1;" : "=r"(d) : "r"(a)); return d; }
DEV void mma16(float (&d)[4], uint32_t a0, uint32_t a1, uint32_t a2, uint32_t a3, uint32_t b0, uint32_t b1) {
  asm volatile("mma.sync.aligned.m16n8k16.row.col.f32.bf16.bf16.f32 {%0,%1,%2,%3},{%4,%5,%6,%7},{%8,%9},{%0,%1,%2,%3};"
    : "+f"(d[0]), "+f"(d[1]), "+f"(d[2]), "+f"(d[3]) : "r"(a0), "r"(a1), "r"(a2), "r"(a3), "r"(b0), "r"(b1));
}
DEV void mma16z(float (&d)[4], uint32_t a0, uint32_t a1, uint32_t a2, uint32_t a3, uint32_t b0, uint32_t b1) {
  asm volatile("mma.sync.aligned.m16n8k16.row.col.f32.bf16.bf16.f32 {%0,%1,%2,%3},{%4,%5,%6,%7},{%8,%9},{%10,%10,%10,%10};"
    : "=f"(d[0]), "=f"(d[1]), "=f"(d[2]), "=f"(d[3]) : "r"(a0), "r"(a1), "r"(a2), "r"(a3), "r"(b0), "r"(b1), "f"(0.f));
}
DEV void mma8(float (&d)[4], uint32_t a0, uint32_t a1, uint32_t b0) {
  asm volatile("mma.sync.aligned.m16n8k8.row.col.f32.bf16.bf16.f32 {%0,%1,%2,%3},{%4,%5},{%6},{%0,%1,%2,%3};"
    : "+f"(d[0]), "+f"(d[1]), "+f"(d[2]), "+f"(d[3]) : "r"(a0), "r"(a1), "r"(b0));
}

DEV void mma8z(float (&d)[4], uint32_t a0, uint32_t a1, uint32_t b0) {
  asm volatile("mma.sync.aligned.m16n8k8.row.col.f32.bf16.bf16.f32 {%0,%1,%2,%3},{%4,%5},{%6},{%7,%7,%7,%7};"
    : "=f"(d[0]), "=f"(d[1]), "=f"(d[2]), "=f"(d[3]) : "r"(a0), "r"(a1), "r"(b0), "f"(0.f));
}
DEV void bar_sync(int id, int n) { asm volatile("bar.sync %0,%1;" :: "r"(id), "r"(n) : "memory"); }
DEV void bar_sync_if(int id, int n, int c) { asm volatile("{.reg .pred q; setp.ne.s32 q,%2,0; @q bar.sync %0,%1;}" :: "r"(id), "r"(n), "r"(c) : "memory"); }
DEV void bar_arrive_if(int id, int n, int c) { asm volatile("{.reg .pred q; setp.ne.s32 q,%2,0; @q bar.arrive %0,%1;}" :: "r"(id), "r"(n), "r"(c) : "memory"); }
DEV bool bar_any(int id, int n, bool c) {
  uint32_t r; asm volatile("{.reg .pred p,q; setp.ne.u32 q,%3,0; bar.red.or.pred p,%1,%2,q; selp.u32 %0,1,0,p;}" : "=r"(r) : "r"(id), "r"(n), "r"((uint32_t)c) : "memory");
  return __any_sync(0xffffffffu, r);
}
DEV void bar_arrive(int id, int n) { asm volatile("bar.arrive %0,%1;" :: "r"(id), "r"(n) : "memory"); }
DEV void fence_async_glob() { asm volatile("fence.proxy.async.global;" ::: "memory"); }
DEV void fence_async_smem() { asm volatile("fence.proxy.async.shared::cta;" ::: "memory"); }
DEV void mbar_init(uint32_t b, int n) { asm volatile("mbarrier.init.shared::cta.b64 [%0],%1;" :: "r"(b), "r"(n) : "memory"); }
DEV void mbar_arrive(uint32_t b) { asm volatile("mbarrier.arrive.shared::cta.b64 _,[%0];" :: "r"(b) : "memory"); }
DEV void mbar_expect(uint32_t b, int bytes) { asm volatile("mbarrier.arrive.expect_tx.shared::cta.b64 _,[%0],%1;" :: "r"(b), "r"(bytes) : "memory"); }
DEV void mbar_wait(uint32_t b, uint32_t ph) {
  asm volatile("{\n.reg .pred p;\nW: mbarrier.try_wait.parity.shared::cta.b64 p,[%0],%1;\n@!p bra W;\n}" :: "r"(b), "r"(ph) : "memory");
}
DEV void mbar_watch(uint32_t b, uint32_t ph) {
  asm volatile("{\n.reg .pred p,q;\n.reg .u32 n;\nmov.u32 n,0;\n"
               "W: mbarrier.try_wait.parity.shared::cta.b64 p,[%0],%1;\n@p bra D;\n"
               "add.u32 n,n,1;\nsetp.lt.u32 q,n,%2;\n@q bra W;\ntrap;\nD:\n}"
               :: "r"(b), "r"(ph), "n"(SPIN_LIMIT) : "memory");
}
DEV void spin_guard(int it) { asm volatile("{.reg .pred p; setp.gt.s32 p,%0,%1; @p trap;}" :: "r"(it), "n"(SPIN_LIMIT)); }
DEV void split(uint32_t zero) {
  asm volatile("{.reg .pred p; setp.ne.u32 p,%0,0; @p trap;}" :: "r"(zero) : "memory");
}
DEV void pause(int n) {
  uint32_t t0, t; asm volatile("mov.u32 %0,%%clock;" : "=r"(t0));
  do asm volatile("mov.u32 %0,%%clock;" : "=r"(t)); while (t - t0 < n);
}
DEV void poll(const uint32_t* k, uint32_t n) {
#pragma unroll 1
  for (int it = 0;; ++it) {
    spin_guard(it);
    if (__all_sync(0xffffffffu, ldr1(k) >= n)) break;
  }
}
DEV void mbar_arrive1(uint32_t b) { asm volatile("{.reg .pred p; elect.sync _|p,0xffffffff; @p mbarrier.arrive.shared::cta.b64 _,[%0];}" :: "r"(b) : "memory"); }
DEV void mbar_arrive1_if(uint32_t b, int c) {
  asm volatile("{.reg .pred p,q; setp.ne.s32 q,%1,0; elect.sync _|p,0xffffffff; and.pred p,p,q; @p mbarrier.arrive.shared::cta.b64 _,[%0];}" :: "r"(b), "r"(c) : "memory");
}
DEV void mbar_expect1(uint32_t b, int bytes) { asm volatile("{.reg .pred p; elect.sync _|p,0xffffffff; @p mbarrier.arrive.expect_tx.shared::cta.b64 _,[%0],%1;}" :: "r"(b), "r"(bytes) : "memory"); }
DEV void cnt_add1(uint32_t* q) { asm volatile("{.reg .pred p; elect.sync _|p,0xffffffff; @p red.relaxed.gpu.global.add.u32 [%0],1;}" :: "l"(q) : "memory"); }
DEV void tma4(uint32_t dst, const CUtensorMap* m, int c0, int c1, int c2, int c3, uint32_t bar) {
  asm volatile("{.reg .pred p; elect.sync _|p,0xffffffff;\n"
    "@p cp.async.bulk.tensor.4d.shared::cluster.global.mbarrier::complete_tx::bytes [%0],[%1,{%2,%3,%4,%5}],[%6];}"
    :: "r"(dst), "l"(m), "r"(c0), "r"(c1), "r"(c2), "r"(c3), "r"(bar) : "memory");
}
DEV void tma3(uint32_t dst, const CUtensorMap* m, int c0, int c1, int c2, uint32_t bar) {
  asm volatile("{.reg .pred p; elect.sync _|p,0xffffffff;\n"
    "@p cp.async.bulk.tensor.3d.shared::cluster.global.mbarrier::complete_tx::bytes [%0],[%1,{%2,%3,%4}],[%5];}"
    :: "r"(dst), "l"(m), "r"(c0), "r"(c1), "r"(c2), "r"(bar) : "memory");
}
DEV void bulk(uint32_t dst, const void* src, int bytes, uint32_t bar) {
  asm volatile("{.reg .pred p; elect.sync _|p,0xffffffff;\n@p cp.async.bulk.shared::cluster.global.mbarrier::complete_tx::bytes [%0],[%1],%2,[%3];}" :: "r"(dst), "l"(src), "r"(bytes), "r"(bar) : "memory");
}

DEV void bulk_store(void* dst, uint32_t src, int bytes) {
  asm volatile("{.reg .pred p; elect.sync _|p,0xffffffff;\n@p cp.async.bulk.global.shared::cta.bulk_group [%0],[%1],%2;}" :: "l"(dst), "r"(src), "r"(bytes) : "memory");
}
DEV void tma2_store(const CUtensorMap* m, uint32_t src, int c0, int c1) {
  asm volatile("{.reg .pred p; elect.sync _|p,0xffffffff;\n@p cp.async.bulk.tensor.2d.global.shared::cta.bulk_group [%0,{%2,%3}],[%1];}" :: "l"(m), "r"(src), "r"(c0), "r"(c1) : "memory");
}
DEV void bulk_wait() { asm volatile("cp.async.bulk.commit_group;\ncp.async.bulk.wait_group 0;\nfence.proxy.async.global;" ::: "memory"); }

DEV uint32_t dlo(uint32_t addr, uint32_t lbo) { return __shfl_sync(0xffffffffu, (addr >> 4) | ((lbo >> 4) << 16), 0); }
__host__ __device__ constexpr uint32_t dhi(uint32_t sbo, uint32_t swz) { return (sbo >> 4) | (swz << 30); }
DEV void wg_fence() { asm volatile("wgmma.fence.sync.aligned;" ::: "memory"); }
DEV void wg_commit() { asm volatile("wgmma.commit_group.sync.aligned;" ::: "memory"); }
template <int N> DEV void wg_wait() { asm volatile("wgmma.wait_group.sync.aligned %0;" :: "n"(N) : "memory"); }
template <int N> DEV void zero(float (&d)[N]) {
#pragma unroll
  for (int i = 0; i < N; ++i) d[i] = 0.f;
}
template <int N> DEV void zerov(float (&d)[N]) {
#pragma unroll
  for (int i = 0; i < N; ++i) asm volatile("mov.b32 %0,0;" : "=f"(d[i]));
}
template <int N> DEV void undef(float (&d)[N]) {
#pragma unroll
  for (int i = 0; i < N; ++i) asm volatile("" : "=f"(d[i]));
}
#define R4(d, o) "+f"(d[o]), "+f"(d[o + 1]), "+f"(d[o + 2]), "+f"(d[o + 3])
#define R8(d, o) R4(d, o), R4(d, o + 4)
#define R16(d, o) R8(d, o), R8(d, o + 8)
template <int ACC> DEV void wg_rs64k(float (&d)[32], const uint32_t (&a)[4], uint32_t db) {
  asm volatile("{.reg .pred p; .reg .b64 b; setp.ne.s32 p,%38,0; mov.b64 b,{%36,%37};\n"
    "wgmma.mma_async.sync.aligned.m64n64k16.f32.bf16.bf16 {%0,%1,%2,%3,%4,%5,%6,%7,%8,%9,%10,%11,%12,%13,%14,%15,%16,%17,%18,%19,%20,%21,%22,%23,%24,%25,%26,%27,%28,%29,%30,%31},{%32,%33,%34,%35},b,p,1,1,0;}"
    : R16(d, 0), R16(d, 16) : "r"(a[0]), "r"(a[1]), "r"(a[2]), "r"(a[3]), "r"(db), "n"(dhi(512, 2)), "n"(ACC));
}
template <int ACC> DEV void wg_rs48t(float (&d)[24], const uint32_t (&a)[4], uint32_t db) {
  asm volatile("{.reg .pred p; .reg .b64 b; setp.ne.s32 p,%30,0; mov.b64 b,{%28,%29};\n"
    "wgmma.mma_async.sync.aligned.m64n48k16.f32.bf16.bf16 {%0,%1,%2,%3,%4,%5,%6,%7,%8,%9,%10,%11,%12,%13,%14,%15,%16,%17,%18,%19,%20,%21,%22,%23},{%24,%25,%26,%27},b,p,1,1,1;}"
    : R16(d, 0), R8(d, 16) : "r"(a[0]), "r"(a[1]), "r"(a[2]), "r"(a[3]), "r"(db), "n"(dhi(512, 0)), "n"(ACC));
}
template <int ACC> DEV void wg_rs32t(float (&d)[16], const uint32_t (&a)[4], uint32_t db) {
  asm volatile("{.reg .pred p; .reg .b64 b; setp.ne.s32 p,%22,0; mov.b64 b,{%20,%21};\n"
    "wgmma.mma_async.sync.aligned.m64n32k16.f32.bf16.bf16 {%0,%1,%2,%3,%4,%5,%6,%7,%8,%9,%10,%11,%12,%13,%14,%15},{%16,%17,%18,%19},b,p,1,1,1;}"
    : R16(d, 0) : "r"(a[0]), "r"(a[1]), "r"(a[2]), "r"(a[3]), "r"(db), "n"(dhi(1024, 0)), "n"(ACC));
}
template <int ACC> DEV void wg_ss192(float (&d)[96], uint32_t da, uint32_t db) {
  asm volatile("{.reg .pred p; .reg .b64 a,b; setp.ne.s32 p,%100,0; mov.b64 a,{%96,%98}; mov.b64 b,{%97,%99};\n"
    "wgmma.mma_async.sync.aligned.m64n192k16.f32.bf16.bf16 {"
    "%0,%1,%2,%3,%4,%5,%6,%7,%8,%9,%10,%11,%12,%13,%14,%15,%16,%17,%18,%19,%20,%21,%22,%23,%24,%25,%26,%27,%28,%29,%30,%31,"
    "%32,%33,%34,%35,%36,%37,%38,%39,%40,%41,%42,%43,%44,%45,%46,%47,%48,%49,%50,%51,%52,%53,%54,%55,%56,%57,%58,%59,%60,%61,%62,%63,"
    "%64,%65,%66,%67,%68,%69,%70,%71,%72,%73,%74,%75,%76,%77,%78,%79,%80,%81,%82,%83,%84,%85,%86,%87,%88,%89,%90,%91,%92,%93,%94,%95},a,b,p,1,1,1,1;}"
    : R16(d, 0), R16(d, 16), R16(d, 32), R16(d, 48), R16(d, 64), R16(d, 80) : "r"(da), "r"(db), "n"(dhi(1024, 1)), "n"(dhi(1024, 1)), "n"(ACC));
}
template <int ACC> DEV void wg_ss64(float (&d)[32], uint32_t da, uint32_t db) {
  asm volatile("{.reg .pred p; .reg .b64 a,b; setp.ne.s32 p,%36,0; mov.b64 a,{%32,%34}; mov.b64 b,{%33,%35};\n"
    "wgmma.mma_async.sync.aligned.m64n64k16.f32.bf16.bf16 {"
    "%0,%1,%2,%3,%4,%5,%6,%7,%8,%9,%10,%11,%12,%13,%14,%15,%16,%17,%18,%19,%20,%21,%22,%23,%24,%25,%26,%27,%28,%29,%30,%31},a,b,p,1,1,0,1;}"
    : R16(d, 0), R16(d, 16) : "r"(da), "r"(db), "n"(dhi(1024, 0)), "n"(dhi(1024, 1)), "n"(ACC));
}

DEV uint32_t cpy(uint32_t v, uint32_t id) {
  uint32_t d; asm volatile("prmt.b32 %0,%1,%1,%2;" : "=r"(d) : "r"(v), "r"(id)); return d;
}
struct Params {
  uint32_t zero, spare;
  char* mid;
  const uint16_t *x0, *Are, *Aim, *Bre, *Bim, *Cre, *Cim, *logdt, *dskip, *wqkv, *wo;
  uint16_t* out;
  uint8_t role[72];
};

DEV uint32_t ln_word(float mean, float var) {
  float v = bfr(var);
  float s = sqrt_(bfr(v + 1e-5f));
  return pack2(mean, s);
}

DEV int stat_group(int c) { return c ^ 4; }
DEV int xg_off(int G, int g) { return (G >> 6) * 1024 + (G & 63) * 8 + (g ^ (G & 2)); }
DEV int sr_off(int G, int g) { return (G >> 6) * 256 + (g & 2) * 64 + 2 * (G & 63) + ((g >> 2) & 1); }
DEV uint32_t region(int chl) { return SM_A + (chl >> 1) * A_E + (chl & 1) * R_SZ; }
template <bool FIRST> DEV void gram(float (&s)[4], float (&q0)[4], float (&q1)[4], uint32_t a0, uint32_t a1, uint32_t a2, uint32_t a3) {
  const uint32_t one = 0x3F803F80u;
  if (FIRST) { mma16z(s, a0, a1, a2, a3, one, one); mma8z(q0, a0, a1, a0); mma8z(q1, a0, a1, a1); }
  else { mma16(s, a0, a1, a2, a3, one, one); mma8(q0, a0, a1, a0); mma8(q1, a0, a1, a1); }
  mma8(q0, a2, a3, a2); mma8(q1, a2, a3, a3);
}
DEV uint32_t ln_sums(float s, float q) { const float m = s * (1.f / 512.f); return ln_word(m, fmaxf(q * (1.f / 512.f) - m * m, 0.f)); }
DEV void cmul(float& orr, float& oi, float ar, float ai, float br, float bi) {
  float r = ar * br - ai * bi, i = ar * bi + ai * br; orr = r; oi = i;
}
DEV void cexp_(float al, float bt, float s, float& er, float& ei) {
  float mag = ex2(al * s), ph = bt * s;
  ph -= rintf(ph);
  float ang = ph * 6.283185307179586f;
  er = mag * __cosf(ang); ei = mag * __sinf(ang);
}

DEV void kgen(const Params& P, int c, int wm, int lane) {
  const int chl = wm >> 1, mh = wm & 1, g = lane >> 2, t = lane & 3;
  const int ch = 256 * (chl >> 1) + 2 * c + (chl & 1);
  const int mo = ch * 64 + mh * 32 + lane;
  const uint32_t vAr = ldw1((const uint32_t*)P.Are + mo), vAi = ldw1((const uint32_t*)P.Aim + mo);
  const uint32_t vBr = ldw1((const uint32_t*)P.Bre + mo), vBi = ldw1((const uint32_t*)P.Bim + mo);
  const uint32_t vCr = ldw1((const uint32_t*)P.Cre + mo), vCi = ldw1((const uint32_t*)P.Cim + mo);
  const uint32_t vld = ldw1((const uint32_t*)P.logdt + (ch >> 1)) >> (16 * (ch & 1)), vds = ldw1((const uint32_t*)P.dskip + (ch >> 1)) >> (16 * (ch & 1));
  bar_arrive(NB_Y, 384);
  PROF(45);
  asm volatile("setmaxnreg.inc.sync.aligned.u32 %0;" :: "n"(REG_MAIN));
  PROF(44);
  {
    const uint32_t tz = SM_TAP + chl * TAP_SZ + (mh * 32 + lane) * 16;
#pragma unroll
    for (int k = 0; k < 3; ++k) sts4(tz + k * 1024, 0, 0, 0, 0);
    static_assert(TAP_SZ > 3072 && TAP_SZ <= 4096, "");
    if (mh * 32 + lane < TAP_SZ / 16 - 192) sts4(tz + 3072, 0, 0, 0, 0);
  }
  const float dt = bfr(__expf(bflo(vld)));
  const uint32_t tb = slot(wm);
  float acc[5][4];
#pragma unroll
  for (int i = 0; i < 5; ++i) { acc[i][0] = acc[i][1] = acc[i][2] = acc[i][3] = 0.f; }
  float k2048 = 0.f;
#pragma unroll 1
  for (int r = 0; r < 2; ++r) {
    const float are = r ? bfhi(vAr) : bflo(vAr), aim = r ? bfhi(vAi) : bflo(vAi);
    const float bre = r ? bfhi(vBr) : bflo(vBr), bim = r ? bfhi(vBi) : bflo(vBi);
    const float cre = r ? bfhi(vCr) : bflo(vCr), cim = r ? bfhi(vCi) : bflo(vCi);
    const float al = dt * are * 1.4426950408889634f, bt = dt * aim * 0.15915494309189535f;
    float wr, wi; cmul(wr, wi, cre, cim, dt * bre, dt * bim);
    if (r == 0) PROFD(2, __float_as_uint(wr + al + bt));
    float e1r, e1i, e8r, e8i, eLr, eLi;
    cexp_(al, bt, 1.f, e1r, e1i); cexp_(al, bt, 8.f, e8r, e8i); cexp_(al, bt, 128.f, eLr, eLi);
    const uint32_t tw = tb + lane * 4;
    float pr[8], pi[8];
    pr[1] = e1r; pi[1] = e1i;
#pragma unroll
    for (int k = 2; k < 8; ++k) cmul(pr[k], pi[k], pr[k - 1], pi[k - 1], e1r, e1i);
    float yr = 1.f, yi = 0.f, qr = wr, qi = wi;
#pragma unroll
    for (int a = 0; a < 16; ++a) {
      sts1(tw + a * 144, pack2(yr, -yi));
      if (a == 0) { yr = e8r; yi = e8i; } else if (a < 15) cmul(yr, yi, yr, yi, e8r, e8i);
      const int step = a < 2 ? 1 : a < 4 ? 2 : a < 8 ? 4 : 8;
      const int row0 = 16 + (a < 2 ? 8 * a : a < 4 ? 16 + 4 * (a - 2) : a < 8 ? 24 + 2 * (a - 4) : 32 + (a - 8));
      sts1(tw + row0 * 144, pack2(qr, qi));
#pragma unroll
      for (int k = step; k < 8; k += step) {
        float xr, xi; cmul(xr, xi, qr, qi, pr[k], pi[k]);
        sts1(tw + (row0 + k / step) * 144, pack2(xr, xi));
      }
      cmul(qr, qi, qr, qi, eLr, eLi);
    }
    k2048 += qr;
    __syncwarp();
    if (r == 0) PROF(3);
#pragma unroll
    for (int kp = 0; kp < 2; ++kp) {
      uint32_t a0[4], a1[4];
      const uint32_t aa = tb + ((lane & 7) + 8 * ((lane >> 3) & 1)) * 144 + (lane >> 4) * 16 + kp * 64;
      ldsm4(a0, aa); ldsm4(a1, aa + 32);
#pragma unroll
      for (int tl = 0; tl < 5; ++tl) {
        uint32_t b[4];
        ldsm4(b, tb + (16 + 8 * tl + (lane & 7)) * 144 + (lane >> 3) * 16 + kp * 64);
        mma16(acc[tl], a0[0], a0[1], a0[2], a0[3], b[0], b[1]);
        mma16(acc[tl], a1[0], a1[1], a1[2], a1[3], b[2], b[3]);
      }
    }
    __syncwarp();
    bar_sync_if(NB_P0 + 1, 288, 1 - r);
  }
#pragma unroll
  for (int o = 16; o > 0; o >>= 1) k2048 += __shfl_xor_sync(0xffffffffu, k2048, o);
  if (mh == 0) {
    sts4f(tb + lane * 16, acc[2][0], acc[2][1], acc[2][2], acc[2][3]);
    sts4f(tb + 512 + lane * 16, acc[3][0], acc[3][1], acc[3][2], acc[3][3]);
  } else {
    sts4f(tb + lane * 16, acc[0][0], acc[0][1], acc[0][2], acc[0][3]);
    sts4f(tb + 512 + lane * 16, acc[1][0], acc[1][1], acc[1][2], acc[1][3]);
    sts4f(tb + 1024 + lane * 16, acc[4][0], acc[4][1], acc[4][2], acc[4][3]);
    if (lane == 0) sts1(tb + 1536, __float_as_uint(k2048));
  }
  PROF(4);
  bar_sync(NB_K + chl, 64);
  const uint32_t ob = slot(wm ^ 1), tp = SM_TAP + chl * TAP_SZ;
  if (mh == 0) {
#pragma unroll
    for (int tl = 0; tl < 2; ++tl) {
      float4 o = lds4f(ob + tl * 512 + lane * 16);
      if (tl == 0 && lane == 0) o.x += bflo(vds);
      uint32_t v0 = pack2(acc[tl][0] + o.x, acc[tl][1] + o.y), v1 = pack2(acc[tl][2] + o.z, acc[tl][3] + o.w);
      const int l = 128 * tl + 8 * g + 2 * t;
      sts16(tp + T_E + 2 * (0 - l), v0); sts16(tp + T_E + 2 * (-1 - l), v0 >> 16);
      sts16(tp + T_O + 2 * (0 - l), v0); sts16(tp + T_O + 2 * (-1 - l), v0 >> 16);
      sts16(tp + T_E + 2 * (-64 - l), v1); sts16(tp + T_E + 2 * (-65 - l), v1 >> 16);
      sts16(tp + T_O + 2 * (-64 - l), v1); sts16(tp + T_O + 2 * (-65 - l), v1 >> 16);
    }
    float4 o = lds4f(ob + 1024 + lane * 16);
    uint32_t v0 = pack2(acc[4][0] + o.x, acc[4][1] + o.y), v1 = pack2(acc[4][2] + o.z, acc[4][3] + o.w);
    const int x = 32 * t + g - 1;
    if (lane == 0) { sts16(tp + T_E - 2 * (X_5 + 63), v0); sts16(tp + T_O - 2 * (X_5 + 63), v0); sts1(tp + T_K, prmt(v0, v0, 0x1010)); }
    else sts16(tp + T_C - 2 * x, v0);
    sts16(tp + T_C - 2 * (x + 16), v0 >> 16);
    sts16(tp + T_C - 2 * (x + 8), v1);
    sts16(tp + T_C - 2 * (x + 24), v1 >> 16);
    if (lane == 0) sts16(tp + T_C - 2 * 127, pack2(k2048 + __uint_as_float(lds1(ob + 1536)), 0.f));
  } else {
    float4 o2 = lds4f(ob + lane * 16), o3 = lds4f(ob + 512 + lane * 16);
    uint32_t v0 = pack2(acc[2][0] + o2.x, acc[2][1] + o2.y), v1 = pack2(acc[2][2] + o2.z, acc[2][3] + o2.w);
    const int l0 = 256 + 128 * (t >> 1) + 4 * (t & 1) + 8 * g;
    if (lane != 0) { sts16(tp + T_E + 2 * (1 - l0), v0); sts16(tp + T_O + 2 * (1 - l0), v0); }
    sts16(tp + T_E + 2 * (0 - l0), v0); sts16(tp + T_O + 2 * (0 - l0), v0);
    sts16(tp + T_E + 2 * (-1 - l0), v0); sts16(tp + T_O + 2 * (-1 - l0), v0);
    sts16(tp + T_E + 2 * (-2 - l0), v0 >> 16); sts16(tp + T_O + 2 * (-2 - l0), v0 >> 16);
    sts16(tp + T_E + 2 * (-63 - l0), v1); sts16(tp + T_O + 2 * (-63 - l0), v1);
    sts16(tp + T_E + 2 * (-64 - l0), v1); sts16(tp + T_O + 2 * (-64 - l0), v1);
    sts16(tp + T_E + 2 * (-65 - l0), v1); sts16(tp + T_O + 2 * (-65 - l0), v1);
    sts16(tp + T_E + 2 * (-66 - l0), v1 >> 16); sts16(tp + T_O + 2 * (-66 - l0), v1 >> 16);
    uint32_t w0 = pack2(acc[3][0] + o3.x, acc[3][1] + o3.y), w1 = pack2(acc[3][2] + o3.z, acc[3][3] + o3.w);
    const int x = 16 * t + g;
    if (lane == 0) {
      const uint32_t k = prmt(w0, w0, 0x1010);
      sts1(tp + T_E - 2 * 514, k); sts1(tp + T_E - 2 * 512, k);
      sts16(tp + T_O - 2 * 514, k); sts1(tp + T_O - 2 * 513, k); sts16(tp + T_O - 2 * 511, k);
    } else { sts16(tp + T_E - 2 * (X_5 - 1 + x), w0); sts16(tp + T_O - 2 * (X_5 - 1 + x), w0); }
    sts16(tp + T_E - 2 * (X_3 + x), w0 >> 16); sts16(tp + T_O - 2 * (X_3 + x), w0 >> 16);
    sts16(tp + T_E - 2 * (X_5 + 7 + x), w1); sts16(tp + T_O - 2 * (X_5 + 7 + x), w1);
    sts16(tp + T_E - 2 * (X_3 + 8 + x), w1 >> 16); sts16(tp + T_O - 2 * (X_3 + 8 + x), w1 >> 16);
  }
}

DEV bool bad8(const uint4& v) { return min(v.x, v.z) == 0u; }
DEV uint32_t uchunk(uint32_t reg, int x) { return reg + R_U + (x ^ ((x >> 3) & 3)) * 16; }
DEV uint32_t& xword(uint4 (&x)[2], int e, int tp) { uint4& v = x[tp >> 1]; return tp & 1 ? (e ? v.w : v.z) : (e ? v.y : v.x); }

DEV void uprep(const Params& P, int c, int wa, int lane, int layer, uint4 (&x)[2][2][2], uint32_t (&u)[4][4]) {
  const int j = 32 * wa + lane, o0 = 2 * j + ((j >> 2) & 1);
  {
    const uint32_t za = region(wa) + lane * 16 - 512;
    sts4(za + R_U, 0, 0, 0, 0); sts4(za + R_X5, 0, 0, 0, 0); sts4(za + R_X3, 0, 0, 0, 0);
    sts4(region(wa) + R_BE, 0, 0, 0, 0);
  }
  const uint4* st = opqp(&SCR->SR[layer][c >> 4][j]);
  const uint32_t xa = opq(SM_X + 16 * o0), xb = opq(SM_X + 16 * (o0 ^ 1)), ua = opq(uchunk(0, j));
  uint4 s[2][2];
#pragma unroll
  for (int z = 0; z < 12; ++z) {
    uint4& v = z < 8 ? x[(z >> 2) & 1][(z >> 1) & 1][z & 1] : s[(z >> 1) & 1][z & 1];
    asm volatile("mov.b32 %0,0; mov.b32 %1,0; mov.b32 %2,0; mov.b32 %3,0;" : "=r"(v.x), "=r"(v.y), "=r"(v.z), "=r"(v.w));
  }
#pragma unroll 1
  for (uint32_t it = P.zero;; ++it) {
    if (it) {
      spin_guard(it);
#pragma unroll
      for (int z = 0; z < 4; ++z) { uint4& v = s[z >> 1][z & 1]; ldr4_if(v, st + z * 128, bad8(v)); }
      const uint4* xp = &SCR->XG[layer][c * 1024 + o0];
#pragma unroll
      for (int z = 0; z < 8; ++z) {
        uint4& v = x[z >> 2][(z >> 1) & 1][z & 1];
        ldr4_if(v, (const uint4*)((uintptr_t)xp ^ (16 * (z & 1))) + (z >> 1) * 256, bad8(v));
      }
    } else {
      mbar_wait(B_U, layer);
      PROF(layer ? 25 : 10);
#pragma unroll
      for (int z = 0; z < 4; ++z) s[z >> 1][z & 1] = ldr4(st + z * 128);
#pragma unroll
      for (int z = 0; z < 4; ++z) { uint4& v = s[z >> 1][z & 1]; ldr4_if(v, st + z * 128, bad8(v)); }
      PROF(layer ? 26 : 11);
      mbar_wait(B_E, layer);
#pragma unroll
      for (int z = 7; z >= 0; --z) x[z >> 2][(z >> 1) & 1][z & 1] = lds4((z & 1 ? xb : xa) + (z >> 1) * 4096);
      PROF(layer ? 27 : 14);
    }
    uint32_t m = ~0u;
#pragma unroll
    for (int z = 7; z >= 0; --z) {
      const int k = z >> 2, chl = z & 3;
#pragma unroll
      for (int tp = 0; tp < 4; ++tp) u[chl][tp] = hfma2(xword(x[k][chl >> 1], chl & 1, tp), xword(s[k], 0, tp), xword(s[k], 1, tp));
      sts4(ua + region(chl) + k * 2048, u[chl][0], u[chl][1], u[chl][2], u[chl][3]);
      const uint4& v = x[k][chl >> 1][chl & 1];
      m = min(m, min(v.x, v.z));
      if (z < 4) m = min(m, min(s[z >> 1][z & 1].x, s[z >> 1][z & 1].z));
    }
    if (!__any_sync(0xffffffffu, m == 0)) break;
  }
  PROF(4 + 12 * layer);
}

template <bool FULL> DEV void box_unit(uint32_t reg, int s, const uint2& a, const uint4& b, const uint32_t (&d)[4], uint32_t (&pv)[4]) {
  const uint32_t u[9] = {a.x, a.y, b.x, b.y, b.z, b.w, d[0], d[1], d[2]};
  uint32_t v[8], p[8];
#pragma unroll
  for (int j = 0; j < 8; ++j) { v[j] = prmt(u[j], u[j + 1], 0x5432); p[j] = hadd2(u[j], v[j]); }
  const uint32_t o = reg + s * 16;
  uint32_t x[4], y[4];
#pragma unroll
  for (int j = 0; j < 4; ++j) { x[j] = hadd2(hadd2(p[1 + j], p[2 + j]), u[3 + j]); y[j] = hadd2(v[3 + j], p[4 + j]); pv[j] = p[4 + j]; }
  sts4(o + R_X5, x[0], x[1], x[2], x[3]);
  sts4(o + R_X3, y[0], y[1], y[2], y[3]);
  if (FULL) {
#pragma unroll
    for (int j = 0; j < 4; ++j) { y[j] = hadd2(hadd2(v[j], v[3 + j]), x[j]); x[j] = hadd2(hadd2(u[j], u[4 + j]), y[j]); }
    const bool od = s & 1;
    sts4(o + R_BO, od ? y[0] : x[0], od ? y[1] : x[1], od ? y[2] : x[2], od ? y[3] : x[3]);
    sts4(o + R_BE + 16, od ? x[0] : y[0], od ? x[1] : y[1], od ? x[2] : y[2], od ? x[3] : y[3]);
  }
}
DEV void box_full(int j, uint32_t (&u)[4][4], uint32_t zero) {
  const uint32_t a2 = uchunk(8, j - 2), a1 = uchunk(0, j - 1);
  uint2 a[4]; uint4 b[4];
#define HALO(n) { a[n] = lds2(region(n) + a2); b[n] = lds4(region(n) + a1); }
  HALO(0) HALO(1)
  split(zero);
#pragma unroll
  for (int chl = 0; chl < 4; ++chl) {
    const uint32_t d[4] = {u[chl][0], u[chl][1], u[chl][2], u[chl][3]};
    box_unit<true>(region(chl), j, a[chl], b[chl], d, u[chl]);
    if (chl < 2) HALO(chl + 2)
    if (chl != 2) {
      fence_async_smem();
      if (chl == 3) bar_arrive(NB_B + 2, 288);
      bar_arrive(NB_B + chl, 288);
    }
    if (chl == 0) PROF(31);
  }
#undef HALO
}
DEV void box_help(int e, int lane) {
  bar_sync(NB_H, 192);
#pragma unroll 1
  for (int n = 0; n < 4; ++n) {
    const int chl = e + (n & 2), s = 128 + 32 * (n & 1) + lane;
    const uint32_t reg = region(chl);
    const uint4 d = lds4(uchunk(reg, s));
    const uint32_t u[4] = {d.x, d.y, d.z, d.w};
    uint32_t v[4];
    box_unit<false>(reg, s, lds2(uchunk(reg, s - 2) + 8), lds4(uchunk(reg, s - 1)), u, v);
    if (n & 1) { fence_async_smem(); bar_arrive(NB_B + chl, 288); }
  }
}

DEV uint4 hadd8(const uint4& a, const uint4& b) { return make_uint4(hadd2(a.x, b.x), hadd2(a.y, b.y), hadd2(a.z, b.z), hadd2(a.w, b.w)); }
DEV void conv_out(int c, int j, int chl, uint4 (&x)[2][2][2], const uint32_t (&v)[4], uint4* XF, uint32_t zero) {
  const int rho = chl >> 1, e = chl & 1;
  const uint32_t ua = uchunk(region(chl), j), fa = region(chl) + R_X5 + j * 16, ha = region(chl) + R_X3 + (j & 1) * 1088 + (j >> 1) * 16;
  const int m8 = ((j & 4) + ((j >> 1) & 1) + 2 * (j & 1)) ^ ((2 * c + e) & 7);
  uint4* xo = XF + (((16 - 2 * (j & 8) + (j >> 4)) * 512 + 256 * rho + 2 * c + e) * 8 + m8);
  bar_sync(NB_Y + e + 7 * rho, 256);
  uint4 y[2], f[2], h[2];
#pragma unroll
  for (int k = 0; k < 2; ++k) {
    y[k] = lds4(ua + k * 2048);
    f[k] = lds4z(ua + k * 2048 + R_BO - R_U, k || j >= 36);
    h[k] = lds4z(fa + k * 2048 - 1024, k || j >= 64);
  }
  const uint32_t q = lds1(SM_TAP + chl * TAP_SZ + T_K);
  const uint4 r = lds4(ha);
  split(zero);
  h[1] = hadd8(h[1], make_uint4(hfma2(q, v[0], r.x), hfma2(q, v[1], r.y), hfma2(q, v[2], r.z), hfma2(q, v[3], r.w)));
#pragma unroll
  for (int k = 0; k < 2; ++k) {
    const uint4 o = hadd8(hadd8(y[k], hadd8(f[k], h[k])), make_uint4(xword(x[k][rho], e, 0), xword(x[k][rho], e, 1), xword(x[k][rho], e, 2), xword(x[k][rho], e, 3)));
    const uint32_t keep = j & 1 ? 0x7632 : 0x5410, k0 = prmt(o.x, o.y, keep), k1 = prmt(o.z, o.w, keep);
    const uint32_t g0 = __shfl_xor_sync(0xffffffffu, prmt(o.x, o.y, keep ^ 0x2222), 1), g1 = __shfl_xor_sync(0xffffffffu, prmt(o.z, o.w, keep ^ 0x2222), 1);
    str4(xo + k * 32768, j & 1 ? g0 : k0, j & 1 ? g1 : k1, j & 1 ? k0 : g0, j & 1 ? k1 : g1);

  }
  if (e) { __syncwarp(); mbar_arrive1(B_RD + rho * 8); }
}

DEV void conv_round(int e, int rho, int w, int lane) {
  const int g = lane >> 2, t = lane & 3, chl = 2 * rho + e;
  const uint32_t reg = region(chl), tp = SM_TAP + chl * TAP_SZ, dr = dlo(reg, 128);
  const uint32_t g0 = tp + ((g & 1) ? T_O : T_E) + 2 * (2 * t - g) - 16;
  const uint32_t ga = g0 - 32 * (w & 1) - 576 * (w >> 1), id = opq(0x3210u);
  float acc[32], f1[24], f2[16];
  uint32_t q[12][4];
  {
    uint32_t qn[18][4];
    qn[0][2] = lds1(ga + 64);
#pragma unroll
    for (int n = 0; n < 18; ++n) {
      const bool nz = n < 15 || w < 2 || (n == 15 && w == 2);
      qn[n][0] = n < 15 ? lds1(ga + 48 - 32 * n) : lds1z(ga + 48 - 32 * n, nz);
      qn[n][1] = n < 15 ? lds1(ga + 32 - 32 * n) : lds1z(ga + 32 - 32 * n, nz);
    }
#pragma unroll
    for (int n = 0; n < 18; ++n) { qn[n][3] = cpy(qn[n][0], id); if (n) qn[n][2] = cpy(qn[n - 1][1], id); }
#pragma unroll
    for (int n = 0; n < 8; ++n) {
      const int i = n & 3;
      const uint32_t a = g0 + 16 - 16 * w - 2 * (n < 4 ? X_5 : X_3) + 16 * i;
      uint32_t (&q1)[4] = q[(n & 4) + (i >> 1)], (&q2)[4] = q[(n & 4) + 2 + (i >> 1)];
      q1[2 * (i & 1)] = lds1z(a, i <= w); q1[2 * (i & 1) + 1] = lds1(a - 64);
      q2[2 * (i & 1)] = cpy(0, id); q2[2 * (i & 1) + 1] = lds1z(a - 128, i >= w);
    }
    const uint32_t gc = tp + T_C - 2 + 4 * (t - g - 8 * w);
#pragma unroll
    for (int kk = 0; kk < 4; ++kk) {
      q[8 + kk][0] = lds1z(gc + 32 * kk, w >= kk); q[8 + kk][2] = lds1z(gc + 32 * kk + 16, w >= kk);
      q[8 + kk][1] = lds1(gc + 32 * kk - 128); q[8 + kk][3] = lds1(gc + 32 * kk - 112);
    }
    PROFD(rho ? 43 : 47, qn[17][2] ^ q[11][3]);
    bar_sync_if(NB_U, NBARU, 1 - rho);
    mbar_arrive1_if(B_V, chl == 1 && w == 0);
    bar_sync_if(NB_T + 1 - e, 256, chl);
    const uint32_t db = dr + (R_U + 32) / 16;
    undef(acc);
    wg_fence();
#pragma unroll
    for (int n = 0; n < 18; ++n) {
      if (n) wg_rs64k<1>(acc, qn[n], db - 2 * n); else wg_rs64k<0>(acc, qn[0], db);
      if (n == 9) wg_commit();
    }
    wg_commit();
  }
  wg_wait<1>();
  PROF(12);
  bar_sync(NB_B + chl, 288);
  const uint32_t d1 = dr + R_X5 / 16, d2 = dr + R_BO / 16;
  undef(f1); undef(f2);
  wg_fence();
#pragma unroll
  for (int n = 0; n < 8; ++n) {
    const uint32_t d = d1 + (n >> 2) * ((R_X3 - R_X5) / 16) + 16 * (n & 1) - 16 * (n & 2);
    if (n) wg_rs48t<1>(f1, q[n], d); else wg_rs48t<0>(f1, q[0], d);
    if (n & 1) { if (n > 1) wg_rs32t<1>(f2, q[8 + (n >> 1)], d2 + 16 * (n >> 1)); else wg_rs32t<0>(f2, q[8], d2); }
  }
  wg_commit();
  wg_wait<1>();
  PROF(13);
  bar_arrive_if(NB_T + e, 256, chl - 3);
  wg_wait<0>();
  PROF(14);
  bar_sync(NB_WG + e, 128);
  {
    const int p = (lane + 9 * (w >> 1)) & 31;
    const uint32_t ya = reg + ((w >> 1) ? R_BO : R_U) + p * 64 + (((2 * (w & 1)) ^ ((p >> 1) & 3)) * 16);
    const uint32_t up = p < lane ? 2048 : 0;
#pragma unroll
    for (int z = 0; z < 4; ++z) {
      const float* a = acc + 16 * (z >> 1) + 2 * (z & 1);
      stsm4t((ya + (up ^ ((z >> 1) * 2048))) ^ ((z & 1) * 16), pack2(a[0], a[1]), pack2(a[4], a[5]), pack2(a[8], a[9]), pack2(a[12], a[13]));
    }
  }
  {
    const uint32_t fa = reg + R_X5 + (8 * w + (lane & 7)) * 16 + (lane >> 3) * 512;
    uint32_t h[6];
#pragma unroll
    for (int p = 0; p < 6; ++p) h[p] = p ? pack2(f1[4 * p] + f1[4 * p - 2], f1[4 * p + 1] + f1[4 * p - 1]) : pack2(f1[0], f1[1]);
    stsm4(fa, h[0], h[1], h[2], h[3]);
    stsm2(fa + 2048, h[4], h[5]);
    stsm4(reg + R_X3 + (lane < 16 ? 1088 : 0) + (8 * w + (lane & 7) + 4 * (lane & 8)) * 16, pack2(f2[0], f2[1]), pack2(f2[2] + f2[4], f2[3] + f2[5]),
          pack2(f2[8], f2[9]), pack2(f2[10] + f2[12], f2[11] + f2[13]));
  }
  bar_arrive(NB_Y + e + 7 * rho, 256);
}
constexpr uint32_t FILL = 0xFFFFFFFFu;
template <int N> DEV void fixo(uint4 (&A)[N], const uint4* p) {
#pragma unroll 1
  for (int it = 0; it < SPIN_LIMIT; ++it) {
    uint32_t m = A[0].x;
#pragma unroll
    for (int k = 1; k < N; ++k) m = max(m, A[k].x);
    if (__all_sync(0xffffffffu, m != FILL)) break;
#pragma unroll
    for (int k = 0; k < N; ++k) ldr4_if(A[k], p + k * 32, A[k].x == FILL);
  }
}
DEV bool rows_nan(float a, float b) {
  return __any_sync(0xffffffffu, a != a || b != b);
}
template <int N> DEV void slow_step(float (&acc)[N], float a0, float a1, const uint16_t* wr, uint32_t zero) {
#pragma unroll
  for (int j = 0; j < N / 4; ++j) {
    const uint32_t v = __ldg((const uint32_t*)(wr + (j >> 3) * 512 + 8 * (j & 7)));
    acc[4 * j] += a0 * bflo(v); acc[4 * j + 1] += a0 * bfhi(v); acc[4 * j + 2] += a1 * bflo(v); acc[4 * j + 3] += a1 * bfhi(v);
    if ((j & 3) == 3) wr += __float_as_uint(acc[4 * j]) & zero;
  }
}
DEV int res_off(int w, int lane) { return ((lane & 7) + 8 * (lane >> 4)) * 8 + ((2 * (w & 2) + (w & 1) + ((lane >> 2) & 2)) ^ (lane & 7)); }
DEV void res_load(uint32_t (&res)[8][2], uint32_t sa, int w, int lane) {
  const uint32_t a = sa + res_off(w, opq(lane)) * 16;
#pragma unroll
  for (int j = 0; j < 8; j += 2) {
    uint32_t r[4];
    ldsm4t(r, a + j * 1024);
    res[j][0] = r[0]; res[j][1] = r[1]; res[j + 1][0] = r[2]; res[j + 1][1] = r[3];
  }
}

DEV void res_init(float (&ac)[32], const uint32_t (&res)[8][2]) {
#pragma unroll
  for (int j = 0; j < 16; ++j) { ac[2 * j] = bflo(res[j >> 1][j & 1]); ac[2 * j + 1] = bfhi(res[j >> 1][j & 1]); }
}
DEV uint32_t after(uint32_t b, const uint32_t (&res)[8][2], uint32_t zero) {
  return b + ((res[0][0] ^ res[2][0] ^ res[4][0] ^ res[6][0]) & zero);
}

DEV void attn_phase(const Params& P, int c, int e, int w, int lane, int layer) {
  lane = opq(lane); c = opq(c);
  const int i = c >> 3, cg = c & 7, J = 16 * e + i, G = 8 * i + 4 - 4 * e + w;
  const int g = lane >> 2, t = lane & 3;
  float acc[96];
  uint32_t res[8][2];
  float2 cs[16];
  float4 st;
  const uint32_t csb = opq(SM_CS + 8 * t);
  {
    const uint32_t sa = SM_A + e * A_E, ba = B_A + 16 * e;
    const uint32_t da = dlo(sa, 8192), db = (SB >> 4) | (512 << 16);
    undef(acc);
#pragma unroll
    for (int j = 0; j < 8; ++j) asm volatile("" : "=r"(res[j][0]), "=r"(res[j][1]));
    mbar_wait(B_WF, layer);
    mbar_wait(ba, 0);
    mbar_wait(B_RD + 8, layer);
    bar_sync_if(NB_T, 256, e);
    PROF(24);
#pragma unroll
    for (int j = 0; j < 4; ++j) {
      if (j == 1) { mbar_wait(ba + 8, 0); PROFK(layer ? 39 : 15); }
      wg_fence();
#pragma unroll
      for (int k = 0; k < 4; ++k) {
        if (j | k) wg_ss192<1>(acc, da + j * 512 + k * 128, db + wslot(j) * 512 + k * 128); else wg_ss192<0>(acc, da, db);
        if (j == 3 && k == 1) wg_commit();
      }
      wg_commit();
      if (j == 1 || j == 2) { wg_wait<1>(); mbar_arrive1_if(B_F + 8 * (j - 1), e); }
    }
    wg_wait<1>();
    bar_arrive(NB_T + e, 256);
    wg_wait<0>();
    if (cg < 4) res_load(res, sa + cg * 8192, w, lane);
    mbar_arrive1(after(B_AE + 8 * e, res, P.zero));
    PROF(25);
#pragma unroll 1
    for (uint32_t late = P.zero;; late = 1) {
      if (late) {
        const uint16_t* xr = (const uint16_t*)SCR->XF[layer] + opq(J) * 32768;
        zero(acc);
#pragma unroll 1
        for (int k = 0; k < 512; ++k)
          slow_step(acc, ldnan(xr + k * 64 + ((2 * w) ^ (k & 7)) * 8 + g), ldnan(xr + k * 64 + ((2 * w + 1) ^ (k & 7)) * 8 + g),
                    P.wqkv + (k * 1536 + 64 * cg + 2 * t), P.zero);
        const uint32_t* q = (const uint32_t*)xr + ((64 * cg + g) * 32 + t);
        const int m8 = (2 * (w & 2) + (w & 1)) ^ g;
#pragma unroll 1
        for (int it = 0; it < SPIN_LIMIT; ++it) {
          uint32_t m = 0;
#pragma unroll
          for (int z = 0; z < 16; ++z) { const uint32_t x = ldr1(q + (z >> 1) * 256 + (m8 ^ (2 * (z & 1))) * 4); m = max(m, x); res[z >> 1][z & 1] = movm(x); }
          if (__all_sync(0xffffffffu, m != FILL)) break;
        }
#pragma unroll
        for (int z = 0; z < 16; ++z) cs[z] = lds2f(csb + 256 + z * 32);
      } else {
        mbar_wait(B_CS, 0);
#pragma unroll
        for (int z = 0; z < 16; ++z) cs[z] = lds2f(csb + 256 + z * 32);
        mbar_wait(B_W4, layer);
        mbar_wait(ba, 1);
        bar_sync(NB_T + 1 - e, 256);
        PROF(26);
#pragma unroll
        for (int j = 4; j < 8; ++j) {
          if (j == 5) mbar_wait(ba + 8, 1);
          if (j >= 6) mbar_wait(B_W6 + 8 * (j - 6), layer);
          if (j > 4) PROF(31 + j);
          wg_fence();
#pragma unroll
          for (int k = 0; k < 4; ++k) {
            wg_ss192<1>(acc, da + (j & 3) * 512 + k * 128, db + wslot(j) * 512 + k * 128);
            if (j == 7 && k == 1) wg_commit();
          }
          wg_commit();
          if (j == 5) {
            if (cg >= 4) res_load(res, sa + (cg - 4) * 8192, w, lane);
            wg_wait<1>(); mbar_arrive1_if(B_F + 16, e); PROF(40);
          }

        }
      }
      uint32_t rs = hadd2(res[0][0], res[0][1]);
#pragma unroll
      for (int z = 2; z < 16; ++z) rs = hadd2(rs, res[z >> 1][z & 1]);
      const float rn = bflo(rs) + bfhi(rs);
      wg_wait<1>();
      bar_arrive_if(NB_T, 256, !(e | late));
      mbar_wait(B_ST + 8 * e, layer);
      st = lds4f(SM_STAT + ((4 * e + w) * 8 + g) * 16);
      PROF(34 + layer);
      wg_wait<0>();
      if (!rows_nan(acc[0] + rn, acc[2]) || late) break;
    }
  }
  mbar_arrive1(B_QE);
  PROFK(8 + 12 * layer);
  uint32_t Q[4][4], K[4][2][2], V[4][2][2];
  {
#pragma unroll
    for (int z = 0; z < 8; ++z) {
      const float* a = acc + 32 + 4 * z; const float* b = acc + 64 + 4 * z;
      K[z >> 1][1][z & 1] = pack2((a[2] - st.z * cs[z].x) * st.w, (a[3] - st.z * cs[z].y) * st.w);
      V[z >> 1][1][z & 1] = movm(pack2((b[2] - st.z * cs[8 + z].x) * st.w, (b[3] - st.z * cs[8 + z].y) * st.w));
    }
    const int hop = (G >> 1) & 3;
    const uint32_t kv = SM_KV + (2 * hop + (w & 1)) * 2048 + lane * 16;
    uint4* h = SCR->H[layer] + (c * 256 + (w & 1) * 128 + lane);
    if (hop == 3) {
#pragma unroll
      for (int z = 0; z < 4; ++z) str4(h + 2048 + z * 32, K[z][1][0], K[z][1][1], V[z][1][0], V[z][1][1]);
    } else {
      mbar_wait(B_F + 16, layer);
#pragma unroll
      for (int z = 0; z < 4; ++z) sts4(kv + z * 512, K[z][1][0], K[z][1][1], V[z][1][0], V[z][1][1]);
      bar_arrive(NB_B + hop, 128);
    }
    PROF(42);
    uint4 hv[4];
#pragma unroll
    for (int z = 0; z < 4; ++z) { hv[z] = make_uint4(0, 0, 0, 0); ldr4_if(hv[z], h + z * 32, G >= 2 && hop == 0); }
#pragma unroll
    for (int z = 0; z < 8; ++z) {
      const float* a = acc + 32 + 4 * z; const float* b = acc + 64 + 4 * z;
      K[z >> 1][0][z & 1] = pack2((a[0] - st.x * cs[z].x) * st.y, (a[1] - st.x * cs[z].y) * st.y);
      V[z >> 1][0][z & 1] = movm(pack2((b[0] - st.x * cs[8 + z].x) * st.y, (b[1] - st.x * cs[8 + z].y) * st.y));
    }
#pragma unroll
    for (int z = 0; z < 8; ++z) {
      const float2 cq = lds2f(csb + z * 32);
      const float* a = acc + 4 * z;
      Q[z >> 1][2 * (z & 1)] = pack2(a[0] - st.x * cq.x, a[1] - st.x * cq.y);
      Q[z >> 1][2 * (z & 1) + 1] = pack2(a[2] - st.z * cq.x, a[3] - st.z * cq.y);
    }
    PROF(27);
    const bool p0 = 2 * t > g, p1 = 2 * t + 1 > g, first = G < 2;
    float s[4][4], mx[4][2];
#pragma unroll
    for (int z = 0; z < 4; ++z) {
      float S[4];
      mma16z(s[z], Q[z][0], Q[z][1], Q[z][2], Q[z][3], K[z][0][0], K[z][0][1]);
      mma16z(S, Q[z][0], Q[z][1], Q[z][2], Q[z][3], K[z][1][0], K[z][1][1]);
      s[z][2] = p0 ? s[z][2] : S[2]; s[z][3] = p1 ? s[z][3] : S[3];
    }
    const float sc0 = st.y * (0.25f * 1.4426950408889634f), sc1 = st.w * (0.25f * 1.4426950408889634f);
    uint32_t pw[4][2];
#pragma unroll
    for (int r = 1; r >= 0; --r) {
      if (r == 0) {
        if (hop) {
          bar_sync(NB_B + hop - 1, 128);
#pragma unroll
          for (int z = 0; z < 4; ++z) hv[z] = lds4(kv - 4096 + z * 512);
        } else fixo(hv, h);
        PROFD(41, hv[3].x);
#pragma unroll
        for (int z = 0; z < 4; ++z) {
          float S[4];
          mma16z(S, Q[z][0], Q[z][1], Q[z][2], Q[z][3], hv[z].x, hv[z].y);
          if (first) S[0] = S[1] = __uint_as_float(0xFF800000u);
          s[z][0] = p0 ? S[0] : s[z][0]; s[z][1] = p1 ? S[1] : s[z][1];
        }
      }
#pragma unroll
      for (int z = 0; z < 4; ++z) mx[z][r] = fmaxf(s[z][2 * r], s[z][2 * r + 1]);
#pragma unroll
      for (int o = 1; o < 3; ++o)
#pragma unroll
        for (int z = 0; z < 4; ++z) mx[z][r] = fmaxf(mx[z][r], __shfl_xor_sync(0xffffffffu, mx[z][r], o));
#pragma unroll
      for (int z = 0; z < 4; ++z) pw[z][r] = pack2(ex2((s[z][2 * r] - mx[z][r]) * (r ? sc1 : sc0)), ex2((s[z][2 * r + 1] - mx[z][r]) * (r ? sc1 : sc0)));
    }
    mbar_wait(layer ? B_N : B_Z, layer);
    const uint32_t M = (p0 ? 0xFFFFu : 0u) | (p1 ? 0xFFFF0000u : 0u);
    uint4* O = SCR->O + ((J * 8 + cg) * 512 + (2 * (w & 2) + (w & 1)) * 64 + t * 8 + g);
#pragma unroll
    for (int h2 = 0; h2 < 2; ++h2) {
      uint32_t ow[2][4];
#pragma unroll
      for (int z = 0; z < 2; ++z) {
        const int n = 2 * h2 + z;
        const uint32_t w0 = pw[n][0], w1 = pw[n][1];
        float sm[4] = {0.f, 0.f, 0.f, 0.f}, Oa[2][4];
        mma8(sm, w0, w1, 0x3F803F80u);
        mma16z(Oa[0], w0 & ~M, w1 & M, 0u, w1 & ~M, V[n][0][0], V[n][1][0]); mma8(Oa[0], w0 & M, 0u, hv[n].z);
        mma16z(Oa[1], w0 & ~M, w1 & M, 0u, w1 & ~M, V[n][0][1], V[n][1][1]); mma8(Oa[1], w0 & M, 0u, hv[n].w);
        const float i0 = rcp(sm[0]), i1 = rcp(sm[2]);
#pragma unroll
        for (int d = 0; d < 2; ++d) { ow[0][2 * z + d] = pack2(Oa[d][0] * i0, Oa[d][1] * i0); ow[1][2 * z + d] = pack2(Oa[d][2] * i1, Oa[d][3] * i1); }
      }
#pragma unroll
      for (int hi = 0; hi < 2; ++hi) str4(O + hi * 128 + h2 * 32, ow[hi][0], ow[hi][1], ow[hi][2], ow[hi][3]);
    }
  }
  str1(SCR->OF[layer] + (J * 32 + cg * 4 + w), 1);
  mbar_arrive1(B_AT + 8 * e + (lds1(csb) & P.zero));
  PROFK(9 + 12 * layer);
  float ac[32];
  res_init(ac, res);
  const uint32_t so = SM_O + e * O_E;
  uint2* xo = opqp(layer ? (uint2*)(P.out + ((16 * G + 2 * (lane >> 3)) * 512 + 64 * cg + 8 * (lane & 7)))
                         : (uint2*)SCR->XG[1] + ((32 * (cg & 3) + t) * 2048 + (cg >> 2) * 512 + xg_off(G, g)));
  const uint32_t stg = SM_X + (4 * e + w) * 2048;
  const uint32_t sw = opq(stg + (lane & 15) * 128 + (((lane >> 4) ^ (lane & 7)) * 16)), sr = opq(stg + (lane >> 3) * 128 + (((lane & 7) ^ (lane >> 3)) * 16));
  uint4* ps = opqp(&SCR->PS[(G * 8 + cg) * 8 + g]);
  {
    const uint32_t bo = B_O + 32 * e;
    const uint32_t dw = (SM_WO >> 4) | (512 << 16), da = dlo(so, 512);
    mbar_wait(B_WO, layer);
#pragma unroll
    for (int j = 0; j < 4; ++j) {
      mbar_wait(bo + 8 * j, layer);
      if (j == 0) { PROFK(32 + layer); mbar_wait(B_AT + 8, layer); }
      wg_fence();
#pragma unroll
      for (int k = 8 * j; k < 8 * j + 8; ++k) {
        const uint32_t a = da + (k >> 2) * 512 + (k & 3) * 8, b = dw + (k & 3) * 1024 + (k >> 2) * 128;
        wg_ss64<1>(ac, a, b);
      }
      wg_commit();
    }
#pragma unroll 1
    for (uint32_t late = P.zero;; late = 1) {
      if (late) {
        const uint16_t* op = (const uint16_t*)(SCR->O + (J * 4096 + w * 128 + g));
        wg_wait<0>();
        res_init(ac, res);
#pragma unroll 1
        for (int k = 0; k < 512; ++k) {
          const uint16_t* q = op + (k >> 6) * 4096 + (k & 56) * 8 + (k & 7);
          slow_step(ac, ldnan(q), ldnan(q + 512), P.wo + (((k & ~31) + 4 * (k & 6) + ((k >> 2) & 6) + (k & 1)) * 512 + 64 * cg + 2 * t), P.zero);
        }
      }
      wg_wait<0>();
      if (!rows_nan(ac[0], ac[2]) || late) break;
    }
  }
  PROFK(10 + 12 * layer);
#pragma unroll
  for (int j = 0; j < 16; ++j) res[j >> 1][j & 1] = pack2(ac[2 * j], ac[2 * j + 1]);
  if (layer == 0) {
    float s[2][4], q0[2][4], q1[2][4];
#pragma unroll
    for (int j = 0; j < 2; ++j) gram<true>(s[j], q0[j], q1[j], res[2 * j][0], res[2 * j][1], res[2 * j + 1][0], res[2 * j + 1][1]);
#pragma unroll
    for (int j = 0; j < 2; ++j) gram<false>(s[j], q0[j], q1[j], res[2 * j + 4][0], res[2 * j + 4][1], res[2 * j + 5][0], res[2 * j + 5][1]);
    const bool od = g & 1;
    str4_if(ps, nzmap(__float_as_uint(s[0][0] + s[1][0])), __float_as_uint(od ? q0[0][1] + q0[1][1] : q0[0][0] + q0[1][0]),
            __float_as_uint(s[0][2] + s[1][2]), __float_as_uint(od ? q1[0][3] + q1[1][3] : q1[0][2] + q1[1][2]), t == (g >> 1));
#pragma unroll
    for (int j = 0; j < 8; ++j) {
      str2(xo + j * 8192, nzmap(prmt(res[j][0], res[j][1], 0x5410)), prmt(res[j][0], res[j][1], 0x7632));
    }
    mbar_arrive1(B_ED + 8 * e);
  } else {
#pragma unroll
    for (int j = 0; j < 8; j += 2) stsm4(sw ^ (j * 16), res[j][0], res[j][1], res[j + 1][0], res[j + 1][1]);
    __syncwarp();
    uint4 v[4];
#pragma unroll
    for (int k = 0; k < 4; ++k) v[k] = lds4((sr ^ ((k & 1) * 64)) + k * 512);
#pragma unroll
    for (int k = 0; k < 4; ++k) stw4(xo + ((k & 1) * 8 + (k >> 1)) * 128, v[k].x, v[k].y, v[k].z, v[k].w);
  }
  PROFK(11 + 12 * layer);
}

DEV void col_sums(const Params& P, int c, int wa, int lane) {
  const int i = c >> 3, cg = c & 7;
  uint4 wv[8];
#pragma unroll
  for (int k = 0; k < 8; ++k) wv[k] = ldnc4(P.wqkv + ((32 * i + (lane >> 3)) * 1536 + wa * 512 + 64 * cg + 8 * (lane & 7)) + 4 * k * 1536);
  float cs[8];
  zero(cs);
#pragma unroll
  for (int k = 0; k < 8; ++k) {
    cs[0] += bflo(wv[k].x); cs[1] += bfhi(wv[k].x); cs[2] += bflo(wv[k].y); cs[3] += bfhi(wv[k].y);
    cs[4] += bflo(wv[k].z); cs[5] += bfhi(wv[k].z); cs[6] += bflo(wv[k].w); cs[7] += bfhi(wv[k].w);
  }
  const bool b4 = lane & 16, b3 = lane & 8;
#pragma unroll
  for (int k = 0; k < 4; ++k) cs[k] = (b4 ? cs[k + 4] : cs[k]) + __shfl_xor_sync(0xffffffffu, b4 ? cs[k] : cs[k + 4], 16);
#pragma unroll
  for (int k = 0; k < 2; ++k) cs[k] = (b3 ? cs[k + 2] : cs[k]) + __shfl_xor_sync(0xffffffffu, b3 ? cs[k] : cs[k + 2], 8);
  str2((uint2*)SCR->CS + (i * 768 + wa * 256 + 32 * cg + 4 * (lane & 7) + (lane >> 3)), nzmap(__float_as_uint(cs[0])), __float_as_uint(cs[1]));
}
DEV void col_gather(const Params& P, int c, int wa, int lane) {
  const uint2* p = (const uint2*)SCR->CS + (wa * 256 + 32 * (c & 7) + lane);
#pragma unroll 1
  for (int it = 0;; ++it) {
    float a = 0.f, b = 0.f;
    uint32_t m = ~0u;
#pragma unroll
    for (int k = 0; k < 16; ++k) { const uint2 q = ldr2(p + k * 768); m = min(m, q.x); a += __uint_as_float(q.x); b += __uint_as_float(q.y); }
    if (__all_sync(0xffffffffu, m != 0u)) { sts2f(SM_CS + wa * 256 + lane * 8, a, b); break; }
    spin_guard(it);
  }
  __syncwarp();
  mbar_arrive1(B_CS);
}

DEV void aux_prologue(const Params& P, int c, int wa, int lane) {
  const int g = lane >> 2, t = lane & 3, G = stat_group(c);
  {
    uint32_t w[16][2];
    const uint16_t* row = P.x0 + ((16 * G + 2 * g) * 512 + 128 * wa + 8 * t);
    bar_sync(NB_Y, 384);
    __nanosleep(100);
#pragma unroll
    for (int z = 0; z < 8; ++z) {
      const uint4 v = ldw4(row + (z & 1) * 512 + (z >> 1) * 32);
      const int o = 4 * (z >> 1);
      w[o][z & 1] = v.x; w[o + 1][z & 1] = v.y; w[o + 2][z & 1] = v.z; w[o + 3][z & 1] = v.w;
    }
    PROF(34);
    PROFD(35, w[0][0]);
    PROFD(36, w[15][1]);
    uint2* xo = (uint2*)SCR->XG[0] + ((64 * (wa & 1) + 4 * t) * 2048 + (wa >> 1) * 512 + xg_off(G, g));
#pragma unroll
    for (int n = 0; n < 16; ++n) str2(xo + (16 * (n >> 2) + (n & 3)) * 2048, nzmap(prmt(w[n][0], w[n][1], 0x5410)), prmt(w[n][0], w[n][1], 0x7632));
    float s[2][4], q0[2][4], q1[2][4];
#pragma unroll
    for (int z = 0; z < 8; ++z) {
      const int o = 4 * (z >> 1), r = z & 1;
      if (z < 2) gram<true>(s[r], q0[r], q1[r], w[o][r], w[o + 1][r], w[o + 2][r], w[o + 3][r]);
      else gram<false>(s[r], q0[r], q1[r], w[o][r], w[o + 1][r], w[o + 2][r], w[o + 3][r]);
    }
    const bool od = g & 1;
    if (t == (g >> 1))
      sts4f(SM_MISC + (wa * 8 + g) * 16, s[0][0] + s[0][2], od ? q0[0][1] + q1[0][3] : q0[0][0] + q1[0][2],
            s[1][0] + s[1][2], od ? q0[1][1] + q1[1][3] : q0[1][0] + q1[1][2]);
    bar_arrive(NB_P0, 192);
  }
  PROF(2);
  if (lane == 0)
    asm volatile("cp.async.bulk.prefetch.L2.global [%0],4096;" :: "l"(wa < 3 ? P.wqkv + (3 * c + wa) * 2048 : P.wo + c * 2048) : "memory");
  bar_sync(NB_Y + 1, 256);
}

DEV void stat_part(const Params& P, int c, int wa, int lane, int layer, int h, float (&v)[2]) {
  lane = opq(lane);
  const int e = wa >> 1;
  uint32_t x[4][4];
  mbar_wait(B_A + 16 * e, h); mbar_wait(B_A + 16 * e + 8, h);
#pragma unroll
  for (int k = 0; k < 4; ++k) ldsm4t(x[k], SM_A + e * A_E + (128 * (wa & 1) + lane) * 128 + (((c ^ lane) & 7) * 16) + k * 4096);
  float s[4] = {0.f, 0.f, 0.f, 0.f};
#pragma unroll
  for (int k = 0; k < 16; ++k) { const float a = bflo(x[k >> 2][k & 3]), b = bfhi(x[k >> 2][k & 3]); s[0] += a; s[1] += a * a; s[2] += b; s[3] += b * b; }
  s[0] += s[2]; s[1] += s[3];
  if (RARE(rows_nan(s[1], s[1]))) {
    const uint16_t* q = (const uint16_t*)(SCR->XF[layer] + ((32 * e + 2 * (c >> 3) + h) * 2048 + (wa & 1) * 1024)) + (lane >> 2);
    s[0] = s[1] = 0.f;
#pragma unroll 1
    for (int k = 0; k < 32; ++k) {
      const int r = 2 * (lane & 3) + (k & 1);
      const float a = ldnan(q + ((k >> 1) * 8 + r) * 64 + ((c ^ r) & 7) * 8);
      s[0] += a; s[1] += a * a;
    }
  }
  v[0] += s[0]; v[1] += s[1];
  __syncwarp();
}
DEV void stat_finish(const Params& P, int c, int wa, int lane, int layer, float (&v)[2]) {
  lane = opq(lane);
  const bool b = lane & 1;
  const float s = (b ? v[1] : v[0]) + __shfl_xor_sync(0xffffffffu, b ? v[0] : v[1], 1);
  str1((uint32_t*)SCR->ST[layer] + ((128 * (wa >> 1) + c) * 64 + (wa & 1) * 32 + lane), nzmap(__float_as_uint(s)));
  const uint4* sp = SCR->ST[layer] + ((128 * (wa >> 1) + (c & ~7) + 4 * (wa & 1) + (lane >> 3)) * 16 + (lane & 7));
  uint4 x, y;
  for (int it = 0;; ++it) {
    x = ldr4(sp); y = ldr4(sp + 8);
    if (__all_sync(0xffffffffu, min(min(min(x.x, x.y), min(x.z, x.w)), min(min(y.x, y.y), min(y.z, y.w))) != 0u)) break;
    spin_guard(it);
  }
  const uint32_t q = ln_sums((__uint_as_float(x.x) + __uint_as_float(x.z)) + (__uint_as_float(y.x) + __uint_as_float(y.z)),
                             (__uint_as_float(x.y) + __uint_as_float(x.w)) + (__uint_as_float(y.y) + __uint_as_float(y.w)));
  sts2f(SM_STAT + (16 * wa + (lane >> 4) * 8 + (lane & 7)) * 16 + (lane & 8), bflo(q), rcp(bfhi(q)));
  __syncwarp();
  mbar_arrive1(B_ST + 4 * (wa & 2));
}

DEV void nan_source(uint32_t a, int lane) {
#pragma unroll
  for (int k = 0; k < 4; ++k) sts4(a + k * 512 + lane * 16, FILL, FILL, FILL, FILL);
  fence_async_smem();
  __syncwarp();
}
__global__ void __launch_bounds__(NTHR, 1)
fused_kernel(const __grid_constant__ Params P, const __grid_constant__ CUtensorMap mapW, const __grid_constant__ CUtensorMap mapWo,
             const __grid_constant__ CUtensorMap mapX) {
  extern __shared__ __align__(1024) uint8_t smem_raw[];
  const int warp = __shfl_sync(0xffffffffu, threadIdx.x >> 5, 0), lane = threadIdx.x & 31;
  uint32_t smid; asm volatile("mov.u32 %0,%%smid;" : "=r"(smid));
  const uint32_t* pw = (const uint32_t*)&P + threadIdx.y;
  const int role = P.role[(smid >> 1) + threadIdx.y] + (smid & 1) + (pw[0] & pw[12]);
  const int c = __shfl_sync(0xffffffffu, pw[1] ? role : blockIdx.x, 0);
  if (c >= 128) {
#pragma unroll 1
    for (int k = (c - 128) * NTHR + threadIdx.x; k < 131072; k += P.spare * NTHR) str4(SCR->XG[1] + k, 0, 0, 0, 0);
    __threadfence();
    __syncthreads();
    if (warp == 0) { poll(SCR->C + 1 + (lane & 3) * 32, 32); cnt_add1(SCR->C + 6); }
    __syncthreads();
#pragma unroll 1
    for (int k = (c - 128) * NTHR + threadIdx.x; k < 131072; k += P.spare * NTHR) str4(SCR->XG[0] + k, 0, 0, 0, 0);
    return;
  }
#define DONE() do {} while (0)
  const int cg = c & 7;
  if (warp < 8) {
    PROF(46);
    kgen(P, c, warp, lane);
    PROFK(1);
    bar_sync(0, 384);
#pragma unroll 1
    for (int layer = 0; layer < 2; ++layer) {
#pragma unroll 1
      for (int rho = 0; rho < 2; ++rho) {
        const int wz = warp + ((rho + layer) & P.zero);
        conv_round(wz >> 2, rho, wz & 3, lane_id());
        PROFK(6 + rho + 12 * layer);
      }
      const int z = layer & P.zero;
      attn_phase(P, c + z, (warp + z) >> 2, (warp + z) & 3, lane_id(), layer);
    }
    DONE();
  } else if (warp < 12) {
    asm volatile("setmaxnreg.dec.sync.aligned.u32 %0;" :: "n"(REG_AUX));
    aux_prologue(P, c, warp - 8, lane);
    PROF(1);
    const int c0 = c;
#pragma unroll 1
    for (int layer = 0;; ++layer) {
      const int c = c0 + (layer & P.zero), wa = warp - 8 + (layer & P.zero);
#define lane lane_id()
#define j (32 * wa + lane_id())
      uint4 x[2][2][2];
      uint32_t u[4][4];
      uprep(P, c, wa, lane, layer, x, u);
      fence_async_smem();
      bar_arrive(NB_U, NBARU);
      PROFK(5 + 12 * layer);
      bar_sync(NB_H, 192);
      box_full(j, u, P.zero);
      PROF(3 + 12 * layer);
      mbar_wait(B_Z, 0);
      conv_out(c, j, 0, x, u[0], SCR->XF[layer], P.zero);
      PROF(32);
      conv_out(c, j, 1, x, u[1], SCR->XF[layer], P.zero);
      PROF(6 + 12 * layer);
      if (layer == 0 && wa < 3) col_sums(P, c, wa, lane);
      conv_out(c, j, 2, x, u[2], SCR->XF[layer], P.zero);
      PROF(33);
      conv_out(c, j, 3, x, u[3], SCR->XF[layer], P.zero);
      PROFK(7 + 12 * layer);
      float v[2];
      zero(v);
#pragma unroll 1
      for (int h = 0; h < 2; ++h) {
        stat_part(P, c, wa, lane, layer, h, v);
        if (h) break;
        mbar_arrive1(B_AE + 4 * (wa & 2));
        if (layer == 0 && wa < 3) col_gather(P, c, wa, lane);
      }
      PROF(9 + 12 * layer);
      stat_finish(P, c, wa, lane, layer, v);
      PROF(8 + 12 * layer);
      if (layer) break;
      mbar_wait(B_ED, 0); mbar_wait(B_ED + 8, 0);
#undef lane
#undef j
    }
    DONE();
  } else {
    asm volatile("setmaxnreg.dec.sync.aligned.u32 %0;" :: "n"(REG_PROD));
    if (s2u(smem_raw) != SB) __trap();
#pragma unroll 1
    for (int n = warp - 12; n < 38; n += 4)
      asm volatile("{.reg .pred p; elect.sync _|p,0xffffffff; @p mbarrier.init.shared::cta.b64 [%0],%1;}"
                   :: "r"(SM_BAR + n * 8), "r"(n > 14 ? 1 : (int)(0x322866444444444ull >> (4 * n)) & 15) : "memory");
    fence_async_smem();
    bar_sync(NB_AUX, 128);
    bar_arrive(0, 384); bar_arrive(NB_Y + 1, 256);
    PROF(1);
    if (warp == 12) {
      if (lane == 0) {
        asm volatile("prefetch.tensormap [%0];" :: "l"(&mapW) : "memory");
        asm volatile("prefetch.tensormap [%0];" :: "l"(&mapWo) : "memory");
        asm volatile("prefetch.tensormap [%0];" :: "l"(&mapX) : "memory");
      }
      nan_source(slot(12), lane);
      mbar_wait(B_U, 0);
#pragma unroll 1
      for (int k = 0; k < 8; ++k) tma2_store(&mapX, slot(12), 128 * c, 8 * k);
#pragma unroll 1
      for (int k = 0; k < 4; ++k) bulk_store(SCR->H[k >> 1] + ((c + 8) * 256 + (k & 1) * 128), slot(12), 2048);
#pragma unroll 1
      for (int k = 0; k < 8; ++k) bulk_store(SCR->O + (c * 512 + (k >> 2) * 65536 + (k & 3) * 128), slot(12), 2048);
      bulk_wait();
      mbar_arrive1(B_Z);
      PROF(24);
#pragma unroll 1
      for (int layer = 0; layer < 2; ++layer) {
        mbar_wait(B_V, layer);
        if (layer == 1 && c < 4 && ((0x47 >> lane) & 1)) str1(SCR->C + c * 32 + lane, 0);
        mbar_expect1(B_WF, 4 * 24576);
#pragma unroll
        for (int k = 0; k < 4; ++k) tma3(slot(wslot(k)), &mapW, 64 * cg, 64 * k, 0, B_WF);
        mbar_wait(B_WF, layer);
        mbar_expect1(B_W4, 2 * 24576);
#pragma unroll
        for (int k = 4; k < 6; ++k) tma3(slot(wslot(k)), &mapW, 64 * cg, 64 * k, 0, B_W4);
        bar_sync(NB_AUX, 64);
#pragma unroll 1
        for (int k = 0; k < 2; ++k) {
          mbar_expect1(B_W6 + 8 * k, 24576);
          mbar_wait(B_F + 8 * k, layer);
          tma3(slot(3 * k), &mapW, 64 * cg, 384 + 64 * k, 0, B_W6 + 8 * k);
        }
        mbar_expect1(B_WO, 65536);
        mbar_wait(B_AE + 8, layer);
        nan_source(slot(12), lane);
        uint4* fp = layer ? SCR->O + c * 512 : SCR->XF[1] + c * 512;
#pragma unroll 1
        for (int r = 7; r >= 0; --r) {
          __nanosleep(30);
          if (r >= 4) {
            bulk_store(fp + (r & 3) * 128, slot(12), 2048); bulk_store(fp + 65536 + (r & 3) * 128, slot(12), 2048);
          }
          if (r == 3) { bulk_wait(); __threadfence(); mbar_arrive1(B_N); PROF(9 + 12 * layer); }
          if (r == 1) mbar_wait(B_F + 16, layer);
          tma4(SM_WO + r * 8192, &mapWo, 64 * cg, 0, r >> 1, 32 * (r & 1), B_WO);
        }
        PROF(8 + 12 * layer);
      }
      DONE();
    } else if (warp == 13) {
      const int G = stat_group(c);
#pragma unroll 1
      for (int layer = 0; layer < 2; ++layer) {
        float z[4];
        uint2* so = opqp((uint2*)&SCR->SR[layer][lane >> 3][sr_off(G, lane)] + (lane & 1));
        if (layer == 0) {
          bar_sync(NB_P0, 192);
          const float4 a = lds4f(SM_MISC + lane * 16);
          z[0] = a.x; z[1] = a.y; z[2] = a.z; z[3] = a.w;
        } else {
          mbar_wait(B_ED + 2 * (c & 4), 0);
          uint4* ps = &SCR->PS[G * 64 + lane];
          uint4 a, b;
          for (int it = 0;; ++it) {
            a = ldr4(ps); b = ldr4(ps + 32);
            if (__all_sync(0xffffffffu, min(a.x, b.x) != 0u)) break;
            spin_guard(it);
          }
          z[0] = __uint_as_float(a.x) + __uint_as_float(b.x); z[1] = __uint_as_float(a.y) + __uint_as_float(b.y);
          z[2] = __uint_as_float(a.z) + __uint_as_float(b.z); z[3] = __uint_as_float(a.w) + __uint_as_float(b.w);
        }
#pragma unroll
        for (int o = 8; o < 32; o <<= 1)
#pragma unroll
          for (int k = 0; k < 4; ++k) z[k] += __shfl_xor_sync(0xffffffffu, z[k], o);
        const uint32_t w0 = ln_sums(z[0], z[1]), w1 = ln_sums(z[2], z[3]);
        const uint32_t r = nzmap(pack2(rcp(bfhi(w0)), rcp(bfhi(w1)))), m = pack2(z[0] * (-1.f / 512.f) * bflo(r), z[2] * (-1.f / 512.f) * bfhi(r));
        str2(so, r, m); str2(so + 4 * 1024, r, m);
        PROF(4 + 12 * layer);
        box_help(0, lane);
        PROF(6 + 12 * layer);
      }
      DONE();
    } else if (warp == 14) {
#pragma unroll 1
      for (int layer = 0; layer < 2; ++layer) {
        uint32_t* ca = opqp(SCR->C + (c >> 5) * 32 + 3 * layer);
        const uint32_t* cw = opqp(SCR->C + (lane & 3) * 32 + 3 * layer);
        const uint4* xg = opqp(SCR->XG[layer] + c * 1024);
        mbar_expect1(B_E, 16384);
        if (layer) { mbar_wait(B_N, 0); mbar_wait(B_ED, 0); mbar_wait(B_ED + 8, 0); } else bar_sync(NB_P0, 192);
        cnt_add1(ca);
        bar_arrive_if(NB_P0 + 1, 288, 1 - layer);
        PROF(4 + 12 * layer);
        poll(cw, 32);
        mbar_arrive1(B_U);
        bulk(SM_X, xg, 16384, B_E);
        PROFK(5 + 12 * layer);
        if (layer == 0) {
          mbar_wait(B_Z, 0);
          __threadfence();
          PROF(11);
        }
#pragma unroll 1
        for (int n = 0; n < 4; ++n) {
          const int e = n & 1;
          const uint4* src = opqp(SCR->XF[layer] + (32 * e + 2 * (c >> 3) + (n >> 1)) * 2048);
          const uint32_t dst = opq(SM_A + e * A_E), b = opq(B_A + 16 * e), f = opq((n & 2 ? B_AE : B_RD) + 8 * e);
          if (n == 0) { mbar_wait(B_RD, layer); cnt_add1(ca + 1); }
          if (!e) poll(cw + 1 + (n >> 1), 32);
          if (n == 2) PROF(7 + 12 * layer);
          mbar_wait(f, layer);
          mbar_expect1(b, 8192); bulk(dst, src, 8192, b);
          mbar_expect1(b + 8, 24576); bulk(dst + 8192, src + 512, 24576, b + 8);
          bar_arrive_if(NB_AUX, 64, n == 2);
          if (!e) PROFK(6 + n + 12 * layer);
        }
#pragma unroll 1
        for (int n = 0; n < 8; ++n) mbar_expect1(B_O + 8 * n, 16384);
        if (layer == 0) poll(SCR->C + 6, P.spare);
        mbar_wait(B_QE, layer);
#pragma unroll 1
        for (int e = 0; e < 2; ++e) {
          const int J = 16 * e + (c >> 3);
          const uint32_t* fl = opqp(SCR->OF[layer] + J * 32 + lane);
          const uint4* src[4];
          uint32_t dst[4], b[4];
#pragma unroll
          for (int n = 0; n < 4; ++n) { src[n] = opqp(SCR->O + (J * 4096 + n * 1024)); dst[n] = opq(SM_O + e * O_E + 16384 * n); b[n] = opq(B_O + 32 * e + 8 * n); }
          mbar_wait(B_AT + 8 * e, layer);
          if (!e) pause(260);
          poll(fl, 1);
#pragma unroll
          for (int n = 0; n < 4; ++n) bulk(dst[n], src[n], 16384, b[n]);
          PROFK(9 + e + 12 * layer);
        }
      }
      DONE();
    }
    if (warp == 15) {
      const int G = stat_group(c);
      str4(&SCR->ST[0][(lane >> 4) * 2048 + c * 16 + (lane & 15)], 0, 0, 0, 0); str4(&SCR->ST[1][(lane >> 4) * 2048 + c * 16 + (lane & 15)], 0, 0, 0, 0);
      if (lane < 4) str4(SCR->OF[lane >> 1] + ((lane & 1) * 512 + c * 4), 0, 0, 0, 0);
      str4(&SCR->PS[G * 64 + lane], 0, 0, 0, 0); str4(&SCR->PS[G * 64 + 32 + lane], 0, 0, 0, 0);
      str4(&SCR->SR[1][lane >> 2][sr_off(G, 2 * lane)], 0, 0, 0, 0);
      if (c < 4 && lane < 3) str1(SCR->C + c * 32 + 3 + lane, 0);
#pragma unroll
      for (int k = 0; k < 3; ++k) str2((uint2*)SCR->CS + ((c >> 3) * 768 + k * 256 + 32 * cg + lane), 0, 0);
      __threadfence();
#pragma unroll 1
      for (int layer = 0; layer < 2; ++layer) {
        PROF(4 + 12 * layer);
        box_help(1, lane);
        if (layer) str4(&SCR->SR[0][lane >> 2][sr_off(G, 2 * lane)], 0, 0, 0, 0);
        uint32_t* ca = opqp(SCR->C + (c >> 5) * 32 + 3 * layer + 2);
        mbar_wait(B_RD + 8, layer);
        cnt_add1(ca);
        if (P.spare == 0) {
#pragma unroll 1
          for (int k = 0; k < 32; ++k) str4(SCR->XG[layer] + (c * 1024 + k * 32 + lane), 0, 0, 0, 0);
        }
      }
      mbar_watch(B_O + 56, 1);
    }
  }
}

typedef CUresult (*EncodeFn)(CUtensorMap*, CUtensorMapDataType, cuuint32_t, void*, const cuuint64_t*, const cuuint64_t*,
                             const cuuint32_t*, const cuuint32_t*, CUtensorMapInterleave, CUtensorMapSwizzle,
                             CUtensorMapL2promotion, CUtensorMapFloatOOBfill);

static int place_roles(uint8_t* role) {
  int dev = 0, nsm = 0;
  cudaGetDevice(&dev);
  cudaDeviceGetAttribute(&nsm, cudaDevAttrMultiProcessorCount, dev);
  if (nsm <= 128 || nsm > 144 || (nsm & 1)) return 0;
  cudaFuncSetAttribute(fused_kernel, cudaFuncAttributeNonPortableClusterSizeAllowed, 1);
  int occ[9] = {0};
  for (int k = 2; k <= 8; ++k) {
    cudaLaunchConfig_t cfg = {};
    cudaLaunchAttribute at[1];
    at[0].id = cudaLaunchAttributeClusterDimension;
    at[0].val.clusterDim.x = 2 * k; at[0].val.clusterDim.y = 1; at[0].val.clusterDim.z = 1;
    cfg.gridDim = dim3(2 * k); cfg.blockDim = dim3(NTHR); cfg.dynamicSmemBytes = SM_TOTAL; cfg.attrs = at; cfg.numAttrs = 1;
    if (cudaOccupancyMaxActiveClusters(&occ[k], fused_kernel, &cfg) != cudaSuccess) { cudaGetLastError(); occ[k] = 0; }
  }
  int n[10];
  n[7] = occ[8]; n[6] = occ[7]; n[5] = occ[6] - 0; n[4] = occ[5];
  n[3] = occ[4] - n[7]; n[1] = occ[2] - n[3] - n[5] - n[7]; n[0] = n[2] = n[1];
  n[8] = occ[3] - n[2] - n[5];
  const int ntpc = nsm / 2;
  int sum = 0;
  bool ok = n[0] > 0 && n[0] <= 8;
  for (int r = 0; r < 9; ++r) { ok = ok && n[r] >= 0 && (r == 0 || n[r] <= n[r - 1]); sum += n[r]; }
  if (!ok || sum > ntpc) { for (int r = 0; r < 9; ++r) n[r] = r < 8 ? 8 : 0; sum = 64; }
  int tp[8][9], cnt[8] = {0}, pool[72], np = 0, id = 0;
  for (int r = 0; r < 9; ++r)
    for (int g = n[0] - n[r]; g < n[0]; ++g) tp[g][cnt[g]++] = id++;
  for (; id < ntpc; ++id) pool[np++] = id;
  int order[72], no = 0;
  for (int g = 0; g < n[0]; ++g) {
    const int full = cnt[g] / 4 * 4;
    for (int k = 0; k < cnt[g]; ++k) { if (k < full) order[no++] = tp[g][k]; else pool[np++] = tp[g][k]; }
  }
  for (int k = 0; k < np; ++k) order[no++] = pool[k];
  for (int k = 0; k < ntpc; ++k) role[order[k]] = 2 * k;
  return nsm;
}

extern "C" void kernel_launch(void* const* d_in, const int* in_sizes, int n_in, void* d_out, int out_size) {
  (void)in_sizes; (void)n_in; (void)out_size;
  static EncodeFn enc = nullptr;
  static uint8_t role[72];
  static int nsm = 0;
  static Scratch* scratch = nullptr;
  if (!enc) {
    void* fn = nullptr;
    cudaDriverEntryPointQueryResult qr;
    cudaGetDriverEntryPoint("cuTensorMapEncodeTiled", &fn, cudaEnableDefault, &qr);
    enc = (EncodeFn)fn;
    cudaFuncSetAttribute(fused_kernel, cudaFuncAttributeMaxDynamicSharedMemorySize, SM_TOTAL);
    nsm = place_roles(role);
    cudaGetSymbolAddress((void**)&scratch, g_S);
  }
  CUtensorMap mW, mWo, mX;
  {
    cuuint64_t dim[3] = {512, 512, 3}, str[2] = {3072, 1024};
    cuuint32_t box[3] = {64, 64, 3}, es[3] = {1, 1, 1};
    enc(&mW, CU_TENSOR_MAP_DATA_TYPE_BFLOAT16, 3, d_in[10], dim, str, box, es, CU_TENSOR_MAP_INTERLEAVE_NONE,
        CU_TENSOR_MAP_SWIZZLE_128B, CU_TENSOR_MAP_L2_PROMOTION_NONE, CU_TENSOR_MAP_FLOAT_OOB_FILL_NONE);
  }
  {
    cuuint64_t dim[4] = {512, 2, 4, 64}, str[3] = {1024, 2048, 8192};
    cuuint32_t box[4] = {64, 2, 1, 32}, es[4] = {1, 1, 1, 1};
    enc(&mWo, CU_TENSOR_MAP_DATA_TYPE_BFLOAT16, 4, d_in[11], dim, str, box, es, CU_TENSOR_MAP_INTERLEAVE_NONE,
        CU_TENSOR_MAP_SWIZZLE_128B, CU_TENSOR_MAP_L2_PROMOTION_NONE, CU_TENSOR_MAP_FLOAT_OOB_FILL_NONE);
  }
  {
    cuuint64_t dim[2] = {16384, 64}, str[1] = {32768};
    cuuint32_t box[2] = {128, 8}, es[2] = {1, 1};
    enc(&mX, CU_TENSOR_MAP_DATA_TYPE_BFLOAT16, 2, scratch->XF[0], dim, str, box, es, CU_TENSOR_MAP_INTERLEAVE_NONE,
        CU_TENSOR_MAP_SWIZZLE_NONE, CU_TENSOR_MAP_L2_PROMOTION_NONE, CU_TENSOR_MAP_FLOAT_OOB_FILL_NONE);
  }
  Params P;
  P.x0 = (const uint16_t*)d_in[0]; P.Are = (const uint16_t*)d_in[1]; P.Aim = (const uint16_t*)d_in[2];
  P.Bre = (const uint16_t*)d_in[3]; P.Bim = (const uint16_t*)d_in[4]; P.Cre = (const uint16_t*)d_in[5];
  P.Cim = (const uint16_t*)d_in[6]; P.logdt = (const uint16_t*)d_in[7]; P.dskip = (const uint16_t*)d_in[8];
  P.wqkv = (const uint16_t*)d_in[10]; P.wo = (const uint16_t*)d_in[11]; P.out = (uint16_t*)d_out;
  for (int k = 0; k < 72; ++k) P.role[k] = role[k];
  P.zero = 0;
  P.mid = (char*)scratch->C;
  P.spare = nsm > 0 ? nsm - 128 : 0;
  fused_kernel<<<nsm > 0 ? nsm : 128, NTHR, SM_TOTAL, cudaStreamPerThread>>>(P, mW, mWo, mX);
}
```

```cpp
#include <cuda_runtime.h>
#include <cuda_bf16.h>
#include <cuda.h>
#include <stdint.h>
#include <stddef.h>

#define DEV __device__ __forceinline__
#define RARE(x) __builtin_expect(!!(x), 0)

#define KXD 200
constexpr int NTHR = 512;
constexpr int REG_MAIN = 192, REG_AUX = 96, REG_PROD = 32;
constexpr int NBARU = 384;
constexpr int SPIN_LIMIT = 1 << 22;

constexpr uint32_t SB = 1024;
__host__ __device__ constexpr uint32_t slot(int n) { return SB + n * 8192; }
__host__ __device__ constexpr int wslot(int k) { return k < 2 ? 3 * k : k < 4 ? 3 * k + 6 : k < 6 ? 21 - 3 * k : 3 * k - 18; }
constexpr uint32_t SM_A = slot(22), A_E = 0u - 32768;
constexpr uint32_t SM_O = slot(18), O_E = 0u - 147456;
constexpr uint32_t SM_WO = slot(10), SM_X = slot(8), SM_KV = slot(9) - 4096;
constexpr uint32_t SM_TAP  = slot(26);
constexpr int TAP_SZ = 3440;
constexpr uint32_t SM_STAT = SM_TAP + 4 * TAP_SZ;
constexpr uint32_t SM_CS   = SM_STAT + 1024;
constexpr uint32_t SM_MISC = SM_CS + 768;
constexpr uint32_t SM_BAR  = SM_MISC + 528;
constexpr int SM_TOTAL = SM_BAR + 304 - SB;
static_assert(SM_TOTAL <= 232448, "");
constexpr int R_SZ = 16384, R_U = 512, R_X5 = 5120, R_X3 = 8704, R_BO = 11776, R_BE = 13824;
constexpr int X_5 = 576, X_3 = 648, T_E = 2 * 720, T_O = 1600 + 2 * 721, T_C = 3390, T_K = 3424;
constexpr uint32_t B_RD = SM_BAR, B_ED = SM_BAR + 16, B_F = SM_BAR + 32, B_AT = SM_BAR + 56, B_L = SM_BAR + 264;
constexpr uint32_t B_AE = SM_BAR + 72, B_QE = SM_BAR + 88, B_ST = SM_BAR + 96, B_CS = SM_BAR + 112;
constexpr uint32_t B_WO = SM_BAR + 120, B_W6 = SM_BAR + 128, B_U = SM_BAR + 144, B_E = SM_BAR + 152, B_A = SM_BAR + 160, B_O = SM_BAR + 192,
                   B_Z = SM_BAR + 256, B_WF = SM_BAR + 272, B_W4 = SM_BAR + 280, B_N = SM_BAR + 288, B_V = SM_BAR + 296;
constexpr int NB_U = 1, NB_B = 2, NB_K = 8, NB_Y = 6, NB_WG = 8, NB_T = 10, NB_AUX = 12, NB_P0 = 13, NB_H = 15;

struct Scratch {
  uint4    XG[2][128 * 1024];
  uint4    O[32 * 8 * 512];
  uint32_t C[8 * 32];
  uint32_t OF[2][32 * 32];
  uint4    CS[16 * 1536 / 4];
  uint4    PS[128 * 64];
  uint4    ST[2][32 * 128];
  uint4    SR[2][8][512];
  uint4    XF[2][32 * 512 * 8];
  uint4    H[2][17 * 8 * 256];
};
__device__ __align__(1024) Scratch g_S;
#define SCR ((Scratch*)(P.mid - offsetof(Scratch, C)))
#define PROFD(slot, v) do {} while (0)
#define PROF(slot) do {} while (0)
#define PROFK(slot) do {} while (0)

DEV uint32_t s2u(const void* p) { return (uint32_t)__cvta_generic_to_shared(p); }
template <class T> DEV T* opqp(T* x) { asm volatile("" : "+l"(x)); return x; }
template <class T> DEV T opq(T x) { asm volatile("" : "+r"(x)); return x; }
DEV int lane_id() { int l; asm volatile("mov.u32 %0,%%laneid;" : "=r"(l)); return l; }
DEV uint32_t pack2(float lo, float hi) { uint32_t d; asm("cvt.rn.bf16x2.f32 %0,%1,%2;" : "=r"(d) : "f"(hi), "f"(lo)); return d; }
DEV float bflo(uint32_t v) { return __uint_as_float(v << 16); }
DEV float bfhi(uint32_t v) { return __uint_as_float(v & 0xFFFF0000u); }
DEV float bfr(float x) { return bflo(pack2(x, 0.f)); }
DEV uint32_t hadd2(uint32_t a, uint32_t b) { uint32_t d; asm("add.rn.bf16x2 %0,%1,%2;" : "=r"(d) : "r"(a), "r"(b)); return d; }
DEV uint32_t hsub2(uint32_t a, uint32_t b) { uint32_t d; asm("sub.rn.bf16x2 %0,%1,%2;" : "=r"(d) : "r"(a), "r"(b)); return d; }
DEV uint32_t hmul2(uint32_t a, uint32_t b) { uint32_t d; asm("mul.rn.bf16x2 %0,%1,%2;" : "=r"(d) : "r"(a), "r"(b)); return d; }
DEV uint32_t hfma2(uint32_t a, uint32_t b, uint32_t c) { uint32_t d; asm("fma.rn.bf16x2 %0,%1,%2,%3;" : "=r"(d) : "r"(a), "r"(b), "r"(c)); return d; }
DEV uint32_t hmax2(uint32_t a, uint32_t b) { uint32_t d; asm("max.bf16x2 %0,%1,%2;" : "=r"(d) : "r"(a), "r"(b)); return d; }
DEV uint32_t prmt(uint32_t a, uint32_t b, uint32_t s) { uint32_t d; asm("prmt.b32 %0,%1,%2,%3;" : "=r"(d) : "r"(a), "r"(b), "r"(s)); return d; }
DEV uint32_t nzmap(uint32_t v) { uint32_t d; asm("max.u32 %0,%1,1;" : "=r"(d) : "r"(v)); return d; }
DEV float rcp(float x) { float y; asm("rcp.approx.ftz.f32 %0,%1;" : "=f"(y) : "f"(x)); return y; }
DEV float sqrt_(float x) { float y; asm("sqrt.approx.ftz.f32 %0,%1;" : "=f"(y) : "f"(x)); return y; }
DEV float ex2(float x) { float y; asm("ex2.approx.ftz.f32 %0,%1;" : "=f"(y) : "f"(x)); return y; }

DEV uint4 ldr4(const void* p) { uint4 v; asm volatile("ld.relaxed.gpu.global.v4.u32 {%0,%1,%2,%3},[%4];" : "=r"(v.x), "=r"(v.y), "=r"(v.z), "=r"(v.w) : "l"(p) : "memory"); return v; }
DEV void ldr4_if(uint4& v, const void* p, bool c) {
  asm volatile("{.reg .pred q; setp.ne.u32 q,%5,0; @q ld.relaxed.gpu.global.v4.u32 {%0,%1,%2,%3},[%4];}"
    : "+r"(v.x), "+r"(v.y), "+r"(v.z), "+r"(v.w) : "l"(p), "r"((uint32_t)c) : "memory");
}
DEV uint2 ldr2(const void* p) { uint2 v; asm volatile("ld.relaxed.gpu.global.v2.u32 {%0,%1},[%2];" : "=r"(v.x), "=r"(v.y) : "l"(p) : "memory"); return v; }
DEV void ldr2_if(uint2& v, const void* p, bool c) {
  asm volatile("{.reg .pred q; setp.ne.u32 q,%3,0; @q ld.relaxed.gpu.global.v2.u32 {%0,%1},[%2];}" : "+r"(v.x), "+r"(v.y) : "l"(p), "r"((uint32_t)c) : "memory");
}
DEV uint32_t ldr1(const void* p) { uint32_t v; asm volatile("ld.relaxed.gpu.global.u32 %0,[%1];" : "=r"(v) : "l"(p) : "memory"); return v; }
DEV float ldnan(const uint16_t* p) {
  uint32_t v = 0xFFFFu;
#pragma unroll 1
  for (int it = 0; it < SPIN_LIMIT && __any_sync(0xffffffffu, v == 0xFFFFu); ++it) asm volatile("ld.relaxed.gpu.global.u16 %0,[%1];" : "=r"(v) : "l"(p) : "memory");
  return __uint_as_float(v << 16);
}
DEV uint4 ldw4(const void* p) { uint4 v; asm volatile("ld.global.v4.u32 {%0,%1,%2,%3},[%4];" : "=r"(v.x), "=r"(v.y), "=r"(v.z), "=r"(v.w) : "l"(p) : "memory"); return v; }
DEV uint2 ldw2(const void* p) { uint2 v; asm volatile("ld.global.v2.u32 {%0,%1},[%2];" : "=r"(v.x), "=r"(v.y) : "l"(p) : "memory"); return v; }
DEV uint32_t ldw1(const void* p) { uint32_t v; asm volatile("ld.global.u32 %0,[%1];" : "=r"(v) : "l"(p) : "memory"); return v; }
DEV void str4(void* p, uint32_t a, uint32_t b, uint32_t c, uint32_t d) { asm volatile("st.relaxed.gpu.global.v4.u32 [%0],{%1,%2,%3,%4};" :: "l"(p), "r"(a), "r"(b), "r"(c), "r"(d) : "memory"); }
DEV void str2(void* p, uint32_t a, uint32_t b) { asm volatile("st.relaxed.gpu.global.v2.u32 [%0],{%1,%2};" :: "l"(p), "r"(a), "r"(b) : "memory"); }
DEV void str1(void* p, uint32_t a) { asm volatile("st.relaxed.gpu.global.u32 [%0],%1;" :: "l"(p), "r"(a) : "memory"); }
DEV void str4_if(void* p, uint32_t a, uint32_t b, uint32_t c, uint32_t d, bool q) {
  asm volatile("{.reg .pred q; setp.ne.u32 q,%5,0; @q st.relaxed.gpu.global.v4.u32 [%0],{%1,%2,%3,%4};}" :: "l"(p), "r"(a), "r"(b), "r"(c), "r"(d), "r"((uint32_t)q) : "memory");
}
DEV void stw4(void* p, uint32_t a, uint32_t b, uint32_t c, uint32_t d) { asm volatile("st.global.v4.u32 [%0],{%1,%2,%3,%4};" :: "l"(p), "r"(a), "r"(b), "r"(c), "r"(d) : "memory"); }
DEV uint4 ldnc4(const void* p) { uint4 v; asm volatile("ld.global.nc.v4.u32 {%0,%1,%2,%3},[%4];" : "=r"(v.x), "=r"(v.y), "=r"(v.z), "=r"(v.w) : "l"(p)); return v; }
DEV uint32_t ldnc1(const void* p) { uint32_t v; asm volatile("ld.global.nc.u32 %0,[%1];" : "=r"(v) : "l"(p)); return v; }
DEV uint2 ldnc2(const void* p) { uint2 v; asm volatile("ld.global.nc.v2.u32 {%0,%1},[%2];" : "=r"(v.x), "=r"(v.y) : "l"(p)); return v; }

DEV uint2 lds2(uint32_t a) { uint2 v; asm volatile("ld.volatile.shared.v2.u32 {%0,%1},[%2];" : "=r"(v.x), "=r"(v.y) : "r"(a)); return v; }
DEV float lds16f(uint32_t a) { uint32_t v; asm volatile("ld.shared.u16 %0,[%1];" : "=r"(v) : "r"(a)); return __uint_as_float(v << 16); }
DEV void sts2(uint32_t a, uint32_t x, uint32_t y) { asm volatile("st.shared.v2.u32 [%0],{%1,%2};" :: "r"(a), "r"(x), "r"(y) : "memory"); }
DEV uint32_t lds1(uint32_t a) { uint32_t v; asm volatile("ld.volatile.shared.u32 %0,[%1];" : "=r"(v) : "r"(a)); return v; }
DEV uint32_t lds1z(uint32_t a, bool c) {
  uint32_t v; asm volatile("{.reg .pred q; setp.ne.u32 q,%2,0; mov.u32 %0,0; @q ld.volatile.shared.u32 %0,[%1];}" : "=r"(v) : "r"(a), "r"((uint32_t)c)); return v;
}
DEV uint4 lds4z(uint32_t a, bool c) {
  uint4 v = make_uint4(0, 0, 0, 0);
  asm volatile("{.reg .pred q; setp.ne.u32 q,%5,0; @q ld.volatile.shared.v4.u32 {%0,%1,%2,%3},[%4];}" : "+r"(v.x), "+r"(v.y), "+r"(v.z), "+r"(v.w) : "r"(a), "r"((uint32_t)c));
  return v;
}
DEV float lds1f(uint32_t a) { float v; asm volatile("ld.shared.f32 %0,[%1];" : "=f"(v) : "r"(a)); return v; }
DEV float2 lds2f(uint32_t a) { float2 v; asm volatile("ld.shared.v2.f32 {%0,%1},[%2];" : "=f"(v.x), "=f"(v.y) : "r"(a)); return v; }
DEV float4 lds4f(uint32_t a) { float4 v; asm volatile("ld.volatile.shared.v4.f32 {%0,%1,%2,%3},[%4];" : "=f"(v.x), "=f"(v.y), "=f"(v.z), "=f"(v.w) : "r"(a)); return v; }
DEV uint4 lds4(uint32_t a) { uint4 v; asm volatile("ld.volatile.shared.v4.u32 {%0,%1,%2,%3},[%4];" : "=r"(v.x), "=r"(v.y), "=r"(v.z), "=r"(v.w) : "r"(a)); return v; }
DEV void sts1(uint32_t a, uint32_t v) { asm volatile("st.shared.u32 [%0],%1;" :: "r"(a), "r"(v) : "memory"); }
DEV void sts16(uint32_t a, uint32_t v) { asm volatile("st.shared.u16 [%0],%1;" :: "r"(a), "r"(v) : "memory"); }
DEV void sts2f(uint32_t a, float x, float y) { asm volatile("st.shared.v2.f32 [%0],{%1,%2};" :: "r"(a), "f"(x), "f"(y) : "memory"); }
DEV void sts4f(uint32_t a, float x, float y, float z, float w) { asm volatile("st.shared.v4.f32 [%0],{%1,%2,%3,%4};" :: "r"(a), "f"(x), "f"(y), "f"(z), "f"(w) : "memory"); }
DEV void sts4(uint32_t a, uint32_t x, uint32_t y, uint32_t z, uint32_t w) { asm volatile("st.shared.v4.u32 [%0],{%1,%2,%3,%4};" :: "r"(a), "r"(x), "r"(y), "r"(z), "r"(w) : "memory"); }

DEV void ldsm4(uint32_t (&r)[4], uint32_t a) { asm volatile("ldmatrix.sync.aligned.m8n8.x4.shared.b16 {%0,%1,%2,%3},[%4];" : "=r"(r[0]), "=r"(r[1]), "=r"(r[2]), "=r"(r[3]) : "r"(a) : "memory"); }
DEV void ldsm4t(uint32_t (&r)[4], uint32_t a) { asm volatile("ldmatrix.sync.aligned.m8n8.x4.trans.shared.b16 {%0,%1,%2,%3},[%4];" : "=r"(r[0]), "=r"(r[1]), "=r"(r[2]), "=r"(r[3]) : "r"(a) : "memory"); }
DEV void ldsm2(uint32_t (&r)[2], uint32_t a) { asm volatile("ldmatrix.sync.aligned.m8n8.x2.shared.b16 {%0,%1},[%2];" : "=r"(r[0]), "=r"(r[1]) : "r"(a) : "memory"); }
DEV void stsm4(uint32_t a, uint32_t r0, uint32_t r1, uint32_t r2, uint32_t r3) { asm volatile("stmatrix.sync.aligned.m8n8.x4.shared.b16 [%0],{%1,%2,%3,%4};" :: "r"(a), "r"(r0), "r"(r1), "r"(r2), "r"(r3) : "memory"); }
DEV void stsm2(uint32_t a, uint32_t r0, uint32_t r1) { asm volatile("stmatrix.sync.aligned.m8n8.x2.shared.b16 [%0],{%1,%2};" :: "r"(a), "r"(r0), "r"(r1) : "memory"); }
DEV void stsm4t(uint32_t a, uint32_t r0, uint32_t r1, uint32_t r2, uint32_t r3) { asm volatile("stmatrix.sync.aligned.m8n8.x4.trans.shared.b16 [%0],{%1,%2,%3,%4};" :: "r"(a), "r"(r0), "r"(r1), "r"(r2), "r"(r3) : "memory"); }
DEV uint32_t movm(uint32_t a) { uint32_t d; asm volatile("movmatrix.sync.aligned.m8n8.trans.b16 %0,%1;" : "=r"(d) : "r"(a)); return d; }
DEV void mma16(float (&d)[4], uint32_t a0, uint32_t a1, uint32_t a2, uint32_t a3, uint32_t b0, uint32_t b1) {
  asm volatile("mma.sync.aligned.m16n8k16.row.col.f32.bf16.bf16.f32 {%0,%1,%2,%3},{%4,%5,%6,%7},{%8,%9},{%0,%1,%2,%3};"
    : "+f"(d[0]), "+f"(d[1]), "+f"(d[2]), "+f"(d[3]) : "r"(a0), "r"(a1), "r"(a2), "r"(a3), "r"(b0), "r"(b1));
}
DEV void mma16z(float (&d)[4], uint32_t a0, uint32_t a1, uint32_t a2, uint32_t a3, uint32_t b0, uint32_t b1) {
  asm volatile("mma.sync.aligned.m16n8k16.row.col.f32.bf16.bf16.f32 {%0,%1,%2,%3},{%4,%5,%6,%7},{%8,%9},{%10,%10,%10,%10};"
    : "=f"(d[0]), "=f"(d[1]), "=f"(d[2]), "=f"(d[3]) : "r"(a0), "r"(a1), "r"(a2), "r"(a3), "r"(b0), "r"(b1), "f"(0.f));
}
DEV void mma8(float (&d)[4], uint32_t a0, uint32_t a1, uint32_t b0) {
  asm volatile("mma.sync.aligned.m16n8k8.row.col.f32.bf16.bf16.f32 {%0,%1,%2,%3},{%4,%5},{%6},{%0,%1,%2,%3};"
    : "+f"(d[0]), "+f"(d[1]), "+f"(d[2]), "+f"(d[3]) : "r"(a0), "r"(a1), "r"(b0));
}

DEV void mma8z(float (&d)[4], uint32_t a0, uint32_t a1, uint32_t b0) {
  asm volatile("mma.sync.aligned.m16n8k8.row.col.f32.bf16.bf16.f32 {%0,%1,%2,%3},{%4,%5},{%6},{%7,%7,%7,%7};"
    : "=f"(d[0]), "=f"(d[1]), "=f"(d[2]), "=f"(d[3]) : "r"(a0), "r"(a1), "r"(b0), "f"(0.f));
}
DEV void bar_sync(int id, int n) { asm volatile("bar.sync %0,%1;" :: "r"(id), "r"(n) : "memory"); }
DEV void bar_sync_if(int id, int n, int c) { asm volatile("{.reg .pred q; setp.ne.s32 q,%2,0; @q bar.sync %0,%1;}" :: "r"(id), "r"(n), "r"(c) : "memory"); }
DEV void bar_arrive_if(int id, int n, int c) { asm volatile("{.reg .pred q; setp.ne.s32 q,%2,0; @q bar.arrive %0,%1;}" :: "r"(id), "r"(n), "r"(c) : "memory"); }
DEV bool bar_any(int id, int n, bool c) {
  uint32_t r; asm volatile("{.reg .pred p,q; setp.ne.u32 q,%3,0; bar.red.or.pred p,%1,%2,q; selp.u32 %0,1,0,p;}" : "=r"(r) : "r"(id), "r"(n), "r"((uint32_t)c) : "memory");
  return __any_sync(0xffffffffu, r);
}
DEV void bar_arrive(int id, int n) { asm volatile("bar.arrive %0,%1;" :: "r"(id), "r"(n) : "memory"); }
DEV void fence_async_glob() { asm volatile("fence.proxy.async.global;" ::: "memory"); }
DEV void fence_async_smem() { asm volatile("fence.proxy.async.shared::cta;" ::: "memory"); }
DEV void mbar_init(uint32_t b, int n) { asm volatile("mbarrier.init.shared::cta.b64 [%0],%1;" :: "r"(b), "r"(n) : "memory"); }
DEV void mbar_arrive(uint32_t b) { asm volatile("mbarrier.arrive.shared::cta.b64 _,[%0];" :: "r"(b) : "memory"); }
DEV void mbar_expect(uint32_t b, int bytes) { asm volatile("mbarrier.arrive.expect_tx.shared::cta.b64 _,[%0],%1;" :: "r"(b), "r"(bytes) : "memory"); }
DEV void mbar_wait(uint32_t b, uint32_t ph) {
  asm volatile("{\n.reg .pred p;\nW: mbarrier.try_wait.parity.shared::cta.b64 p,[%0],%1;\n@!p bra W;\n}" :: "r"(b), "r"(ph) : "memory");
}
DEV void mbar_watch(uint32_t b, uint32_t ph) {
  asm volatile("{\n.reg .pred p,q;\n.reg .u32 n;\nmov.u32 n,0;\n"
               "W: mbarrier.try_wait.parity.shared::cta.b64 p,[%0],%1;\n@p bra D;\n"
               "add.u32 n,n,1;\nsetp.lt.u32 q,n,%2;\n@q bra W;\ntrap;\nD:\n}"
               :: "r"(b), "r"(ph), "n"(SPIN_LIMIT) : "memory");
}
DEV void spin_guard(int it) { asm volatile("{.reg .pred p; setp.gt.s32 p,%0,%1; @p trap;}" :: "r"(it), "n"(SPIN_LIMIT)); }
DEV void split(uint32_t zero) {
  asm volatile("{.reg .pred p; setp.ne.u32 p,%0,0; @p trap;}" :: "r"(zero) : "memory");
}
DEV void pause(int n) {
  uint32_t t0, t; asm volatile("mov.u32 %0,%%clock;" : "=r"(t0));
  do asm volatile("mov.u32 %0,%%clock;" : "=r"(t)); while (t - t0 < n);
}
DEV void poll(const uint32_t* k, uint32_t n) {
#pragma unroll 1
  for (int it = 0;; ++it) {
    spin_guard(it);
    if (__all_sync(0xffffffffu, ldr1(k) >= n)) break;
  }
}
DEV void mbar_arrive1(uint32_t b) { asm volatile("{.reg .pred p; elect.sync _|p,0xffffffff; @p mbarrier.arrive.shared::cta.b64 _,[%0];}" :: "r"(b) : "memory"); }
DEV void mbar_arrive1_if(uint32_t b, int c) {
  asm volatile("{.reg .pred p,q; setp.ne.s32 q,%1,0; elect.sync _|p,0xffffffff; and.pred p,p,q; @p mbarrier.arrive.shared::cta.b64 _,[%0];}" :: "r"(b), "r"(c) : "memory");
}
DEV void mbar_expect1(uint32_t b, int bytes) { asm volatile("{.reg .pred p; elect.sync _|p,0xffffffff; @p mbarrier.arrive.expect_tx.shared::cta.b64 _,[%0],%1;}" :: "r"(b), "r"(bytes) : "memory"); }
DEV void cnt_add1(uint32_t* q) { asm volatile("{.reg .pred p; elect.sync _|p,0xffffffff; @p red.relaxed.gpu.global.add.u32 [%0],1;}" :: "l"(q) : "memory"); }
DEV void tma4(uint32_t dst, const CUtensorMap* m, int c0, int c1, int c2, int c3, uint32_t bar) {
  asm volatile("{.reg .pred p; elect.sync _|p,0xffffffff;\n"
    "@p cp.async.bulk.tensor.4d.shared::cluster.global.mbarrier::complete_tx::bytes [%0],[%1,{%2,%3,%4,%5}],[%6];}"
    :: "r"(dst), "l"(m), "r"(c0), "r"(c1), "r"(c2), "r"(c3), "r"(bar) : "memory");
}
DEV void tma3(uint32_t dst, const CUtensorMap* m, int c0, int c1, int c2, uint32_t bar) {
  asm volatile("{.reg .pred p; elect.sync _|p,0xffffffff;\n"
    "@p cp.async.bulk.tensor.3d.shared::cluster.global.mbarrier::complete_tx::bytes [%0],[%1,{%2,%3,%4}],[%5];}"
    :: "r"(dst), "l"(m), "r"(c0), "r"(c1), "r"(c2), "r"(bar) : "memory");
}
DEV void bulk(uint32_t dst, const void* src, int bytes, uint32_t bar) {
  asm volatile("{.reg .pred p; elect.sync _|p,0xffffffff;\n@p cp.async.bulk.shared::cluster.global.mbarrier::complete_tx::bytes [%0],[%1],%2,[%3];}" :: "r"(dst), "l"(src), "r"(bytes), "r"(bar) : "memory");
}

DEV void bulk_store(void* dst, uint32_t src, int bytes) {
  asm volatile("{.reg .pred p; elect.sync _|p,0xffffffff;\n@p cp.async.bulk.global.shared::cta.bulk_group [%0],[%1],%2;}" :: "l"(dst), "r"(src), "r"(bytes) : "memory");
}
DEV void tma2_store(const CUtensorMap* m, uint32_t src, int c0, int c1) {
  asm volatile("{.reg .pred p; elect.sync _|p,0xffffffff;\n@p cp.async.bulk.tensor.2d.global.shared::cta.bulk_group [%0,{%2,%3}],[%1];}" :: "l"(m), "r"(src), "r"(c0), "r"(c1) : "memory");
}
DEV void bulk_wait() { asm volatile("cp.async.bulk.commit_group;\ncp.async.bulk.wait_group 0;\nfence.proxy.async.global;" ::: "memory"); }

DEV uint32_t dlo(uint32_t addr, uint32_t lbo) { return __shfl_sync(0xffffffffu, (addr >> 4) | ((lbo >> 4) << 16), 0); }
__host__ __device__ constexpr uint32_t dhi(uint32_t sbo, uint32_t swz) { return (sbo >> 4) | (swz << 30); }
DEV void wg_fence() { asm volatile("wgmma.fence.sync.aligned;" ::: "memory"); }
DEV void wg_commit() { asm volatile("wgmma.commit_group.sync.aligned;" ::: "memory"); }
template <int N> DEV void wg_wait() { asm volatile("wgmma.wait_group.sync.aligned %0;" :: "n"(N) : "memory"); }
template <int N> DEV void zero(float (&d)[N]) {
#pragma unroll
  for (int i = 0; i < N; ++i) d[i] = 0.f;
}
template <int N> DEV void zerov(float (&d)[N]) {
#pragma unroll
  for (int i = 0; i < N; ++i) asm volatile("mov.b32 %0,0;" : "=f"(d[i]));
}
template <int N> DEV void undef(float (&d)[N]) {
#pragma unroll
  for (int i = 0; i < N; ++i) asm volatile("" : "=f"(d[i]));
}
#define R4(d, o) "+f"(d[o]), "+f"(d[o + 1]), "+f"(d[o + 2]), "+f"(d[o + 3])
#define R8(d, o) R4(d, o), R4(d, o + 4)
#define R16(d, o) R8(d, o), R8(d, o + 8)
template <int ACC> DEV void wg_rs64k(float (&d)[32], const uint32_t (&a)[4], uint32_t db) {
  asm volatile("{.reg .pred p; .reg .b64 b; setp.ne.s32 p,%38,0; mov.b64 b,{%36,%37};\n"
    "wgmma.mma_async.sync.aligned.m64n64k16.f32.bf16.bf16 {%0,%1,%2,%3,%4,%5,%6,%7,%8,%9,%10,%11,%12,%13,%14,%15,%16,%17,%18,%19,%20,%21,%22,%23,%24,%25,%26,%27,%28,%29,%30,%31},{%32,%33,%34,%35},b,p,1,1,0;}"
    : R16(d, 0), R16(d, 16) : "r"(a[0]), "r"(a[1]), "r"(a[2]), "r"(a[3]), "r"(db), "n"(dhi(512, 2)), "n"(ACC));
}
template <int ACC> DEV void wg_rs48t(float (&d)[24], const uint32_t (&a)[4], uint32_t db) {
  asm volatile("{.reg .pred p; .reg .b64 b; setp.ne.s32 p,%30,0; mov.b64 b,{%28,%29};\n"
    "wgmma.mma_async.sync.aligned.m64n48k16.f32.bf16.bf16 {%0,%1,%2,%3,%4,%5,%6,%7,%8,%9,%10,%11,%12,%13,%14,%15,%16,%17,%18,%19,%20,%21,%22,%23},{%24,%25,%26,%27},b,p,1,1,1;}"
    : R16(d, 0), R8(d, 16) : "r"(a[0]), "r"(a[1]), "r"(a[2]), "r"(a[3]), "r"(db), "n"(dhi(512, 0)), "n"(ACC));
}
template <int ACC> DEV void wg_rs32t(float (&d)[16], const uint32_t (&a)[4], uint32_t db) {
  asm volatile("{.reg .pred p; .reg .b64 b; setp.ne.s32 p,%22,0; mov.b64 b,{%20,%21};\n"
    "wgmma.mma_async.sync.aligned.m64n32k16.f32.bf16.bf16 {%0,%1,%2,%3,%4,%5,%6,%7,%8,%9,%10,%11,%12,%13,%14,%15},{%16,%17,%18,%19},b,p,1,1,1;}"
    : R16(d, 0) : "r"(a[0]), "r"(a[1]), "r"(a[2]), "r"(a[3]), "r"(db), "n"(dhi(1024, 0)), "n"(ACC));
}
template <int ACC> DEV void wg_ss192(float (&d)[96], uint32_t da, uint32_t db) {
  asm volatile("{.reg .pred p; .reg .b64 a,b; setp.ne.s32 p,%100,0; mov.b64 a,{%96,%98}; mov.b64 b,{%97,%99};\n"
    "wgmma.mma_async.sync.aligned.m64n192k16.f32.bf16.bf16 {"
    "%0,%1,%2,%3,%4,%5,%6,%7,%8,%9,%10,%11,%12,%13,%14,%15,%16,%17,%18,%19,%20,%21,%22,%23,%24,%25,%26,%27,%28,%29,%30,%31,"
    "%32,%33,%34,%35,%36,%37,%38,%39,%40,%41,%42,%43,%44,%45,%46,%47,%48,%49,%50,%51,%52,%53,%54,%55,%56,%57,%58,%59,%60,%61,%62,%63,"
    "%64,%65,%66,%67,%68,%69,%70,%71,%72,%73,%74,%75,%76,%77,%78,%79,%80,%81,%82,%83,%84,%85,%86,%87,%88,%89,%90,%91,%92,%93,%94,%95},a,b,p,1,1,1,1;}"
    : R16(d, 0), R16(d, 16), R16(d, 32), R16(d, 48), R16(d, 64), R16(d, 80) : "r"(da), "r"(db), "n"(dhi(1024, 1)), "n"(dhi(1024, 1)), "n"(ACC));
}
template <int ACC> DEV void wg_ss64(float (&d)[32], uint32_t da, uint32_t db) {
  asm volatile("{.reg .pred p; .reg .b64 a,b; setp.ne.s32 p,%36,0; mov.b64 a,{%32,%34}; mov.b64 b,{%33,%35};\n"
    "wgmma.mma_async.sync.aligned.m64n64k16.f32.bf16.bf16 {"
    "%0,%1,%2,%3,%4,%5,%6,%7,%8,%9,%10,%11,%12,%13,%14,%15,%16,%17,%18,%19,%20,%21,%22,%23,%24,%25,%26,%27,%28,%29,%30,%31},a,b,p,1,1,0,1;}"
    : R16(d, 0), R16(d, 16) : "r"(da), "r"(db), "n"(dhi(1024, 0)), "n"(dhi(1024, 1)), "n"(ACC));
}

DEV uint32_t cpy(uint32_t v, uint32_t id) {
  uint32_t d; asm volatile("prmt.b32 %0,%1,%1,%2;" : "=r"(d) : "r"(v), "r"(id)); return d;
}
struct Params {
  uint32_t zero, spare;
  char* mid;
  const uint16_t *x0, *Are, *Aim, *Bre, *Bim, *Cre, *Cim, *logdt, *dskip, *wqkv, *wo;
  uint16_t* out;
  uint8_t role[72];
};

DEV uint32_t ln_word(float mean, float var) {
  float v = bfr(var);
  float s = sqrt_(bfr(v + 1e-5f));
  return pack2(mean, s);
}

DEV int stat_group(int c) { return c ^ 4; }
DEV int xg_off(int G, int g) { return (G >> 6) * 1024 + (G & 63) * 8 + (g ^ (G & 2)); }
DEV int sr_off(int G, int g) { return (G >> 6) * 256 + (g & 2) * 64 + 2 * (G & 63) + ((g >> 2) & 1); }
DEV uint32_t region(int chl) { return SM_A + (chl >> 1) * A_E + (chl & 1) * R_SZ; }
template <bool FIRST> DEV void gram(float (&s)[4], float (&q0)[4], float (&q1)[4], uint32_t a0, uint32_t a1, uint32_t a2, uint32_t a3) {
  const uint32_t one = 0x3F803F80u;
  if (FIRST) { mma16z(s, a0, a1, a2, a3, one, one); mma8z(q0, a0, a1, a0); mma8z(q1, a0, a1, a1); }
  else { mma16(s, a0, a1, a2, a3, one, one); mma8(q0, a0, a1, a0); mma8(q1, a0, a1, a1); }
  mma8(q0, a2, a3, a2); mma8(q1, a2, a3, a3);
}
DEV uint32_t ln_sums(float s, float q) { const float m = s * (1.f / 512.f); return ln_word(m, fmaxf(q * (1.f / 512.f) - m * m, 0.f)); }
DEV void cmul(float& orr, float& oi, float ar, float ai, float br, float bi) {
  float r = ar * br - ai * bi, i = ar * bi + ai * br; orr = r; oi = i;
}
DEV void cexp_(float al, float bt, float s, float& er, float& ei) {
  float mag = ex2(al * s), ph = bt * s;
  ph -= rintf(ph);
  float ang = ph * 6.283185307179586f;
  er = mag * __cosf(ang); ei = mag * __sinf(ang);
}

DEV void kgen(const Params& P, int c, int wm, int lane) {
  const int chl = wm >> 1, mh = wm & 1, g = lane >> 2, t = lane & 3;
  const int ch = 256 * (chl >> 1) + 2 * c + (chl & 1);
  const int mo = ch * 64 + mh * 32 + lane;
  const uint32_t vAr = ldw1((const uint32_t*)P.Are + mo), vAi = ldw1((const uint32_t*)P.Aim + mo);
  const uint32_t vBr = ldw1((const uint32_t*)P.Bre + mo), vBi = ldw1((const uint32_t*)P.Bim + mo);
  const uint32_t vCr = ldw1((const uint32_t*)P.Cre + mo), vCi = ldw1((const uint32_t*)P.Cim + mo);
  const uint32_t vld = ldw1((const uint32_t*)P.logdt + (ch >> 1)), vds = ldw1((const uint32_t*)P.dskip + (ch >> 1));
  bar_arrive(NB_Y, 384);
  PROF(45);
  {
    const uint32_t tz = SM_TAP + chl * TAP_SZ + (mh * 32 + lane) * 16;
#pragma unroll
    for (int k = 0; k < 3; ++k) sts4(tz + k * 1024, 0, 0, 0, 0);
    static_assert(TAP_SZ > 3072 && TAP_SZ <= 4096, "");
    if (mh * 32 + lane < TAP_SZ / 16 - 192) sts4(tz + 3072, 0, 0, 0, 0);
  }
  const uint32_t tb = slot(wm), tw = opq(tb + lane * 4);
  const uint32_t aa = opq(tb + (lane & 15) * 144 + (lane >> 4) * 16), ba = opq(tb + (16 + (lane & 7)) * 144 + (lane >> 3) * 16);
  float acc[5][4], k2048 = 0.f;
#pragma unroll
  for (int i = 0; i < 5; ++i) zerov(acc[i]);
  sts1(tw, 0x3F80u);
  asm volatile("setmaxnreg.inc.sync.aligned.u32 %0;" :: "n"(REG_MAIN));
  PROF(44);
  const float dt = bfr(ex2((ch & 1 ? bfhi(vld) : bflo(vld)) * 1.4426950408889634f));
#pragma unroll 1
  for (int r = 0; r < 2; ++r) {
    const uint32_t sel = r ? 0x3244 : 0x1044;
    const float are = __uint_as_float(prmt(vAr, 0, sel)), aim = __uint_as_float(prmt(vAi, 0, sel)), bre = __uint_as_float(prmt(vBr, 0, sel));
    const float bim = __uint_as_float(prmt(vBi, 0, sel)), cre = __uint_as_float(prmt(vCr, 0, sel)), cim = __uint_as_float(prmt(vCi, 0, sel));
    const float al = dt * are * 1.4426950408889634f, bt = dt * aim * 0.15915494309189535f;
    float qr, qi; cmul(qr, qi, cre, cim, dt * bre, dt * bim);
    if (r == 0) PROFD(2, __float_as_uint(qr + al + bt));
    float er[3], ei[3], e8r, e8i, eLr, eLi;
    cexp_(al, bt, 1.f, er[0], ei[0]); cexp_(al, -bt, 8.f, e8r, e8i); cexp_(al, bt, 128.f, eLr, eLi);
    cmul(er[1], ei[1], er[0], ei[0], er[0], ei[0]); cmul(er[2], ei[2], er[1], ei[1], er[1], ei[1]);
    float yr = e8r, yi = e8i;
#pragma unroll
    for (int a = 0; a < 16; ++a) {
      if (a) sts1(tw + a * 144, pack2(yr, yi));
      if (a && a < 15) cmul(yr, yi, yr, yi, e8r, e8i);
      const int ls = a < 2 ? 0 : a < 4 ? 1 : a < 8 ? 2 : 3;
      const int row0 = 16 + (a < 2 ? 8 * a : a < 4 ? 16 + 4 * (a - 2) : a < 8 ? 24 + 2 * (a - 4) : 32 + (a - 8));
      float xr[8], xi[8];
      xr[0] = qr; xi[0] = qi;
#pragma unroll
      for (int k = 0; k < (8 >> ls); ++k) {
        const int hb = k >= 4 ? 2 : k >= 2 ? 1 : 0;
        if (k) cmul(xr[k], xi[k], xr[k - (1 << hb)], xi[k - (1 << hb)], er[(ls + hb) % 3], ei[(ls + hb) % 3]);
        sts1(tw + (row0 + k) * 144, pack2(xr[k], xi[k]));
      }
      cmul(qr, qi, qr, qi, eLr, eLi);
    }
    __syncwarp();
    if (r == 0) PROF(3);
#pragma unroll
    for (int kp = 0; kp < 2; ++kp) {
      uint32_t a0[4], a1[4];
      ldsm4(a0, aa + kp * 64); ldsm4(a1, aa + kp * 64 + 32);
#pragma unroll
      for (int tl = 0; tl < 5; ++tl) {
        uint32_t b[4];
        ldsm4(b, ba + 8 * tl * 144 + kp * 64);
        if (kp == 0) qr += __shfl_xor_sync(0xffffffffu, qr, 1 << tl);
        mma16(acc[tl], a0[0], a0[1], a0[2], a0[3], b[0], b[1]);
        mma16(acc[tl], a1[0], a1[1], a1[2], a1[3], b[2], b[3]);
      }
    }
    k2048 += qr;
    __syncwarp();
  }
  const uint32_t xa = tb + lane * 16, ob = xa ^ 8192, tp = SM_TAP + chl * TAP_SZ;
  if (mh == 0) {
    sts4f(xa, acc[2][0], acc[2][1], acc[2][2], acc[2][3]);
    sts4f(xa + 512, acc[3][0], acc[3][1], acc[3][2], acc[3][3]);
    sts1(tb + 1024, __float_as_uint(k2048));
  } else {
    sts4f(xa, acc[0][0], acc[0][1], acc[0][2], acc[0][3]);
    sts4f(xa + 512, acc[1][0], acc[1][1], acc[1][2], acc[1][3]);
    sts4f(xa + 1024, acc[4][0], acc[4][1], acc[4][2], acc[4][3]);
  }
  PROF(4);
  bar_sync(NB_K + chl, 64);
  float4 o[3];
#pragma unroll
  for (int k = 0; k < 3; ++k) o[k] = lds4f(ob + k * 512);
  if (mh == 0) {
    if (lane == 0) o[0].x += ch & 1 ? bfhi(vds) : bflo(vds);
    const uint32_t a = tp - 2 * (8 * g + 2 * t + 1);
#pragma unroll
    for (int z = 0; z < 4; ++z) {
      const float* k = acc[z >> 1] + 2 * (z & 1);
      const uint32_t v = z & 1 ? pack2(k[1] + o[z >> 1].w, k[0] + o[z >> 1].z) : pack2(k[1] + o[z >> 1].y, k[0] + o[z >> 1].x);
      sts1(a + T_O - 128 * z, v); sts16(a + T_E - 128 * z, v); sts16(a + T_E + 2 - 128 * z, v >> 16);
    }
    const uint32_t v0 = pack2(acc[4][0] + o[2].x, acc[4][1] + o[2].y), v1 = pack2(acc[4][2] + o[2].z, acc[4][3] + o[2].w);
    const uint32_t b = tp + T_C - 2 * (32 * t + g - 1);
    if (lane == 0) { sts16(tp + T_E - 2 * (X_5 + 63), v0); sts16(tp + T_O - 2 * (X_5 + 63), v0); sts1(tp + T_K, prmt(v0, v0, 0x1010)); }
    else sts16(b, v0);
    sts16(b - 32, v0 >> 16); sts16(b - 16, v1); sts16(b - 48, v1 >> 16);
  } else {
    const uint32_t a = tp - 2 * (256 + 128 * (t >> 1) + 4 * (t & 1) + 8 * g);
#pragma unroll
    for (int z = 0; z < 2; ++z) {
      const uint32_t v = z ? pack2(acc[2][3] + o[0].w, acc[2][2] + o[0].z) : pack2(acc[2][1] + o[0].y, acc[2][0] + o[0].x), d = prmt(v, v, 0x3232);
      sts1(a + T_E - 4 - 128 * z, v); sts16(a + T_O - 4 - 128 * z, v); sts1(a + T_O - 2 - 128 * z, d);
      if (z || lane) { sts1(a + T_E - 128 * z, d); sts16(a + T_O + 2 - 128 * z, d); } else sts16(a + T_E, d);
    }
    const uint32_t w0 = pack2(acc[3][0] + o[1].x, acc[3][1] + o[1].y), w1 = pack2(acc[3][2] + o[1].z, acc[3][3] + o[1].w);
    const uint32_t b = tp - 2 * (16 * t + g);
    if (lane == 0) {
      const uint32_t k = prmt(w0, w0, 0x1010);
      sts1(tp + T_E - 2 * 514, k); sts1(tp + T_E - 2 * 512, k);
      sts16(tp + T_O - 2 * 514, k); sts1(tp + T_O - 2 * 513, k); sts16(tp + T_O - 2 * 511, k);
      sts16(tp + T_C - 2 * 127, pack2(k2048 + o[2].x, 0.f));
    } else { sts16(b + T_E - 2 * (X_5 - 1), w0); sts16(b + T_O - 2 * (X_5 - 1), w0); }
    sts16(b + T_E - 2 * X_3, w0 >> 16); sts16(b + T_O - 2 * X_3, w0 >> 16);
    sts16(b + T_E - 2 * (X_5 + 7), w1); sts16(b + T_O - 2 * (X_5 + 7), w1);
    sts16(b + T_E - 2 * (X_3 + 8), w1 >> 16); sts16(b + T_O - 2 * (X_3 + 8), w1 >> 16);
  }
}

DEV bool bad8(const uint4& v) { return min(v.x, v.z) == 0u; }
DEV uint32_t uchunk(uint32_t reg, int x) { return reg + R_U + (x ^ ((x >> 3) & 3)) * 16; }
DEV uint32_t& xword(uint4 (&x)[2], int e, int tp) { uint4& v = x[tp >> 1]; return tp & 1 ? (e ? v.w : v.z) : (e ? v.y : v.x); }

DEV void uprep(const Params& P, int c, int wa, int lane, int layer, uint4 (&x)[2][2][2], uint32_t (&u)[4][4]) {
  const int j = 32 * wa + lane, o0 = 2 * j + ((j >> 2) & 1);
  {
    const uint32_t za = region(wa) + lane * 16 - 512;
    sts4(za + R_U, 0, 0, 0, 0); sts4(za + R_X5, 0, 0, 0, 0); sts4(za + R_X3, 0, 0, 0, 0);
    sts4(region(wa) + R_BE, 0, 0, 0, 0);
  }
  const uint4* st = opqp(&SCR->SR[layer][c >> 4][j]);
  const uint32_t xa = opq(SM_X + 16 * o0), xb = opq(SM_X + 16 * (o0 ^ 1)), ua = opq(uchunk(0, j));
  uint4 s[2][2];
#pragma unroll
  for (int z = 0; z < 12; ++z) {
    uint4& v = z < 8 ? x[(z >> 2) & 1][(z >> 1) & 1][z & 1] : s[(z >> 1) & 1][z & 1];
    asm volatile("mov.b32 %0,0; mov.b32 %1,0; mov.b32 %2,0; mov.b32 %3,0;" : "=r"(v.x), "=r"(v.y), "=r"(v.z), "=r"(v.w));
  }
#pragma unroll 1
  for (uint32_t it = P.zero;; ++it) {
    if (it) {
      spin_guard(it);
#pragma unroll
      for (int z = 0; z < 4; ++z) { uint4& v = s[z >> 1][z & 1]; ldr4_if(v, st + z * 128, bad8(v)); }
      const uint4* xp = &SCR->XG[layer][c * 1024 + o0];
#pragma unroll
      for (int z = 0; z < 8; ++z) {
        uint4& v = x[z >> 2][(z >> 1) & 1][z & 1];
        ldr4_if(v, (const uint4*)((uintptr_t)xp ^ (16 * (z & 1))) + (z >> 1) * 256, bad8(v));
      }
    } else {
      mbar_wait(B_U, layer);
      PROF(layer ? 25 : 10);
#pragma unroll
      for (int z = 0; z < 4; ++z) s[z >> 1][z & 1] = ldr4(st + z * 128);
#pragma unroll
      for (int z = 0; z < 4; ++z) { uint4& v = s[z >> 1][z & 1]; ldr4_if(v, st + z * 128, bad8(v)); }
      PROF(layer ? 26 : 11);
      mbar_wait(B_E, layer);
#pragma unroll
      for (int z = 7; z >= 0; --z) x[z >> 2][(z >> 1) & 1][z & 1] = lds4((z & 1 ? xb : xa) + (z >> 1) * 4096);
      PROF(layer ? 27 : 14);
    }
    uint32_t m = ~0u;
#pragma unroll
    for (int z = 7; z >= 0; --z) {
      const int k = z >> 2, chl = z & 3;
#pragma unroll
      for (int tp = 0; tp < 4; ++tp) u[chl][tp] = hfma2(xword(x[k][chl >> 1], chl & 1, tp), xword(s[k], 0, tp), xword(s[k], 1, tp));
      sts4(ua + region(chl) + k * 2048, u[chl][0], u[chl][1], u[chl][2], u[chl][3]);
      const uint4& v = x[k][chl >> 1][chl & 1];
      m = min(m, min(v.x, v.z));
      if (z < 4) m = min(m, min(s[z >> 1][z & 1].x, s[z >> 1][z & 1].z));
    }
    if (!__any_sync(0xffffffffu, m == 0)) break;
  }
  PROF(4 + 12 * layer);
}

template <bool FULL> DEV void box_unit(uint32_t reg, int s, const uint2& a, const uint4& b, const uint32_t (&d)[4], uint32_t (&pv)[4]) {
  const uint32_t u[9] = {a.x, a.y, b.x, b.y, b.z, b.w, d[0], d[1], d[2]};
  uint32_t v[8], p[8];
#pragma unroll
  for (int j = 0; j < 8; ++j) { v[j] = prmt(u[j], u[j + 1], 0x5432); p[j] = hadd2(u[j], v[j]); }
  const uint32_t o = reg + s * 16;
  uint32_t x[4], y[4];
#pragma unroll
  for (int j = 0; j < 4; ++j) { x[j] = hadd2(hadd2(p[1 + j], p[2 + j]), u[3 + j]); y[j] = hadd2(v[3 + j], p[4 + j]); pv[j] = p[4 + j]; }
  sts4(o + R_X5, x[0], x[1], x[2], x[3]);
  sts4(o + R_X3, y[0], y[1], y[2], y[3]);
  if (FULL) {
#pragma unroll
    for (int j = 0; j < 4; ++j) { y[j] = hadd2(hadd2(v[j], v[3 + j]), x[j]); x[j] = hadd2(hadd2(u[j], u[4 + j]), y[j]); }
    const bool od = s & 1;
    sts4(o + R_BO, od ? y[0] : x[0], od ? y[1] : x[1], od ? y[2] : x[2], od ? y[3] : x[3]);
    sts4(o + R_BE + 16, od ? x[0] : y[0], od ? x[1] : y[1], od ? x[2] : y[2], od ? x[3] : y[3]);
  }
}
DEV void box_full(int j, uint32_t (&u)[4][4], uint32_t zero) {
  const uint32_t a2 = uchunk(8, j - 2), a1 = uchunk(0, j - 1);
  uint2 a[4]; uint4 b[4];
#define HALO(n) { a[n] = lds2(region(n) + a2); b[n] = lds4(region(n) + a1); }
  HALO(0) HALO(1)
  split(zero);
#pragma unroll
  for (int chl = 0; chl < 4; ++chl) {
    const uint32_t d[4] = {u[chl][0], u[chl][1], u[chl][2], u[chl][3]};
    box_unit<true>(region(chl), j, a[chl], b[chl], d, u[chl]);
    if (chl < 2) HALO(chl + 2)
    if (chl != 2) {
      fence_async_smem();
      if (chl == 3) bar_arrive(NB_B + 2, 288);
      bar_arrive(NB_B + chl, 288);
    }
    if (chl == 0) PROF(31);
  }
#undef HALO
}
DEV void box_help(int e, int lane) {
  bar_sync(NB_H, 192);
#pragma unroll 1
  for (int n = 0; n < 4; ++n) {
    const int chl = e + (n & 2), s = 128 + 32 * (n & 1) + lane;
    const uint32_t reg = region(chl);
    const uint4 d = lds4(uchunk(reg, s));
    const uint32_t u[4] = {d.x, d.y, d.z, d.w};
    uint32_t v[4];
    box_unit<false>(reg, s, lds2(uchunk(reg, s - 2) + 8), lds4(uchunk(reg, s - 1)), u, v);
    if (n & 1) { fence_async_smem(); bar_arrive(NB_B + chl, 288); }
  }
}

DEV uint4 hadd8(const uint4& a, const uint4& b) { return make_uint4(hadd2(a.x, b.x), hadd2(a.y, b.y), hadd2(a.z, b.z), hadd2(a.w, b.w)); }
DEV void conv_out(int c, int j, int chl, uint4 (&x)[2][2][2], const uint32_t (&v)[4], uint4* XF, uint32_t zero) {
  const int rho = chl >> 1, e = chl & 1;
  const uint32_t ua = uchunk(region(chl), j), fa = region(chl) + R_X5 + j * 16, ha = region(chl) + R_X3 + (j & 1) * 1088 + (j >> 1) * 16;
  const int m8 = ((j & 4) + ((j >> 1) & 1) + 2 * (j & 1)) ^ ((2 * c + e) & 7);
  uint4* xo = XF + (((16 - 2 * (j & 8) + (j >> 4)) * 512 + 256 * rho + 2 * c + e) * 8 + m8);
  bar_sync(NB_Y + e + 7 * rho, 256);
  uint4 y[2], f[2], h[2];
#pragma unroll
  for (int k = 0; k < 2; ++k) {
    y[k] = lds4(ua + k * 2048);
    f[k] = lds4z(ua + k * 2048 + R_BO - R_U, k || j >= 36);
    h[k] = lds4z(fa + k * 2048 - 1024, k || j >= 64);
  }
  const uint32_t q = lds1(SM_TAP + chl * TAP_SZ + T_K);
  const uint4 r = lds4(ha);
  split(zero);
  if (chl == 3) mbar_arrive1(B_L + (r.x & zero));
  h[1] = hadd8(h[1], make_uint4(hfma2(q, v[0], r.x), hfma2(q, v[1], r.y), hfma2(q, v[2], r.z), hfma2(q, v[3], r.w)));
#pragma unroll
  for (int k = 0; k < 2; ++k) {
    const uint4 o = hadd8(hadd8(y[k], hadd8(f[k], h[k])), make_uint4(xword(x[k][rho], e, 0), xword(x[k][rho], e, 1), xword(x[k][rho], e, 2), xword(x[k][rho], e, 3)));
    const uint32_t keep = j & 1 ? 0x7632 : 0x5410, k0 = prmt(o.x, o.y, keep), k1 = prmt(o.z, o.w, keep);
    const uint32_t g0 = __shfl_xor_sync(0xffffffffu, prmt(o.x, o.y, keep ^ 0x2222), 1), g1 = __shfl_xor_sync(0xffffffffu, prmt(o.z, o.w, keep ^ 0x2222), 1);
    str4(xo + k * 32768, j & 1 ? g0 : k0, j & 1 ? g1 : k1, j & 1 ? k0 : g0, j & 1 ? k1 : g1);

  }
  if (e) { __syncwarp(); mbar_arrive1(B_RD + rho * 8); }
}

DEV void conv_round(int e, int rho, int w, int lane) {
  const int g = lane >> 2, t = lane & 3, chl = 2 * rho + e;
  const uint32_t reg = region(chl), tp = SM_TAP + chl * TAP_SZ, dr = dlo(reg, 128);
  const uint32_t g0 = tp + ((g & 1) ? T_O : T_E) + 2 * (2 * t - g) - 16;
  const uint32_t ga = g0 - 32 * (w & 1) - 576 * (w >> 1), id = opq(0x3210u);
  float acc[32], f1[24], f2[16];
  uint32_t q[12][4];
  {
    uint32_t qn[18][4];
    qn[0][2] = lds1(ga + 64);
#pragma unroll
    for (int n = 0; n < 18; ++n) {
      const bool nz = n < 15 || w < 2 || (n == 15 && w == 2);
      qn[n][0] = n < 15 ? lds1(ga + 48 - 32 * n) : lds1z(ga + 48 - 32 * n, nz);
      qn[n][1] = n < 15 ? lds1(ga + 32 - 32 * n) : lds1z(ga + 32 - 32 * n, nz);
    }
#pragma unroll
    for (int n = 0; n < 18; ++n) { qn[n][3] = cpy(qn[n][0], id); if (n) qn[n][2] = cpy(qn[n - 1][1], id); }
#pragma unroll
    for (int n = 0; n < 8; ++n) {
      const int i = n & 3;
      const uint32_t a = g0 + 16 - 16 * w - 2 * (n < 4 ? X_5 : X_3) + 16 * i;
      uint32_t (&q1)[4] = q[(n & 4) + (i >> 1)], (&q2)[4] = q[(n & 4) + 2 + (i >> 1)];
      q1[2 * (i & 1)] = lds1z(a, i <= w); q1[2 * (i & 1) + 1] = lds1(a - 64);
      q2[2 * (i & 1)] = cpy(0, id); q2[2 * (i & 1) + 1] = lds1z(a - 128, i >= w);
    }
    const uint32_t gc = tp + T_C - 2 + 4 * (t - g - 8 * w);
#pragma unroll
    for (int kk = 0; kk < 4; ++kk) {
      q[8 + kk][0] = lds1z(gc + 32 * kk, w >= kk); q[8 + kk][2] = lds1z(gc + 32 * kk + 16, w >= kk);
      q[8 + kk][1] = lds1(gc + 32 * kk - 128); q[8 + kk][3] = lds1(gc + 32 * kk - 112);
    }
    PROFD(rho ? 43 : 47, qn[17][2] ^ q[11][3]);
    bar_sync_if(NB_U, NBARU, 1 - rho);
    mbar_arrive1_if(B_V, chl == 1 && w == 0);
    bar_sync_if(NB_T + 1 - e, 256, chl);
    const uint32_t db = dr + (R_U + 32) / 16;
    undef(acc);
    wg_fence();
#pragma unroll
    for (int n = 0; n < 18; ++n) {
      if (n) wg_rs64k<1>(acc, qn[n], db - 2 * n); else wg_rs64k<0>(acc, qn[0], db);
      if (n == 9) wg_commit();
    }
    wg_commit();
  }
  wg_wait<1>();
  PROF(12);
  bar_sync(NB_B + chl, 288);
  const uint32_t d1 = dr + R_X5 / 16, d2 = dr + R_BO / 16;
  undef(f1); undef(f2);
  wg_fence();
#pragma unroll
  for (int n = 0; n < 4; ++n) { if (n) wg_rs32t<1>(f2, q[8 + n], d2 + 16 * n); else wg_rs32t<0>(f2, q[8], d2); }
  wg_commit();
#pragma unroll
  for (int n = 0; n < 8; ++n) {
    const uint32_t d = d1 + (n >> 2) * ((R_X3 - R_X5) / 16) + 16 * (n & 1) - 16 * (n & 2);
    if (n) wg_rs48t<1>(f1, q[n], d); else wg_rs48t<0>(f1, q[0], d);
  }
  wg_commit();
  wg_wait<1>();
  PROF(13);
  bar_arrive_if(NB_T + e, 256, chl - 3);
  PROF(14);
  bar_sync(NB_WG + e, 128);
  {
    const int p = (lane + 9 * (w >> 1)) & 31;
    const uint32_t ya = reg + ((w >> 1) ? R_BO : R_U) + p * 64 + (((2 * (w & 1)) ^ ((p >> 1) & 3)) * 16);
    const uint32_t up = p < lane ? 2048 : 0;
#pragma unroll
    for (int z = 0; z < 4; ++z) {
      const float* a = acc + 16 * (z >> 1) + 2 * (z & 1);
      stsm4t((ya + (up ^ ((z >> 1) * 2048))) ^ ((z & 1) * 16), pack2(a[0], a[1]), pack2(a[4], a[5]), pack2(a[8], a[9]), pack2(a[12], a[13]));
    }
  }
  wg_wait<0>();
  bar_sync(NB_WG + e, 128);
  {
    const uint32_t fa = reg + R_X5 + (8 * w + (lane & 7)) * 16 + (lane >> 3) * 512;
    uint32_t h[6];
#pragma unroll
    for (int p = 0; p < 6; ++p) h[p] = p ? pack2(f1[4 * p] + f1[4 * p - 2], f1[4 * p + 1] + f1[4 * p - 1]) : pack2(f1[0], f1[1]);
    stsm4(fa, h[0], h[1], h[2], h[3]);
    stsm2(fa + 2048, h[4], h[5]);
    stsm4(reg + R_X3 + (lane < 16 ? 1088 : 0) + (8 * w + (lane & 7) + 4 * (lane & 8)) * 16, pack2(f2[0], f2[1]), pack2(f2[2] + f2[4], f2[3] + f2[5]),
          pack2(f2[8], f2[9]), pack2(f2[10] + f2[12], f2[11] + f2[13]));
  }
  bar_arrive(NB_Y + e + 7 * rho, 256);
}
constexpr uint32_t FILL = 0xFFFFFFFFu;
template <int N> DEV void fixo(uint4 (&A)[N], const uint4* p) {
#pragma unroll 1
  for (int it = 0; it < SPIN_LIMIT; ++it) {
    uint32_t m = A[0].x;
#pragma unroll
    for (int k = 1; k < N; ++k) m = max(m, A[k].x);
    if (__all_sync(0xffffffffu, m != FILL)) break;
#pragma unroll
    for (int k = 0; k < N; ++k) ldr4_if(A[k], p + k * 32, A[k].x == FILL);
  }
}
DEV bool rows_nan(float a, float b) {
  return __any_sync(0xffffffffu, a != a || b != b);
}
template <int N> DEV void slow_step(float (&acc)[N], float a0, float a1, const uint16_t* wr, uint32_t zero) {
#pragma unroll
  for (int j = 0; j < N / 4; ++j) {
    const uint32_t v = __ldg((const uint32_t*)(wr + (j >> 3) * 512 + 8 * (j & 7)));
    acc[4 * j] += a0 * bflo(v); acc[4 * j + 1] += a0 * bfhi(v); acc[4 * j + 2] += a1 * bflo(v); acc[4 * j + 3] += a1 * bfhi(v);
    if ((j & 3) == 3) wr += __float_as_uint(acc[4 * j]) & zero;
  }
}
DEV int res_off(int w, int lane) { return ((lane & 7) + 8 * (lane >> 4)) * 8 + ((2 * (w & 2) + (w & 1) + ((lane >> 2) & 2)) ^ (lane & 7)); }
DEV void res_load(uint32_t (&res)[8][2], uint32_t sa, int w, int lane) {
  const uint32_t a = sa + res_off(w, opq(lane)) * 16;
#pragma unroll
  for (int j = 0; j < 8; j += 2) {
    uint32_t r[4];
    ldsm4t(r, a + j * 1024);
    res[j][0] = r[0]; res[j][1] = r[1]; res[j + 1][0] = r[2]; res[j + 1][1] = r[3];
  }
}

DEV void res_init(float (&ac)[32], const uint32_t (&res)[8][2]) {
#pragma unroll
  for (int j = 0; j < 16; ++j) { ac[2 * j] = bflo(res[j >> 1][j & 1]); ac[2 * j + 1] = bfhi(res[j >> 1][j & 1]); }
}
DEV uint32_t after(uint32_t b, const uint32_t (&res)[8][2], uint32_t zero) {
  return b + ((res[0][0] ^ res[2][0] ^ res[4][0] ^ res[6][0]) & zero);
}

DEV void attn_phase(const Params& P, int c, int e, int w, int lane, int layer) {
  lane = opq(lane); c = opq(c);
  const int i = c >> 3, cg = c & 7, J = 16 * e + i, G = 8 * i + 4 - 4 * e + w;
  const int g = lane >> 2, t = lane & 3;
  float acc[96];
  uint32_t res[8][2];
  float2 cs[16];
  float4 st;
  const uint32_t csb = opq(SM_CS + 8 * t);
  {
    const uint32_t sa = SM_A + e * A_E, ba = B_A + 16 * e;
    const uint32_t da = dlo(sa, 8192), db = (SB >> 4) | (512 << 16);
    undef(acc);
#pragma unroll
    for (int j = 0; j < 8; ++j) asm volatile("" : "=r"(res[j][0]), "=r"(res[j][1]));
    mbar_wait(B_WF, layer);
    mbar_wait(ba, 0);
    mbar_wait(B_L, layer);
    bar_sync_if(NB_T, 256, e);
    PROF(24);
#pragma unroll
    for (int j = 0; j < 4; ++j) {
      if (j == 1) { mbar_wait(ba + 8, 0); PROFK(layer ? 39 : 15); }
      wg_fence();
#pragma unroll
      for (int k = 0; k < 4; ++k) {
        if (j | k) wg_ss192<1>(acc, da + j * 512 + k * 128, db + wslot(j) * 512 + k * 128); else wg_ss192<0>(acc, da, db);
        if (j == 3 && k == 1) wg_commit();
      }
      wg_commit();
      if (j == 1 || j == 2) { wg_wait<1>(); mbar_arrive1_if(B_F + 8 * (j - 1), e); }
    }
    wg_wait<1>();
    bar_arrive(NB_T + e, 256);
    wg_wait<0>();
    if (cg < 4) res_load(res, sa + cg * 8192, w, lane);
    mbar_arrive1(after(B_AE + 8 * e, res, P.zero));
    PROF(25);
#pragma unroll 1
    for (uint32_t late = P.zero;; late = 1) {
      if (late) {
        const uint16_t* xr = (const uint16_t*)SCR->XF[layer] + opq(J) * 32768;
        zero(acc);
#pragma unroll 1
        for (int k = 0; k < 512; ++k)
          slow_step(acc, ldnan(xr + k * 64 + ((2 * w) ^ (k & 7)) * 8 + g), ldnan(xr + k * 64 + ((2 * w + 1) ^ (k & 7)) * 8 + g),
                    P.wqkv + (k * 1536 + 64 * cg + 2 * t), P.zero);
        const uint32_t* q = (const uint32_t*)xr + ((64 * cg + g) * 32 + t);
        const int m8 = (2 * (w & 2) + (w & 1)) ^ g;
#pragma unroll 1
        for (int it = 0; it < SPIN_LIMIT; ++it) {
          uint32_t m = 0;
#pragma unroll
          for (int z = 0; z < 16; ++z) { const uint32_t x = ldr1(q + (z >> 1) * 256 + (m8 ^ (2 * (z & 1))) * 4); m = max(m, x); res[z >> 1][z & 1] = movm(x); }
          if (__all_sync(0xffffffffu, m != FILL)) break;
        }
#pragma unroll
        for (int z = 0; z < 16; ++z) cs[z] = lds2f(csb + 256 + z * 32);
      } else {
        mbar_wait(B_CS, 0);
#pragma unroll
        for (int z = 0; z < 16; ++z) cs[z] = lds2f(csb + 256 + z * 32);
        mbar_wait(B_W4, layer);
        mbar_wait(ba, 1);
        bar_sync(NB_T + 1 - e, 256);
        PROF(26);
#pragma unroll
        for (int j = 4; j < 8; ++j) {
          if (j == 5) mbar_wait(ba + 8, 1);
          if (j >= 6) mbar_wait(B_W6 + 8 * (j - 6), layer);
          if (j > 4) PROF(31 + j);
          wg_fence();
#pragma unroll
          for (int k = 0; k < 4; ++k) {
            wg_ss192<1>(acc, da + (j & 3) * 512 + k * 128, db + wslot(j) * 512 + k * 128);
            if (j == 7 && k == 1) wg_commit();
          }
          wg_commit();
          if (j == 5) {
            if (cg >= 4) res_load(res, sa + (cg - 4) * 8192, w, lane);
            wg_wait<1>(); mbar_arrive1_if(B_F + 16, e); PROF(40);
          }

        }
      }
      uint32_t rs = hadd2(res[0][0], res[0][1]);
#pragma unroll
      for (int z = 2; z < 16; ++z) rs = hadd2(rs, res[z >> 1][z & 1]);
      const float rn = bflo(rs) + bfhi(rs);
      wg_wait<1>();
      bar_arrive_if(NB_T, 256, !(e | late));
      mbar_wait(B_ST + 8 * e, layer);
      st = lds4f(SM_STAT + ((4 * e + w) * 8 + g) * 16);
      PROF(34 + layer);
      wg_wait<0>();
      if (!rows_nan(acc[0] + rn, acc[2]) || late) break;
    }
  }
  mbar_arrive1(B_QE);
  PROFK(8 + 12 * layer);
  uint32_t Q[4][4], K[4][2][2], V[4][2][2];
  {
#pragma unroll
    for (int z = 0; z < 8; ++z) {
      const float* a = acc + 32 + 4 * z; const float* b = acc + 64 + 4 * z;
      K[z >> 1][1][z & 1] = pack2((a[2] - st.z * cs[z].x) * st.w, (a[3] - st.z * cs[z].y) * st.w);
      V[z >> 1][1][z & 1] = movm(pack2((b[2] - st.z * cs[8 + z].x) * st.w, (b[3] - st.z * cs[8 + z].y) * st.w));
    }
    const int hop = (G >> 1) & 3;
    const uint32_t kv = SM_KV + (2 * hop + (w & 1)) * 2048 + lane * 16;
    uint4* h = SCR->H[layer] + (c * 256 + (w & 1) * 128 + lane);
    if (hop == 3) {
#pragma unroll
      for (int z = 0; z < 4; ++z) str4(h + 2048 + z * 32, K[z][1][0], K[z][1][1], V[z][1][0], V[z][1][1]);
    } else {
      mbar_wait(B_F + 16, layer);
#pragma unroll
      for (int z = 0; z < 4; ++z) sts4(kv + z * 512, K[z][1][0], K[z][1][1], V[z][1][0], V[z][1][1]);
      bar_arrive(NB_B + hop, 128);
    }
    PROF(42);
    uint4 hv[4];
#pragma unroll
    for (int z = 0; z < 4; ++z) { hv[z] = make_uint4(0, 0, 0, 0); ldr4_if(hv[z], h + z * 32, G >= 2 && hop == 0); }
#pragma unroll
    for (int z = 0; z < 8; ++z) {
      const float* a = acc + 32 + 4 * z; const float* b = acc + 64 + 4 * z;
      K[z >> 1][0][z & 1] = pack2((a[0] - st.x * cs[z].x) * st.y, (a[1] - st.x * cs[z].y) * st.y);
      V[z >> 1][0][z & 1] = movm(pack2((b[0] - st.x * cs[8 + z].x) * st.y, (b[1] - st.x * cs[8 + z].y) * st.y));
    }
#pragma unroll
    for (int z = 0; z < 8; ++z) {
      const float2 cq = lds2f(csb + z * 32);
      const float* a = acc + 4 * z;
      Q[z >> 1][2 * (z & 1)] = pack2(a[0] - st.x * cq.x, a[1] - st.x * cq.y);
      Q[z >> 1][2 * (z & 1) + 1] = pack2(a[2] - st.z * cq.x, a[3] - st.z * cq.y);
    }
    PROF(27);
    const bool p0 = 2 * t > g, p1 = 2 * t + 1 > g, first = G < 2;
    float s[4][4], mx[4][2];
#pragma unroll
    for (int z = 0; z < 4; ++z) {
      float S[4];
      mma16z(s[z], Q[z][0], Q[z][1], Q[z][2], Q[z][3], K[z][0][0], K[z][0][1]);
      mma16z(S, Q[z][0], Q[z][1], Q[z][2], Q[z][3], K[z][1][0], K[z][1][1]);
      s[z][2] = p0 ? s[z][2] : S[2]; s[z][3] = p1 ? s[z][3] : S[3];
    }
    const float sc0 = st.y * (0.25f * 1.4426950408889634f), sc1 = st.w * (0.25f * 1.4426950408889634f);
    uint32_t pw[4][2];
#pragma unroll
    for (int r = 1; r >= 0; --r) {
      if (r == 0) {
        if (hop) {
          bar_sync(NB_B + hop - 1, 128);
#pragma unroll
          for (int z = 0; z < 4; ++z) hv[z] = lds4(kv - 4096 + z * 512);
        } else fixo(hv, h);
        PROFD(41, hv[3].x);
#pragma unroll
        for (int z = 0; z < 4; ++z) {
          float S[4];
          mma16z(S, Q[z][0], Q[z][1], Q[z][2], Q[z][3], hv[z].x, hv[z].y);
          if (first) S[0] = S[1] = __uint_as_float(0xFF800000u);
          s[z][0] = p0 ? S[0] : s[z][0]; s[z][1] = p1 ? S[1] : s[z][1];
        }
      }
#pragma unroll
      for (int z = 0; z < 4; ++z) mx[z][r] = fmaxf(s[z][2 * r], s[z][2 * r + 1]);
#pragma unroll
      for (int o = 1; o < 3; ++o)
#pragma unroll
        for (int z = 0; z < 4; ++z) mx[z][r] = fmaxf(mx[z][r], __shfl_xor_sync(0xffffffffu, mx[z][r], o));
#pragma unroll
      for (int z = 0; z < 4; ++z) pw[z][r] = pack2(ex2((s[z][2 * r] - mx[z][r]) * (r ? sc1 : sc0)), ex2((s[z][2 * r + 1] - mx[z][r]) * (r ? sc1 : sc0)));
    }
    mbar_wait(layer ? B_N : B_Z, layer);
    const uint32_t M = (p0 ? 0xFFFFu : 0u) | (p1 ? 0xFFFF0000u : 0u);
    uint4* O = SCR->O + ((J * 8 + cg) * 512 + (2 * (w & 2) + (w & 1)) * 64 + t * 8 + g);
#pragma unroll
    for (int h2 = 0; h2 < 2; ++h2) {
      uint32_t ow[2][4];
#pragma unroll
      for (int z = 0; z < 2; ++z) {
        const int n = 2 * h2 + z;
        const uint32_t w0 = pw[n][0], w1 = pw[n][1];
        float sm[4] = {0.f, 0.f, 0.f, 0.f}, Oa[2][4];
        mma8(sm, w0, w1, 0x3F803F80u);
        mma16z(Oa[0], w0 & ~M, w1 & M, 0u, w1 & ~M, V[n][0][0], V[n][1][0]); mma8(Oa[0], w0 & M, 0u, hv[n].z);
        mma16z(Oa[1], w0 & ~M, w1 & M, 0u, w1 & ~M, V[n][0][1], V[n][1][1]); mma8(Oa[1], w0 & M, 0u, hv[n].w);
        const float i0 = rcp(sm[0]), i1 = rcp(sm[2]);
#pragma unroll
        for (int d = 0; d < 2; ++d) { ow[0][2 * z + d] = pack2(Oa[d][0] * i0, Oa[d][1] * i0); ow[1][2 * z + d] = pack2(Oa[d][2] * i1, Oa[d][3] * i1); }
      }
#pragma unroll
      for (int hi = 0; hi < 2; ++hi) str4(O + hi * 128 + h2 * 32, ow[hi][0], ow[hi][1], ow[hi][2], ow[hi][3]);
    }
  }
  str1(SCR->OF[layer] + (J * 32 + cg * 4 + w), 1);
  mbar_arrive1(B_AT + 8 * e + (lds1(csb) & P.zero));
  PROFK(9 + 12 * layer);
  float ac[32];
  res_init(ac, res);
  const uint32_t so = SM_O + e * O_E;
  uint2* xo = opqp(layer ? (uint2*)(P.out + ((16 * G + 2 * (lane >> 3)) * 512 + 64 * cg + 8 * (lane & 7)))
                         : (uint2*)SCR->XG[1] + ((32 * (cg & 3) + t) * 2048 + (cg >> 2) * 512 + xg_off(G, g)));
  const uint32_t stg = SM_X + (4 * e + w) * 2048;
  const uint32_t sw = opq(stg + (lane & 15) * 128 + (((lane >> 4) ^ (lane & 7)) * 16)), sr = opq(stg + (lane >> 3) * 128 + (((lane & 7) ^ (lane >> 3)) * 16));
  uint4* ps = opqp(&SCR->PS[(G * 8 + cg) * 8 + g]);
  {
    const uint32_t bo = B_O + 32 * e;
    const uint32_t dw = (SM_WO >> 4) | (512 << 16), da = dlo(so, 512);
    mbar_wait(B_WO, layer);
#pragma unroll
    for (int j = 0; j < 4; ++j) {
      mbar_wait(bo + 8 * j, layer);
      if (j == 0) { PROFK(32 + layer); mbar_wait(B_AT + 8, layer); }
      wg_fence();
#pragma unroll
      for (int k = 8 * j; k < 8 * j + 8; ++k) {
        const uint32_t a = da + (k >> 2) * 512 + (k & 3) * 8, b = dw + (k & 3) * 1024 + (k >> 2) * 128;
        wg_ss64<1>(ac, a, b);
      }
      wg_commit();
    }
#pragma unroll 1
    for (uint32_t late = P.zero;; late = 1) {
      if (late) {
        const uint16_t* op = (const uint16_t*)(SCR->O + (J * 4096 + w * 128 + g));
        wg_wait<0>();
        res_init(ac, res);
#pragma unroll 1
        for (int k = 0; k < 512; ++k) {
          const uint16_t* q = op + (k >> 6) * 4096 + (k & 56) * 8 + (k & 7);
          slow_step(ac, ldnan(q), ldnan(q + 512), P.wo + (((k & ~31) + 4 * (k & 6) + ((k >> 2) & 6) + (k & 1)) * 512 + 64 * cg + 2 * t), P.zero);
        }
      }
      wg_wait<0>();
      if (!rows_nan(ac[0], ac[2]) || late) break;
    }
  }
  PROFK(10 + 12 * layer);
#pragma unroll
  for (int j = 0; j < 16; ++j) res[j >> 1][j & 1] = pack2(ac[2 * j], ac[2 * j + 1]);
  if (layer == 0) {
    float s[2][4], q0[2][4], q1[2][4];
#pragma unroll
    for (int j = 0; j < 2; ++j) gram<true>(s[j], q0[j], q1[j], res[2 * j][0], res[2 * j][1], res[2 * j + 1][0], res[2 * j + 1][1]);
#pragma unroll
    for (int j = 0; j < 2; ++j) gram<false>(s[j], q0[j], q1[j], res[2 * j + 4][0], res[2 * j + 4][1], res[2 * j + 5][0], res[2 * j + 5][1]);
    const bool od = g & 1;
    str4_if(ps, nzmap(__float_as_uint(s[0][0] + s[1][0])), __float_as_uint(od ? q0[0][1] + q0[1][1] : q0[0][0] + q0[1][0]),
            __float_as_uint(s[0][2] + s[1][2]), __float_as_uint(od ? q1[0][3] + q1[1][3] : q1[0][2] + q1[1][2]), t == (g >> 1));
#pragma unroll
    for (int j = 0; j < 8; ++j) {
      str2(xo + j * 8192, nzmap(prmt(res[j][0], res[j][1], 0x5410)), prmt(res[j][0], res[j][1], 0x7632));
    }
    mbar_arrive1(B_ED + 8 * e);
  } else {
#pragma unroll
    for (int j = 0; j < 8; j += 2) stsm4(sw ^ (j * 16), res[j][0], res[j][1], res[j + 1][0], res[j + 1][1]);
    __syncwarp();
    uint4 v[4];
#pragma unroll
    for (int k = 0; k < 4; ++k) v[k] = lds4((sr ^ ((k & 1) * 64)) + k * 512);
#pragma unroll
    for (int k = 0; k < 4; ++k) stw4(xo + ((k & 1) * 8 + (k >> 1)) * 128, v[k].x, v[k].y, v[k].z, v[k].w);
  }
  PROFK(11 + 12 * layer);
}

DEV void col_sums(const Params& P, int c, int wa, int lane) {
  const int i = c >> 3, cg = c & 7;
  uint4 wv[8];
#pragma unroll
  for (int k = 0; k < 8; ++k) wv[k] = ldnc4(P.wqkv + ((32 * i + (lane >> 3)) * 1536 + wa * 512 + 64 * cg + 8 * (lane & 7)) + 4 * k * 1536);
  float cs[8];
  zero(cs);
#pragma unroll
  for (int k = 0; k < 8; ++k) {
    cs[0] += bflo(wv[k].x); cs[1] += bfhi(wv[k].x); cs[2] += bflo(wv[k].y); cs[3] += bfhi(wv[k].y);
    cs[4] += bflo(wv[k].z); cs[5] += bfhi(wv[k].z); cs[6] += bflo(wv[k].w); cs[7] += bfhi(wv[k].w);
  }
  const bool b4 = lane & 16, b3 = lane & 8;
#pragma unroll
  for (int k = 0; k < 4; ++k) cs[k] = (b4 ? cs[k + 4] : cs[k]) + __shfl_xor_sync(0xffffffffu, b4 ? cs[k] : cs[k + 4], 16);
#pragma unroll
  for (int k = 0; k < 2; ++k) cs[k] = (b3 ? cs[k + 2] : cs[k]) + __shfl_xor_sync(0xffffffffu, b3 ? cs[k] : cs[k + 2], 8);
  str2((uint2*)SCR->CS + (i * 768 + wa * 256 + 32 * cg + 4 * (lane & 7) + (lane >> 3)), nzmap(__float_as_uint(cs[0])), __float_as_uint(cs[1]));
}
DEV void col_gather(const Params& P, int c, int wa, int lane) {
  const uint2* p = (const uint2*)SCR->CS + (wa * 256 + 32 * (c & 7) + lane);
#pragma unroll 1
  for (int it = 0;; ++it) {
    float a = 0.f, b = 0.f;
    uint32_t m = ~0u;
#pragma unroll
    for (int k = 0; k < 16; ++k) { const uint2 q = ldr2(p + k * 768); m = min(m, q.x); a += __uint_as_float(q.x); b += __uint_as_float(q.y); }
    if (__all_sync(0xffffffffu, m != 0u)) { sts2f(SM_CS + wa * 256 + lane * 8, a, b); break; }
    spin_guard(it);
  }
  __syncwarp();
  mbar_arrive1(B_CS);
}

DEV void aux_prologue(const Params& P, int c, int wa, int lane) {
  const int g = lane >> 2, t = lane & 3, G = stat_group(c);
  {
    uint32_t w[16][2];
    const uint16_t* row = P.x0 + ((16 * G + 2 * g) * 512 + 128 * wa + 8 * t);
    bar_sync(NB_Y, 384);
    __nanosleep(KXD);
#pragma unroll
    for (int z = 0; z < 8; ++z) {
      const uint4 v = ldw4(row + (z & 1) * 512 + (z >> 1) * 32);
      const int o = 4 * (z >> 1);
      w[o][z & 1] = v.x; w[o + 1][z & 1] = v.y; w[o + 2][z & 1] = v.z; w[o + 3][z & 1] = v.w;
    }
    PROF(34);
    PROFD(35, w[0][0]);
    PROFD(36, w[15][1]);
    uint2* xo = (uint2*)SCR->XG[0] + ((64 * (wa & 1) + 4 * t) * 2048 + (wa >> 1) * 512 + xg_off(G, g));
#pragma unroll
    for (int n = 0; n < 16; ++n) str2(xo + (16 * (n >> 2) + (n & 3)) * 2048, nzmap(prmt(w[n][0], w[n][1], 0x5410)), prmt(w[n][0], w[n][1], 0x7632));
    float s[2][4], q0[2][4], q1[2][4];
#pragma unroll
    for (int z = 0; z < 8; ++z) {
      const int o = 4 * (z >> 1), r = z & 1;
      if (z < 2) gram<true>(s[r], q0[r], q1[r], w[o][r], w[o + 1][r], w[o + 2][r], w[o + 3][r]);
      else gram<false>(s[r], q0[r], q1[r], w[o][r], w[o + 1][r], w[o + 2][r], w[o + 3][r]);
    }
    const bool od = g & 1;
    if (t == (g >> 1))
      sts4f(SM_MISC + (wa * 8 + g) * 16, s[0][0] + s[0][2], od ? q0[0][1] + q1[0][3] : q0[0][0] + q1[0][2],
            s[1][0] + s[1][2], od ? q0[1][1] + q1[1][3] : q0[1][0] + q1[1][2]);
    bar_arrive(NB_P0, 192);
  }
  PROF(2);
  if (lane == 0)
    asm volatile("cp.async.bulk.prefetch.L2.global [%0],4096;" :: "l"(wa < 3 ? P.wqkv + (3 * c + wa) * 2048 : P.wo + c * 2048) : "memory");
  bar_sync(NB_Y + 1, 256);
}

DEV void stat_part(const Params& P, int c, int wa, int lane, int layer, int h, float (&v)[2]) {
  lane = opq(lane);
  const int e = wa >> 1;
  uint32_t x[4][4];
  mbar_wait(B_A + 16 * e, h); mbar_wait(B_A + 16 * e + 8, h);
#pragma unroll
  for (int k = 0; k < 4; ++k) ldsm4t(x[k], SM_A + e * A_E + (128 * (wa & 1) + lane) * 128 + (((c ^ lane) & 7) * 16) + k * 4096);
  float s[4] = {0.f, 0.f, 0.f, 0.f};
#pragma unroll
  for (int k = 0; k < 16; ++k) { const float a = bflo(x[k >> 2][k & 3]), b = bfhi(x[k >> 2][k & 3]); s[0] += a; s[1] += a * a; s[2] += b; s[3] += b * b; }
  s[0] += s[2]; s[1] += s[3];
  if (RARE(rows_nan(s[1], s[1]))) {
    const uint16_t* q = (const uint16_t*)(SCR->XF[layer] + ((32 * e + 2 * (c >> 3) + h) * 2048 + (wa & 1) * 1024)) + (lane >> 2);
    s[0] = s[1] = 0.f;
#pragma unroll 1
    for (int k = 0; k < 32; ++k) {
      const int r = 2 * (lane & 3) + (k & 1);
      const float a = ldnan(q + ((k >> 1) * 8 + r) * 64 + ((c ^ r) & 7) * 8);
      s[0] += a; s[1] += a * a;
    }
  }
  v[0] += s[0]; v[1] += s[1];
  __syncwarp();
}
DEV void stat_finish(const Params& P, int c, int wa, int lane, int layer, float (&v)[2]) {
  lane = opq(lane);
  const bool b = lane & 1;
  const float s = (b ? v[1] : v[0]) + __shfl_xor_sync(0xffffffffu, b ? v[0] : v[1], 1);
  str1((uint32_t*)SCR->ST[layer] + ((128 * (wa >> 1) + c) * 64 + (wa & 1) * 32 + lane), nzmap(__float_as_uint(s)));
  const uint4* sp = SCR->ST[layer] + ((128 * (wa >> 1) + (c & ~7) + 4 * (wa & 1) + (lane >> 3)) * 16 + (lane & 7));
  uint4 x, y;
  for (int it = 0;; ++it) {
    x = ldr4(sp); y = ldr4(sp + 8);
    if (__all_sync(0xffffffffu, min(min(min(x.x, x.y), min(x.z, x.w)), min(min(y.x, y.y), min(y.z, y.w))) != 0u)) break;
    spin_guard(it);
  }
  const uint32_t q = ln_sums((__uint_as_float(x.x) + __uint_as_float(x.z)) + (__uint_as_float(y.x) + __uint_as_float(y.z)),
                             (__uint_as_float(x.y) + __uint_as_float(x.w)) + (__uint_as_float(y.y) + __uint_as_float(y.w)));
  sts2f(SM_STAT + (16 * wa + (lane >> 4) * 8 + (lane & 7)) * 16 + (lane & 8), bflo(q), rcp(bfhi(q)));
  __syncwarp();
  mbar_arrive1(B_ST + 4 * (wa & 2));
}

DEV void nan_source(uint32_t a, int lane) {
#pragma unroll
  for (int k = 0; k < 4; ++k) sts4(a + k * 512 + lane * 16, FILL, FILL, FILL, FILL);
  fence_async_smem();
  __syncwarp();
}
__global__ void __launch_bounds__(NTHR, 1)
fused_kernel(const __grid_constant__ Params P, const __grid_constant__ CUtensorMap mapW, const __grid_constant__ CUtensorMap mapWo,
             const __grid_constant__ CUtensorMap mapX) {
  extern __shared__ __align__(1024) uint8_t smem_raw[];
  const int warp = __shfl_sync(0xffffffffu, threadIdx.x >> 5, 0), lane = threadIdx.x & 31;
  uint32_t smid; asm volatile("mov.u32 %0,%%smid;" : "=r"(smid));
  const uint32_t* pw = (const uint32_t*)&P + threadIdx.y;
  const int role = P.role[(smid >> 1) + threadIdx.y] + (smid & 1) + (pw[0] & pw[12]);
  const int c = __shfl_sync(0xffffffffu, pw[1] ? role : blockIdx.x, 0);
  if (c >= 128) {
#pragma unroll 1
    for (int k = (c - 128) * NTHR + threadIdx.x; k < 131072; k += P.spare * NTHR) str4(SCR->XG[1] + k, 0, 0, 0, 0);
    __threadfence();
    __syncthreads();
    if (warp == 0) { poll(SCR->C + 1 + (lane & 3) * 32, 32); cnt_add1(SCR->C + 6); }
    __syncthreads();
#pragma unroll 1
    for (int k = (c - 128) * NTHR + threadIdx.x; k < 131072; k += P.spare * NTHR) str4(SCR->XG[0] + k, 0, 0, 0, 0);
    return;
  }
#define DONE() do {} while (0)
  const int cg = c & 7;
  if (warp < 8) {
    PROF(46);
    kgen(P, c, warp, lane);
    PROFK(1);
    bar_sync(0, 384);
#pragma unroll 1
    for (int layer = 0; layer < 2; ++layer) {
#pragma unroll 1
      for (int rho = 0; rho < 2; ++rho) {
        const int wz = warp + ((rho + layer) & P.zero);
        conv_round(wz >> 2, rho, wz & 3, lane_id());
        PROFK(6 + rho + 12 * layer);
      }
      const int z = layer & P.zero;
      attn_phase(P, c + z, (warp + z) >> 2, (warp + z) & 3, lane_id(), layer);
    }
    DONE();
  } else if (warp < 12) {
    asm volatile("setmaxnreg.dec.sync.aligned.u32 %0;" :: "n"(REG_AUX));
    aux_prologue(P, c, warp - 8, lane);
    PROF(1);
    const int c0 = c;
#pragma unroll 1
    for (int layer = 0;; ++layer) {
      const int c = c0 + (layer & P.zero), wa = warp - 8 + (layer & P.zero);
#define lane lane_id()
#define j (32 * wa + lane_id())
      uint4 x[2][2][2];
      uint32_t u[4][4];
      uprep(P, c, wa, lane, layer, x, u);
      fence_async_smem();
      bar_arrive(NB_U, NBARU);
      PROFK(5 + 12 * layer);
      bar_sync(NB_H, 192);
      box_full(j, u, P.zero);
      PROF(3 + 12 * layer);
      mbar_wait(B_Z, 0);
      conv_out(c, j, 0, x, u[0], SCR->XF[layer], P.zero);
      PROF(32);
      conv_out(c, j, 1, x, u[1], SCR->XF[layer], P.zero);
      PROF(6 + 12 * layer);
      if (layer == 0 && wa < 3) col_sums(P, c, wa, lane);
      conv_out(c, j, 2, x, u[2], SCR->XF[layer], P.zero);
      PROF(33);
      conv_out(c, j, 3, x, u[3], SCR->XF[layer], P.zero);
      PROFK(7 + 12 * layer);
      float v[2];
      zero(v);
#pragma unroll 1
      for (int h = 0; h < 2; ++h) {
        stat_part(P, c, wa, lane, layer, h, v);
        if (h) break;
        mbar_arrive1(B_AE + 4 * (wa & 2));
        if (layer == 0 && wa < 3) col_gather(P, c, wa, lane);
      }
      PROF(9 + 12 * layer);
      stat_finish(P, c, wa, lane, layer, v);
      PROF(8 + 12 * layer);
      if (layer) break;
      mbar_wait(B_ED, 0); mbar_wait(B_ED + 8, 0);
#undef lane
#undef j
    }
    DONE();
  } else {
    asm volatile("setmaxnreg.dec.sync.aligned.u32 %0;" :: "n"(REG_PROD));
    if (s2u(smem_raw) != SB) __trap();
#pragma unroll 1
    for (int n = warp - 12; n < 38; n += 4)
      asm volatile("{.reg .pred p; elect.sync _|p,0xffffffff; @p mbarrier.init.shared::cta.b64 [%0],%1;}"
                   :: "r"(SM_BAR + n * 8), "r"(n == 33 ? 4 : n > 14 ? 1 : (int)(0x322866444444444ull >> (4 * n)) & 15) : "memory");
    fence_async_smem();
    bar_sync(NB_AUX, 128);
    bar_arrive(0, 384); bar_arrive(NB_Y + 1, 256);
    PROF(1);
    if (warp == 12) {
      if (lane == 0) {
        asm volatile("prefetch.tensormap [%0];" :: "l"(&mapW) : "memory");
        asm volatile("prefetch.tensormap [%0];" :: "l"(&mapWo) : "memory");
        asm volatile("prefetch.tensormap [%0];" :: "l"(&mapX) : "memory");
      }
      nan_source(slot(12), lane);
      mbar_wait(B_U, 0);
#pragma unroll 1
      for (int k = 0; k < 8; ++k) tma2_store(&mapX, slot(12), 128 * c, 8 * k);
#pragma unroll 1
      for (int k = 0; k < 4; ++k) bulk_store(SCR->H[k >> 1] + ((c + 8) * 256 + (k & 1) * 128), slot(12), 2048);
#pragma unroll 1
      for (int k = 0; k < 8; ++k) bulk_store(SCR->O + (c * 512 + (k >> 2) * 65536 + (k & 3) * 128), slot(12), 2048);
      bulk_wait();
      mbar_arrive1(B_Z);
      PROF(24);
#pragma unroll 1
      for (int layer = 0; layer < 2; ++layer) {
        mbar_wait(B_V, layer);
        if (layer == 1 && c < 4 && ((0x47 >> lane) & 1)) str1(SCR->C + c * 32 + lane, 0);
        mbar_expect1(B_WF, 4 * 24576);
#pragma unroll
        for (int k = 0; k < 4; ++k) tma3(slot(wslot(k)), &mapW, 64 * cg, 64 * k, 0, B_WF);
        mbar_wait(B_WF, layer);
        mbar_expect1(B_W4, 2 * 24576);
#pragma unroll
        for (int k = 4; k < 6; ++k) tma3(slot(wslot(k)), &mapW, 64 * cg, 64 * k, 0, B_W4);
        bar_sync(NB_AUX, 64);
#pragma unroll 1
        for (int k = 0; k < 2; ++k) {
          mbar_expect1(B_W6 + 8 * k, 24576);
          mbar_wait(B_F + 8 * k, layer);
          tma3(slot(3 * k), &mapW, 64 * cg, 384 + 64 * k, 0, B_W6 + 8 * k);
        }
        mbar_expect1(B_WO, 65536);
        mbar_wait(B_AE + 8, layer);
        nan_source(slot(12), lane);
        uint4* fp = layer ? SCR->O + c * 512 : SCR->XF[1] + c * 512;
#pragma unroll 1
        for (int r = 7; r >= 0; --r) {
          __nanosleep(30);
          if (r >= 4) {
            bulk_store(fp + (r & 3) * 128, slot(12), 2048); bulk_store(fp + 65536 + (r & 3) * 128, slot(12), 2048);
          }
          if (r == 3) { bulk_wait(); __threadfence(); mbar_arrive1(B_N); PROF(9 + 12 * layer); }
          if (r == 1) mbar_wait(B_F + 16, layer);
          tma4(SM_WO + r * 8192, &mapWo, 64 * cg, 0, r >> 1, 32 * (r & 1), B_WO);
        }
        PROF(8 + 12 * layer);
      }
      DONE();
    } else if (warp == 13) {
      const int G = stat_group(c);
#pragma unroll 1
      for (int layer = 0; layer < 2; ++layer) {
        float z[4];
        uint2* so = opqp((uint2*)&SCR->SR[layer][lane >> 3][sr_off(G, lane)] + (lane & 1));
        if (layer == 0) {
          bar_sync(NB_P0, 192);
          const float4 a = lds4f(SM_MISC + lane * 16);
          z[0] = a.x; z[1] = a.y; z[2] = a.z; z[3] = a.w;
        } else {
          mbar_wait(B_ED + 2 * (c & 4), 0);
          uint4* ps = &SCR->PS[G * 64 + lane];
          uint4 a, b;
          for (int it = 0;; ++it) {
            a = ldr4(ps); b = ldr4(ps + 32);
            if (__all_sync(0xffffffffu, min(a.x, b.x) != 0u)) break;
            spin_guard(it);
          }
          z[0] = __uint_as_float(a.x) + __uint_as_float(b.x); z[1] = __uint_as_float(a.y) + __uint_as_float(b.y);
          z[2] = __uint_as_float(a.z) + __uint_as_float(b.z); z[3] = __uint_as_float(a.w) + __uint_as_float(b.w);
        }
#pragma unroll
        for (int o = 8; o < 32; o <<= 1)
#pragma unroll
          for (int k = 0; k < 4; ++k) z[k] += __shfl_xor_sync(0xffffffffu, z[k], o);
        const uint32_t w0 = ln_sums(z[0], z[1]), w1 = ln_sums(z[2], z[3]);
        const uint32_t r = nzmap(pack2(rcp(bfhi(w0)), rcp(bfhi(w1)))), m = pack2(z[0] * (-1.f / 512.f) * bflo(r), z[2] * (-1.f / 512.f) * bfhi(r));
        str2(so, r, m); str2(so + 4 * 1024, r, m);
        PROF(4 + 12 * layer);
        box_help(0, lane);
        PROF(6 + 12 * layer);
      }
      DONE();
    } else if (warp == 14) {
#pragma unroll 1
      for (int layer = 0; layer < 2; ++layer) {
        uint32_t* ca = opqp(SCR->C + (c >> 5) * 32 + 3 * layer);
        const uint32_t* cw = opqp(SCR->C + (lane & 3) * 32 + 3 * layer);
        const uint4* xg = opqp(SCR->XG[layer] + c * 1024);
        mbar_expect1(B_E, 16384);
        if (layer) { mbar_wait(B_N, 0); mbar_wait(B_ED, 0); mbar_wait(B_ED + 8, 0); } else bar_sync(NB_P0, 192);
        cnt_add1(ca);
        PROF(4 + 12 * layer);
        poll(cw, 32);
        mbar_arrive1(B_U);
        bulk(SM_X, xg, 16384, B_E);
        PROFK(5 + 12 * layer);
        if (layer == 0) {
          mbar_wait(B_Z, 0);
          __threadfence();
          PROF(11);
        }
#pragma unroll 1
        for (int n = 0; n < 4; ++n) {
          const int e = n & 1;
          const uint4* src = opqp(SCR->XF[layer] + (32 * e + 2 * (c >> 3) + (n >> 1)) * 2048);
          const uint32_t dst = opq(SM_A + e * A_E), b = opq(B_A + 16 * e), f = opq(n == 1 ? B_L : (n & 2 ? B_AE : B_RD) + 8 * e);
          if (n == 0) { mbar_wait(B_RD, layer); cnt_add1(ca + 1); }
          if (!e) poll(cw + 1 + (n >> 1), 32);
          if (n == 2) PROF(7 + 12 * layer);
          mbar_wait(f, layer);
          mbar_expect1(b, 8192); bulk(dst, src, 8192, b);
          mbar_expect1(b + 8, 24576); bulk(dst + 8192, src + 512, 24576, b + 8);
          bar_arrive_if(NB_AUX, 64, n == 2);
          if (!e) PROFK(6 + n + 12 * layer);
        }
#pragma unroll 1
        for (int n = 0; n < 8; ++n) mbar_expect1(B_O + 8 * n, 16384);
        if (layer == 0) poll(SCR->C + 6, P.spare);
        mbar_wait(B_QE, layer);
#pragma unroll 1
        for (int e = 0; e < 2; ++e) {
          const int J = 16 * e + (c >> 3);
          const uint32_t* fl = opqp(SCR->OF[layer] + J * 32 + lane);
          const uint4* src[4];
          uint32_t dst[4], b[4];
#pragma unroll
          for (int n = 0; n < 4; ++n) { src[n] = opqp(SCR->O + (J * 4096 + n * 1024)); dst[n] = opq(SM_O + e * O_E + 16384 * n); b[n] = opq(B_O + 32 * e + 8 * n); }
          mbar_wait(B_AT + 8 * e, layer);
          if (!e) pause(260);
          poll(fl, 1);
#pragma unroll
          for (int n = 0; n < 4; ++n) bulk(dst[n], src[n], 16384, b[n]);
          PROFK(9 + e + 12 * layer);
        }
      }
      DONE();
    }
    if (warp == 15) {
      const int G = stat_group(c);
      str4(&SCR->ST[0][(lane >> 4) * 2048 + c * 16 + (lane & 15)], 0, 0, 0, 0); str4(&SCR->ST[1][(lane >> 4) * 2048 + c * 16 + (lane & 15)], 0, 0, 0, 0);
      if (lane < 4) str4(SCR->OF[lane >> 1] + ((lane & 1) * 512 + c * 4), 0, 0, 0, 0);
      str4(&SCR->PS[G * 64 + lane], 0, 0, 0, 0); str4(&SCR->PS[G * 64 + 32 + lane], 0, 0, 0, 0);
      str4(&SCR->SR[1][lane >> 2][sr_off(G, 2 * lane)], 0, 0, 0, 0);
      if (c < 4 && lane < 3) str1(SCR->C + c * 32 + 3 + lane, 0);
#pragma unroll
      for (int k = 0; k < 3; ++k) str2((uint2*)SCR->CS + ((c >> 3) * 768 + k * 256 + 32 * cg + lane), 0, 0);
      __threadfence();
#pragma unroll 1
      for (int layer = 0; layer < 2; ++layer) {
        PROF(4 + 12 * layer);
        box_help(1, lane);
        if (layer) str4(&SCR->SR[0][lane >> 2][sr_off(G, 2 * lane)], 0, 0, 0, 0);
        uint32_t* ca = opqp(SCR->C + (c >> 5) * 32 + 3 * layer + 2);
        mbar_wait(B_RD + 8, layer);
        cnt_add1(ca);
        if (P.spare == 0) {
#pragma unroll 1
          for (int k = 0; k < 32; ++k) str4(SCR->XG[layer] + (c * 1024 + k * 32 + lane), 0, 0, 0, 0);
        }
      }
      mbar_watch(B_O + 56, 1);
    }
  }
}

typedef CUresult (*EncodeFn)(CUtensorMap*, CUtensorMapDataType, cuuint32_t, void*, const cuuint64_t*, const cuuint64_t*,
                             const cuuint32_t*, const cuuint32_t*, CUtensorMapInterleave, CUtensorMapSwizzle,
                             CUtensorMapL2promotion, CUtensorMapFloatOOBfill);

static int place_roles(uint8_t* role) {
  int dev = 0, nsm = 0;
  cudaGetDevice(&dev);
  cudaDeviceGetAttribute(&nsm, cudaDevAttrMultiProcessorCount, dev);
  if (nsm <= 128 || nsm > 144 || (nsm & 1)) return 0;
  cudaFuncSetAttribute(fused_kernel, cudaFuncAttributeNonPortableClusterSizeAllowed, 1);
  int occ[9] = {0};
  for (int k = 2; k <= 8; ++k) {
    cudaLaunchConfig_t cfg = {};
    cudaLaunchAttribute at[1];
    at[0].id = cudaLaunchAttributeClusterDimension;
    at[0].val.clusterDim.x = 2 * k; at[0].val.clusterDim.y = 1; at[0].val.clusterDim.z = 1;
    cfg.gridDim = dim3(2 * k); cfg.blockDim = dim3(NTHR); cfg.dynamicSmemBytes = SM_TOTAL; cfg.attrs = at; cfg.numAttrs = 1;
    if (cudaOccupancyMaxActiveClusters(&occ[k], fused_kernel, &cfg) != cudaSuccess) { cudaGetLastError(); occ[k] = 0; }
  }
  int n[10];
  n[7] = occ[8]; n[6] = occ[7]; n[5] = occ[6] - 0; n[4] = occ[5];
  n[3] = occ[4] - n[7]; n[1] = occ[2] - n[3] - n[5] - n[7]; n[0] = n[2] = n[1];
  n[8] = occ[3] - n[2] - n[5];
  const int ntpc = nsm / 2;
  int sum = 0;
  bool ok = n[0] > 0 && n[0] <= 8;
  for (int r = 0; r < 9; ++r) { ok = ok && n[r] >= 0 && (r == 0 || n[r] <= n[r - 1]); sum += n[r]; }
  if (!ok || sum > ntpc) { for (int r = 0; r < 9; ++r) n[r] = r < 8 ? 8 : 0; sum = 64; }
  int tp[8][9], cnt[8] = {0}, pool[72], np = 0, id = 0;
  for (int r = 0; r < 9; ++r)
    for (int g = n[0] - n[r]; g < n[0]; ++g) tp[g][cnt[g]++] = id++;
  for (; id < ntpc; ++id) pool[np++] = id;
  int order[72], no = 0;
  for (int g = 0; g < n[0]; ++g) {
    const int full = cnt[g] / 4 * 4;
    for (int k = 0; k < cnt[g]; ++k) { if (k < full) order[no++] = tp[g][k]; else pool[np++] = tp[g][k]; }
  }
  for (int k = 0; k < np; ++k) order[no++] = pool[k];
  for (int k = 0; k < ntpc; ++k) role[order[k]] = 2 * k;
  return nsm;
}

extern "C" void kernel_launch(void* const* d_in, const int* in_sizes, int n_in, void* d_out, int out_size) {
  (void)in_sizes; (void)n_in; (void)out_size;
  static EncodeFn enc = nullptr;
  static uint8_t role[72];
  static int nsm = 0;
  static Scratch* scratch = nullptr;
  if (!enc) {
    void* fn = nullptr;
    cudaDriverEntryPointQueryResult qr;
    cudaGetDriverEntryPoint("cuTensorMapEncodeTiled", &fn, cudaEnableDefault, &qr);
    enc = (EncodeFn)fn;
    cudaFuncSetAttribute(fused_kernel, cudaFuncAttributeMaxDynamicSharedMemorySize, SM_TOTAL);
    nsm = place_roles(role);
    cudaGetSymbolAddress((void**)&scratch, g_S);
  }
  CUtensorMap mW, mWo, mX;
  {
    cuuint64_t dim[3] = {512, 512, 3}, str[2] = {3072, 1024};
    cuuint32_t box[3] = {64, 64, 3}, es[3] = {1, 1, 1};
    enc(&mW, CU_TENSOR_MAP_DATA_TYPE_BFLOAT16, 3, d_in[10], dim, str, box, es, CU_TENSOR_MAP_INTERLEAVE_NONE,
        CU_TENSOR_MAP_SWIZZLE_128B, CU_TENSOR_MAP_L2_PROMOTION_NONE, CU_TENSOR_MAP_FLOAT_OOB_FILL_NONE);
  }
  {
    cuuint64_t dim[4] = {512, 2, 4, 64}, str[3] = {1024, 2048, 8192};
    cuuint32_t box[4] = {64, 2, 1, 32}, es[4] = {1, 1, 1, 1};
    enc(&mWo, CU_TENSOR_MAP_DATA_TYPE_BFLOAT16, 4, d_in[11], dim, str, box, es, CU_TENSOR_MAP_INTERLEAVE_NONE,
        CU_TENSOR_MAP_SWIZZLE_128B, CU_TENSOR_MAP_L2_PROMOTION_NONE, CU_TENSOR_MAP_FLOAT_OOB_FILL_NONE);
  }
  {
    cuuint64_t dim[2] = {16384, 64}, str[1] = {32768};
    cuuint32_t box[2] = {128, 8}, es[2] = {1, 1};
    enc(&mX, CU_TENSOR_MAP_DATA_TYPE_BFLOAT16, 2, scratch->XF[0], dim, str, box, es, CU_TENSOR_MAP_INTERLEAVE_NONE,
        CU_TENSOR_MAP_SWIZZLE_NONE, CU_TENSOR_MAP_L2_PROMOTION_NONE, CU_TENSOR_MAP_FLOAT_OOB_FILL_NONE);
  }
  Params P;
  P.x0 = (const uint16_t*)d_in[0]; P.Are = (const uint16_t*)d_in[1]; P.Aim = (const uint16_t*)d_in[2];
  P.Bre = (const uint16_t*)d_in[3]; P.Bim = (const uint16_t*)d_in[4]; P.Cre = (const uint16_t*)d_in[5];
  P.Cim = (const uint16_t*)d_in[6]; P.logdt = (const uint16_t*)d_in[7]; P.dskip = (const uint16_t*)d_in[8];
  P.wqkv = (const uint16_t*)d_in[10]; P.wo = (const uint16_t*)d_in[11]; P.out = (uint16_t*)d_out;
  for (int k = 0; k < 72; ++k) P.role[k] = role[k];
  P.zero = 0;
  P.mid = (char*)scratch->C;
  P.spare = nsm > 0 ? nsm - 128 : 0;
  fused_kernel<<<nsm > 0 ? nsm : 128, NTHR, SM_TOTAL, cudaStreamPerThread>>>(P, mW, mWo, mX);
}
```

```cpp
#include <cuda_runtime.h>
#include <cuda_bf16.h>
#include <cuda.h>
#include <stdint.h>
#include <stddef.h>

#define DEV __device__ __forceinline__
#define RARE(x) __builtin_expect(!!(x), 0)

constexpr int NTHR = 512;
constexpr int REG_MAIN = 192, REG_AUX = 96, REG_PROD = 32;
constexpr int NBARU = 384;
constexpr int SPIN_LIMIT = 1 << 22;

constexpr uint32_t SB = 1024;
__host__ __device__ constexpr uint32_t slot(int n) { return SB + n * 8192; }
__host__ __device__ constexpr int wslot(int k) { return k < 2 ? 3 * k : k < 4 ? 3 * k + 6 : k < 6 ? 21 - 3 * k : 3 * k - 18; }
constexpr uint32_t SM_A = slot(22), A_E = 0u - 32768;
constexpr uint32_t SM_O = slot(18), O_E = 0u - 147456;
constexpr uint32_t SM_WO = slot(10), SM_X = slot(8), SM_KV = slot(9) - 4096;
constexpr uint32_t SM_TAP  = slot(26);
constexpr int TAP_SZ = 3440;
constexpr uint32_t SM_STAT = SM_TAP + 4 * TAP_SZ;
constexpr uint32_t SM_CS   = SM_STAT + 1024;
constexpr uint32_t SM_MISC = SM_CS + 768;
constexpr uint32_t SM_BAR  = SM_MISC + 528;
constexpr int SM_TOTAL = SM_BAR + 304 - SB;
static_assert(SM_TOTAL <= 232448, "");
constexpr int R_SZ = 16384, R_U = 512, R_X5 = 5120, R_X3 = 8704, R_BO = 11776, R_BE = 13824;
constexpr int X_5 = 576, X_3 = 648, T_E = 2 * 720, T_O = 1600 + 2 * 721, T_C = 3390, T_K = 3424;
constexpr uint32_t B_RD = SM_BAR, B_ED = SM_BAR + 16, B_F = SM_BAR + 32, B_AT = SM_BAR + 56, B_L = SM_BAR + 264;
constexpr uint32_t B_AE = SM_BAR + 72, B_QE = SM_BAR + 88, B_ST = SM_BAR + 96, B_CS = SM_BAR + 112;
constexpr uint32_t B_WO = SM_BAR + 120, B_W6 = SM_BAR + 128, B_U = SM_BAR + 144, B_E = SM_BAR + 152, B_A = SM_BAR + 160, B_O = SM_BAR + 192,
                   B_Z = SM_BAR + 256, B_WF = SM_BAR + 272, B_W4 = SM_BAR + 280, B_N = SM_BAR + 288, B_V = SM_BAR + 296;
constexpr int NB_U = 1, NB_B = 2, NB_K = 8, NB_Y = 6, NB_WG = 8, NB_T = 10, NB_AUX = 12, NB_P0 = 13, NB_H = 15;

struct Scratch {
  uint4    XG[2][128 * 1024];
  uint4    O[32 * 8 * 512];
  uint32_t C[8 * 32];
  uint32_t OF[2][32 * 32];
  uint4    CS[16 * 1536 / 4];
  uint4    PS[128 * 64];
  uint4    ST[2][32 * 128];
  uint4    SR[2][8][512];
  uint4    XF[2][32 * 512 * 8];
  uint4    H[2][17 * 8 * 256];
};
__device__ __align__(1024) Scratch g_S;
#define SCR ((Scratch*)(P.mid - offsetof(Scratch, C)))
#define PROFD(slot, v) do {} while (0)
#define PROF(slot) do {} while (0)
#define PROFK(slot) do {} while (0)

DEV uint32_t s2u(const void* p) { return (uint32_t)__cvta_generic_to_shared(p); }
template <class T> DEV T* opqp(T* x) { asm volatile("" : "+l"(x)); return x; }
template <class T> DEV T opq(T x) { asm volatile("" : "+r"(x)); return x; }
DEV int lane_id() { int l; asm volatile("mov.u32 %0,%%laneid;" : "=r"(l)); return l; }
DEV uint32_t pack2(float lo, float hi) { uint32_t d; asm("cvt.rn.bf16x2.f32 %0,%1,%2;" : "=r"(d) : "f"(hi), "f"(lo)); return d; }
DEV float bflo(uint32_t v) { return __uint_as_float(v << 16); }
DEV float bfhi(uint32_t v) { return __uint_as_float(v & 0xFFFF0000u); }
DEV float bfr(float x) { return bflo(pack2(x, 0.f)); }
DEV uint32_t hadd2(uint32_t a, uint32_t b) { uint32_t d; asm("add.rn.bf16x2 %0,%1,%2;" : "=r"(d) : "r"(a), "r"(b)); return d; }
DEV uint32_t hsub2(uint32_t a, uint32_t b) { uint32_t d; asm("sub.rn.bf16x2 %0,%1,%2;" : "=r"(d) : "r"(a), "r"(b)); return d; }
DEV uint32_t hmul2(uint32_t a, uint32_t b) { uint32_t d; asm("mul.rn.bf16x2 %0,%1,%2;" : "=r"(d) : "r"(a), "r"(b)); return d; }
DEV uint32_t hfma2(uint32_t a, uint32_t b, uint32_t c) { uint32_t d; asm("fma.rn.bf16x2 %0,%1,%2,%3;" : "=r"(d) : "r"(a), "r"(b), "r"(c)); return d; }
DEV uint32_t hmax2(uint32_t a, uint32_t b) { uint32_t d; asm("max.bf16x2 %0,%1,%2;" : "=r"(d) : "r"(a), "r"(b)); return d; }
DEV uint32_t prmt(uint32_t a, uint32_t b, uint32_t s) { uint32_t d; asm("prmt.b32 %0,%1,%2,%3;" : "=r"(d) : "r"(a), "r"(b), "r"(s)); return d; }
DEV uint32_t nzmap(uint32_t v) { uint32_t d; asm("max.u32 %0,%1,1;" : "=r"(d) : "r"(v)); return d; }
DEV float rcp(float x) { float y; asm("rcp.approx.ftz.f32 %0,%1;" : "=f"(y) : "f"(x)); return y; }
DEV float sqrt_(float x) { float y; asm("sqrt.approx.ftz.f32 %0,%1;" : "=f"(y) : "f"(x)); return y; }
DEV float ex2(float x) { float y; asm("ex2.approx.ftz.f32 %0,%1;" : "=f"(y) : "f"(x)); return y; }

DEV uint4 ldr4(const void* p) { uint4 v; asm volatile("ld.relaxed.gpu.global.v4.u32 {%0,%1,%2,%3},[%4];" : "=r"(v.x), "=r"(v.y), "=r"(v.z), "=r"(v.w) : "l"(p) : "memory"); return v; }
DEV void ldr4_if(uint4& v, const void* p, bool c) {
  asm volatile("{.reg .pred q; setp.ne.u32 q,%5,0; @q ld.relaxed.gpu.global.v4.u32 {%0,%1,%2,%3},[%4];}"
    : "+r"(v.x), "+r"(v.y), "+r"(v.z), "+r"(v.w) : "l"(p), "r"((uint32_t)c) : "memory");
}
DEV uint2 ldr2(const void* p) { uint2 v; asm volatile("ld.relaxed.gpu.global.v2.u32 {%0,%1},[%2];" : "=r"(v.x), "=r"(v.y) : "l"(p) : "memory"); return v; }
DEV void ldr2_if(uint2& v, const void* p, bool c) {
  asm volatile("{.reg .pred q; setp.ne.u32 q,%3,0; @q ld.relaxed.gpu.global.v2.u32 {%0,%1},[%2];}" : "+r"(v.x), "+r"(v.y) : "l"(p), "r"((uint32_t)c) : "memory");
}
DEV uint32_t ldr1(const void* p) { uint32_t v; asm volatile("ld.relaxed.gpu.global.u32 %0,[%1];" : "=r"(v) : "l"(p) : "memory"); return v; }
DEV float ldnan(const uint16_t* p) {
  uint32_t v = 0xFFFFu;
#pragma unroll 1
  for (int it = 0; it < SPIN_LIMIT && __any_sync(0xffffffffu, v == 0xFFFFu); ++it) asm volatile("ld.relaxed.gpu.global.u16 %0,[%1];" : "=r"(v) : "l"(p) : "memory");
  return __uint_as_float(v << 16);
}
DEV uint4 ldw4(const void* p) { uint4 v; asm volatile("ld.global.v4.u32 {%0,%1,%2,%3},[%4];" : "=r"(v.x), "=r"(v.y), "=r"(v.z), "=r"(v.w) : "l"(p) : "memory"); return v; }
DEV uint2 ldw2(const void* p) { uint2 v; asm volatile("ld.global.v2.u32 {%0,%1},[%2];" : "=r"(v.x), "=r"(v.y) : "l"(p) : "memory"); return v; }
DEV uint32_t ldw1(const void* p) { uint32_t v; asm volatile("ld.global.u32 %0,[%1];" : "=r"(v) : "l"(p) : "memory"); return v; }
DEV void str4(void* p, uint32_t a, uint32_t b, uint32_t c, uint32_t d) { asm volatile("st.relaxed.gpu.global.v4.u32 [%0],{%1,%2,%3,%4};" :: "l"(p), "r"(a), "r"(b), "r"(c), "r"(d) : "memory"); }
DEV void str2(void* p, uint32_t a, uint32_t b) { asm volatile("st.relaxed.gpu.global.v2.u32 [%0],{%1,%2};" :: "l"(p), "r"(a), "r"(b) : "memory"); }
DEV void str1(void* p, uint32_t a) { asm volatile("st.relaxed.gpu.global.u32 [%0],%1;" :: "l"(p), "r"(a) : "memory"); }
DEV void str4_if(void* p, uint32_t a, uint32_t b, uint32_t c, uint32_t d, bool q) {
  asm volatile("{.reg .pred q; setp.ne.u32 q,%5,0; @q st.relaxed.gpu.global.v4.u32 [%0],{%1,%2,%3,%4};}" :: "l"(p), "r"(a), "r"(b), "r"(c), "r"(d), "r"((uint32_t)q) : "memory");
}
DEV void stw4(void* p, uint32_t a, uint32_t b, uint32_t c, uint32_t d) { asm volatile("st.global.v4.u32 [%0],{%1,%2,%3,%4};" :: "l"(p), "r"(a), "r"(b), "r"(c), "r"(d) : "memory"); }
DEV uint4 ldnc4(const void* p) { uint4 v; asm volatile("ld.global.nc.v4.u32 {%0,%1,%2,%3},[%4];" : "=r"(v.x), "=r"(v.y), "=r"(v.z), "=r"(v.w) : "l"(p)); return v; }
DEV uint32_t ldnc1(const void* p) { uint32_t v; asm volatile("ld.global.nc.u32 %0,[%1];" : "=r"(v) : "l"(p)); return v; }
DEV uint2 ldnc2(const void* p) { uint2 v; asm volatile("ld.global.nc.v2.u32 {%0,%1},[%2];" : "=r"(v.x), "=r"(v.y) : "l"(p)); return v; }

DEV uint2 lds2(uint32_t a) { uint2 v; asm volatile("ld.volatile.shared.v2.u32 {%0,%1},[%2];" : "=r"(v.x), "=r"(v.y) : "r"(a)); return v; }
DEV float lds16f(uint32_t a) { uint32_t v; asm volatile("ld.shared.u16 %0,[%1];" : "=r"(v) : "r"(a)); return __uint_as_float(v << 16); }
DEV void sts2(uint32_t a, uint32_t x, uint32_t y) { asm volatile("st.shared.v2.u32 [%0],{%1,%2};" :: "r"(a), "r"(x), "r"(y) : "memory"); }
DEV uint32_t lds1(uint32_t a) { uint32_t v; asm volatile("ld.volatile.shared.u32 %0,[%1];" : "=r"(v) : "r"(a)); return v; }
DEV uint32_t lds1z(uint32_t a, bool c) {
  uint32_t v; asm volatile("{.reg .pred q; setp.ne.u32 q,%2,0; mov.u32 %0,0; @q ld.volatile.shared.u32 %0,[%1];}" : "=r"(v) : "r"(a), "r"((uint32_t)c)); return v;
}
DEV uint4 lds4z(uint32_t a, bool c) {
  uint4 v = make_uint4(0, 0, 0, 0);
  asm volatile("{.reg .pred q; setp.ne.u32 q,%5,0; @q ld.volatile.shared.v4.u32 {%0,%1,%2,%3},[%4];}" : "+r"(v.x), "+r"(v.y), "+r"(v.z), "+r"(v.w) : "r"(a), "r"((uint32_t)c));
  return v;
}
DEV float lds1f(uint32_t a) { float v; asm volatile("ld.shared.f32 %0,[%1];" : "=f"(v) : "r"(a)); return v; }
DEV float2 lds2f(uint32_t a) { float2 v; asm volatile("ld.shared.v2.f32 {%0,%1},[%2];" : "=f"(v.x), "=f"(v.y) : "r"(a)); return v; }
DEV float4 lds4f(uint32_t a) { float4 v; asm volatile("ld.volatile.shared.v4.f32 {%0,%1,%2,%3},[%4];" : "=f"(v.x), "=f"(v.y), "=f"(v.z), "=f"(v.w) : "r"(a)); return v; }
DEV uint4 lds4(uint32_t a) { uint4 v; asm volatile("ld.volatile.shared.v4.u32 {%0,%1,%2,%3},[%4];" : "=r"(v.x), "=r"(v.y), "=r"(v.z), "=r"(v.w) : "r"(a)); return v; }
DEV void sts1(uint32_t a, uint32_t v) { asm volatile("st.shared.u32 [%0],%1;" :: "r"(a), "r"(v) : "memory"); }
DEV void sts16(uint32_t a, uint32_t v) { asm volatile("st.shared.u16 [%0],%1;" :: "r"(a), "r"(v) : "memory"); }
DEV void sts2f(uint32_t a, float x, float y) { asm volatile("st.shared.v2.f32 [%0],{%1,%2};" :: "r"(a), "f"(x), "f"(y) : "memory"); }
DEV void sts4f(uint32_t a, float x, float y, float z, float w) { asm volatile("st.shared.v4.f32 [%0],{%1,%2,%3,%4};" :: "r"(a), "f"(x), "f"(y), "f"(z), "f"(w) : "memory"); }
DEV void sts4(uint32_t a, uint32_t x, uint32_t y, uint32_t z, uint32_t w) { asm volatile("st.shared.v4.u32 [%0],{%1,%2,%3,%4};" :: "r"(a), "r"(x), "r"(y), "r"(z), "r"(w) : "memory"); }

DEV void ldsm4(uint32_t (&r)[4], uint32_t a) { asm volatile("ldmatrix.sync.aligned.m8n8.x4.shared.b16 {%0,%1,%2,%3},[%4];" : "=r"(r[0]), "=r"(r[1]), "=r"(r[2]), "=r"(r[3]) : "r"(a) : "memory"); }
DEV void ldsm4t(uint32_t (&r)[4], uint32_t a) { asm volatile("ldmatrix.sync.aligned.m8n8.x4.trans.shared.b16 {%0,%1,%2,%3},[%4];" : "=r"(r[0]), "=r"(r[1]), "=r"(r[2]), "=r"(r[3]) : "r"(a) : "memory"); }
DEV void ldsm2(uint32_t (&r)[2], uint32_t a) { asm volatile("ldmatrix.sync.aligned.m8n8.x2.shared.b16 {%0,%1},[%2];" : "=r"(r[0]), "=r"(r[1]) : "r"(a) : "memory"); }
DEV void stsm4(uint32_t a, uint32_t r0, uint32_t r1, uint32_t r2, uint32_t r3) { asm volatile("stmatrix.sync.aligned.m8n8.x4.shared.b16 [%0],{%1,%2,%3,%4};" :: "r"(a), "r"(r0), "r"(r1), "r"(r2), "r"(r3) : "memory"); }
DEV void stsm2(uint32_t a, uint32_t r0, uint32_t r1) { asm volatile("stmatrix.sync.aligned.m8n8.x2.shared.b16 [%0],{%1,%2};" :: "r"(a), "r"(r0), "r"(r1) : "memory"); }
DEV void stsm4t(uint32_t a, uint32_t r0, uint32_t r1, uint32_t r2, uint32_t r3) { asm volatile("stmatrix.sync.aligned.m8n8.x4.trans.shared.b16 [%0],{%1,%2,%3,%4};" :: "r"(a), "r"(r0), "r"(r1), "r"(r2), "r"(r3) : "memory"); }
DEV uint32_t movm(uint32_t a) { uint32_t d; asm volatile("movmatrix.sync.aligned.m8n8.trans.b16 %0,%1;" : "=r"(d) : "r"(a)); return d; }
DEV void mma16(float (&d)[4], uint32_t a0, uint32_t a1, uint32_t a2, uint32_t a3, uint32_t b0, uint32_t b1) {
  asm volatile("mma.sync.aligned.m16n8k16.row.col.f32.bf16.bf16.f32 {%0,%1,%2,%3},{%4,%5,%6,%7},{%8,%9},{%0,%1,%2,%3};"
    : "+f"(d[0]), "+f"(d[1]), "+f"(d[2]), "+f"(d[3]) : "r"(a0), "r"(a1), "r"(a2), "r"(a3), "r"(b0), "r"(b1));
}
DEV void mma16z(float (&d)[4], uint32_t a0, uint32_t a1, uint32_t a2, uint32_t a3, uint32_t b0, uint32_t b1) {
  asm volatile("mma.sync.aligned.m16n8k16.row.col.f32.bf16.bf16.f32 {%0,%1,%2,%3},{%4,%5,%6,%7},{%8,%9},{%10,%10,%10,%10};"
    : "=f"(d[0]), "=f"(d[1]), "=f"(d[2]), "=f"(d[3]) : "r"(a0), "r"(a1), "r"(a2), "r"(a3), "r"(b0), "r"(b1), "f"(0.f));
}
DEV void mma8(float (&d)[4], uint32_t a0, uint32_t a1, uint32_t b0) {
  asm volatile("mma.sync.aligned.m16n8k8.row.col.f32.bf16.bf16.f32 {%0,%1,%2,%3},{%4,%5},{%6},{%0,%1,%2,%3};"
    : "+f"(d[0]), "+f"(d[1]), "+f"(d[2]), "+f"(d[3]) : "r"(a0), "r"(a1), "r"(b0));
}

DEV void mma8z(float (&d)[4], uint32_t a0, uint32_t a1, uint32_t b0) {
  asm volatile("mma.sync.aligned.m16n8k8.row.col.f32.bf16.bf16.f32 {%0,%1,%2,%3},{%4,%5},{%6},{%7,%7,%7,%7};"
    : "=f"(d[0]), "=f"(d[1]), "=f"(d[2]), "=f"(d[3]) : "r"(a0), "r"(a1), "r"(b0), "f"(0.f));
}
DEV void bar_sync(int id, int n) { asm volatile("bar.sync %0,%1;" :: "r"(id), "r"(n) : "memory"); }
DEV void bar_sync_if(int id, int n, int c) { asm volatile("{.reg .pred q; setp.ne.s32 q,%2,0; @q bar.sync %0,%1;}" :: "r"(id), "r"(n), "r"(c) : "memory"); }
DEV void bar_arrive_if(int id, int n, int c) { asm volatile("{.reg .pred q; setp.ne.s32 q,%2,0; @q bar.arrive %0,%1;}" :: "r"(id), "r"(n), "r"(c) : "memory"); }
DEV bool bar_any(int id, int n, bool c) {
  uint32_t r; asm volatile("{.reg .pred p,q; setp.ne.u32 q,%3,0; bar.red.or.pred p,%1,%2,q; selp.u32 %0,1,0,p;}" : "=r"(r) : "r"(id), "r"(n), "r"((uint32_t)c) : "memory");
  return __any_sync(0xffffffffu, r);
}
DEV void bar_arrive(int id, int n) { asm volatile("bar.arrive %0,%1;" :: "r"(id), "r"(n) : "memory"); }
DEV void fence_async_glob() { asm volatile("fence.proxy.async.global;" ::: "memory"); }
DEV void fence_async_smem() { asm volatile("fence.proxy.async.shared::cta;" ::: "memory"); }
DEV void mbar_init(uint32_t b, int n) { asm volatile("mbarrier.init.shared::cta.b64 [%0],%1;" :: "r"(b), "r"(n) : "memory"); }
DEV void mbar_arrive(uint32_t b) { asm volatile("mbarrier.arrive.shared::cta.b64 _,[%0];" :: "r"(b) : "memory"); }
DEV void mbar_expect(uint32_t b, int bytes) { asm volatile("mbarrier.arrive.expect_tx.shared::cta.b64 _,[%0],%1;" :: "r"(b), "r"(bytes) : "memory"); }
DEV void mbar_wait(uint32_t b, uint32_t ph) {
  asm volatile("{\n.reg .pred p;\nW: mbarrier.try_wait.parity.shared::cta.b64 p,[%0],%1;\n@!p bra W;\n}" :: "r"(b), "r"(ph) : "memory");
}
DEV void mbar_watch(uint32_t b, uint32_t ph) {
  asm volatile("{\n.reg .pred p,q;\n.reg .u32 n;\nmov.u32 n,0;\n"
               "W: mbarrier.try_wait.parity.shared::cta.b64 p,[%0],%1;\n@p bra D;\n"
               "add.u32 n,n,1;\nsetp.lt.u32 q,n,%2;\n@q bra W;\ntrap;\nD:\n}"
               :: "r"(b), "r"(ph), "n"(SPIN_LIMIT) : "memory");
}
DEV void spin_guard(int it) { asm volatile("{.reg .pred p; setp.gt.s32 p,%0,%1; @p trap;}" :: "r"(it), "n"(SPIN_LIMIT)); }
DEV void split(uint32_t zero) {
  asm volatile("{.reg .pred p; setp.ne.u32 p,%0,0; @p trap;}" :: "r"(zero) : "memory");
}
DEV void pause(int n) {
  uint32_t t0, t; asm volatile("mov.u32 %0,%%clock;" : "=r"(t0));
  do asm volatile("mov.u32 %0,%%clock;" : "=r"(t)); while (t - t0 < n);
}
DEV void poll(const uint32_t* k, uint32_t n) {
#pragma unroll 1
  for (int it = 0;; ++it) {
    spin_guard(it);
    if (__all_sync(0xffffffffu, ldr1(k) >= n)) break;
  }
}
DEV void mbar_arrive1(uint32_t b) { asm volatile("{.reg .pred p; elect.sync _|p,0xffffffff; @p mbarrier.arrive.shared::cta.b64 _,[%0];}" :: "r"(b) : "memory"); }
DEV void mbar_arrive1_if(uint32_t b, int c) {
  asm volatile("{.reg .pred p,q; setp.ne.s32 q,%1,0; elect.sync _|p,0xffffffff; and.pred p,p,q; @p mbarrier.arrive.shared::cta.b64 _,[%0];}" :: "r"(b), "r"(c) : "memory");
}
DEV void mbar_expect1(uint32_t b, int bytes) { asm volatile("{.reg .pred p; elect.sync _|p,0xffffffff; @p mbarrier.arrive.expect_tx.shared::cta.b64 _,[%0],%1;}" :: "r"(b), "r"(bytes) : "memory"); }
DEV void cnt_add1(uint32_t* q) { asm volatile("{.reg .pred p; elect.sync _|p,0xffffffff; @p red.relaxed.gpu.global.add.u32 [%0],1;}" :: "l"(q) : "memory"); }
DEV void tma4(uint32_t dst, const CUtensorMap* m, int c0, int c1, int c2, int c3, uint32_t bar) {
  asm volatile("{.reg .pred p; elect.sync _|p,0xffffffff;\n"
    "@p cp.async.bulk.tensor.4d.shared::cluster.global.mbarrier::complete_tx::bytes [%0],[%1,{%2,%3,%4,%5}],[%6];}"
    :: "r"(dst), "l"(m), "r"(c0), "r"(c1), "r"(c2), "r"(c3), "r"(bar) : "memory");
}
DEV void tma3(uint32_t dst, const CUtensorMap* m, int c0, int c1, int c2, uint32_t bar) {
  asm volatile("{.reg .pred p; elect.sync _|p,0xffffffff;\n"
    "@p cp.async.bulk.tensor.3d.shared::cluster.global.mbarrier::complete_tx::bytes [%0],[%1,{%2,%3,%4}],[%5];}"
    :: "r"(dst), "l"(m), "r"(c0), "r"(c1), "r"(c2), "r"(bar) : "memory");
}
DEV void bulk(uint32_t dst, const void* src, int bytes, uint32_t bar) {
  asm volatile("{.reg .pred p; elect.sync _|p,0xffffffff;\n@p cp.async.bulk.shared::cluster.global.mbarrier::complete_tx::bytes [%0],[%1],%2,[%3];}" :: "r"(dst), "l"(src), "r"(bytes), "r"(bar) : "memory");
}

DEV void bulk_store(void* dst, uint32_t src, int bytes) {
  asm volatile("{.reg .pred p; elect.sync _|p,0xffffffff;\n@p cp.async.bulk.global.shared::cta.bulk_group [%0],[%1],%2;}" :: "l"(dst), "r"(src), "r"(bytes) : "memory");
}
DEV void tma2_store(const CUtensorMap* m, uint32_t src, int c0, int c1) {
  asm volatile("{.reg .pred p; elect.sync _|p,0xffffffff;\n@p cp.async.bulk.tensor.2d.global.shared::cta.bulk_group [%0,{%2,%3}],[%1];}" :: "l"(m), "r"(src), "r"(c0), "r"(c1) : "memory");
}
DEV void bulk_wait() { asm volatile("cp.async.bulk.commit_group;\ncp.async.bulk.wait_group 0;\nfence.proxy.async.global;" ::: "memory"); }

DEV uint32_t dlo(uint32_t addr, uint32_t lbo) { return __shfl_sync(0xffffffffu, (addr >> 4) | ((lbo >> 4) << 16), 0); }
__host__ __device__ constexpr uint32_t dhi(uint32_t sbo, uint32_t swz) { return (sbo >> 4) | (swz << 30); }
DEV void wg_fence() { asm volatile("wgmma.fence.sync.aligned;" ::: "memory"); }
DEV void wg_commit() { asm volatile("wgmma.commit_group.sync.aligned;" ::: "memory"); }
template <int N> DEV void wg_wait() { asm volatile("wgmma.wait_group.sync.aligned %0;" :: "n"(N) : "memory"); }
template <int N> DEV void zero(float (&d)[N]) {
#pragma unroll
  for (int i = 0; i < N; ++i) d[i] = 0.f;
}
template <int N> DEV void zerov(float (&d)[N]) {
#pragma unroll
  for (int i = 0; i < N; ++i) asm volatile("mov.b32 %0,0;" : "=f"(d[i]));
}
template <int N> DEV void undef(float (&d)[N]) {
#pragma unroll
  for (int i = 0; i < N; ++i) asm volatile("" : "=f"(d[i]));
}
#define R4(d, o) "+f"(d[o]), "+f"(d[o + 1]), "+f"(d[o + 2]), "+f"(d[o + 3])
#define R8(d, o) R4(d, o), R4(d, o + 4)
#define R16(d, o) R8(d, o), R8(d, o + 8)
template <int ACC> DEV void wg_rs64k(float (&d)[32], const uint32_t (&a)[4], uint32_t db) {
  asm volatile("{.reg .pred p; .reg .b64 b; setp.ne.s32 p,%38,0; mov.b64 b,{%36,%37};\n"
    "wgmma.mma_async.sync.aligned.m64n64k16.f32.bf16.bf16 {%0,%1,%2,%3,%4,%5,%6,%7,%8,%9,%10,%11,%12,%13,%14,%15,%16,%17,%18,%19,%20,%21,%22,%23,%24,%25,%26,%27,%28,%29,%30,%31},{%32,%33,%34,%35},b,p,1,1,0;}"
    : R16(d, 0), R16(d, 16) : "r"(a[0]), "r"(a[1]), "r"(a[2]), "r"(a[3]), "r"(db), "n"(dhi(512, 2)), "n"(ACC));
}
template <int ACC> DEV void wg_rs48t(float (&d)[24], const uint32_t (&a)[4], uint32_t db) {
  asm volatile("{.reg .pred p; .reg .b64 b; setp.ne.s32 p,%30,0; mov.b64 b,{%28,%29};\n"
    "wgmma.mma_async.sync.aligned.m64n48k16.f32.bf16.bf16 {%0,%1,%2,%3,%4,%5,%6,%7,%8,%9,%10,%11,%12,%13,%14,%15,%16,%17,%18,%19,%20,%21,%22,%23},{%24,%25,%26,%27},b,p,1,1,1;}"
    : R16(d, 0), R8(d, 16) : "r"(a[0]), "r"(a[1]), "r"(a[2]), "r"(a[3]), "r"(db), "n"(dhi(512, 0)), "n"(ACC));
}
template <int ACC> DEV void wg_rs32t(float (&d)[16], const uint32_t (&a)[4], uint32_t db) {
  asm volatile("{.reg .pred p; .reg .b64 b; setp.ne.s32 p,%22,0; mov.b64 b,{%20,%21};\n"
    "wgmma.mma_async.sync.aligned.m64n32k16.f32.bf16.bf16 {%0,%1,%2,%3,%4,%5,%6,%7,%8,%9,%10,%11,%12,%13,%14,%15},{%16,%17,%18,%19},b,p,1,1,1;}"
    : R16(d, 0) : "r"(a[0]), "r"(a[1]), "r"(a[2]), "r"(a[3]), "r"(db), "n"(dhi(1024, 0)), "n"(ACC));
}
template <int ACC> DEV void wg_ss192(float (&d)[96], uint32_t da, uint32_t db) {
  asm volatile("{.reg .pred p; .reg .b64 a,b; setp.ne.s32 p,%100,0; mov.b64 a,{%96,%98}; mov.b64 b,{%97,%99};\n"
    "wgmma.mma_async.sync.aligned.m64n192k16.f32.bf16.bf16 {"
    "%0,%1,%2,%3,%4,%5,%6,%7,%8,%9,%10,%11,%12,%13,%14,%15,%16,%17,%18,%19,%20,%21,%22,%23,%24,%25,%26,%27,%28,%29,%30,%31,"
    "%32,%33,%34,%35,%36,%37,%38,%39,%40,%41,%42,%43,%44,%45,%46,%47,%48,%49,%50,%51,%52,%53,%54,%55,%56,%57,%58,%59,%60,%61,%62,%63,"
    "%64,%65,%66,%67,%68,%69,%70,%71,%72,%73,%74,%75,%76,%77,%78,%79,%80,%81,%82,%83,%84,%85,%86,%87,%88,%89,%90,%91,%92,%93,%94,%95},a,b,p,1,1,1,1;}"
    : R16(d, 0), R16(d, 16), R16(d, 32), R16(d, 48), R16(d, 64), R16(d, 80) : "r"(da), "r"(db), "n"(dhi(1024, 1)), "n"(dhi(1024, 1)), "n"(ACC));
}
template <int ACC> DEV void wg_ss64(float (&d)[32], uint32_t da, uint32_t db) {
  asm volatile("{.reg .pred p; .reg .b64 a,b; setp.ne.s32 p,%36,0; mov.b64 a,{%32,%34}; mov.b64 b,{%33,%35};\n"
    "wgmma.mma_async.sync.aligned.m64n64k16.f32.bf16.bf16 {"
    "%0,%1,%2,%3,%4,%5,%6,%7,%8,%9,%10,%11,%12,%13,%14,%15,%16,%17,%18,%19,%20,%21,%22,%23,%24,%25,%26,%27,%28,%29,%30,%31},a,b,p,1,1,0,1;}"
    : R16(d, 0), R16(d, 16) : "r"(da), "r"(db), "n"(dhi(1024, 0)), "n"(dhi(1024, 1)), "n"(ACC));
}

DEV uint32_t cpy(uint32_t v, uint32_t id) {
  uint32_t d; asm volatile("prmt.b32 %0,%1,%1,%2;" : "=r"(d) : "r"(v), "r"(id)); return d;
}
struct Params {
  uint32_t zero, spare;
  char* mid;
  const uint16_t *x0, *Are, *Aim, *Bre, *Bim, *Cre, *Cim, *logdt, *dskip, *wqkv, *wo;
  uint16_t* out;
  uint8_t role[72];
};

DEV uint32_t ln_word(float mean, float var) {
  float v = bfr(var);
  float s = sqrt_(bfr(v + 1e-5f));
  return pack2(mean, s);
}

DEV int stat_group(int c) { return c ^ 4; }
DEV int xg_off(int G, int g) { return (G >> 6) * 1024 + (G & 63) * 8 + (g ^ (G & 2)); }
DEV int sr_off(int G, int g) { return (G >> 6) * 256 + (g & 2) * 64 + 2 * (G & 63) + ((g >> 2) & 1); }
DEV uint32_t region(int chl) { return SM_A + (chl >> 1) * A_E + (chl & 1) * R_SZ; }
template <bool FIRST> DEV void gram(float (&s)[4], float (&q0)[4], float (&q1)[4], uint32_t a0, uint32_t a1, uint32_t a2, uint32_t a3) {
  const uint32_t one = 0x3F803F80u;
  if (FIRST) { mma16z(s, a0, a1, a2, a3, one, one); mma8z(q0, a0, a1, a0); mma8z(q1, a0, a1, a1); }
  else { mma16(s, a0, a1, a2, a3, one, one); mma8(q0, a0, a1, a0); mma8(q1, a0, a1, a1); }
  mma8(q0, a2, a3, a2); mma8(q1, a2, a3, a3);
}
DEV uint32_t ln_sums(float s, float q) { const float m = s * (1.f / 512.f); return ln_word(m, fmaxf(q * (1.f / 512.f) - m * m, 0.f)); }
DEV void cmul(float& orr, float& oi, float ar, float ai, float br, float bi) {
  float r = ar * br - ai * bi, i = ar * bi + ai * br; orr = r; oi = i;
}
DEV void cexp_(float al, float bt, float s, float& er, float& ei) {
  float mag = ex2(al * s), ph = bt * s;
  ph -= rintf(ph);
  float ang = ph * 6.283185307179586f;
  er = mag * __cosf(ang); ei = mag * __sinf(ang);
}

DEV void kgen(const Params& P, int c, int wm, int lane) {
  const int chl = wm >> 1, mh = wm & 1, g = lane >> 2, t = lane & 3;
  const int ch = 256 * (chl >> 1) + 2 * c + (chl & 1);
  const int mo = ch * 64 + mh * 32 + lane;
  const uint32_t vAr = ldw1((const uint32_t*)P.Are + mo), vAi = ldw1((const uint32_t*)P.Aim + mo);
  const uint32_t vBr = ldw1((const uint32_t*)P.Bre + mo), vBi = ldw1((const uint32_t*)P.Bim + mo);
  const uint32_t vCr = ldw1((const uint32_t*)P.Cre + mo), vCi = ldw1((const uint32_t*)P.Cim + mo);
  const uint32_t vld = ldw1((const uint32_t*)P.logdt + (ch >> 1)), vds = ldw1((const uint32_t*)P.dskip + (ch >> 1));
  bar_arrive(NB_Y, 384);
  PROF(45);
  {
    const uint32_t tz = SM_TAP + chl * TAP_SZ + (mh * 32 + lane) * 16;
#pragma unroll
    for (int k = 0; k < 3; ++k) sts4(tz + k * 1024, 0, 0, 0, 0);
    static_assert(TAP_SZ > 3072 && TAP_SZ <= 4096, "");
    if (mh * 32 + lane < TAP_SZ / 16 - 192) sts4(tz + 3072, 0, 0, 0, 0);
  }
  const uint32_t tb = slot(wm), tw = opq(tb + lane * 4);
  const uint32_t aa = opq(tb + (lane & 15) * 144 + (lane >> 4) * 16), ba = opq(tb + (16 + (lane & 7)) * 144 + (lane >> 3) * 16);
  float acc[5][4], k2048 = 0.f;
#pragma unroll
  for (int i = 0; i < 5; ++i) zerov(acc[i]);
  sts1(tw, 0x3F80u);
  asm volatile("setmaxnreg.inc.sync.aligned.u32 %0;" :: "n"(REG_MAIN));
  PROF(44);
  const float dt = bfr(ex2((ch & 1 ? bfhi(vld) : bflo(vld)) * 1.4426950408889634f));
#pragma unroll 1
  for (int r = 0; r < 2; ++r) {
    const uint32_t sel = r ? 0x3244 : 0x1044;
    const float are = __uint_as_float(prmt(vAr, 0, sel)), aim = __uint_as_float(prmt(vAi, 0, sel)), bre = __uint_as_float(prmt(vBr, 0, sel));
    const float bim = __uint_as_float(prmt(vBi, 0, sel)), cre = __uint_as_float(prmt(vCr, 0, sel)), cim = __uint_as_float(prmt(vCi, 0, sel));
    const float al = dt * are * 1.4426950408889634f, bt = dt * aim * 0.15915494309189535f;
    float qr, qi; cmul(qr, qi, cre, cim, dt * bre, dt * bim);
    if (r == 0) PROFD(2, __float_as_uint(qr + al + bt));
    float er[3], ei[3], e8r, e8i, eLr, eLi;
    cexp_(al, bt, 1.f, er[0], ei[0]); cexp_(al, -bt, 8.f, e8r, e8i); cexp_(al, bt, 128.f, eLr, eLi);
    cmul(er[1], ei[1], er[0], ei[0], er[0], ei[0]); cmul(er[2], ei[2], er[1], ei[1], er[1], ei[1]);
    float yr = e8r, yi = e8i;
#pragma unroll
    for (int a = 0; a < 16; ++a) {
      if (a) sts1(tw + a * 144, pack2(yr, yi));
      if (a && a < 15) cmul(yr, yi, yr, yi, e8r, e8i);
      const int ls = a < 2 ? 0 : a < 4 ? 1 : a < 8 ? 2 : 3;
      const int row0 = 16 + (a < 2 ? 8 * a : a < 4 ? 16 + 4 * (a - 2) : a < 8 ? 24 + 2 * (a - 4) : 32 + (a - 8));
      float xr[8], xi[8];
      xr[0] = qr; xi[0] = qi;
#pragma unroll
      for (int k = 0; k < (8 >> ls); ++k) {
        const int hb = k >= 4 ? 2 : k >= 2 ? 1 : 0;
        if (k) cmul(xr[k], xi[k], xr[k - (1 << hb)], xi[k - (1 << hb)], er[(ls + hb) % 3], ei[(ls + hb) % 3]);
        sts1(tw + (row0 + k) * 144, pack2(xr[k], xi[k]));
      }
      cmul(qr, qi, qr, qi, eLr, eLi);
    }
    __syncwarp();
    if (r == 0) PROF(3);
#pragma unroll
    for (int kp = 0; kp < 2; ++kp) {
      uint32_t a0[4], a1[4];
      ldsm4(a0, aa + kp * 64); ldsm4(a1, aa + kp * 64 + 32);
#pragma unroll
      for (int tl = 0; tl < 5; ++tl) {
        uint32_t b[4];
        ldsm4(b, ba + 8 * tl * 144 + kp * 64);
        if (kp == 0) qr += __shfl_xor_sync(0xffffffffu, qr, 1 << tl);
        mma16(acc[tl], a0[0], a0[1], a0[2], a0[3], b[0], b[1]);
        mma16(acc[tl], a1[0], a1[1], a1[2], a1[3], b[2], b[3]);
      }
    }
    k2048 += qr;
    __syncwarp();
  }
  const uint32_t xa = tb + lane * 16, ob = xa ^ 8192, tp = SM_TAP + chl * TAP_SZ;
  if (mh == 0) {
    sts4f(xa, acc[2][0], acc[2][1], acc[2][2], acc[2][3]);
    sts4f(xa + 512, acc[3][0], acc[3][1], acc[3][2], acc[3][3]);
    sts1(tb + 1024, __float_as_uint(k2048));
  } else {
    sts4f(xa, acc[0][0], acc[0][1], acc[0][2], acc[0][3]);
    sts4f(xa + 512, acc[1][0], acc[1][1], acc[1][2], acc[1][3]);
    sts4f(xa + 1024, acc[4][0], acc[4][1], acc[4][2], acc[4][3]);
  }
  PROF(4);
  bar_sync(NB_K + chl, 64);
  float4 o[3];
#pragma unroll
  for (int k = 0; k < 3; ++k) o[k] = lds4f(ob + k * 512);
  if (mh == 0) {
    if (lane == 0) o[0].x += ch & 1 ? bfhi(vds) : bflo(vds);
    const uint32_t a = tp - 2 * (8 * g + 2 * t + 1);
#pragma unroll
    for (int z = 0; z < 4; ++z) {
      const float* k = acc[z >> 1] + 2 * (z & 1);
      const uint32_t v = z & 1 ? pack2(k[1] + o[z >> 1].w, k[0] + o[z >> 1].z) : pack2(k[1] + o[z >> 1].y, k[0] + o[z >> 1].x);
      sts1(a + T_O - 128 * z, v); sts16(a + T_E - 128 * z, v); sts16(a + T_E + 2 - 128 * z, v >> 16);
    }
    const uint32_t v0 = pack2(acc[4][0] + o[2].x, acc[4][1] + o[2].y), v1 = pack2(acc[4][2] + o[2].z, acc[4][3] + o[2].w);
    const uint32_t b = tp + T_C - 2 * (32 * t + g - 1);
    if (lane == 0) { sts16(tp + T_E - 2 * (X_5 + 63), v0); sts16(tp + T_O - 2 * (X_5 + 63), v0); sts1(tp + T_K, prmt(v0, v0, 0x1010)); }
    else sts16(b, v0);
    sts16(b - 32, v0 >> 16); sts16(b - 16, v1); sts16(b - 48, v1 >> 16);
  } else {
    const uint32_t a = tp - 2 * (256 + 128 * (t >> 1) + 4 * (t & 1) + 8 * g);
#pragma unroll
    for (int z = 0; z < 2; ++z) {
      const uint32_t v = z ? pack2(acc[2][3] + o[0].w, acc[2][2] + o[0].z) : pack2(acc[2][1] + o[0].y, acc[2][0] + o[0].x), d = prmt(v, v, 0x3232);
      sts1(a + T_E - 4 - 128 * z, v); sts16(a + T_O - 4 - 128 * z, v); sts1(a + T_O - 2 - 128 * z, d);
      if (z || lane) { sts1(a + T_E - 128 * z, d); sts16(a + T_O + 2 - 128 * z, d); } else sts16(a + T_E, d);
    }
    const uint32_t w0 = pack2(acc[3][0] + o[1].x, acc[3][1] + o[1].y), w1 = pack2(acc[3][2] + o[1].z, acc[3][3] + o[1].w);
    const uint32_t b = tp - 2 * (16 * t + g);
    if (lane == 0) {
      const uint32_t k = prmt(w0, w0, 0x1010);
      sts1(tp + T_E - 2 * 514, k); sts1(tp + T_E - 2 * 512, k);
      sts16(tp + T_O - 2 * 514, k); sts1(tp + T_O - 2 * 513, k); sts16(tp + T_O - 2 * 511, k);
      sts16(tp + T_C - 2 * 127, pack2(k2048 + o[2].x, 0.f));
    } else { sts16(b + T_E - 2 * (X_5 - 1), w0); sts16(b + T_O - 2 * (X_5 - 1), w0); }
    sts16(b + T_E - 2 * X_3, w0 >> 16); sts16(b + T_O - 2 * X_3, w0 >> 16);
    sts16(b + T_E - 2 * (X_5 + 7), w1); sts16(b + T_O - 2 * (X_5 + 7), w1);
    sts16(b + T_E - 2 * (X_3 + 8), w1 >> 16); sts16(b + T_O - 2 * (X_3 + 8), w1 >> 16);
  }
}

DEV bool bad8(const uint4& v) { return min(v.x, v.z) == 0u; }
DEV uint32_t uchunk(uint32_t reg, int x) { return reg + R_U + (x ^ ((x >> 3) & 3)) * 16; }
DEV uint32_t& xword(uint4 (&x)[2], int e, int tp) { uint4& v = x[tp >> 1]; return tp & 1 ? (e ? v.w : v.z) : (e ? v.y : v.x); }

DEV void uprep(const Params& P, int c, int wa, int lane, int layer, uint4 (&x)[2][2][2], uint32_t (&u)[4][4]) {
  const int j = 32 * wa + lane, o0 = 2 * j + ((j >> 2) & 1);
  {
    const uint32_t za = region(wa) + lane * 16 - 512;
    sts4(za + R_U, 0, 0, 0, 0); sts4(za + R_X5, 0, 0, 0, 0); sts4(za + R_X3, 0, 0, 0, 0);
    sts4(region(wa) + R_BE, 0, 0, 0, 0);
  }
  const uint4* st = opqp(&SCR->SR[layer][c >> 4][j]);
  const uint32_t xa = opq(SM_X + 16 * o0), xb = opq(SM_X + 16 * (o0 ^ 1)), ua = opq(uchunk(0, j));
  uint4 s[2][2];
#pragma unroll
  for (int z = 0; z < 12; ++z) {
    uint4& v = z < 8 ? x[(z >> 2) & 1][(z >> 1) & 1][z & 1] : s[(z >> 1) & 1][z & 1];
    asm volatile("mov.b32 %0,0; mov.b32 %1,0; mov.b32 %2,0; mov.b32 %3,0;" : "=r"(v.x), "=r"(v.y), "=r"(v.z), "=r"(v.w));
  }
#pragma unroll 1
  for (uint32_t it = P.zero;; ++it) {
    if (it) {
      spin_guard(it);
#pragma unroll
      for (int z = 0; z < 4; ++z) { uint4& v = s[z >> 1][z & 1]; ldr4_if(v, st + z * 128, bad8(v)); }
      const uint4* xp = &SCR->XG[layer][c * 1024 + o0];
#pragma unroll
      for (int z = 0; z < 8; ++z) {
        uint4& v = x[z >> 2][(z >> 1) & 1][z & 1];
        ldr4_if(v, (const uint4*)((uintptr_t)xp ^ (16 * (z & 1))) + (z >> 1) * 256, bad8(v));
      }
    } else {
      mbar_wait(B_U, layer);
      PROF(layer ? 25 : 10);
#pragma unroll
      for (int z = 0; z < 4; ++z) s[z >> 1][z & 1] = ldr4(st + z * 128);
#pragma unroll
      for (int z = 0; z < 4; ++z) { uint4& v = s[z >> 1][z & 1]; ldr4_if(v, st + z * 128, bad8(v)); }
      PROF(layer ? 26 : 11);
      mbar_wait(B_E, layer);
#pragma unroll
      for (int z = 7; z >= 0; --z) x[z >> 2][(z >> 1) & 1][z & 1] = lds4((z & 1 ? xb : xa) + (z >> 1) * 4096);
      PROF(layer ? 27 : 14);
    }
    uint32_t m = ~0u;
#pragma unroll
    for (int z = 7; z >= 0; --z) {
      const int k = z >> 2, chl = z & 3;
#pragma unroll
      for (int tp = 0; tp < 4; ++tp) u[chl][tp] = hfma2(xword(x[k][chl >> 1], chl & 1, tp), xword(s[k], 0, tp), xword(s[k], 1, tp));
      sts4(ua + region(chl) + k * 2048, u[chl][0], u[chl][1], u[chl][2], u[chl][3]);
      const uint4& v = x[k][chl >> 1][chl & 1];
      m = min(m, min(v.x, v.z));
      if (z < 4) m = min(m, min(s[z >> 1][z & 1].x, s[z >> 1][z & 1].z));
    }
    if (!__any_sync(0xffffffffu, m == 0)) break;
  }
  PROF(4 + 12 * layer);
}

template <bool FULL> DEV void box_unit(uint32_t reg, int s, const uint2& a, const uint4& b, const uint32_t (&d)[4], uint32_t (&pv)[4]) {
  const uint32_t u[9] = {a.x, a.y, b.x, b.y, b.z, b.w, d[0], d[1], d[2]};
  uint32_t v[8], p[8];
#pragma unroll
  for (int j = 0; j < 8; ++j) { v[j] = prmt(u[j], u[j + 1], 0x5432); p[j] = hadd2(u[j], v[j]); }
  const uint32_t o = reg + s * 16;
  uint32_t x[4], y[4];
#pragma unroll
  for (int j = 0; j < 4; ++j) { x[j] = hadd2(hadd2(p[1 + j], p[2 + j]), u[3 + j]); y[j] = hadd2(v[3 + j], p[4 + j]); pv[j] = p[4 + j]; }
  sts4(o + R_X5, x[0], x[1], x[2], x[3]);
  sts4(o + R_X3, y[0], y[1], y[2], y[3]);
  if (FULL) {
#pragma unroll
    for (int j = 0; j < 4; ++j) { y[j] = hadd2(hadd2(v[j], v[3 + j]), x[j]); x[j] = hadd2(hadd2(u[j], u[4 + j]), y[j]); }
    const bool od = s & 1;
    sts4(o + R_BO, od ? y[0] : x[0], od ? y[1] : x[1], od ? y[2] : x[2], od ? y[3] : x[3]);
    sts4(o + R_BE + 16, od ? x[0] : y[0], od ? x[1] : y[1], od ? x[2] : y[2], od ? x[3] : y[3]);
  }
}
DEV void box_full(int j, uint32_t (&u)[4][4], uint32_t zero) {
  const uint32_t a2 = uchunk(8, j - 2), a1 = uchunk(0, j - 1);
  uint2 a[4]; uint4 b[4];
#define HALO(n) { a[n] = lds2(region(n) + a2); b[n] = lds4(region(n) + a1); }
  HALO(0) HALO(1)
  split(zero);
#pragma unroll
  for (int chl = 0; chl < 4; ++chl) {
    const uint32_t d[4] = {u[chl][0], u[chl][1], u[chl][2], u[chl][3]};
    box_unit<true>(region(chl), j, a[chl], b[chl], d, u[chl]);
    if (chl < 2) HALO(chl + 2)
    if (chl != 2) {
      fence_async_smem();
      if (chl == 3) bar_arrive(NB_B + 2, 288);
      bar_arrive(NB_B + chl, 288);
    }
    if (chl == 0) PROF(31);
  }
#undef HALO
}
DEV void box_help(int e, int lane) {
  bar_sync(NB_H, 192);
#pragma unroll 1
  for (int n = 0; n < 4; ++n) {
    const int chl = e + (n & 2), s = 128 + 32 * (n & 1) + lane;
    const uint32_t reg = region(chl);
    const uint4 d = lds4(uchunk(reg, s));
    const uint32_t u[4] = {d.x, d.y, d.z, d.w};
    uint32_t v[4];
    box_unit<false>(reg, s, lds2(uchunk(reg, s - 2) + 8), lds4(uchunk(reg, s - 1)), u, v);
    if (n & 1) { fence_async_smem(); bar_arrive(NB_B + chl, 288); }
  }
}

DEV uint4 hadd8(const uint4& a, const uint4& b) { return make_uint4(hadd2(a.x, b.x), hadd2(a.y, b.y), hadd2(a.z, b.z), hadd2(a.w, b.w)); }
DEV void conv_out(int c, int j, int chl, uint4 (&x)[2][2][2], const uint32_t (&v)[4], uint4* XF, uint32_t zero) {
  const int rho = chl >> 1, e = chl & 1;
  const uint32_t ua = uchunk(region(chl), j), fa = region(chl) + R_X5 + j * 16, ha = region(chl) + R_X3 + (j & 1) * 1088 + (j >> 1) * 16;
  const int m8 = ((j & 4) + ((j >> 1) & 1) + 2 * (j & 1)) ^ ((2 * c + e) & 7);
  uint4* xo = XF + (((16 - 2 * (j & 8) + (j >> 4)) * 512 + 256 * rho + 2 * c + e) * 8 + m8);
  bar_sync(NB_Y + e + 7 * rho, 256);
  uint4 y[2], f[2], h[2];
#pragma unroll
  for (int k = 0; k < 2; ++k) {
    y[k] = lds4(ua + k * 2048);
    f[k] = lds4z(ua + k * 2048 + R_BO - R_U, k || j >= 36);
    h[k] = lds4z(fa + k * 2048 - 1024, k || j >= 64);
  }
  const uint32_t q = lds1(SM_TAP + chl * TAP_SZ + T_K);
  const uint4 r = lds4(ha);
  split(zero);
  if (chl == 3) mbar_arrive1(B_L + (r.x & zero));
  h[1] = hadd8(h[1], make_uint4(hfma2(q, v[0], r.x), hfma2(q, v[1], r.y), hfma2(q, v[2], r.z), hfma2(q, v[3], r.w)));
#pragma unroll
  for (int k = 0; k < 2; ++k) {
    const uint4 o = hadd8(hadd8(y[k], hadd8(f[k], h[k])), make_uint4(xword(x[k][rho], e, 0), xword(x[k][rho], e, 1), xword(x[k][rho], e, 2), xword(x[k][rho], e, 3)));
    const uint32_t keep = j & 1 ? 0x7632 : 0x5410, k0 = prmt(o.x, o.y, keep), k1 = prmt(o.z, o.w, keep);
    const uint32_t g0 = __shfl_xor_sync(0xffffffffu, prmt(o.x, o.y, keep ^ 0x2222), 1), g1 = __shfl_xor_sync(0xffffffffu, prmt(o.z, o.w, keep ^ 0x2222), 1);
    str4(xo + k * 32768, j & 1 ? g0 : k0, j & 1 ? g1 : k1, j & 1 ? k0 : g0, j & 1 ? k1 : g1);

  }
  if (e) { __syncwarp(); mbar_arrive1(B_RD + rho * 8); }
}

DEV void conv_round(int e, int rho, int w, int lane) {
  const int g = lane >> 2, t = lane & 3, chl = 2 * rho + e;
  const uint32_t reg = region(chl), tp = SM_TAP + chl * TAP_SZ, dr = dlo(reg, 128);
  const uint32_t g0 = tp + ((g & 1) ? T_O : T_E) + 2 * (2 * t - g) - 16;
  const uint32_t ga = g0 - 32 * (w & 1) - 576 * (w >> 1), id = opq(0x3210u);
  float acc[32], f1[24], f2[16];
  uint32_t q[12][4];
  {
    uint32_t qn[18][4];
    qn[0][2] = lds1(ga + 64);
#pragma unroll
    for (int n = 0; n < 18; ++n) {
      const bool nz = n < 15 || w < 2 || (n == 15 && w == 2);
      qn[n][0] = n < 15 ? lds1(ga + 48 - 32 * n) : lds1z(ga + 48 - 32 * n, nz);
      qn[n][1] = n < 15 ? lds1(ga + 32 - 32 * n) : lds1z(ga + 32 - 32 * n, nz);
    }
#pragma unroll
    for (int n = 0; n < 18; ++n) { qn[n][3] = cpy(qn[n][0], id); if (n) qn[n][2] = cpy(qn[n - 1][1], id); }
#pragma unroll
    for (int n = 0; n < 8; ++n) {
      const int i = n & 3;
      const uint32_t a = g0 + 16 - 16 * w - 2 * (n < 4 ? X_5 : X_3) + 16 * i;
      uint32_t (&q1)[4] = q[(n & 4) + (i >> 1)], (&q2)[4] = q[(n & 4) + 2 + (i >> 1)];
      q1[2 * (i & 1)] = lds1z(a, i <= w); q1[2 * (i & 1) + 1] = lds1(a - 64);
      q2[2 * (i & 1)] = cpy(0, id); q2[2 * (i & 1) + 1] = lds1z(a - 128, i >= w);
    }
    const uint32_t gc = tp + T_C - 2 + 4 * (t - g - 8 * w);
#pragma unroll
    for (int kk = 0; kk < 4; ++kk) {
      q[8 + kk][0] = lds1z(gc + 32 * kk, w >= kk); q[8 + kk][2] = lds1z(gc + 32 * kk + 16, w >= kk);
      q[8 + kk][1] = lds1(gc + 32 * kk - 128); q[8 + kk][3] = lds1(gc + 32 * kk - 112);
    }
    PROFD(rho ? 43 : 47, qn[17][2] ^ q[11][3]);
    bar_sync_if(NB_U, NBARU, 1 - rho);
    mbar_arrive1_if(B_V, chl == 1 && w == 0);
    bar_sync_if(NB_T + 1 - e, 256, chl);
    const uint32_t db = dr + (R_U + 32) / 16;
    undef(acc);
    wg_fence();
#pragma unroll
    for (int n = 0; n < 18; ++n) {
      if (n) wg_rs64k<1>(acc, qn[n], db - 2 * n); else wg_rs64k<0>(acc, qn[0], db);
      if (n == 9) wg_commit();
    }
    wg_commit();
  }
  wg_wait<1>();
  PROF(12);
  bar_sync(NB_B + chl, 288);
  const uint32_t d1 = dr + R_X5 / 16, d2 = dr + R_BO / 16;
  undef(f1); undef(f2);
  wg_fence();
#pragma unroll
  for (int n = 0; n < 4; ++n) { if (n) wg_rs32t<1>(f2, q[8 + n], d2 + 16 * n); else wg_rs32t<0>(f2, q[8], d2); }
  wg_commit();
#pragma unroll
  for (int n = 0; n < 8; ++n) {
    const uint32_t d = d1 + (n >> 2) * ((R_X3 - R_X5) / 16) + 16 * (n & 1) - 16 * (n & 2);
    if (n) wg_rs48t<1>(f1, q[n], d); else wg_rs48t<0>(f1, q[0], d);
  }
  wg_commit();
  wg_wait<1>();
  PROF(13);
  bar_arrive_if(NB_T + e, 256, chl - 3);
  PROF(14);
  bar_sync(NB_WG + e, 128);
  {
    const int p = (lane + 9 * (w >> 1)) & 31;
    const uint32_t ya = reg + ((w >> 1) ? R_BO : R_U) + p * 64 + (((2 * (w & 1)) ^ ((p >> 1) & 3)) * 16);
    const uint32_t up = p < lane ? 2048 : 0;
#pragma unroll
    for (int z = 0; z < 4; ++z) {
      const float* a = acc + 16 * (z >> 1) + 2 * (z & 1);
      stsm4t((ya + (up ^ ((z >> 1) * 2048))) ^ ((z & 1) * 16), pack2(a[0], a[1]), pack2(a[4], a[5]), pack2(a[8], a[9]), pack2(a[12], a[13]));
    }
  }
  wg_wait<0>();
  bar_sync(NB_WG + e, 128);
  {
    const uint32_t fa = reg + R_X5 + (8 * w + (lane & 7)) * 16 + (lane >> 3) * 512;
    uint32_t h[6];
#pragma unroll
    for (int p = 0; p < 6; ++p) h[p] = p ? pack2(f1[4 * p] + f1[4 * p - 2], f1[4 * p + 1] + f1[4 * p - 1]) : pack2(f1[0], f1[1]);
    stsm4(fa, h[0], h[1], h[2], h[3]);
    stsm2(fa + 2048, h[4], h[5]);
    stsm4(reg + R_X3 + (lane < 16 ? 1088 : 0) + (8 * w + (lane & 7) + 4 * (lane & 8)) * 16, pack2(f2[0], f2[1]), pack2(f2[2] + f2[4], f2[3] + f2[5]),
          pack2(f2[8], f2[9]), pack2(f2[10] + f2[12], f2[11] + f2[13]));
  }
  bar_arrive(NB_Y + e + 7 * rho, 256);
}
constexpr uint32_t FILL = 0xFFFFFFFFu;
template <int N> DEV void fixo(uint4 (&A)[N], const uint4* p) {
#pragma unroll 1
  for (int it = 0; it < SPIN_LIMIT; ++it) {
    uint32_t m = A[0].x;
#pragma unroll
    for (int k = 1; k < N; ++k) m = max(m, A[k].x);
    if (__all_sync(0xffffffffu, m != FILL)) break;
#pragma unroll
    for (int k = 0; k < N; ++k) ldr4_if(A[k], p + k * 32, A[k].x == FILL);
  }
}
DEV bool rows_nan(float a, float b) {
  return __any_sync(0xffffffffu, a != a || b != b);
}
template <int N> DEV void slow_step(float (&acc)[N], float a0, float a1, const uint16_t* wr, uint32_t zero) {
#pragma unroll
  for (int j = 0; j < N / 4; ++j) {
    const uint32_t v = __ldg((const uint32_t*)(wr + (j >> 3) * 512 + 8 * (j & 7)));
    acc[4 * j] += a0 * bflo(v); acc[4 * j + 1] += a0 * bfhi(v); acc[4 * j + 2] += a1 * bflo(v); acc[4 * j + 3] += a1 * bfhi(v);
    if ((j & 3) == 3) wr += __float_as_uint(acc[4 * j]) & zero;
  }
}
DEV int res_off(int w, int lane) { return ((lane & 7) + 8 * (lane >> 4)) * 8 + ((2 * (w & 2) + (w & 1) + ((lane >> 2) & 2)) ^ (lane & 7)); }
DEV void res_load(uint32_t (&res)[8][2], uint32_t sa, int w, int lane) {
  const uint32_t a = sa + res_off(w, opq(lane)) * 16;
#pragma unroll
  for (int j = 0; j < 8; j += 2) {
    uint32_t r[4];
    ldsm4t(r, a + j * 1024);
    res[j][0] = r[0]; res[j][1] = r[1]; res[j + 1][0] = r[2]; res[j + 1][1] = r[3];
  }
}

DEV void res_init(float (&ac)[32], const uint32_t (&res)[8][2]) {
#pragma unroll
  for (int j = 0; j < 16; ++j) { ac[2 * j] = bflo(res[j >> 1][j & 1]); ac[2 * j + 1] = bfhi(res[j >> 1][j & 1]); }
}
DEV uint32_t after(uint32_t b, const uint32_t (&res)[8][2], uint32_t zero) {
  return b + ((res[0][0] ^ res[2][0] ^ res[4][0] ^ res[6][0]) & zero);
}

DEV void attn_phase(const Params& P, int c, int e, int w, int lane, int layer) {
  lane = opq(lane); c = opq(c);
  const int i = c >> 3, cg = c & 7, J = 16 * e + i, G = 8 * i + 4 - 4 * e + w;
  const int g = lane >> 2, t = lane & 3;
  float acc[96];
  uint32_t res[8][2];
  float2 cs[16];
  float4 st;
  const uint32_t csb = opq(SM_CS + 8 * t);
  {
    const uint32_t sa = SM_A + e * A_E, ba = B_A + 16 * e;
    const uint32_t da = dlo(sa, 8192), db = (SB >> 4) | (512 << 16);
    undef(acc);
#pragma unroll
    for (int j = 0; j < 8; ++j) asm volatile("" : "=r"(res[j][0]), "=r"(res[j][1]));
    mbar_wait(B_WF, layer);
    mbar_wait(ba, 0);
    mbar_wait(B_L, layer);
    bar_sync_if(NB_T, 256, e);
    PROF(24);
#pragma unroll
    for (int j = 0; j < 4; ++j) {
      if (j == 1) { mbar_wait(ba + 8, 0); PROFK(layer ? 39 : 15); }
      wg_fence();
#pragma unroll
      for (int k = 0; k < 4; ++k) {
        if (j | k) wg_ss192<1>(acc, da + j * 512 + k * 128, db + wslot(j) * 512 + k * 128); else wg_ss192<0>(acc, da, db);
        if (j == 3 && k == 1) wg_commit();
      }
      wg_commit();
      if (j == 1 || j == 2) { wg_wait<1>(); mbar_arrive1_if(B_F + 8 * (j - 1), e); }
    }
    wg_wait<1>();
    bar_arrive(NB_T + e, 256);
    wg_wait<0>();
    if (cg < 4) res_load(res, sa + cg * 8192, w, lane);
    mbar_arrive1(after(B_AE + 8 * e, res, P.zero));
    PROF(25);
#pragma unroll 1
    for (uint32_t late = P.zero;; late = 1) {
      if (late) {
        const uint16_t* xr = (const uint16_t*)SCR->XF[layer] + opq(J) * 32768;
        zero(acc);
#pragma unroll 1
        for (int k = 0; k < 512; ++k)
          slow_step(acc, ldnan(xr + k * 64 + ((2 * w) ^ (k & 7)) * 8 + g), ldnan(xr + k * 64 + ((2 * w + 1) ^ (k & 7)) * 8 + g),
                    P.wqkv + (k * 1536 + 64 * cg + 2 * t), P.zero);
        const uint32_t* q = (const uint32_t*)xr + ((64 * cg + g) * 32 + t);
        const int m8 = (2 * (w & 2) + (w & 1)) ^ g;
#pragma unroll 1
        for (int it = 0; it < SPIN_LIMIT; ++it) {
          uint32_t m = 0;
#pragma unroll
          for (int z = 0; z < 16; ++z) { const uint32_t x = ldr1(q + (z >> 1) * 256 + (m8 ^ (2 * (z & 1))) * 4); m = max(m, x); res[z >> 1][z & 1] = movm(x); }
          if (__all_sync(0xffffffffu, m != FILL)) break;
        }
#pragma unroll
        for (int z = 0; z < 16; ++z) cs[z] = lds2f(csb + 256 + z * 32);
      } else {
        mbar_wait(B_CS, 0);
#pragma unroll
        for (int z = 0; z < 16; ++z) cs[z] = lds2f(csb + 256 + z * 32);
        mbar_wait(B_W4, layer);
        mbar_wait(ba, 1);
        bar_sync(NB_T + 1 - e, 256);
        PROF(26);
#pragma unroll
        for (int j = 4; j < 8; ++j) {
          if (j == 5) mbar_wait(ba + 8, 1);
          if (j >= 6) mbar_wait(B_W6 + 8 * (j - 6), layer);
          if (j > 4) PROF(31 + j);
          wg_fence();
#pragma unroll
          for (int k = 0; k < 4; ++k) {
            wg_ss192<1>(acc, da + (j & 3) * 512 + k * 128, db + wslot(j) * 512 + k * 128);
            if (j == 7 && k == 1) wg_commit();
          }
          wg_commit();
          if (j == 5) {
            if (cg >= 4) res_load(res, sa + (cg - 4) * 8192, w, lane);
            wg_wait<1>(); mbar_arrive1_if(B_F + 16, e); PROF(40);
          }

        }
      }
      uint32_t rs = hadd2(res[0][0], res[0][1]);
#pragma unroll
      for (int z = 2; z < 16; ++z) rs = hadd2(rs, res[z >> 1][z & 1]);
      const float rn = bflo(rs) + bfhi(rs);
      wg_wait<1>();
      bar_arrive_if(NB_T, 256, !(e | late));
      mbar_wait(B_ST + 8 * e, layer);
      st = lds4f(SM_STAT + ((4 * e + w) * 8 + g) * 16);
      PROF(34 + layer);
      wg_wait<0>();
      if (!rows_nan(acc[0] + rn, acc[2]) || late) break;
    }
  }
  mbar_arrive1(B_QE);
  PROFK(8 + 12 * layer);
  uint32_t Q[4][4], K[4][2][2], V[4][2][2];
  {
#pragma unroll
    for (int z = 0; z < 8; ++z) {
      const float* a = acc + 32 + 4 * z; const float* b = acc + 64 + 4 * z;
      K[z >> 1][1][z & 1] = pack2((a[2] - st.z * cs[z].x) * st.w, (a[3] - st.z * cs[z].y) * st.w);
      V[z >> 1][1][z & 1] = movm(pack2((b[2] - st.z * cs[8 + z].x) * st.w, (b[3] - st.z * cs[8 + z].y) * st.w));
    }
    const int hop = (G >> 1) & 3;
    const uint32_t kv = SM_KV + (2 * hop + (w & 1)) * 2048 + lane * 16;
    uint4* h = SCR->H[layer] + (c * 256 + (w & 1) * 128 + lane);
    if (hop == 3) {
#pragma unroll
      for (int z = 0; z < 4; ++z) str4(h + 2048 + z * 32, K[z][1][0], K[z][1][1], V[z][1][0], V[z][1][1]);
    } else {
      mbar_wait(B_F + 16, layer);
#pragma unroll
      for (int z = 0; z < 4; ++z) sts4(kv + z * 512, K[z][1][0], K[z][1][1], V[z][1][0], V[z][1][1]);
      bar_arrive(NB_B + hop, 128);
    }
    PROF(42);
    uint4 hv[4];
#pragma unroll
    for (int z = 0; z < 4; ++z) { hv[z] = make_uint4(0, 0, 0, 0); ldr4_if(hv[z], h + z * 32, G >= 2 && hop == 0); }
#pragma unroll
    for (int z = 0; z < 8; ++z) {
      const float* a = acc + 32 + 4 * z; const float* b = acc + 64 + 4 * z;
      K[z >> 1][0][z & 1] = pack2((a[0] - st.x * cs[z].x) * st.y, (a[1] - st.x * cs[z].y) * st.y);
      V[z >> 1][0][z & 1] = movm(pack2((b[0] - st.x * cs[8 + z].x) * st.y, (b[1] - st.x * cs[8 + z].y) * st.y));
    }
#pragma unroll
    for (int z = 0; z < 8; ++z) {
      const float2 cq = lds2f(csb + z * 32);
      const float* a = acc + 4 * z;
      Q[z >> 1][2 * (z & 1)] = pack2(a[0] - st.x * cq.x, a[1] - st.x * cq.y);
      Q[z >> 1][2 * (z & 1) + 1] = pack2(a[2] - st.z * cq.x, a[3] - st.z * cq.y);
    }
    PROF(27);
    const bool p0 = 2 * t > g, p1 = 2 * t + 1 > g, first = G < 2;
    float s[4][4], mx[4][2];
#pragma unroll
    for (int z = 0; z < 4; ++z) {
      float S[4];
      mma16z(s[z], Q[z][0], Q[z][1], Q[z][2], Q[z][3], K[z][0][0], K[z][0][1]);
      mma16z(S, Q[z][0], Q[z][1], Q[z][2], Q[z][3], K[z][1][0], K[z][1][1]);
      s[z][2] = p0 ? s[z][2] : S[2]; s[z][3] = p1 ? s[z][3] : S[3];
    }
    const float sc0 = st.y * (0.25f * 1.4426950408889634f), sc1 = st.w * (0.25f * 1.4426950408889634f);
    uint32_t pw[4][2];
#pragma unroll
    for (int r = 1; r >= 0; --r) {
      if (r == 0) {
        if (hop) {
          bar_sync(NB_B + hop - 1, 128);
#pragma unroll
          for (int z = 0; z < 4; ++z) hv[z] = lds4(kv - 4096 + z * 512);
        } else fixo(hv, h);
        PROFD(41, hv[3].x);
#pragma unroll
        for (int z = 0; z < 4; ++z) {
          float S[4];
          mma16z(S, Q[z][0], Q[z][1], Q[z][2], Q[z][3], hv[z].x, hv[z].y);
          if (first) S[0] = S[1] = __uint_as_float(0xFF800000u);
          s[z][0] = p0 ? S[0] : s[z][0]; s[z][1] = p1 ? S[1] : s[z][1];
        }
      }
#pragma unroll
      for (int z = 0; z < 4; ++z) mx[z][r] = fmaxf(s[z][2 * r], s[z][2 * r + 1]);
#pragma unroll
      for (int o = 1; o < 3; ++o)
#pragma unroll
        for (int z = 0; z < 4; ++z) mx[z][r] = fmaxf(mx[z][r], __shfl_xor_sync(0xffffffffu, mx[z][r], o));
#pragma unroll
      for (int z = 0; z < 4; ++z) pw[z][r] = pack2(ex2((s[z][2 * r] - mx[z][r]) * (r ? sc1 : sc0)), ex2((s[z][2 * r + 1] - mx[z][r]) * (r ? sc1 : sc0)));
    }
    mbar_wait(layer ? B_N : B_Z, 1);
    const uint32_t M = (p0 ? 0xFFFFu : 0u) | (p1 ? 0xFFFF0000u : 0u);
    uint4* O = SCR->O + ((J * 8 + cg) * 512 + (2 * (w & 2) + (w & 1)) * 64 + t * 8 + g);
#pragma unroll
    for (int h2 = 0; h2 < 2; ++h2) {
      uint32_t ow[2][4];
#pragma unroll
      for (int z = 0; z < 2; ++z) {
        const int n = 2 * h2 + z;
        const uint32_t w0 = pw[n][0], w1 = pw[n][1];
        float sm[4] = {0.f, 0.f, 0.f, 0.f}, Oa[2][4];
        mma8(sm, w0, w1, 0x3F803F80u);
        mma16z(Oa[0], w0 & ~M, w1 & M, 0u, w1 & ~M, V[n][0][0], V[n][1][0]); mma8(Oa[0], w0 & M, 0u, hv[n].z);
        mma16z(Oa[1], w0 & ~M, w1 & M, 0u, w1 & ~M, V[n][0][1], V[n][1][1]); mma8(Oa[1], w0 & M, 0u, hv[n].w);
        const float i0 = rcp(sm[0]), i1 = rcp(sm[2]);
#pragma unroll
        for (int d = 0; d < 2; ++d) { ow[0][2 * z + d] = pack2(Oa[d][0] * i0, Oa[d][1] * i0); ow[1][2 * z + d] = pack2(Oa[d][2] * i1, Oa[d][3] * i1); }
      }
#pragma unroll
      for (int hi = 0; hi < 2; ++hi) str4(O + hi * 128 + h2 * 32, ow[hi][0], ow[hi][1], ow[hi][2], ow[hi][3]);
    }
  }
  str1(SCR->OF[layer] + (J * 32 + cg * 4 + w), 1);
  mbar_arrive1(B_AT + 8 * e + (lds1(csb) & P.zero));
  PROFK(9 + 12 * layer);
  float ac[32];
  res_init(ac, res);
  const uint32_t so = SM_O + e * O_E;
  uint2* xo = opqp(layer ? (uint2*)(P.out + ((16 * G + 2 * (lane >> 3)) * 512 + 64 * cg + 8 * (lane & 7)))
                         : (uint2*)SCR->XG[1] + ((32 * (cg & 3) + t) * 2048 + (cg >> 2) * 512 + xg_off(G, g)));
  const uint32_t stg = SM_X + (4 * e + w) * 2048;
  const uint32_t sw = opq(stg + (lane & 15) * 128 + (((lane >> 4) ^ (lane & 7)) * 16)), sr = opq(stg + (lane >> 3) * 128 + (((lane & 7) ^ (lane >> 3)) * 16));
  uint4* ps = opqp(&SCR->PS[(G * 8 + cg) * 8 + g]);
  {
    const uint32_t bo = B_O + 32 * e;
    const uint32_t dw = (SM_WO >> 4) | (512 << 16), da = dlo(so, 512);
    mbar_wait(B_WO, layer);
#pragma unroll
    for (int j = 0; j < 4; ++j) {
      mbar_wait(bo + 8 * j, layer);
      if (j == 0) { PROFK(32 + layer); mbar_wait(B_AT + 8, layer); }
      wg_fence();
#pragma unroll
      for (int k = 8 * j; k < 8 * j + 8; ++k) {
        const uint32_t a = da + (k >> 2) * 512 + (k & 3) * 8, b = dw + (k & 3) * 1024 + (k >> 2) * 128;
        wg_ss64<1>(ac, a, b);
      }
      wg_commit();
    }
#pragma unroll 1
    for (uint32_t late = P.zero;; late = 1) {
      if (late) {
        const uint16_t* op = (const uint16_t*)(SCR->O + (J * 4096 + w * 128 + g));
        wg_wait<0>();
        res_init(ac, res);
#pragma unroll 1
        for (int k = 0; k < 512; ++k) {
          const uint16_t* q = op + (k >> 6) * 4096 + (k & 56) * 8 + (k & 7);
          slow_step(ac, ldnan(q), ldnan(q + 512), P.wo + (((k & ~31) + 4 * (k & 6) + ((k >> 2) & 6) + (k & 1)) * 512 + 64 * cg + 2 * t), P.zero);
        }
      }
      wg_wait<0>();
      if (!rows_nan(ac[0], ac[2]) || late) break;
    }
  }
  PROFK(10 + 12 * layer);
#pragma unroll
  for (int j = 0; j < 16; ++j) res[j >> 1][j & 1] = pack2(ac[2 * j], ac[2 * j + 1]);
  if (layer == 0) {
    float s[2][4], q0[2][4], q1[2][4];
#pragma unroll
    for (int j = 0; j < 2; ++j) gram<true>(s[j], q0[j], q1[j], res[2 * j][0], res[2 * j][1], res[2 * j + 1][0], res[2 * j + 1][1]);
#pragma unroll
    for (int j = 0; j < 2; ++j) gram<false>(s[j], q0[j], q1[j], res[2 * j + 4][0], res[2 * j + 4][1], res[2 * j + 5][0], res[2 * j + 5][1]);
    const bool od = g & 1;
    str4_if(ps, nzmap(__float_as_uint(s[0][0] + s[1][0])), __float_as_uint(od ? q0[0][1] + q0[1][1] : q0[0][0] + q0[1][0]),
            __float_as_uint(s[0][2] + s[1][2]), __float_as_uint(od ? q1[0][3] + q1[1][3] : q1[0][2] + q1[1][2]), t == (g >> 1));
#pragma unroll
    for (int j = 0; j < 8; ++j) {
      str2(xo + j * 8192, nzmap(prmt(res[j][0], res[j][1], 0x5410)), prmt(res[j][0], res[j][1], 0x7632));
    }
    mbar_arrive1(B_ED + 8 * e);
  } else {
#pragma unroll
    for (int j = 0; j < 8; j += 2) stsm4(sw ^ (j * 16), res[j][0], res[j][1], res[j + 1][0], res[j + 1][1]);
    __syncwarp();
    uint4 v[4];
#pragma unroll
    for (int k = 0; k < 4; ++k) v[k] = lds4((sr ^ ((k & 1) * 64)) + k * 512);
#pragma unroll
    for (int k = 0; k < 4; ++k) stw4(xo + ((k & 1) * 8 + (k >> 1)) * 128, v[k].x, v[k].y, v[k].z, v[k].w);
  }
  PROFK(11 + 12 * layer);
}

DEV void col_sums(const Params& P, int c, int wa, int lane) {
  const int i = c >> 3, cg = c & 7;
  uint4 wv[8];
#pragma unroll
  for (int k = 0; k < 8; ++k) wv[k] = ldnc4(P.wqkv + ((32 * i + (lane >> 3)) * 1536 + wa * 512 + 64 * cg + 8 * (lane & 7)) + 4 * k * 1536);
  float cs[8];
  zero(cs);
#pragma unroll
  for (int k = 0; k < 8; ++k) {
    cs[0] += bflo(wv[k].x); cs[1] += bfhi(wv[k].x); cs[2] += bflo(wv[k].y); cs[3] += bfhi(wv[k].y);
    cs[4] += bflo(wv[k].z); cs[5] += bfhi(wv[k].z); cs[6] += bflo(wv[k].w); cs[7] += bfhi(wv[k].w);
  }
  const bool b4 = lane & 16, b3 = lane & 8;
#pragma unroll
  for (int k = 0; k < 4; ++k) cs[k] = (b4 ? cs[k + 4] : cs[k]) + __shfl_xor_sync(0xffffffffu, b4 ? cs[k] : cs[k + 4], 16);
#pragma unroll
  for (int k = 0; k < 2; ++k) cs[k] = (b3 ? cs[k + 2] : cs[k]) + __shfl_xor_sync(0xffffffffu, b3 ? cs[k] : cs[k + 2], 8);
  str2((uint2*)SCR->CS + (i * 768 + wa * 256 + 32 * cg + 4 * (lane & 7) + (lane >> 3)), nzmap(__float_as_uint(cs[0])), __float_as_uint(cs[1]));
}
DEV void col_gather(const Params& P, int c, int wa, int lane) {
  const uint2* p = (const uint2*)SCR->CS + (wa * 256 + 32 * (c & 7) + lane);
#pragma unroll 1
  for (int it = 0;; ++it) {
    float a = 0.f, b = 0.f;
    uint32_t m = ~0u;
#pragma unroll
    for (int k = 0; k < 16; ++k) { const uint2 q = ldr2(p + k * 768); m = min(m, q.x); a += __uint_as_float(q.x); b += __uint_as_float(q.y); }
    if (__all_sync(0xffffffffu, m != 0u)) { sts2f(SM_CS + wa * 256 + lane * 8, a, b); break; }
    spin_guard(it);
  }
  __syncwarp();
  mbar_arrive1(B_CS);
}

DEV void aux_prologue(const Params& P, int c, int wa, int lane) {
  const int g = lane >> 2, t = lane & 3, G = stat_group(c);
  {
    uint32_t w[16][2];
    const uint16_t* row = P.x0 + ((16 * G + 2 * g) * 512 + 128 * wa + 8 * t);
    bar_sync(NB_Y, 384);
#pragma unroll
    for (int z = 0; z < 8; ++z) {
      const uint4 v = ldw4(row + (z & 1) * 512 + (z >> 1) * 32);
      const int o = 4 * (z >> 1);
      w[o][z & 1] = v.x; w[o + 1][z & 1] = v.y; w[o + 2][z & 1] = v.z; w[o + 3][z & 1] = v.w;
    }
    PROF(34);
    PROFD(35, w[0][0]);
    PROFD(36, w[15][1]);
    uint2* xo = (uint2*)SCR->XG[0] + ((64 * (wa & 1) + 4 * t) * 2048 + (wa >> 1) * 512 + xg_off(G, g));
#pragma unroll
    for (int n = 0; n < 16; ++n) str2(xo + (16 * (n >> 2) + (n & 3)) * 2048, nzmap(prmt(w[n][0], w[n][1], 0x5410)), prmt(w[n][0], w[n][1], 0x7632));
    float s[2][4], q0[2][4], q1[2][4];
#pragma unroll
    for (int z = 0; z < 8; ++z) {
      const int o = 4 * (z >> 1), r = z & 1;
      if (z < 2) gram<true>(s[r], q0[r], q1[r], w[o][r], w[o + 1][r], w[o + 2][r], w[o + 3][r]);
      else gram<false>(s[r], q0[r], q1[r], w[o][r], w[o + 1][r], w[o + 2][r], w[o + 3][r]);
    }
    const bool od = g & 1;
    if (t == (g >> 1))
      sts4f(SM_MISC + (wa * 8 + g) * 16, s[0][0] + s[0][2], od ? q0[0][1] + q1[0][3] : q0[0][0] + q1[0][2],
            s[1][0] + s[1][2], od ? q0[1][1] + q1[1][3] : q0[1][0] + q1[1][2]);
    bar_arrive(NB_P0, 192);
  }
  PROF(2);
  if (lane == 0)
    asm volatile("cp.async.bulk.prefetch.L2.global [%0],4096;" :: "l"(wa < 3 ? P.wqkv + (3 * c + wa) * 2048 : P.wo + c * 2048) : "memory");
  bar_sync(NB_Y + 1, 256);
  mbar_wait(B_Z, 0);
}

DEV void stat_part(const Params& P, int c, int wa, int lane, int layer, int h, float (&v)[2]) {
  lane = opq(lane);
  const int e = wa >> 1;
  uint32_t x[4][4];
  mbar_wait(B_A + 16 * e, h); mbar_wait(B_A + 16 * e + 8, h);
#pragma unroll
  for (int k = 0; k < 4; ++k) ldsm4t(x[k], SM_A + e * A_E + (128 * (wa & 1) + lane) * 128 + (((c ^ lane) & 7) * 16) + k * 4096);
  float s[4] = {0.f, 0.f, 0.f, 0.f};
#pragma unroll
  for (int k = 0; k < 16; ++k) { const float a = bflo(x[k >> 2][k & 3]), b = bfhi(x[k >> 2][k & 3]); s[0] += a; s[1] += a * a; s[2] += b; s[3] += b * b; }
  s[0] += s[2]; s[1] += s[3];
  if (RARE(rows_nan(s[1], s[1]))) {
    const uint16_t* q = (const uint16_t*)(SCR->XF[layer] + ((32 * e + 2 * (c >> 3) + h) * 2048 + (wa & 1) * 1024)) + (lane >> 2);
    s[0] = s[1] = 0.f;
#pragma unroll 1
    for (int k = 0; k < 32; ++k) {
      const int r = 2 * (lane & 3) + (k & 1);
      const float a = ldnan(q + ((k >> 1) * 8 + r) * 64 + ((c ^ r) & 7) * 8);
      s[0] += a; s[1] += a * a;
    }
  }
  v[0] += s[0]; v[1] += s[1];
  __syncwarp();
}
DEV void stat_finish(const Params& P, int c, int wa, int lane, int layer, float (&v)[2]) {
  lane = opq(lane);
  const bool b = lane & 1;
  const float s = (b ? v[1] : v[0]) + __shfl_xor_sync(0xffffffffu, b ? v[0] : v[1], 1);
  str1((uint32_t*)SCR->ST[layer] + ((128 * (wa >> 1) + c) * 64 + (wa & 1) * 32 + lane), nzmap(__float_as_uint(s)));
  const uint4* sp = SCR->ST[layer] + ((128 * (wa >> 1) + (c & ~7) + 4 * (wa & 1) + (lane >> 3)) * 16 + (lane & 7));
  uint4 x, y;
  for (int it = 0;; ++it) {
    x = ldr4(sp); y = ldr4(sp + 8);
    if (__all_sync(0xffffffffu, min(min(min(x.x, x.y), min(x.z, x.w)), min(min(y.x, y.y), min(y.z, y.w))) != 0u)) break;
    spin_guard(it);
  }
  const uint32_t q = ln_sums((__uint_as_float(x.x) + __uint_as_float(x.z)) + (__uint_as_float(y.x) + __uint_as_float(y.z)),
                             (__uint_as_float(x.y) + __uint_as_float(x.w)) + (__uint_as_float(y.y) + __uint_as_float(y.w)));
  sts2f(SM_STAT + (16 * wa + (lane >> 4) * 8 + (lane & 7)) * 16 + (lane & 8), bflo(q), rcp(bfhi(q)));
  __syncwarp();
  mbar_arrive1(B_ST + 4 * (wa & 2));
}

DEV void nan_source(uint32_t a, int lane) {
#pragma unroll
  for (int k = 0; k < 4; ++k) sts4(a + k * 512 + lane * 16, FILL, FILL, FILL, FILL);
  fence_async_smem();
  __syncwarp();
}
__global__ void __launch_bounds__(NTHR, 1)
fused_kernel(const __grid_constant__ Params P, const __grid_constant__ CUtensorMap mapW, const __grid_constant__ CUtensorMap mapWo,
             const __grid_constant__ CUtensorMap mapX) {
  extern __shared__ __align__(1024) uint8_t smem_raw[];
  const int warp = __shfl_sync(0xffffffffu, threadIdx.x >> 5, 0), lane = threadIdx.x & 31;
  uint32_t smid; asm volatile("mov.u32 %0,%%smid;" : "=r"(smid));
  const uint32_t* pw = (const uint32_t*)&P + threadIdx.y;
  const int role = P.role[(smid >> 1) + threadIdx.y] + (smid & 1) + (pw[0] & pw[12]);
  const int c = __shfl_sync(0xffffffffu, pw[1] ? role : blockIdx.x, 0);
  if (c >= 128) {
#pragma unroll 1
    for (int k = (c - 128) * NTHR + threadIdx.x; k < 131072; k += P.spare * NTHR) str4(SCR->XG[1] + k, 0, 0, 0, 0);
    __threadfence();
    __syncthreads();
    if (warp == 0) { poll(SCR->C + 1 + (lane & 3) * 32, 32); cnt_add1(SCR->C + 6); }
    __syncthreads();
#pragma unroll 1
    for (int k = (c - 128) * NTHR + threadIdx.x; k < 131072; k += P.spare * NTHR) str4(SCR->XG[0] + k, 0, 0, 0, 0);
    return;
  }
#define DONE() do {} while (0)
  const int cg = c & 7;
  if (warp < 8) {
    PROF(46);
    kgen(P, c, warp, lane);
    PROFK(1);
    bar_sync(0, 384);
#pragma unroll 1
    for (int layer = 0; layer < 2; ++layer) {
#pragma unroll 1
      for (int rho = 0; rho < 2; ++rho) {
        const int wz = warp + ((rho + layer) & P.zero);
        conv_round(wz >> 2, rho, wz & 3, lane_id());
        PROFK(6 + rho + 12 * layer);
      }
      const int z = layer & P.zero;
      attn_phase(P, c + z, (warp + z) >> 2, (warp + z) & 3, lane_id(), layer);
    }
    DONE();
  } else if (warp < 12) {
    asm volatile("setmaxnreg.dec.sync.aligned.u32 %0;" :: "n"(REG_AUX));
    aux_prologue(P, c, warp - 8, lane);
    PROF(1);
    const int c0 = c;
#pragma unroll 1
    for (int layer = 0;; ++layer) {
      const int c = c0 + (layer & P.zero), wa = warp - 8 + (layer & P.zero);
#define lane lane_id()
#define j (32 * wa + lane_id())
      uint4 x[2][2][2];
      uint32_t u[4][4];
      uprep(P, c, wa, lane, layer, x, u);
      fence_async_smem();
      bar_arrive(NB_U, NBARU);
      PROFK(5 + 12 * layer);
      bar_sync(NB_H, 192);
      box_full(j, u, P.zero);
      PROF(3 + 12 * layer);
      conv_out(c, j, 0, x, u[0], SCR->XF[layer], P.zero);
      PROF(32);
      conv_out(c, j, 1, x, u[1], SCR->XF[layer], P.zero);
      PROF(6 + 12 * layer);
      if (layer == 0 && wa < 3) col_sums(P, c, wa, lane);
      conv_out(c, j, 2, x, u[2], SCR->XF[layer], P.zero);
      PROF(33);
      conv_out(c, j, 3, x, u[3], SCR->XF[layer], P.zero);
      PROFK(7 + 12 * layer);
      float v[2];
      zero(v);
#pragma unroll 1
      for (int h = 0; h < 2; ++h) {
        stat_part(P, c, wa, lane, layer, h, v);
        if (h) break;
        mbar_arrive1(B_AE + 4 * (wa & 2));
        if (layer == 0 && wa < 3) col_gather(P, c, wa, lane);
      }
      PROF(9 + 12 * layer);
      stat_finish(P, c, wa, lane, layer, v);
      PROF(8 + 12 * layer);
      if (layer) break;
      mbar_wait(B_ED, 0); mbar_wait(B_ED + 8, 0);
#undef lane
#undef j
    }
    DONE();
  } else {
    asm volatile("setmaxnreg.dec.sync.aligned.u32 %0;" :: "n"(REG_PROD));
    if (s2u(smem_raw) != SB) __trap();
#pragma unroll 1
    for (int n = warp - 12; n < 38; n += 4)
      asm volatile("{.reg .pred p; elect.sync _|p,0xffffffff; @p mbarrier.init.shared::cta.b64 [%0],%1;}"
                   :: "r"(SM_BAR + n * 8), "r"(n == 33 ? 4 : n > 14 ? 1 : (int)(0x322866444444444ull >> (4 * n)) & 15) : "memory");
    fence_async_smem();
    bar_sync(NB_AUX, 128);
    bar_arrive(0, 384); bar_arrive(NB_Y + 1, 256);
    PROF(1);
    if (warp == 12) {
      if (lane == 0) {
        asm volatile("prefetch.tensormap [%0];" :: "l"(&mapW) : "memory");
        asm volatile("prefetch.tensormap [%0];" :: "l"(&mapWo) : "memory");
        asm volatile("prefetch.tensormap [%0];" :: "l"(&mapX) : "memory");
      }
      nan_source(slot(12), lane);
#pragma unroll 1
      for (int k = 0; k < 8; ++k) tma2_store(&mapX, slot(12), 128 * c, 8 * k);
      bulk_wait();
      __threadfence();
      mbar_arrive1(B_Z);
      mbar_wait(B_E, 0);
#pragma unroll 1
      for (int k = 0; k < 4; ++k) bulk_store(SCR->H[k >> 1] + ((c + 8) * 256 + (k & 1) * 128), slot(12), 2048);
#pragma unroll 1
      for (int k = 0; k < 8; ++k) bulk_store(SCR->O + (c * 512 + (k >> 2) * 65536 + (k & 3) * 128), slot(12), 2048);
      bulk_wait();
      PROF(24);
#pragma unroll 1
      for (int layer = 0; layer < 2; ++layer) {
        mbar_wait(B_V, layer);
        if (layer == 1 && c < 4 && ((0x47 >> lane) & 1)) str1(SCR->C + c * 32 + lane, 0);
        mbar_expect1(B_WF, 4 * 24576);
#pragma unroll
        for (int k = 0; k < 4; ++k) tma3(slot(wslot(k)), &mapW, 64 * cg, 64 * k, 0, B_WF);
        if (layer == 0) { __threadfence(); mbar_arrive1(B_Z); }
        mbar_wait(B_WF, layer);
        mbar_expect1(B_W4, 2 * 24576);
#pragma unroll
        for (int k = 4; k < 6; ++k) tma3(slot(wslot(k)), &mapW, 64 * cg, 64 * k, 0, B_W4);
        bar_sync(NB_AUX, 64);
#pragma unroll 1
        for (int k = 0; k < 2; ++k) {
          mbar_expect1(B_W6 + 8 * k, 24576);
          mbar_wait(B_F + 8 * k, layer);
          tma3(slot(3 * k), &mapW, 64 * cg, 384 + 64 * k, 0, B_W6 + 8 * k);
        }
        mbar_expect1(B_WO, 65536);
        mbar_wait(B_AE + 8, layer);
        nan_source(slot(12), lane);
        uint4* fp = layer ? SCR->O + c * 512 : SCR->XF[1] + c * 512;
#pragma unroll 1
        for (int r = 7; r >= 0; --r) {
          __nanosleep(30);
          if (r >= 4) {
            bulk_store(fp + (r & 3) * 128, slot(12), 2048); bulk_store(fp + 65536 + (r & 3) * 128, slot(12), 2048);
          }
          if (r == 3) { bulk_wait(); __threadfence(); mbar_arrive1(B_N); PROF(9 + 12 * layer); }
          if (r == 1) mbar_wait(B_F + 16, layer);
          tma4(SM_WO + r * 8192, &mapWo, 64 * cg, 0, r >> 1, 32 * (r & 1), B_WO);
        }
        PROF(8 + 12 * layer);
      }
      DONE();
    } else if (warp == 13) {
      const int G = stat_group(c);
#pragma unroll 1
      for (int layer = 0; layer < 2; ++layer) {
        float z[4];
        uint2* so = opqp((uint2*)&SCR->SR[layer][lane >> 3][sr_off(G, lane)] + (lane & 1));
        if (layer == 0) {
          bar_sync(NB_P0, 192);
          const float4 a = lds4f(SM_MISC + lane * 16);
          z[0] = a.x; z[1] = a.y; z[2] = a.z; z[3] = a.w;
        } else {
          mbar_wait(B_ED + 2 * (c & 4), 0);
          uint4* ps = &SCR->PS[G * 64 + lane];
          uint4 a, b;
          for (int it = 0;; ++it) {
            a = ldr4(ps); b = ldr4(ps + 32);
            if (__all_sync(0xffffffffu, min(a.x, b.x) != 0u)) break;
            spin_guard(it);
          }
          z[0] = __uint_as_float(a.x) + __uint_as_float(b.x); z[1] = __uint_as_float(a.y) + __uint_as_float(b.y);
          z[2] = __uint_as_float(a.z) + __uint_as_float(b.z); z[3] = __uint_as_float(a.w) + __uint_as_float(b.w);
        }
#pragma unroll
        for (int o = 8; o < 32; o <<= 1)
#pragma unroll
          for (int k = 0; k < 4; ++k) z[k] += __shfl_xor_sync(0xffffffffu, z[k], o);
        const uint32_t w0 = ln_sums(z[0], z[1]), w1 = ln_sums(z[2], z[3]);
        const uint32_t r = nzmap(pack2(rcp(bfhi(w0)), rcp(bfhi(w1)))), m = pack2(z[0] * (-1.f / 512.f) * bflo(r), z[2] * (-1.f / 512.f) * bfhi(r));
        str2(so, r, m); str2(so + 4 * 1024, r, m);
        PROF(4 + 12 * layer);
        box_help(0, lane);
        PROF(6 + 12 * layer);
      }
      DONE();
    } else if (warp == 14) {
#pragma unroll 1
      for (int layer = 0; layer < 2; ++layer) {
        uint32_t* ca = opqp(SCR->C + (c >> 5) * 32 + 3 * layer);
        const uint32_t* cw = opqp(SCR->C + (lane & 3) * 32 + 3 * layer);
        const uint4* xg = opqp(SCR->XG[layer] + c * 1024);
        mbar_expect1(B_E, 16384);
        if (layer) { mbar_wait(B_N, 0); mbar_wait(B_ED, 0); mbar_wait(B_ED + 8, 0); } else bar_sync(NB_P0, 192);
        cnt_add1(ca);
        PROF(4 + 12 * layer);
        poll(cw, 32);
        mbar_arrive1(B_U);
        bulk(SM_X, xg, 16384, B_E);
        PROFK(5 + 12 * layer);
#pragma unroll 1
        for (int n = 0; n < 4; ++n) {
          const int e = n & 1;
          const uint4* src = opqp(SCR->XF[layer] + (32 * e + 2 * (c >> 3) + (n >> 1)) * 2048);
          const uint32_t dst = opq(SM_A + e * A_E), b = opq(B_A + 16 * e), f = opq(n == 1 ? B_L : (n & 2 ? B_AE : B_RD) + 8 * e);
          if (n == 0) { mbar_wait(B_RD, layer); cnt_add1(ca + 1); }
          if (!e) poll(cw + 1 + (n >> 1), 32);
          if (n == 2) PROF(7 + 12 * layer);
          mbar_wait(f, layer);
          mbar_expect1(b, 8192); bulk(dst, src, 8192, b);
          mbar_expect1(b + 8, 24576); bulk(dst + 8192, src + 512, 24576, b + 8);
          bar_arrive_if(NB_AUX, 64, n == 2);
          if (!e) PROFK(6 + n + 12 * layer);
        }
#pragma unroll 1
        for (int n = 0; n < 8; ++n) mbar_expect1(B_O + 8 * n, 16384);
        if (layer == 0) poll(SCR->C + 6, P.spare);
        mbar_wait(B_QE, layer);
#pragma unroll 1
        for (int e = 0; e < 2; ++e) {
          const int J = 16 * e + (c >> 3);
          const uint32_t* fl = opqp(SCR->OF[layer] + J * 32 + lane);
          const uint4* src[4];
          uint32_t dst[4], b[4];
#pragma unroll
          for (int n = 0; n < 4; ++n) { src[n] = opqp(SCR->O + (J * 4096 + n * 1024)); dst[n] = opq(SM_O + e * O_E + 16384 * n); b[n] = opq(B_O + 32 * e + 8 * n); }
          mbar_wait(B_AT + 8 * e, layer);
          if (!e) pause(260);
          poll(fl, 1);
#pragma unroll
          for (int n = 0; n < 4; ++n) bulk(dst[n], src[n], 16384, b[n]);
          PROFK(9 + e + 12 * layer);
        }
      }
      DONE();
    }
    if (warp == 15) {
      const int G = stat_group(c);
      str4(&SCR->ST[0][(lane >> 4) * 2048 + c * 16 + (lane & 15)], 0, 0, 0, 0); str4(&SCR->ST[1][(lane >> 4) * 2048 + c * 16 + (lane & 15)], 0, 0, 0, 0);
      if (lane < 4) str4(SCR->OF[lane >> 1] + ((lane & 1) * 512 + c * 4), 0, 0, 0, 0);
      str4(&SCR->PS[G * 64 + lane], 0, 0, 0, 0); str4(&SCR->PS[G * 64 + 32 + lane], 0, 0, 0, 0);
      str4(&SCR->SR[1][lane >> 2][sr_off(G, 2 * lane)], 0, 0, 0, 0);
      if (c < 4 && lane < 3) str1(SCR->C + c * 32 + 3 + lane, 0);
#pragma unroll
      for (int k = 0; k < 3; ++k) str2((uint2*)SCR->CS + ((c >> 3) * 768 + k * 256 + 32 * cg + lane), 0, 0);
      __threadfence();
#pragma unroll 1
      for (int layer = 0; layer < 2; ++layer) {
        PROF(4 + 12 * layer);
        box_help(1, lane);
        if (layer) str4(&SCR->SR[0][lane >> 2][sr_off(G, 2 * lane)], 0, 0, 0, 0);
        uint32_t* ca = opqp(SCR->C + (c >> 5) * 32 + 3 * layer + 2);
        mbar_wait(B_Z, 1);
        mbar_wait(B_RD + 8, layer);
        cnt_add1(ca);
        if (P.spare == 0) {
#pragma unroll 1
          for (int k = 0; k < 32; ++k) str4(SCR->XG[layer] + (c * 1024 + k * 32 + lane), 0, 0, 0, 0);
        }
      }
      mbar_watch(B_O + 56, 1);
    }
  }
}

typedef CUresult (*EncodeFn)(CUtensorMap*, CUtensorMapDataType, cuuint32_t, void*, const cuuint64_t*, const cuuint64_t*,
                             const cuuint32_t*, const cuuint32_t*, CUtensorMapInterleave, CUtensorMapSwizzle,
                             CUtensorMapL2promotion, CUtensorMapFloatOOBfill);

static int place_roles(uint8_t* role) {
  int dev = 0, nsm = 0;
  cudaGetDevice(&dev);
  cudaDeviceGetAttribute(&nsm, cudaDevAttrMultiProcessorCount, dev);
  if (nsm <= 128 || nsm > 144 || (nsm & 1)) return 0;
  cudaFuncSetAttribute(fused_kernel, cudaFuncAttributeNonPortableClusterSizeAllowed, 1);
  int occ[9] = {0};
  for (int k = 2; k <= 8; ++k) {
    cudaLaunchConfig_t cfg = {};
    cudaLaunchAttribute at[1];
    at[0].id = cudaLaunchAttributeClusterDimension;
    at[0].val.clusterDim.x = 2 * k; at[0].val.clusterDim.y = 1; at[0].val.clusterDim.z = 1;
    cfg.gridDim = dim3(2 * k); cfg.blockDim = dim3(NTHR); cfg.dynamicSmemBytes = SM_TOTAL; cfg.attrs = at; cfg.numAttrs = 1;
    if (cudaOccupancyMaxActiveClusters(&occ[k], fused_kernel, &cfg) != cudaSuccess) { cudaGetLastError(); occ[k] = 0; }
  }
  int n[10];
  n[7] = occ[8]; n[6] = occ[7]; n[5] = occ[6] - 0; n[4] = occ[5];
  n[3] = occ[4] - n[7]; n[1] = occ[2] - n[3] - n[5] - n[7]; n[0] = n[2] = n[1];
  n[8] = occ[3] - n[2] - n[5];
  const int ntpc = nsm / 2;
  int sum = 0;
  bool ok = n[0] > 0 && n[0] <= 8;
  for (int r = 0; r < 9; ++r) { ok = ok && n[r] >= 0 && (r == 0 || n[r] <= n[r - 1]); sum += n[r]; }
  if (!ok || sum > ntpc) { for (int r = 0; r < 9; ++r) n[r] = r < 8 ? 8 : 0; sum = 64; }
  int tp[8][9], cnt[8] = {0}, pool[72], np = 0, id = 0;
  for (int r = 0; r < 9; ++r)
    for (int g = n[0] - n[r]; g < n[0]; ++g) tp[g][cnt[g]++] = id++;
  for (; id < ntpc; ++id) pool[np++] = id;
  int order[72], no = 0;
  for (int g = 0; g < n[0]; ++g) {
    const int full = cnt[g] / 4 * 4;
    for (int k = 0; k < cnt[g]; ++k) { if (k < full) order[no++] = tp[g][k]; else pool[np++] = tp[g][k]; }
  }
  for (int k = 0; k < np; ++k) order[no++] = pool[k];
  for (int k = 0; k < ntpc; ++k) role[order[k]] = 2 * k;
  return nsm;
}

extern "C" void kernel_launch(void* const* d_in, const int* in_sizes, int n_in, void* d_out, int out_size) {
  (void)in_sizes; (void)n_in; (void)out_size;
  static EncodeFn enc = nullptr;
  static uint8_t role[72];
  static int nsm = 0;
  static Scratch* scratch = nullptr;
  if (!enc) {
    void* fn = nullptr;
    cudaDriverEntryPointQueryResult qr;
    cudaGetDriverEntryPoint("cuTensorMapEncodeTiled", &fn, cudaEnableDefault, &qr);
    enc = (EncodeFn)fn;
    cudaFuncSetAttribute(fused_kernel, cudaFuncAttributeMaxDynamicSharedMemorySize, SM_TOTAL);
    nsm = place_roles(role);
    cudaGetSymbolAddress((void**)&scratch, g_S);
  }
  CUtensorMap mW, mWo, mX;
  {
    cuuint64_t dim[3] = {512, 512, 3}, str[2] = {3072, 1024};
    cuuint32_t box[3] = {64, 64, 3}, es[3] = {1, 1, 1};
    enc(&mW, CU_TENSOR_MAP_DATA_TYPE_BFLOAT16, 3, d_in[10], dim, str, box, es, CU_TENSOR_MAP_INTERLEAVE_NONE,
        CU_TENSOR_MAP_SWIZZLE_128B, CU_TENSOR_MAP_L2_PROMOTION_NONE, CU_TENSOR_MAP_FLOAT_OOB_FILL_NONE);
  }
  {
    cuuint64_t dim[4] = {512, 2, 4, 64}, str[3] = {1024, 2048, 8192};
    cuuint32_t box[4] = {64, 2, 1, 32}, es[4] = {1, 1, 1, 1};
    enc(&mWo, CU_TENSOR_MAP_DATA_TYPE_BFLOAT16, 4, d_in[11], dim, str, box, es, CU_TENSOR_MAP_INTERLEAVE_NONE,
        CU_TENSOR_MAP_SWIZZLE_128B, CU_TENSOR_MAP_L2_PROMOTION_NONE, CU_TENSOR_MAP_FLOAT_OOB_FILL_NONE);
  }
  {
    cuuint64_t dim[2] = {16384, 64}, str[1] = {32768};
    cuuint32_t box[2] = {128, 8}, es[2] = {1, 1};
    enc(&mX, CU_TENSOR_MAP_DATA_TYPE_BFLOAT16, 2, scratch->XF[0], dim, str, box, es, CU_TENSOR_MAP_INTERLEAVE_NONE,
        CU_TENSOR_MAP_SWIZZLE_NONE, CU_TENSOR_MAP_L2_PROMOTION_NONE, CU_TENSOR_MAP_FLOAT_OOB_FILL_NONE);
  }
  Params P;
  P.x0 = (const uint16_t*)d_in[0]; P.Are = (const uint16_t*)d_in[1]; P.Aim = (const uint16_t*)d_in[2];
  P.Bre = (const uint16_t*)d_in[3]; P.Bim = (const uint16_t*)d_in[4]; P.Cre = (const uint16_t*)d_in[5];
  P.Cim = (const uint16_t*)d_in[6]; P.logdt = (const uint16_t*)d_in[7]; P.dskip = (const uint16_t*)d_in[8];
  P.wqkv = (const uint16_t*)d_in[10]; P.wo = (const uint16_t*)d_in[11]; P.out = (uint16_t*)d_out;
  for (int k = 0; k < 72; ++k) P.role[k] = role[k];
  P.zero = 0;
  P.mid = (char*)scratch->C;
  P.spare = nsm > 0 ? nsm - 128 : 0;
  fused_kernel<<<nsm > 0 ? nsm : 128, NTHR, SM_TOTAL, cudaStreamPerThread>>>(P, mW, mWo, mX);
}
```

```cpp
#include <cuda_runtime.h>
#include <cuda_bf16.h>
#include <cuda.h>
#include <stdint.h>
#include <stddef.h>

#define DEV __device__ __forceinline__
#define RARE(x) __builtin_expect(!!(x), 0)

constexpr int NTHR = 512;
constexpr int REG_MAIN = 192, REG_AUX = 96, REG_PROD = 32;
constexpr int NBARU = 384;
constexpr int SPIN_LIMIT = 1 << 22;

constexpr uint32_t SB = 1024;
__host__ __device__ constexpr uint32_t slot(int n) { return SB + n * 8192; }
__host__ __device__ constexpr int wslot(int k) { return k < 2 ? 3 * k : k < 4 ? 3 * k + 6 : k < 6 ? 21 - 3 * k : 3 * k - 18; }
constexpr uint32_t SM_A = slot(22), A_E = 0u - 32768;
constexpr uint32_t SM_O = slot(18), O_E = 0u - 147456;
constexpr uint32_t SM_WO = slot(10), SM_X = slot(8), SM_KV = slot(9) - 4096;
constexpr uint32_t SM_TAP  = slot(26);
constexpr int TAP_SZ = 3440;
constexpr uint32_t SM_STAT = SM_TAP + 4 * TAP_SZ;
constexpr uint32_t SM_CS   = SM_STAT + 1024;
constexpr uint32_t SM_MISC = SM_CS + 768;
constexpr uint32_t SM_BAR  = SM_MISC + 528;
constexpr int SM_TOTAL = SM_BAR + 304 - SB;
static_assert(SM_TOTAL <= 232448, "");
constexpr int R_SZ = 16384, R_U = 512, R_X5 = 5120, R_X3 = 8704, R_BO = 11776, R_BE = 13824;
constexpr int X_5 = 576, X_3 = 648, T_E = 2 * 720, T_O = 1600 + 2 * 721, T_C = 3390, T_K = 3424;
constexpr uint32_t B_RD = SM_BAR, B_ED = SM_BAR + 16, B_F = SM_BAR + 32, B_AT = SM_BAR + 56, B_L = SM_BAR + 264;
constexpr uint32_t B_AE = SM_BAR + 72, B_QE = SM_BAR + 88, B_ST = SM_BAR + 96, B_CS = SM_BAR + 112;
constexpr uint32_t B_WO = SM_BAR + 120, B_W6 = SM_BAR + 128, B_U = SM_BAR + 144, B_E = SM_BAR + 152, B_A = SM_BAR + 160, B_O = SM_BAR + 192,
                   B_Z = SM_BAR + 256, B_WF = SM_BAR + 272, B_W4 = SM_BAR + 280, B_N = SM_BAR + 288, B_V = SM_BAR + 296;
constexpr int NB_U = 1, NB_B = 2, NB_K = 8, NB_Y = 6, NB_WG = 8, NB_T = 10, NB_AUX = 12, NB_P0 = 13, NB_H = 15;

struct Scratch {
  uint4    XG[2][128 * 1024];
  uint4    O[32 * 8 * 512];
  uint32_t C[8 * 32];
  uint32_t OF[2][32 * 32];
  uint4    CS[16 * 1536 / 4];
  uint4    PS[128 * 64];
  uint4    ST[2][32 * 128];
  uint4    SR[2][8][512];
  uint4    XF[2][32 * 512 * 8];
  uint4    H[2][17 * 8 * 256];
};
__device__ __align__(1024) Scratch g_S;
#define SCR ((Scratch*)(P.mid - offsetof(Scratch, C)))
#define PROFD(slot, v) do {} while (0)
#define PROF(slot) do {} while (0)
#define PROFK(slot) do {} while (0)

DEV uint32_t s2u(const void* p) { return (uint32_t)__cvta_generic_to_shared(p); }
template <class T> DEV T* opqp(T* x) { asm volatile("" : "+l"(x)); return x; }
template <class T> DEV T opq(T x) { asm volatile("" : "+r"(x)); return x; }
DEV int lane_id() { int l; asm volatile("mov.u32 %0,%%laneid;" : "=r"(l)); return l; }
DEV uint32_t pack2(float lo, float hi) { uint32_t d; asm("cvt.rn.bf16x2.f32 %0,%1,%2;" : "=r"(d) : "f"(hi), "f"(lo)); return d; }
DEV float bflo(uint32_t v) { return __uint_as_float(v << 16); }
DEV float bfhi(uint32_t v) { return __uint_as_float(v & 0xFFFF0000u); }
DEV float bfr(float x) { return bflo(pack2(x, 0.f)); }
DEV uint32_t hadd2(uint32_t a, uint32_t b) { uint32_t d; asm("add.rn.bf16x2 %0,%1,%2;" : "=r"(d) : "r"(a), "r"(b)); return d; }
DEV uint32_t hsub2(uint32_t a, uint32_t b) { uint32_t d; asm("sub.rn.bf16x2 %0,%1,%2;" : "=r"(d) : "r"(a), "r"(b)); return d; }
DEV uint32_t hmul2(uint32_t a, uint32_t b) { uint32_t d; asm("mul.rn.bf16x2 %0,%1,%2;" : "=r"(d) : "r"(a), "r"(b)); return d; }
DEV uint32_t hfma2(uint32_t a, uint32_t b, uint32_t c) { uint32_t d; asm("fma.rn.bf16x2 %0,%1,%2,%3;" : "=r"(d) : "r"(a), "r"(b), "r"(c)); return d; }
DEV uint32_t hmax2(uint32_t a, uint32_t b) { uint32_t d; asm("max.bf16x2 %0,%1,%2;" : "=r"(d) : "r"(a), "r"(b)); return d; }
DEV uint32_t prmt(uint32_t a, uint32_t b, uint32_t s) { uint32_t d; asm("prmt.b32 %0,%1,%2,%3;" : "=r"(d) : "r"(a), "r"(b), "r"(s)); return d; }
DEV uint32_t nzmap(uint32_t v) { uint32_t d; asm("max.u32 %0,%1,1;" : "=r"(d) : "r"(v)); return d; }
DEV float rcp(float x) { float y; asm("rcp.approx.ftz.f32 %0,%1;" : "=f"(y) : "f"(x)); return y; }
DEV float sqrt_(float x) { float y; asm("sqrt.approx.ftz.f32 %0,%1;" : "=f"(y) : "f"(x)); return y; }
DEV float ex2(float x) { float y; asm("ex2.approx.ftz.f32 %0,%1;" : "=f"(y) : "f"(x)); return y; }

DEV uint4 ldr4(const void* p) { uint4 v; asm volatile("ld.relaxed.gpu.global.v4.u32 {%0,%1,%2,%3},[%4];" : "=r"(v.x), "=r"(v.y), "=r"(v.z), "=r"(v.w) : "l"(p) : "memory"); return v; }
DEV void ldr4_if(uint4& v, const void* p, bool c) {
  asm volatile("{.reg .pred q; setp.ne.u32 q,%5,0; @q ld.relaxed.gpu.global.v4.u32 {%0,%1,%2,%3},[%4];}"
    : "+r"(v.x), "+r"(v.y), "+r"(v.z), "+r"(v.w) : "l"(p), "r"((uint32_t)c) : "memory");
}
DEV uint2 ldr2(const void* p) { uint2 v; asm volatile("ld.relaxed.gpu.global.v2.u32 {%0,%1},[%2];" : "=r"(v.x), "=r"(v.y) : "l"(p) : "memory"); return v; }
DEV void ldr2_if(uint2& v, const void* p, bool c) {
  asm volatile("{.reg .pred q; setp.ne.u32 q,%3,0; @q ld.relaxed.gpu.global.v2.u32 {%0,%1},[%2];}" : "+r"(v.x), "+r"(v.y) : "l"(p), "r"((uint32_t)c) : "memory");
}
DEV uint32_t ldr1(const void* p) { uint32_t v; asm volatile("ld.relaxed.gpu.global.u32 %0,[%1];" : "=r"(v) : "l"(p) : "memory"); return v; }
DEV float ldnan(const uint16_t* p) {
  uint32_t v = 0xFFFFu;
#pragma unroll 1
  for (int it = 0; it < SPIN_LIMIT && __any_sync(0xffffffffu, v == 0xFFFFu); ++it) asm volatile("ld.relaxed.gpu.global.u16 %0,[%1];" : "=r"(v) : "l"(p) : "memory");
  return __uint_as_float(v << 16);
}
DEV uint4 ldw4(const void* p) { uint4 v; asm volatile("ld.global.v4.u32 {%0,%1,%2,%3},[%4];" : "=r"(v.x), "=r"(v.y), "=r"(v.z), "=r"(v.w) : "l"(p) : "memory"); return v; }
DEV uint2 ldw2(const void* p) { uint2 v; asm volatile("ld.global.v2.u32 {%0,%1},[%2];" : "=r"(v.x), "=r"(v.y) : "l"(p) : "memory"); return v; }
DEV uint32_t ldw1(const void* p) { uint32_t v; asm volatile("ld.global.u32 %0,[%1];" : "=r"(v) : "l"(p) : "memory"); return v; }
DEV void str4(void* p, uint32_t a, uint32_t b, uint32_t c, uint32_t d) { asm volatile("st.relaxed.gpu.global.v4.u32 [%0],{%1,%2,%3,%4};" :: "l"(p), "r"(a), "r"(b), "r"(c), "r"(d) : "memory"); }
DEV void str2(void* p, uint32_t a, uint32_t b) { asm volatile("st.relaxed.gpu.global.v2.u32 [%0],{%1,%2};" :: "l"(p), "r"(a), "r"(b) : "memory"); }
DEV void str1(void* p, uint32_t a) { asm volatile("st.relaxed.gpu.global.u32 [%0],%1;" :: "l"(p), "r"(a) : "memory"); }
DEV void str4_if(void* p, uint32_t a, uint32_t b, uint32_t c, uint32_t d, bool q) {
  asm volatile("{.reg .pred q; setp.ne.u32 q,%5,0; @q st.relaxed.gpu.global.v4.u32 [%0],{%1,%2,%3,%4};}" :: "l"(p), "r"(a), "r"(b), "r"(c), "r"(d), "r"((uint32_t)q) : "memory");
}
DEV void stw4(void* p, uint32_t a, uint32_t b, uint32_t c, uint32_t d) { asm volatile("st.global.v4.u32 [%0],{%1,%2,%3,%4};" :: "l"(p), "r"(a), "r"(b), "r"(c), "r"(d) : "memory"); }
DEV uint4 ldnc4(const void* p) { uint4 v; asm volatile("ld.global.nc.v4.u32 {%0,%1,%2,%3},[%4];" : "=r"(v.x), "=r"(v.y), "=r"(v.z), "=r"(v.w) : "l"(p)); return v; }
DEV uint32_t ldnc1(const void* p) { uint32_t v; asm volatile("ld.global.nc.u32 %0,[%1];" : "=r"(v) : "l"(p)); return v; }
DEV uint2 ldnc2(const void* p) { uint2 v; asm volatile("ld.global.nc.v2.u32 {%0,%1},[%2];" : "=r"(v.x), "=r"(v.y) : "l"(p)); return v; }

DEV uint2 lds2(uint32_t a) { uint2 v; asm volatile("ld.volatile.shared.v2.u32 {%0,%1},[%2];" : "=r"(v.x), "=r"(v.y) : "r"(a)); return v; }
DEV float lds16f(uint32_t a) { uint32_t v; asm volatile("ld.shared.u16 %0,[%1];" : "=r"(v) : "r"(a)); return __uint_as_float(v << 16); }
DEV void sts2(uint32_t a, uint32_t x, uint32_t y) { asm volatile("st.shared.v2.u32 [%0],{%1,%2};" :: "r"(a), "r"(x), "r"(y) : "memory"); }
DEV uint32_t lds1(uint32_t a) { uint32_t v; asm volatile("ld.volatile.shared.u32 %0,[%1];" : "=r"(v) : "r"(a)); return v; }
DEV uint32_t lds1z(uint32_t a, bool c) {
  uint32_t v; asm volatile("{.reg .pred q; setp.ne.u32 q,%2,0; mov.u32 %0,0; @q ld.volatile.shared.u32 %0,[%1];}" : "=r"(v) : "r"(a), "r"((uint32_t)c)); return v;
}
DEV uint4 lds4z(uint32_t a, bool c) {
  uint4 v = make_uint4(0, 0, 0, 0);
  asm volatile("{.reg .pred q; setp.ne.u32 q,%5,0; @q ld.volatile.shared.v4.u32 {%0,%1,%2,%3},[%4];}" : "+r"(v.x), "+r"(v.y), "+r"(v.z), "+r"(v.w) : "r"(a), "r"((uint32_t)c));
  return v;
}
DEV float lds1f(uint32_t a) { float v; asm volatile("ld.shared.f32 %0,[%1];" : "=f"(v) : "r"(a)); return v; }
DEV float2 lds2f(uint32_t a) { float2 v; asm volatile("ld.shared.v2.f32 {%0,%1},[%2];" : "=f"(v.x), "=f"(v.y) : "r"(a)); return v; }
DEV float4 lds4f(uint32_t a) { float4 v; asm volatile("ld.volatile.shared.v4.f32 {%0,%1,%2,%3},[%4];" : "=f"(v.x), "=f"(v.y), "=f"(v.z), "=f"(v.w) : "r"(a)); return v; }
DEV uint4 lds4(uint32_t a) { uint4 v; asm volatile("ld.volatile.shared.v4.u32 {%0,%1,%2,%3},[%4];" : "=r"(v.x), "=r"(v.y), "=r"(v.z), "=r"(v.w) : "r"(a)); return v; }
DEV void sts1(uint32_t a, uint32_t v) { asm volatile("st.shared.u32 [%0],%1;" :: "r"(a), "r"(v) : "memory"); }
DEV void sts16(uint32_t a, uint32_t v) { asm volatile("st.shared.u16 [%0],%1;" :: "r"(a), "r"(v) : "memory"); }
DEV void sts2f(uint32_t a, float x, float y) { asm volatile("st.shared.v2.f32 [%0],{%1,%2};" :: "r"(a), "f"(x), "f"(y) : "memory"); }
DEV void sts4f(uint32_t a, float x, float y, float z, float w) { asm volatile("st.shared.v4.f32 [%0],{%1,%2,%3,%4};" :: "r"(a), "f"(x), "f"(y), "f"(z), "f"(w) : "memory"); }
DEV void sts4(uint32_t a, uint32_t x, uint32_t y, uint32_t z, uint32_t w) { asm volatile("st.shared.v4.u32 [%0],{%1,%2,%3,%4};" :: "r"(a), "r"(x), "r"(y), "r"(z), "r"(w) : "memory"); }

DEV void ldsm4(uint32_t (&r)[4], uint32_t a) { asm volatile("ldmatrix.sync.aligned.m8n8.x4.shared.b16 {%0,%1,%2,%3},[%4];" : "=r"(r[0]), "=r"(r[1]), "=r"(r[2]), "=r"(r[3]) : "r"(a) : "memory"); }
DEV void ldsm4t(uint32_t (&r)[4], uint32_t a) { asm volatile("ldmatrix.sync.aligned.m8n8.x4.trans.shared.b16 {%0,%1,%2,%3},[%4];" : "=r"(r[0]), "=r"(r[1]), "=r"(r[2]), "=r"(r[3]) : "r"(a) : "memory"); }
DEV void ldsm2(uint32_t (&r)[2], uint32_t a) { asm volatile("ldmatrix.sync.aligned.m8n8.x2.shared.b16 {%0,%1},[%2];" : "=r"(r[0]), "=r"(r[1]) : "r"(a) : "memory"); }
DEV void stsm4(uint32_t a, uint32_t r0, uint32_t r1, uint32_t r2, uint32_t r3) { asm volatile("stmatrix.sync.aligned.m8n8.x4.shared.b16 [%0],{%1,%2,%3,%4};" :: "r"(a), "r"(r0), "r"(r1), "r"(r2), "r"(r3) : "memory"); }
DEV void stsm2(uint32_t a, uint32_t r0, uint32_t r1) { asm volatile("stmatrix.sync.aligned.m8n8.x2.shared.b16 [%0],{%1,%2};" :: "r"(a), "r"(r0), "r"(r1) : "memory"); }
DEV void stsm4t(uint32_t a, uint32_t r0, uint32_t r1, uint32_t r2, uint32_t r3) { asm volatile("stmatrix.sync.aligned.m8n8.x4.trans.shared.b16 [%0],{%1,%2,%3,%4};" :: "r"(a), "r"(r0), "r"(r1), "r"(r2), "r"(r3) : "memory"); }
DEV uint32_t movm(uint32_t a) { uint32_t d; asm volatile("movmatrix.sync.aligned.m8n8.trans.b16 %0,%1;" : "=r"(d) : "r"(a)); return d; }
DEV void mma16(float (&d)[4], uint32_t a0, uint32_t a1, uint32_t a2, uint32_t a3, uint32_t b0, uint32_t b1) {
  asm volatile("mma.sync.aligned.m16n8k16.row.col.f32.bf16.bf16.f32 {%0,%1,%2,%3},{%4,%5,%6,%7},{%8,%9},{%0,%1,%2,%3};"
    : "+f"(d[0]), "+f"(d[1]), "+f"(d[2]), "+f"(d[3]) : "r"(a0), "r"(a1), "r"(a2), "r"(a3), "r"(b0), "r"(b1));
}
DEV void mma16z(float (&d)[4], uint32_t a0, uint32_t a1, uint32_t a2, uint32_t a3, uint32_t b0, uint32_t b1) {
  asm volatile("mma.sync.aligned.m16n8k16.row.col.f32.bf16.bf16.f32 {%0,%1,%2,%3},{%4,%5,%6,%7},{%8,%9},{%10,%10,%10,%10};"
    : "=f"(d[0]), "=f"(d[1]), "=f"(d[2]), "=f"(d[3]) : "r"(a0), "r"(a1), "r"(a2), "r"(a3), "r"(b0), "r"(b1), "f"(0.f));
}
DEV void mma8(float (&d)[4], uint32_t a0, uint32_t a1, uint32_t b0) {
  asm volatile("mma.sync.aligned.m16n8k8.row.col.f32.bf16.bf16.f32 {%0,%1,%2,%3},{%4,%5},{%6},{%0,%1,%2,%3};"
    : "+f"(d[0]), "+f"(d[1]), "+f"(d[2]), "+f"(d[3]) : "r"(a0), "r"(a1), "r"(b0));
}

DEV void mma8z(float (&d)[4], uint32_t a0, uint32_t a1, uint32_t b0) {
  asm volatile("mma.sync.aligned.m16n8k8.row.col.f32.bf16.bf16.f32 {%0,%1,%2,%3},{%4,%5},{%6},{%7,%7,%7,%7};"
    : "=f"(d[0]), "=f"(d[1]), "=f"(d[2]), "=f"(d[3]) : "r"(a0), "r"(a1), "r"(b0), "f"(0.f));
}
DEV void bar_sync(int id, int n) { asm volatile("bar.sync %0,%1;" :: "r"(id), "r"(n) : "memory"); }
DEV void bar_sync_if(int id, int n, int c) { asm volatile("{.reg .pred q; setp.ne.s32 q,%2,0; @q bar.sync %0,%1;}" :: "r"(id), "r"(n), "r"(c) : "memory"); }
DEV void bar_arrive_if(int id, int n, int c) { asm volatile("{.reg .pred q; setp.ne.s32 q,%2,0; @q bar.arrive %0,%1;}" :: "r"(id), "r"(n), "r"(c) : "memory"); }
DEV bool bar_any(int id, int n, bool c) {
  uint32_t r; asm volatile("{.reg .pred p,q; setp.ne.u32 q,%3,0; bar.red.or.pred p,%1,%2,q; selp.u32 %0,1,0,p;}" : "=r"(r) : "r"(id), "r"(n), "r"((uint32_t)c) : "memory");
  return __any_sync(0xffffffffu, r);
}
DEV void bar_arrive(int id, int n) { asm volatile("bar.arrive %0,%1;" :: "r"(id), "r"(n) : "memory"); }
DEV void fence_async_glob() { asm volatile("fence.proxy.async.global;" ::: "memory"); }
DEV void fence_async_smem() { asm volatile("fence.proxy.async.shared::cta;" ::: "memory"); }
DEV void mbar_init(uint32_t b, int n) { asm volatile("mbarrier.init.shared::cta.b64 [%0],%1;" :: "r"(b), "r"(n) : "memory"); }
DEV void mbar_arrive(uint32_t b) { asm volatile("mbarrier.arrive.shared::cta.b64 _,[%0];" :: "r"(b) : "memory"); }
DEV void mbar_expect(uint32_t b, int bytes) { asm volatile("mbarrier.arrive.expect_tx.shared::cta.b64 _,[%0],%1;" :: "r"(b), "r"(bytes) : "memory"); }
DEV void mbar_wait(uint32_t b, uint32_t ph) {
  asm volatile("{\n.reg .pred p;\nW: mbarrier.try_wait.parity.shared::cta.b64 p,[%0],%1;\n@!p bra W;\n}" :: "r"(b), "r"(ph) : "memory");
}
DEV void mbar_watch(uint32_t b, uint32_t ph) {
  asm volatile("{\n.reg .pred p,q;\n.reg .u32 n;\nmov.u32 n,0;\n"
               "W: mbarrier.try_wait.parity.shared::cta.b64 p,[%0],%1;\n@p bra D;\n"
               "add.u32 n,n,1;\nsetp.lt.u32 q,n,%2;\n@q bra W;\ntrap;\nD:\n}"
               :: "r"(b), "r"(ph), "n"(SPIN_LIMIT) : "memory");
}
DEV void spin_guard(int it) { asm volatile("{.reg .pred p; setp.gt.s32 p,%0,%1; @p trap;}" :: "r"(it), "n"(SPIN_LIMIT)); }
DEV void split(uint32_t zero) {
  asm volatile("{.reg .pred p; setp.ne.u32 p,%0,0; @p trap;}" :: "r"(zero) : "memory");
}
DEV void pause(int n) {
  uint32_t t0, t; asm volatile("mov.u32 %0,%%clock;" : "=r"(t0));
  do asm volatile("mov.u32 %0,%%clock;" : "=r"(t)); while (t - t0 < n);
}
DEV void poll(const uint32_t* k, uint32_t n) {
#pragma unroll 1
  for (int it = 0;; ++it) {
    spin_guard(it);
    if (__all_sync(0xffffffffu, ldr1(k) >= n)) break;
  }
}
DEV void mbar_arrive1(uint32_t b) { asm volatile("{.reg .pred p; elect.sync _|p,0xffffffff; @p mbarrier.arrive.shared::cta.b64 _,[%0];}" :: "r"(b) : "memory"); }
DEV void mbar_arrive1_if(uint32_t b, int c) {
  asm volatile("{.reg .pred p,q; setp.ne.s32 q,%1,0; elect.sync _|p,0xffffffff; and.pred p,p,q; @p mbarrier.arrive.shared::cta.b64 _,[%0];}" :: "r"(b), "r"(c) : "memory");
}
DEV void mbar_expect1(uint32_t b, int bytes) { asm volatile("{.reg .pred p; elect.sync _|p,0xffffffff; @p mbarrier.arrive.expect_tx.shared::cta.b64 _,[%0],%1;}" :: "r"(b), "r"(bytes) : "memory"); }
DEV void cnt_add1(uint32_t* q) { asm volatile("{.reg .pred p; elect.sync _|p,0xffffffff; @p red.relaxed.gpu.global.add.u32 [%0],1;}" :: "l"(q) : "memory"); }
DEV void tma4(uint32_t dst, const CUtensorMap* m, int c0, int c1, int c2, int c3, uint32_t bar) {
  asm volatile("{.reg .pred p; elect.sync _|p,0xffffffff;\n"
    "@p cp.async.bulk.tensor.4d.shared::cluster.global.mbarrier::complete_tx::bytes [%0],[%1,{%2,%3,%4,%5}],[%6];}"
    :: "r"(dst), "l"(m), "r"(c0), "r"(c1), "r"(c2), "r"(c3), "r"(bar) : "memory");
}
DEV void tma3(uint32_t dst, const CUtensorMap* m, int c0, int c1, int c2, uint32_t bar) {
  asm volatile("{.reg .pred p; elect.sync _|p,0xffffffff;\n"
    "@p cp.async.bulk.tensor.3d.shared::cluster.global.mbarrier::complete_tx::bytes [%0],[%1,{%2,%3,%4}],[%5];}"
    :: "r"(dst), "l"(m), "r"(c0), "r"(c1), "r"(c2), "r"(bar) : "memory");
}
DEV void bulk(uint32_t dst, const void* src, int bytes, uint32_t bar) {
  asm volatile("{.reg .pred p; elect.sync _|p,0xffffffff;\n@p cp.async.bulk.shared::cluster.global.mbarrier::complete_tx::bytes [%0],[%1],%2,[%3];}" :: "r"(dst), "l"(src), "r"(bytes), "r"(bar) : "memory");
}

DEV void bulk_store(void* dst, uint32_t src, int bytes) {
  asm volatile("{.reg .pred p; elect.sync _|p,0xffffffff;\n@p cp.async.bulk.global.shared::cta.bulk_group [%0],[%1],%2;}" :: "l"(dst), "r"(src), "r"(bytes) : "memory");
}
DEV void tma2_store(const CUtensorMap* m, uint32_t src, int c0, int c1) {
  asm volatile("{.reg .pred p; elect.sync _|p,0xffffffff;\n@p cp.async.bulk.tensor.2d.global.shared::cta.bulk_group [%0,{%2,%3}],[%1];}" :: "l"(m), "r"(src), "r"(c0), "r"(c1) : "memory");
}
DEV void bulk_wait() { asm volatile("cp.async.bulk.commit_group;\ncp.async.bulk.wait_group 0;\nfence.proxy.async.global;" ::: "memory"); }

DEV uint32_t dlo(uint32_t addr, uint32_t lbo) { return __shfl_sync(0xffffffffu, (addr >> 4) | ((lbo >> 4) << 16), 0); }
__host__ __device__ constexpr uint32_t dhi(uint32_t sbo, uint32_t swz) { return (sbo >> 4) | (swz << 30); }
DEV void wg_fence() { asm volatile("wgmma.fence.sync.aligned;" ::: "memory"); }
DEV void wg_commit() { asm volatile("wgmma.commit_group.sync.aligned;" ::: "memory"); }
template <int N> DEV void wg_wait() { asm volatile("wgmma.wait_group.sync.aligned %0;" :: "n"(N) : "memory"); }
template <int N> DEV void zero(float (&d)[N]) {
#pragma unroll
  for (int i = 0; i < N; ++i) d[i] = 0.f;
}
template <int N> DEV void zerov(float (&d)[N]) {
#pragma unroll
  for (int i = 0; i < N; ++i) asm volatile("mov.b32 %0,0;" : "=f"(d[i]));
}
template <int N> DEV void undef(float (&d)[N]) {
#pragma unroll
  for (int i = 0; i < N; ++i) asm volatile("" : "=f"(d[i]));
}
#define R4(d, o) "+f"(d[o]), "+f"(d[o + 1]), "+f"(d[o + 2]), "+f"(d[o + 3])
#define R8(d, o) R4(d, o), R4(d, o + 4)
#define R16(d, o) R8(d, o), R8(d, o + 8)
template <int ACC> DEV void wg_rs64k(float (&d)[32], const uint32_t (&a)[4], uint32_t db) {
  asm volatile("{.reg .pred p; .reg .b64 b; setp.ne.s32 p,%38,0; mov.b64 b,{%36,%37};\n"
    "wgmma.mma_async.sync.aligned.m64n64k16.f32.bf16.bf16 {%0,%1,%2,%3,%4,%5,%6,%7,%8,%9,%10,%11,%12,%13,%14,%15,%16,%17,%18,%19,%20,%21,%22,%23,%24,%25,%26,%27,%28,%29,%30,%31},{%32,%33,%34,%35},b,p,1,1,0;}"
    : R16(d, 0), R16(d, 16) : "r"(a[0]), "r"(a[1]), "r"(a[2]), "r"(a[3]), "r"(db), "n"(dhi(512, 2)), "n"(ACC));
}
template <int ACC> DEV void wg_rs48t(float (&d)[24], const uint32_t (&a)[4], uint32_t db) {
  asm volatile("{.reg .pred p; .reg .b64 b; setp.ne.s32 p,%30,0; mov.b64 b,{%28,%29};\n"
    "wgmma.mma_async.sync.aligned.m64n48k16.f32.bf16.bf16 {%0,%1,%2,%3,%4,%5,%6,%7,%8,%9,%10,%11,%12,%13,%14,%15,%16,%17,%18,%19,%20,%21,%22,%23},{%24,%25,%26,%27},b,p,1,1,1;}"
    : R16(d, 0), R8(d, 16) : "r"(a[0]), "r"(a[1]), "r"(a[2]), "r"(a[3]), "r"(db), "n"(dhi(512, 0)), "n"(ACC));
}
template <int ACC> DEV void wg_rs32t(float (&d)[16], const uint32_t (&a)[4], uint32_t db) {
  asm volatile("{.reg .pred p; .reg .b64 b; setp.ne.s32 p,%22,0; mov.b64 b,{%20,%21};\n"
    "wgmma.mma_async.sync.aligned.m64n32k16.f32.bf16.bf16 {%0,%1,%2,%3,%4,%5,%6,%7,%8,%9,%10,%11,%12,%13,%14,%15},{%16,%17,%18,%19},b,p,1,1,1;}"
    : R16(d, 0) : "r"(a[0]), "r"(a[1]), "r"(a[2]), "r"(a[3]), "r"(db), "n"(dhi(1024, 0)), "n"(ACC));
}
template <int ACC> DEV void wg_ss192(float (&d)[96], uint32_t da, uint32_t db) {
  asm volatile("{.reg .pred p; .reg .b64 a,b; setp.ne.s32 p,%100,0; mov.b64 a,{%96,%98}; mov.b64 b,{%97,%99};\n"
    "wgmma.mma_async.sync.aligned.m64n192k16.f32.bf16.bf16 {"
    "%0,%1,%2,%3,%4,%5,%6,%7,%8,%9,%10,%11,%12,%13,%14,%15,%16,%17,%18,%19,%20,%21,%22,%23,%24,%25,%26,%27,%28,%29,%30,%31,"
    "%32,%33,%34,%35,%36,%37,%38,%39,%40,%41,%42,%43,%44,%45,%46,%47,%48,%49,%50,%51,%52,%53,%54,%55,%56,%57,%58,%59,%60,%61,%62,%63,"
    "%64,%65,%66,%67,%68,%69,%70,%71,%72,%73,%74,%75,%76,%77,%78,%79,%80,%81,%82,%83,%84,%85,%86,%87,%88,%89,%90,%91,%92,%93,%94,%95},a,b,p,1,1,1,1;}"
    : R16(d, 0), R16(d, 16), R16(d, 32), R16(d, 48), R16(d, 64), R16(d, 80) : "r"(da), "r"(db), "n"(dhi(1024, 1)), "n"(dhi(1024, 1)), "n"(ACC));
}
template <int ACC> DEV void wg_ss64(float (&d)[32], uint32_t da, uint32_t db) {
  asm volatile("{.reg .pred p; .reg .b64 a,b; setp.ne.s32 p,%36,0; mov.b64 a,{%32,%34}; mov.b64 b,{%33,%35};\n"
    "wgmma.mma_async.sync.aligned.m64n64k16.f32.bf16.bf16 {"
    "%0,%1,%2,%3,%4,%5,%6,%7,%8,%9,%10,%11,%12,%13,%14,%15,%16,%17,%18,%19,%20,%21,%22,%23,%24,%25,%26,%27,%28,%29,%30,%31},a,b,p,1,1,0,1;}"
    : R16(d, 0), R16(d, 16) : "r"(da), "r"(db), "n"(dhi(1024, 0)), "n"(dhi(1024, 1)), "n"(ACC));
}

DEV uint32_t cpy(uint32_t v, uint32_t id) {
  uint32_t d; asm volatile("prmt.b32 %0,%1,%1,%2;" : "=r"(d) : "r"(v), "r"(id)); return d;
}
struct Params {
  uint32_t zero, spare;
  char* mid;
  const uint16_t *x0, *Are, *Aim, *Bre, *Bim, *Cre, *Cim, *logdt, *dskip, *wqkv, *wo;
  uint16_t* out;
  uint8_t role[72];
};

DEV uint32_t ln_word(float mean, float var) {
  float v = bfr(var);
  float s = sqrt_(bfr(v + 1e-5f));
  return pack2(mean, s);
}

DEV int stat_group(int c) { return c ^ 4; }
DEV int xg_off(int G, int g) { return (G >> 6) * 1024 + (G & 63) * 8 + (g ^ (G & 2)); }
DEV int sr_off(int G, int g) { return (G >> 6) * 256 + (g & 2) * 64 + 2 * (G & 63) + ((g >> 2) & 1); }
DEV uint32_t region(int chl) { return SM_A + (chl >> 1) * A_E + (chl & 1) * R_SZ; }
template <bool FIRST> DEV void gram(float (&s)[4], float (&q0)[4], float (&q1)[4], uint32_t a0, uint32_t a1, uint32_t a2, uint32_t a3) {
  const uint32_t one = 0x3F803F80u;
  if (FIRST) { mma16z(s, a0, a1, a2, a3, one, one); mma8z(q0, a0, a1, a0); mma8z(q1, a0, a1, a1); }
  else { mma16(s, a0, a1, a2, a3, one, one); mma8(q0, a0, a1, a0); mma8(q1, a0, a1, a1); }
  mma8(q0, a2, a3, a2); mma8(q1, a2, a3, a3);
}
DEV uint32_t ln_sums(float s, float q) { const float m = s * (1.f / 512.f); return ln_word(m, fmaxf(q * (1.f / 512.f) - m * m, 0.f)); }
DEV void cmul(float& orr, float& oi, float ar, float ai, float br, float bi) {
  float r = ar * br - ai * bi, i = ar * bi + ai * br; orr = r; oi = i;
}
DEV void cexp_(float al, float bt, float s, float& er, float& ei) {
  float mag = ex2(al * s), ph = bt * s;
  ph -= rintf(ph);
  float ang = ph * 6.283185307179586f;
  er = mag * __cosf(ang); ei = mag * __sinf(ang);
}

DEV void kgen(const Params& P, int c, int wm, int lane) {
  const int chl = wm >> 1, mh = wm & 1, g = lane >> 2, t = lane & 3;
  const int ch = 256 * (chl >> 1) + 2 * c + (chl & 1);
  const int mo = ch * 64 + mh * 32 + lane;
  const uint32_t vAr = ldw1((const uint32_t*)P.Are + mo), vAi = ldw1((const uint32_t*)P.Aim + mo);
  const uint32_t vBr = ldw1((const uint32_t*)P.Bre + mo), vBi = ldw1((const uint32_t*)P.Bim + mo);
  const uint32_t vCr = ldw1((const uint32_t*)P.Cre + mo), vCi = ldw1((const uint32_t*)P.Cim + mo);
  const uint32_t vld = ldw1((const uint32_t*)P.logdt + (ch >> 1)), vds = ldw1((const uint32_t*)P.dskip + (ch >> 1));
  bar_arrive(NB_Y, 384);
  PROF(45);
  {
    const uint32_t tz = SM_TAP + chl * TAP_SZ + (mh * 32 + lane) * 16;
#pragma unroll
    for (int k = 0; k < 3; ++k) sts4(tz + k * 1024, 0, 0, 0, 0);
    static_assert(TAP_SZ > 3072 && TAP_SZ <= 4096, "");
    if (mh * 32 + lane < TAP_SZ / 16 - 192) sts4(tz + 3072, 0, 0, 0, 0);
  }
  const uint32_t tb = slot(wm), tw = opq(tb + lane * 4);
  const uint32_t aa = opq(tb + (lane & 15) * 144 + (lane >> 4) * 16), ba = opq(tb + (16 + (lane & 7)) * 144 + (lane >> 3) * 16);
  float acc[5][4], k2048 = 0.f;
#pragma unroll
  for (int i = 0; i < 5; ++i) zerov(acc[i]);
  sts1(tw, 0x3F80u);
  asm volatile("setmaxnreg.inc.sync.aligned.u32 %0;" :: "n"(REG_MAIN));
  PROF(44);
  const float dt = bfr(ex2((ch & 1 ? bfhi(vld) : bflo(vld)) * 1.4426950408889634f));
#pragma unroll 1
  for (int r = 0; r < 2; ++r) {
    const uint32_t sel = r ? 0x3244 : 0x1044;
    const float are = __uint_as_float(prmt(vAr, 0, sel)), aim = __uint_as_float(prmt(vAi, 0, sel)), bre = __uint_as_float(prmt(vBr, 0, sel));
    const float bim = __uint_as_float(prmt(vBi, 0, sel)), cre = __uint_as_float(prmt(vCr, 0, sel)), cim = __uint_as_float(prmt(vCi, 0, sel));
    const float al = dt * are * 1.4426950408889634f, bt = dt * aim * 0.15915494309189535f;
    float qr, qi; cmul(qr, qi, cre, cim, dt * bre, dt * bim);
    if (r == 0) PROFD(2, __float_as_uint(qr + al + bt));
    float er[3], ei[3], e8r, e8i, eLr, eLi;
    cexp_(al, bt, 1.f, er[0], ei[0]); cexp_(al, -bt, 8.f, e8r, e8i); cexp_(al, bt, 128.f, eLr, eLi);
    cmul(er[1], ei[1], er[0], ei[0], er[0], ei[0]); cmul(er[2], ei[2], er[1], ei[1], er[1], ei[1]);
    float yr = e8r, yi = e8i;
#pragma unroll
    for (int a = 0; a < 16; ++a) {
      if (a) sts1(tw + a * 144, pack2(yr, yi));
      if (a && a < 15) cmul(yr, yi, yr, yi, e8r, e8i);
      const int ls = a < 2 ? 0 : a < 4 ? 1 : a < 8 ? 2 : 3;
      const int row0 = 16 + (a < 2 ? 8 * a : a < 4 ? 16 + 4 * (a - 2) : a < 8 ? 24 + 2 * (a - 4) : 32 + (a - 8));
      float xr[8], xi[8];
      xr[0] = qr; xi[0] = qi;
#pragma unroll
      for (int k = 0; k < (8 >> ls); ++k) {
        const int hb = k >= 4 ? 2 : k >= 2 ? 1 : 0;
        if (k) cmul(xr[k], xi[k], xr[k - (1 << hb)], xi[k - (1 << hb)], er[(ls + hb) % 3], ei[(ls + hb) % 3]);
        sts1(tw + (row0 + k) * 144, pack2(xr[k], xi[k]));
      }
      cmul(qr, qi, qr, qi, eLr, eLi);
    }
    __syncwarp();
    if (r == 0) PROF(3);
#pragma unroll
    for (int kp = 0; kp < 2; ++kp) {
      uint32_t a0[4], a1[4];
      ldsm4(a0, aa + kp * 64); ldsm4(a1, aa + kp * 64 + 32);
#pragma unroll
      for (int tl = 0; tl < 5; ++tl) {
        uint32_t b[4];
        ldsm4(b, ba + 8 * tl * 144 + kp * 64);
        if (kp == 0) qr += __shfl_xor_sync(0xffffffffu, qr, 1 << tl);
        mma16(acc[tl], a0[0], a0[1], a0[2], a0[3], b[0], b[1]);
        mma16(acc[tl], a1[0], a1[1], a1[2], a1[3], b[2], b[3]);
      }
    }
    k2048 += qr;
    __syncwarp();
  }
  const uint32_t xa = tb + lane * 16, ob = xa ^ 8192, tp = SM_TAP + chl * TAP_SZ;
  if (mh == 0) {
    sts4f(xa, acc[2][0], acc[2][1], acc[2][2], acc[2][3]);
    sts4f(xa + 512, acc[3][0], acc[3][1], acc[3][2], acc[3][3]);
    sts1(tb + 1024, __float_as_uint(k2048));
  } else {
    sts4f(xa, acc[0][0], acc[0][1], acc[0][2], acc[0][3]);
    sts4f(xa + 512, acc[1][0], acc[1][1], acc[1][2], acc[1][3]);
    sts4f(xa + 1024, acc[4][0], acc[4][1], acc[4][2], acc[4][3]);
  }
  PROF(4);
  bar_sync(NB_K + chl, 64);
  float4 o[3];
#pragma unroll
  for (int k = 0; k < 3; ++k) o[k] = lds4f(ob + k * 512);
  if (mh == 0) {
    if (lane == 0) o[0].x += ch & 1 ? bfhi(vds) : bflo(vds);
    const uint32_t a = tp - 2 * (8 * g + 2 * t + 1);
#pragma unroll
    for (int z = 0; z < 4; ++z) {
      const float* k = acc[z >> 1] + 2 * (z & 1);
      const uint32_t v = z & 1 ? pack2(k[1] + o[z >> 1].w, k[0] + o[z >> 1].z) : pack2(k[1] + o[z >> 1].y, k[0] + o[z >> 1].x);
      sts1(a + T_O - 128 * z, v); sts16(a + T_E - 128 * z, v); sts16(a + T_E + 2 - 128 * z, v >> 16);
    }
    const uint32_t v0 = pack2(acc[4][0] + o[2].x, acc[4][1] + o[2].y), v1 = pack2(acc[4][2] + o[2].z, acc[4][3] + o[2].w);
    const uint32_t b = tp + T_C - 2 * (32 * t + g - 1);
    if (lane == 0) { sts16(tp + T_E - 2 * (X_5 + 63), v0); sts16(tp + T_O - 2 * (X_5 + 63), v0); sts1(tp + T_K, prmt(v0, v0, 0x1010)); }
    else sts16(b, v0);
    sts16(b - 32, v0 >> 16); sts16(b - 16, v1); sts16(b - 48, v1 >> 16);
  } else {
    const uint32_t a = tp - 2 * (256 + 128 * (t >> 1) + 4 * (t & 1) + 8 * g);
#pragma unroll
    for (int z = 0; z < 2; ++z) {
      const uint32_t v = z ? pack2(acc[2][3] + o[0].w, acc[2][2] + o[0].z) : pack2(acc[2][1] + o[0].y, acc[2][0] + o[0].x), d = prmt(v, v, 0x3232);
      sts1(a + T_E - 4 - 128 * z, v); sts16(a + T_O - 4 - 128 * z, v); sts1(a + T_O - 2 - 128 * z, d);
      if (z || lane) { sts1(a + T_E - 128 * z, d); sts16(a + T_O + 2 - 128 * z, d); } else sts16(a + T_E, d);
    }
    const uint32_t w0 = pack2(acc[3][0] + o[1].x, acc[3][1] + o[1].y), w1 = pack2(acc[3][2] + o[1].z, acc[3][3] + o[1].w);
    const uint32_t b = tp - 2 * (16 * t + g);
    if (lane == 0) {
      const uint32_t k = prmt(w0, w0, 0x1010);
      sts1(tp + T_E - 2 * 514, k); sts1(tp + T_E - 2 * 512, k);
      sts16(tp + T_O - 2 * 514, k); sts1(tp + T_O - 2 * 513, k); sts16(tp + T_O - 2 * 511, k);
      sts16(tp + T_C - 2 * 127, pack2(k2048 + o[2].x, 0.f));
    } else { sts16(b + T_E - 2 * (X_5 - 1), w0); sts16(b + T_O - 2 * (X_5 - 1), w0); }
    sts16(b + T_E - 2 * X_3, w0 >> 16); sts16(b + T_O - 2 * X_3, w0 >> 16);
    sts16(b + T_E - 2 * (X_5 + 7), w1); sts16(b + T_O - 2 * (X_5 + 7), w1);
    sts16(b + T_E - 2 * (X_3 + 8), w1 >> 16); sts16(b + T_O - 2 * (X_3 + 8), w1 >> 16);
  }
}

DEV bool bad8(const uint4& v) { return min(v.x, v.z) == 0u; }
DEV uint32_t uchunk(uint32_t reg, int x) { return reg + R_U + (x ^ ((x >> 3) & 3)) * 16; }
DEV uint32_t& xword(uint4 (&x)[2], int e, int tp) { uint4& v = x[tp >> 1]; return tp & 1 ? (e ? v.w : v.z) : (e ? v.y : v.x); }

DEV void uprep(const Params& P, int c, int wa, int lane, int layer, uint4 (&x)[2][2][2], uint32_t (&u)[4][4]) {
  const int j = 32 * wa + lane, o0 = 2 * j + ((j >> 2) & 1);
  {
    const uint32_t za = region(wa) + lane * 16 - 512;
    sts4(za + R_U, 0, 0, 0, 0); sts4(za + R_X5, 0, 0, 0, 0); sts4(za + R_X3, 0, 0, 0, 0);
    sts4(region(wa) + R_BE, 0, 0, 0, 0);
  }
  const uint4* st = opqp(&SCR->SR[layer][c >> 4][j]);
  const uint32_t xa = opq(SM_X + 16 * o0), xb = opq(SM_X + 16 * (o0 ^ 1)), ua = opq(uchunk(0, j));
  uint4 s[2][2];
#pragma unroll
  for (int z = 0; z < 12; ++z) {
    uint4& v = z < 8 ? x[(z >> 2) & 1][(z >> 1) & 1][z & 1] : s[(z >> 1) & 1][z & 1];
    asm volatile("mov.b32 %0,0; mov.b32 %1,0; mov.b32 %2,0; mov.b32 %3,0;" : "=r"(v.x), "=r"(v.y), "=r"(v.z), "=r"(v.w));
  }
#pragma unroll 1
  for (uint32_t it = P.zero;; ++it) {
    if (it) {
      spin_guard(it);
#pragma unroll
      for (int z = 0; z < 4; ++z) { uint4& v = s[z >> 1][z & 1]; ldr4_if(v, st + z * 128, bad8(v)); }
      const uint4* xp = &SCR->XG[layer][c * 1024 + o0];
#pragma unroll
      for (int z = 0; z < 8; ++z) {
        uint4& v = x[z >> 2][(z >> 1) & 1][z & 1];
        ldr4_if(v, (const uint4*)((uintptr_t)xp ^ (16 * (z & 1))) + (z >> 1) * 256, bad8(v));
      }
    } else {
      mbar_wait(B_U, layer);
      PROF(layer ? 25 : 10);
#pragma unroll
      for (int z = 0; z < 4; ++z) s[z >> 1][z & 1] = ldr4(st + z * 128);
#pragma unroll
      for (int z = 0; z < 4; ++z) { uint4& v = s[z >> 1][z & 1]; ldr4_if(v, st + z * 128, bad8(v)); }
      PROF(layer ? 26 : 11);
      mbar_wait(B_E, layer);
#pragma unroll
      for (int z = 7; z >= 0; --z) x[z >> 2][(z >> 1) & 1][z & 1] = lds4((z & 1 ? xb : xa) + (z >> 1) * 4096);
      PROF(layer ? 27 : 14);
    }
    uint32_t m = ~0u;
#pragma unroll
    for (int z = 7; z >= 0; --z) {
      const int k = z >> 2, chl = z & 3;
#pragma unroll
      for (int tp = 0; tp < 4; ++tp) u[chl][tp] = hfma2(xword(x[k][chl >> 1], chl & 1, tp), xword(s[k], 0, tp), xword(s[k], 1, tp));
      sts4(ua + region(chl) + k * 2048, u[chl][0], u[chl][1], u[chl][2], u[chl][3]);
      const uint4& v = x[k][chl >> 1][chl & 1];
      m = min(m, min(v.x, v.z));
      if (z < 4) m = min(m, min(s[z >> 1][z & 1].x, s[z >> 1][z & 1].z));
    }
    if (!__any_sync(0xffffffffu, m == 0)) break;
  }
  PROF(4 + 12 * layer);
}

template <bool FULL> DEV void box_unit(uint32_t reg, int s, const uint2& a, const uint4& b, const uint32_t (&d)[4], uint32_t (&pv)[4]) {
  const uint32_t u[9] = {a.x, a.y, b.x, b.y, b.z, b.w, d[0], d[1], d[2]};
  uint32_t v[8], p[8];
#pragma unroll
  for (int j = 0; j < 8; ++j) { v[j] = prmt(u[j], u[j + 1], 0x5432); p[j] = hadd2(u[j], v[j]); }
  const uint32_t o = reg + s * 16;
  uint32_t x[4], y[4];
#pragma unroll
  for (int j = 0; j < 4; ++j) { x[j] = hadd2(hadd2(p[1 + j], p[2 + j]), u[3 + j]); y[j] = hadd2(v[3 + j], p[4 + j]); pv[j] = p[4 + j]; }
  sts4(o + R_X5, x[0], x[1], x[2], x[3]);
  sts4(o + R_X3, y[0], y[1], y[2], y[3]);
  if (FULL) {
#pragma unroll
    for (int j = 0; j < 4; ++j) { y[j] = hadd2(hadd2(v[j], v[3 + j]), x[j]); x[j] = hadd2(hadd2(u[j], u[4 + j]), y[j]); }
    const bool od = s & 1;
    sts4(o + R_BO, od ? y[0] : x[0], od ? y[1] : x[1], od ? y[2] : x[2], od ? y[3] : x[3]);
    sts4(o + R_BE + 16, od ? x[0] : y[0], od ? x[1] : y[1], od ? x[2] : y[2], od ? x[3] : y[3]);
  }
}
DEV void box_full(int j, uint32_t (&u)[4][4], uint32_t zero) {
  const uint32_t a2 = uchunk(8, j - 2), a1 = uchunk(0, j - 1);
  uint2 a[4]; uint4 b[4];
#define HALO(n) { a[n] = lds2(region(n) + a2); b[n] = lds4(region(n) + a1); }
  HALO(0) HALO(1)
  split(zero);
#pragma unroll
  for (int chl = 0; chl < 4; ++chl) {
    const uint32_t d[4] = {u[chl][0], u[chl][1], u[chl][2], u[chl][3]};
    box_unit<true>(region(chl), j, a[chl], b[chl], d, u[chl]);
    if (chl != 2) {
      fence_async_smem();
      if (chl == 3) bar_arrive(NB_B + 2, 288);
      bar_arrive(NB_B + chl, 288);
    }
    if (chl == 0) { HALO(2) HALO(3) }
    if (chl == 0) PROF(31);
  }
#undef HALO
}
DEV void box_help(int e, int lane) {
  bar_sync(NB_H, 192);
#pragma unroll 1
  for (int n = 0; n < 4; ++n) {
    const int chl = e + (n & 2), s = 128 + 32 * (n & 1) + lane;
    const uint32_t reg = region(chl);
    const uint4 d = lds4(uchunk(reg, s));
    const uint32_t u[4] = {d.x, d.y, d.z, d.w};
    uint32_t v[4];
    box_unit<false>(reg, s, lds2(uchunk(reg, s - 2) + 8), lds4(uchunk(reg, s - 1)), u, v);
    if (n & 1) { fence_async_smem(); bar_arrive(NB_B + chl, 288); }
  }
}

DEV uint4 hadd8(const uint4& a, const uint4& b) { return make_uint4(hadd2(a.x, b.x), hadd2(a.y, b.y), hadd2(a.z, b.z), hadd2(a.w, b.w)); }
DEV void conv_out(int c, int j, int chl, uint4 (&x)[2][2][2], const uint32_t (&v)[4], uint4* XF, uint32_t zero) {
  const int rho = chl >> 1, e = chl & 1;
  const uint32_t ua = uchunk(region(chl), j), fa = region(chl) + R_X5 + j * 16, ha = region(chl) + R_X3 + (j & 1) * 1088 + (j >> 1) * 16;
  const int m8 = ((j & 4) + ((j >> 1) & 1) + 2 * (j & 1)) ^ ((2 * c + e) & 7);
  uint4* xo = XF + (((16 - 2 * (j & 8) + (j >> 4)) * 512 + 256 * rho + 2 * c + e) * 8 + m8);
  bar_sync(NB_Y + e + 7 * rho, 256);
  uint4 y[2], f[2], h[2];
#pragma unroll
  for (int k = 0; k < 2; ++k) {
    y[k] = lds4(ua + k * 2048);
    f[k] = lds4z(ua + k * 2048 + R_BO - R_U, k || j >= 36);
    h[k] = lds4z(fa + k * 2048 - 1024, k || j >= 64);
  }
  const uint32_t q = lds1(SM_TAP + chl * TAP_SZ + T_K);
  const uint4 r = lds4(ha);
  split(zero);
  if (chl == 3) mbar_arrive1(B_L + (r.x & zero));
  h[1] = hadd8(h[1], make_uint4(hfma2(q, v[0], r.x), hfma2(q, v[1], r.y), hfma2(q, v[2], r.z), hfma2(q, v[3], r.w)));
#pragma unroll
  for (int k = 0; k < 2; ++k) {
    const uint4 o = hadd8(hadd8(y[k], hadd8(f[k], h[k])), make_uint4(xword(x[k][rho], e, 0), xword(x[k][rho], e, 1), xword(x[k][rho], e, 2), xword(x[k][rho], e, 3)));
    const uint32_t keep = j & 1 ? 0x7632 : 0x5410, k0 = prmt(o.x, o.y, keep), k1 = prmt(o.z, o.w, keep);
    const uint32_t g0 = __shfl_xor_sync(0xffffffffu, prmt(o.x, o.y, keep ^ 0x2222), 1), g1 = __shfl_xor_sync(0xffffffffu, prmt(o.z, o.w, keep ^ 0x2222), 1);
    str4(xo + k * 32768, j & 1 ? g0 : k0, j & 1 ? g1 : k1, j & 1 ? k0 : g0, j & 1 ? k1 : g1);

  }
  if (e) { __syncwarp(); mbar_arrive1(B_RD + rho * 8); }
}

DEV void conv_round(int e, int rho, int w, int lane) {
  const int g = lane >> 2, t = lane & 3, chl = 2 * rho + e;
  const uint32_t reg = region(chl), tp = SM_TAP + chl * TAP_SZ, dr = dlo(reg, 128);
  const uint32_t g0 = tp + ((g & 1) ? T_O : T_E) + 2 * (2 * t - g) - 16;
  const uint32_t ga = g0 - 32 * (w & 1) - 576 * (w >> 1), id = opq(0x3210u);
  float acc[32], f1[24], f2[16];
  uint32_t q[12][4];
  {
    uint32_t qn[18][4];
    qn[0][2] = lds1(ga + 64);
#pragma unroll
    for (int n = 0; n < 18; ++n) {
      const bool nz = n < 15 || w < 2 || (n == 15 && w == 2);
      qn[n][0] = n < 15 ? lds1(ga + 48 - 32 * n) : lds1z(ga + 48 - 32 * n, nz);
      qn[n][1] = n < 15 ? lds1(ga + 32 - 32 * n) : lds1z(ga + 32 - 32 * n, nz);
    }
#pragma unroll
    for (int n = 0; n < 18; ++n) { qn[n][3] = cpy(qn[n][0], id); if (n) qn[n][2] = cpy(qn[n - 1][1], id); }
#pragma unroll
    for (int n = 0; n < 8; ++n) {
      const int i = n & 3;
      const uint32_t a = g0 + 16 - 16 * w - 2 * (n < 4 ? X_5 : X_3) + 16 * i;
      uint32_t (&q1)[4] = q[(n & 4) + (i >> 1)], (&q2)[4] = q[(n & 4) + 2 + (i >> 1)];
      q1[2 * (i & 1)] = lds1z(a, i <= w); q1[2 * (i & 1) + 1] = lds1(a - 64);
      q2[2 * (i & 1)] = cpy(0, id); q2[2 * (i & 1) + 1] = lds1z(a - 128, i >= w);
    }
    const uint32_t gc = tp + T_C - 2 + 4 * (t - g - 8 * w);
#pragma unroll
    for (int kk = 0; kk < 4; ++kk) {
      q[8 + kk][0] = lds1z(gc + 32 * kk, w >= kk); q[8 + kk][2] = lds1z(gc + 32 * kk + 16, w >= kk);
      q[8 + kk][1] = lds1(gc + 32 * kk - 128); q[8 + kk][3] = lds1(gc + 32 * kk - 112);
    }
    PROFD(rho ? 43 : 47, qn[17][2] ^ q[11][3]);
    bar_sync_if(NB_U, NBARU, 1 - rho);
    mbar_arrive1_if(B_V, chl == 1 && w == 0);
    bar_sync_if(NB_T + 1 - e, 256, chl);
    const uint32_t db = dr + (R_U + 32) / 16;
    undef(acc);
    wg_fence();
#pragma unroll
    for (int n = 0; n < 18; ++n) {
      if (n) wg_rs64k<1>(acc, qn[n], db - 2 * n); else wg_rs64k<0>(acc, qn[0], db);
      if (n == 9) wg_commit();
    }
    wg_commit();
  }
  wg_wait<1>();
  PROF(12);
  bar_sync(NB_B + chl, 288);
  const uint32_t d1 = dr + R_X5 / 16, d2 = dr + R_BO / 16;
  undef(f1); undef(f2);
  wg_fence();
#pragma unroll
  for (int n = 0; n < 4; ++n) { if (n) wg_rs32t<1>(f2, q[8 + n], d2 + 16 * n); else wg_rs32t<0>(f2, q[8], d2); }
  wg_commit();
#pragma unroll
  for (int n = 0; n < 8; ++n) {
    const uint32_t d = d1 + (n >> 2) * ((R_X3 - R_X5) / 16) + 16 * (n & 1) - 16 * (n & 2);
    if (n) wg_rs48t<1>(f1, q[n], d); else wg_rs48t<0>(f1, q[0], d);
  }
  wg_commit();
  wg_wait<1>();
  PROF(13);
  bar_arrive_if(NB_T + e, 256, chl - 3);
  PROF(14);
  bar_sync(NB_WG + e, 128);
  {
    const int p = (lane + 9 * (w >> 1)) & 31;
    const uint32_t ya = reg + ((w >> 1) ? R_BO : R_U) + p * 64 + (((2 * (w & 1)) ^ ((p >> 1) & 3)) * 16);
    const uint32_t up = p < lane ? 2048 : 0;
#pragma unroll
    for (int z = 0; z < 4; ++z) {
      const float* a = acc + 16 * (z >> 1) + 2 * (z & 1);
      stsm4t((ya + (up ^ ((z >> 1) * 2048))) ^ ((z & 1) * 16), pack2(a[0], a[1]), pack2(a[4], a[5]), pack2(a[8], a[9]), pack2(a[12], a[13]));
    }
  }
  wg_wait<0>();
  bar_sync(NB_WG + e, 128);
  {
    const uint32_t fa = reg + R_X5 + (8 * w + (lane & 7)) * 16 + (lane >> 3) * 512;
    uint32_t h[6];
#pragma unroll
    for (int p = 0; p < 6; ++p) h[p] = p ? pack2(f1[4 * p] + f1[4 * p - 2], f1[4 * p + 1] + f1[4 * p - 1]) : pack2(f1[0], f1[1]);
    stsm4(fa, h[0], h[1], h[2], h[3]);
    stsm2(fa + 2048, h[4], h[5]);
    stsm4(reg + R_X3 + (lane < 16 ? 1088 : 0) + (8 * w + (lane & 7) + 4 * (lane & 8)) * 16, pack2(f2[0], f2[1]), pack2(f2[2] + f2[4], f2[3] + f2[5]),
          pack2(f2[8], f2[9]), pack2(f2[10] + f2[12], f2[11] + f2[13]));
  }
  bar_arrive(NB_Y + e + 7 * rho, 256);
}
constexpr uint32_t FILL = 0xFFFFFFFFu;
template <int N> DEV void fixo(uint4 (&A)[N], const uint4* p) {
#pragma unroll 1
  for (int it = 0; it < SPIN_LIMIT; ++it) {
    uint32_t m = A[0].x;
#pragma unroll
    for (int k = 1; k < N; ++k) m = max(m, A[k].x);
    if (__all_sync(0xffffffffu, m != FILL)) break;
#pragma unroll
    for (int k = 0; k < N; ++k) ldr4_if(A[k], p + k * 32, A[k].x == FILL);
  }
}
DEV bool rows_nan(float a, float b) {
  return __any_sync(0xffffffffu, a != a || b != b);
}
template <int N> DEV void slow_step(float (&acc)[N], float a0, float a1, const uint16_t* wr, uint32_t zero) {
#pragma unroll
  for (int j = 0; j < N / 4; ++j) {
    const uint32_t v = __ldg((const uint32_t*)(wr + (j >> 3) * 512 + 8 * (j & 7)));
    acc[4 * j] += a0 * bflo(v); acc[4 * j + 1] += a0 * bfhi(v); acc[4 * j + 2] += a1 * bflo(v); acc[4 * j + 3] += a1 * bfhi(v);
    if ((j & 3) == 3) wr += __float_as_uint(acc[4 * j]) & zero;
  }
}
DEV int res_off(int w, int lane) { return ((lane & 7) + 8 * (lane >> 4)) * 8 + ((2 * (w & 2) + (w & 1) + ((lane >> 2) & 2)) ^ (lane & 7)); }
DEV void res_load(uint32_t (&res)[8][2], uint32_t sa, int w, int lane) {
  const uint32_t a = sa + res_off(w, opq(lane)) * 16;
#pragma unroll
  for (int j = 0; j < 8; j += 2) {
    uint32_t r[4];
    ldsm4t(r, a + j * 1024);
    res[j][0] = r[0]; res[j][1] = r[1]; res[j + 1][0] = r[2]; res[j + 1][1] = r[3];
  }
}

DEV void res_init(float (&ac)[32], const uint32_t (&res)[8][2]) {
#pragma unroll
  for (int j = 0; j < 16; ++j)
    asm volatile("shl.b32 %0,%2,16; and.b32 %1,%2,0xFFFF0000;" : "=&f"(ac[2 * j]), "=f"(ac[2 * j + 1]) : "r"(res[j >> 1][j & 1]));
}
DEV uint32_t after(uint32_t b, const uint32_t (&res)[8][2], uint32_t zero) {
  return b + ((res[0][0] ^ res[2][0] ^ res[4][0] ^ res[6][0]) & zero);
}

DEV void attn_phase(const Params& P, int c, int e, int w, int lane, int layer) {
  lane = opq(lane); c = opq(c);
  const int i = c >> 3, cg = c & 7, J = 16 * e + i, G = 8 * i + 4 - 4 * e + w;
  const int g = lane >> 2, t = lane & 3;
  float acc[96];
  uint32_t res[8][2];
  float2 cs[16];
  float4 st;
  const uint32_t csb = opq(SM_CS + 8 * t);
  {
    const uint32_t sa = SM_A + e * A_E, ba = B_A + 16 * e;
    const uint32_t da = dlo(sa, 8192), db = (SB >> 4) | (512 << 16);
    undef(acc);
#pragma unroll
    for (int j = 0; j < 8; ++j) asm volatile("" : "=r"(res[j][0]), "=r"(res[j][1]));
    mbar_wait(B_WF, layer);
    mbar_wait(ba, 0);
    mbar_wait(B_L, layer);
    bar_sync_if(NB_T, 256, e);
    PROF(24);
#pragma unroll
    for (int j = 0; j < 4; ++j) {
      if (j == 1) { mbar_wait(ba + 8, 0); PROFK(layer ? 39 : 15); }
      wg_fence();
#pragma unroll
      for (int k = 0; k < 4; ++k) {
        if (j | k) wg_ss192<1>(acc, da + j * 512 + k * 128, db + wslot(j) * 512 + k * 128); else wg_ss192<0>(acc, da, db);
        if (j == 3 && k == 1) wg_commit();
      }
      wg_commit();
      if (j == 1 || j == 2) { wg_wait<1>(); mbar_arrive1_if(B_F + 8 * (j - 1), e); }
    }
    wg_wait<1>();
    bar_arrive(NB_T + e, 256);
    wg_wait<0>();
    if (cg < 4) res_load(res, sa + cg * 8192, w, lane);
    mbar_arrive1(after(B_AE + 8 * e, res, P.zero));
    PROF(25);
#pragma unroll 1
    for (uint32_t late = P.zero;; late = 1) {
      if (late) {
        const uint16_t* xr = (const uint16_t*)SCR->XF[layer] + opq(J) * 32768;
        zero(acc);
#pragma unroll 1
        for (int k = 0; k < 512; ++k)
          slow_step(acc, ldnan(xr + k * 64 + ((2 * w) ^ (k & 7)) * 8 + g), ldnan(xr + k * 64 + ((2 * w + 1) ^ (k & 7)) * 8 + g),
                    P.wqkv + (k * 1536 + 64 * cg + 2 * t), P.zero);
        const uint32_t* q = (const uint32_t*)xr + ((64 * cg + g) * 32 + t);
        const int m8 = (2 * (w & 2) + (w & 1)) ^ g;
#pragma unroll 1
        for (int it = 0; it < SPIN_LIMIT; ++it) {
          uint32_t m = 0;
#pragma unroll
          for (int z = 0; z < 16; ++z) { const uint32_t x = ldr1(q + (z >> 1) * 256 + (m8 ^ (2 * (z & 1))) * 4); m = max(m, x); res[z >> 1][z & 1] = movm(x); }
          if (__all_sync(0xffffffffu, m != FILL)) break;
        }
#pragma unroll
        for (int z = 0; z < 16; ++z) cs[z] = lds2f(csb + 256 + z * 32);
      } else {
        mbar_wait(B_CS, 0);
#pragma unroll
        for (int z = 0; z < 16; ++z) cs[z] = lds2f(csb + 256 + z * 32);
        mbar_wait(B_W4, layer);
        mbar_wait(ba, 1);
        bar_sync(NB_T + 1 - e, 256);
        PROF(26);
#pragma unroll
        for (int j = 4; j < 8; ++j) {
          if (j == 5) mbar_wait(ba + 8, 1);
          if (j >= 6) mbar_wait(B_W6 + 8 * (j - 6), layer);
          if (j > 4) PROF(31 + j);
          wg_fence();
#pragma unroll
          for (int k = 0; k < 4; ++k) {
            wg_ss192<1>(acc, da + (j & 3) * 512 + k * 128, db + wslot(j) * 512 + k * 128);
            if (j == 7 && k == 1) wg_commit();
          }
          wg_commit();
          if (j == 5) {
            if (cg >= 4) res_load(res, sa + (cg - 4) * 8192, w, lane);
            wg_wait<1>(); mbar_arrive1_if(B_F + 16, e); PROF(40);
          }

        }
      }
      uint32_t rs = hadd2(res[0][0], res[0][1]);
#pragma unroll
      for (int z = 2; z < 16; ++z) rs = hadd2(rs, res[z >> 1][z & 1]);
      const float rn = bflo(rs) + bfhi(rs);
      wg_wait<1>();
      bar_arrive_if(NB_T, 256, !(e | late));
      mbar_wait(B_ST + 8 * e, layer);
      st = lds4f(SM_STAT + ((4 * e + w) * 8 + g) * 16);
      PROF(34 + layer);
      wg_wait<0>();
      if (!rows_nan(acc[0] + rn, acc[2]) || late) break;
    }
  }
  mbar_arrive1(B_QE);
  PROFK(8 + 12 * layer);
  uint32_t Q[4][4], K[4][2][2], V[4][2][2];
  {
#pragma unroll
    for (int z = 0; z < 8; ++z) {
      const float* a = acc + 32 + 4 * z; const float* b = acc + 64 + 4 * z;
      K[z >> 1][1][z & 1] = pack2((a[2] - st.z * cs[z].x) * st.w, (a[3] - st.z * cs[z].y) * st.w);
      V[z >> 1][1][z & 1] = movm(pack2((b[2] - st.z * cs[8 + z].x) * st.w, (b[3] - st.z * cs[8 + z].y) * st.w));
    }
    const int hop = (G >> 1) & 3;
    const uint32_t kv = SM_KV + (2 * hop + (w & 1)) * 2048 + lane * 16;
    uint4* h = SCR->H[layer] + (c * 256 + (w & 1) * 128 + lane);
    if (hop == 3) {
#pragma unroll
      for (int z = 0; z < 4; ++z) str4(h + 2048 + z * 32, K[z][1][0], K[z][1][1], V[z][1][0], V[z][1][1]);
    } else {
      mbar_wait(B_F + 16, layer);
#pragma unroll
      for (int z = 0; z < 4; ++z) sts4(kv + z * 512, K[z][1][0], K[z][1][1], V[z][1][0], V[z][1][1]);
      bar_arrive(NB_B + hop, 128);
    }
    PROF(42);
    uint4 hv[4];
#pragma unroll
    for (int z = 0; z < 4; ++z) { hv[z] = make_uint4(0, 0, 0, 0); ldr4_if(hv[z], h + z * 32, G >= 2 && hop == 0); }
#pragma unroll
    for (int z = 0; z < 8; ++z) {
      const float* a = acc + 32 + 4 * z; const float* b = acc + 64 + 4 * z;
      K[z >> 1][0][z & 1] = pack2((a[0] - st.x * cs[z].x) * st.y, (a[1] - st.x * cs[z].y) * st.y);
      V[z >> 1][0][z & 1] = movm(pack2((b[0] - st.x * cs[8 + z].x) * st.y, (b[1] - st.x * cs[8 + z].y) * st.y));
    }
#pragma unroll
    for (int z = 0; z < 8; ++z) {
      const float2 cq = lds2f(csb + z * 32);
      const float* a = acc + 4 * z;
      Q[z >> 1][2 * (z & 1)] = pack2(a[0] - st.x * cq.x, a[1] - st.x * cq.y);
      Q[z >> 1][2 * (z & 1) + 1] = pack2(a[2] - st.z * cq.x, a[3] - st.z * cq.y);
    }
    PROF(27);
    const bool p0 = 2 * t > g, p1 = 2 * t + 1 > g, first = G < 2;
    float s[4][4], mx[4][2];
#pragma unroll
    for (int z = 0; z < 4; ++z) {
      float S[4];
      mma16z(s[z], Q[z][0], Q[z][1], Q[z][2], Q[z][3], K[z][0][0], K[z][0][1]);
      mma16z(S, Q[z][0], Q[z][1], Q[z][2], Q[z][3], K[z][1][0], K[z][1][1]);
      s[z][2] = p0 ? s[z][2] : S[2]; s[z][3] = p1 ? s[z][3] : S[3];
    }
    const float sc0 = st.y * (0.25f * 1.4426950408889634f), sc1 = st.w * (0.25f * 1.4426950408889634f);
    uint32_t pw[4][2];
#pragma unroll
    for (int r = 1; r >= 0; --r) {
      if (r == 0) {
        if (hop) {
          bar_sync(NB_B + hop - 1, 128);
#pragma unroll
          for (int z = 0; z < 4; ++z) hv[z] = lds4(kv - 4096 + z * 512);
        } else fixo(hv, h);
        PROFD(41, hv[3].x);
#pragma unroll
        for (int z = 0; z < 4; ++z) {
          float S[4];
          mma16z(S, Q[z][0], Q[z][1], Q[z][2], Q[z][3], hv[z].x, hv[z].y);
          if (first) S[0] = S[1] = __uint_as_float(0xFF800000u);
          s[z][0] = p0 ? S[0] : s[z][0]; s[z][1] = p1 ? S[1] : s[z][1];
        }
      }
#pragma unroll
      for (int z = 0; z < 4; ++z) mx[z][r] = fmaxf(s[z][2 * r], s[z][2 * r + 1]);
#pragma unroll
      for (int o = 1; o < 3; ++o)
#pragma unroll
        for (int z = 0; z < 4; ++z) mx[z][r] = fmaxf(mx[z][r], __shfl_xor_sync(0xffffffffu, mx[z][r], o));
#pragma unroll
      for (int z = 0; z < 4; ++z) pw[z][r] = pack2(ex2((s[z][2 * r] - mx[z][r]) * (r ? sc1 : sc0)), ex2((s[z][2 * r + 1] - mx[z][r]) * (r ? sc1 : sc0)));
    }
    mbar_wait(layer ? B_N : B_Z, 1);
    const uint32_t M = (p0 ? 0xFFFFu : 0u) | (p1 ? 0xFFFF0000u : 0u);
    uint4* O = SCR->O + ((J * 8 + cg) * 512 + (2 * (w & 2) + (w & 1)) * 64 + t * 8 + g);
#pragma unroll
    for (int h2 = 0; h2 < 2; ++h2) {
      uint32_t ow[2][4];
#pragma unroll
      for (int z = 0; z < 2; ++z) {
        const int n = 2 * h2 + z;
        const uint32_t w0 = pw[n][0], w1 = pw[n][1];
        float sm[4] = {0.f, 0.f, 0.f, 0.f}, Oa[2][4];
        mma8(sm, w0, w1, 0x3F803F80u);
        mma16z(Oa[0], w0 & ~M, w1 & M, 0u, w1 & ~M, V[n][0][0], V[n][1][0]); mma8(Oa[0], w0 & M, 0u, hv[n].z);
        mma16z(Oa[1], w0 & ~M, w1 & M, 0u, w1 & ~M, V[n][0][1], V[n][1][1]); mma8(Oa[1], w0 & M, 0u, hv[n].w);
        const float i0 = rcp(sm[0]), i1 = rcp(sm[2]);
#pragma unroll
        for (int d = 0; d < 2; ++d) { ow[0][2 * z + d] = pack2(Oa[d][0] * i0, Oa[d][1] * i0); ow[1][2 * z + d] = pack2(Oa[d][2] * i1, Oa[d][3] * i1); }
      }
#pragma unroll
      for (int hi = 0; hi < 2; ++hi) str4(O + hi * 128 + h2 * 32, ow[hi][0], ow[hi][1], ow[hi][2], ow[hi][3]);
    }
  }
  str1(SCR->OF[layer] + (J * 32 + cg * 4 + w), 1);
  mbar_arrive1(B_AT + 8 * e);
  PROFK(9 + 12 * layer);
  float ac[32];
  const uint32_t so = SM_O + e * O_E;
  uint2* xo = opqp(layer ? (uint2*)(P.out + ((16 * G + 2 * (lane >> 3)) * 512 + 64 * cg + 8 * (lane & 7)))
                         : (uint2*)SCR->XG[1] + ((32 * (cg & 3) + t) * 2048 + (cg >> 2) * 512 + xg_off(G, g)));
  const uint32_t stg = SM_X + (4 * e + w) * 2048;
  const uint32_t sw = opq(stg + (lane & 15) * 128 + (((lane >> 4) ^ (lane & 7)) * 16)), sr = opq(stg + (lane >> 3) * 128 + (((lane & 7) ^ (lane >> 3)) * 16));
  uint4* ps = opqp(&SCR->PS[(G * 8 + cg) * 8 + g]);
  {
    const uint32_t bo = B_O + 32 * e;
    const uint32_t dw = (SM_WO >> 4) | (512 << 16), da = dlo(so, 512);
    mbar_wait(B_WO, layer);
    res_init(ac, res);
    mbar_wait(B_AT + 8, layer);
#pragma unroll
    for (int j = 0; j < 4; ++j) {
      mbar_wait(bo + 8 * j, layer);
      if (j == 0) PROFK(32 + layer);
      wg_fence();
#pragma unroll
      for (int k = 8 * j; k < 8 * j + 8; ++k) {
        const uint32_t a = da + (k >> 2) * 512 + (k & 3) * 8, b = dw + (k & 3) * 1024 + (k >> 2) * 128;
        wg_ss64<1>(ac, a, b);
      }
      wg_commit();
    }
#pragma unroll 1
    for (uint32_t late = P.zero;; late = 1) {
      if (late) {
        const uint16_t* op = (const uint16_t*)(SCR->O + (J * 4096 + w * 128 + g));
        wg_wait<0>();
        res_init(ac, res);
#pragma unroll 1
        for (int k = 0; k < 512; ++k) {
          const uint16_t* q = op + (k >> 6) * 4096 + (k & 56) * 8 + (k & 7);
          slow_step(ac, ldnan(q), ldnan(q + 512), P.wo + (((k & ~31) + 4 * (k & 6) + ((k >> 2) & 6) + (k & 1)) * 512 + 64 * cg + 2 * t), P.zero);
        }
      }
      wg_wait<0>();
      if (!rows_nan(ac[0], ac[2]) || late) break;
    }
  }
  PROFK(10 + 12 * layer);
#pragma unroll
  for (int j = 0; j < 16; ++j) res[j >> 1][j & 1] = pack2(ac[2 * j], ac[2 * j + 1]);
  if (layer == 0) {
    float s[2][4], q0[2][4], q1[2][4];
#pragma unroll
    for (int j = 0; j < 2; ++j) gram<true>(s[j], q0[j], q1[j], res[2 * j][0], res[2 * j][1], res[2 * j + 1][0], res[2 * j + 1][1]);
#pragma unroll
    for (int j = 0; j < 2; ++j) gram<false>(s[j], q0[j], q1[j], res[2 * j + 4][0], res[2 * j + 4][1], res[2 * j + 5][0], res[2 * j + 5][1]);
    const bool od = g & 1;
    str4_if(ps, nzmap(__float_as_uint(s[0][0] + s[1][0])), __float_as_uint(od ? q0[0][1] + q0[1][1] : q0[0][0] + q0[1][0]),
            __float_as_uint(s[0][2] + s[1][2]), __float_as_uint(od ? q1[0][3] + q1[1][3] : q1[0][2] + q1[1][2]), t == (g >> 1));
#pragma unroll
    for (int j = 0; j < 8; ++j) {
      str2(xo + j * 8192, nzmap(prmt(res[j][0], res[j][1], 0x5410)), prmt(res[j][0], res[j][1], 0x7632));
    }
    mbar_arrive1(B_ED + 8 * e);
  } else {
#pragma unroll
    for (int j = 0; j < 8; j += 2) stsm4(sw ^ (j * 16), res[j][0], res[j][1], res[j + 1][0], res[j + 1][1]);
    __syncwarp();
    uint4 v[4];
#pragma unroll
    for (int k = 0; k < 4; ++k) v[k] = lds4((sr ^ ((k & 1) * 64)) + k * 512);
#pragma unroll
    for (int k = 0; k < 4; ++k) stw4(xo + ((k & 1) * 8 + (k >> 1)) * 128, v[k].x, v[k].y, v[k].z, v[k].w);
  }
  PROFK(11 + 12 * layer);
}

DEV void col_sums(const Params& P, int c, int wa, int lane) {
  const int i = c >> 3, cg = c & 7;
  uint4 wv[8];
#pragma unroll
  for (int k = 0; k < 8; ++k) wv[k] = ldnc4(P.wqkv + ((32 * i + (lane >> 3)) * 1536 + wa * 512 + 64 * cg + 8 * (lane & 7)) + 4 * k * 1536);
  float cs[8];
  zero(cs);
#pragma unroll
  for (int k = 0; k < 8; ++k) {
    cs[0] += bflo(wv[k].x); cs[1] += bfhi(wv[k].x); cs[2] += bflo(wv[k].y); cs[3] += bfhi(wv[k].y);
    cs[4] += bflo(wv[k].z); cs[5] += bfhi(wv[k].z); cs[6] += bflo(wv[k].w); cs[7] += bfhi(wv[k].w);
  }
  const bool b4 = lane & 16, b3 = lane & 8;
#pragma unroll
  for (int k = 0; k < 4; ++k) cs[k] = (b4 ? cs[k + 4] : cs[k]) + __shfl_xor_sync(0xffffffffu, b4 ? cs[k] : cs[k + 4], 16);
#pragma unroll
  for (int k = 0; k < 2; ++k) cs[k] = (b3 ? cs[k + 2] : cs[k]) + __shfl_xor_sync(0xffffffffu, b3 ? cs[k] : cs[k + 2], 8);
  str2((uint2*)SCR->CS + (i * 768 + wa * 256 + 32 * cg + 4 * (lane & 7) + (lane >> 3)), nzmap(__float_as_uint(cs[0])), __float_as_uint(cs[1]));
}
DEV void col_gather(const Params& P, int c, int wa, int lane) {
  const uint2* p = (const uint2*)SCR->CS + (wa * 256 + 32 * (c & 7) + lane);
#pragma unroll 1
  for (int it = 0;; ++it) {
    float a = 0.f, b = 0.f;
    uint32_t m = ~0u;
#pragma unroll
    for (int k = 0; k < 16; ++k) { const uint2 q = ldr2(p + k * 768); m = min(m, q.x); a += __uint_as_float(q.x); b += __uint_as_float(q.y); }
    if (__all_sync(0xffffffffu, m != 0u)) { sts2f(SM_CS + wa * 256 + lane * 8, a, b); break; }
    spin_guard(it);
  }
  __syncwarp();
  mbar_arrive1(B_CS);
}

DEV void aux_prologue(const Params& P, int c, int wa, int lane) {
  const int g = lane >> 2, t = lane & 3, G = stat_group(c);
  {
    uint32_t w[16][2];
    const uint16_t* row = P.x0 + ((16 * G + 2 * g) * 512 + 128 * wa + 8 * t);
    bar_sync(NB_Y, 384);
#pragma unroll
    for (int z = 0; z < 8; ++z) {
      const uint4 v = ldw4(row + (z & 1) * 512 + (z >> 1) * 32);
      const int o = 4 * (z >> 1);
      w[o][z & 1] = v.x; w[o + 1][z & 1] = v.y; w[o + 2][z & 1] = v.z; w[o + 3][z & 1] = v.w;
    }
    PROF(34);
    PROFD(35, w[0][0]);
    PROFD(36, w[15][1]);
    uint2* xo = (uint2*)SCR->XG[0] + ((64 * (wa & 1) + 4 * t) * 2048 + (wa >> 1) * 512 + xg_off(G, g));
#pragma unroll
    for (int n = 0; n < 16; ++n) str2(xo + (16 * (n >> 2) + (n & 3)) * 2048, nzmap(prmt(w[n][0], w[n][1], 0x5410)), prmt(w[n][0], w[n][1], 0x7632));
    float s[2][4], q0[2][4], q1[2][4];
#pragma unroll
    for (int z = 0; z < 8; ++z) {
      const int o = 4 * (z >> 1), r = z & 1;
      if (z < 2) gram<true>(s[r], q0[r], q1[r], w[o][r], w[o + 1][r], w[o + 2][r], w[o + 3][r]);
      else gram<false>(s[r], q0[r], q1[r], w[o][r], w[o + 1][r], w[o + 2][r], w[o + 3][r]);
    }
    const bool od = g & 1;
    if (t == (g >> 1))
      sts4f(SM_MISC + (wa * 8 + g) * 16, s[0][0] + s[0][2], od ? q0[0][1] + q1[0][3] : q0[0][0] + q1[0][2],
            s[1][0] + s[1][2], od ? q0[1][1] + q1[1][3] : q0[1][0] + q1[1][2]);
    bar_arrive(NB_P0, 192);
  }
  PROF(2);
  if (lane == 0)
    asm volatile("cp.async.bulk.prefetch.L2.global [%0],4096;" :: "l"(wa < 3 ? P.wqkv + (3 * c + wa) * 2048 : P.wo + c * 2048) : "memory");
  bar_sync(NB_Y + 1, 256);
  mbar_wait(B_Z, 0);
}

DEV void stat_part(const Params& P, int c, int wa, int lane, int layer, int h, float (&v)[2]) {
  lane = opq(lane);
  const int e = wa >> 1;
  uint32_t x[4][4];
  mbar_wait(B_A + 16 * e, h); mbar_wait(B_A + 16 * e + 8, h);
#pragma unroll
  for (int k = 0; k < 4; ++k) ldsm4t(x[k], SM_A + e * A_E + (128 * (wa & 1) + lane) * 128 + (((c ^ lane) & 7) * 16) + k * 4096);
  float s[4] = {0.f, 0.f, 0.f, 0.f};
#pragma unroll
  for (int k = 0; k < 16; ++k) { const float a = bflo(x[k >> 2][k & 3]), b = bfhi(x[k >> 2][k & 3]); s[0] += a; s[1] += a * a; s[2] += b; s[3] += b * b; }
  s[0] += s[2]; s[1] += s[3];
  if (RARE(rows_nan(s[1], s[1]))) {
    const uint16_t* q = (const uint16_t*)(SCR->XF[layer] + ((32 * e + 2 * (c >> 3) + h) * 2048 + (wa & 1) * 1024)) + (lane >> 2);
    s[0] = s[1] = 0.f;
#pragma unroll 1
    for (int k = 0; k < 32; ++k) {
      const int r = 2 * (lane & 3) + (k & 1);
      const float a = ldnan(q + ((k >> 1) * 8 + r) * 64 + ((c ^ r) & 7) * 8);
      s[0] += a; s[1] += a * a;
    }
  }
  v[0] += s[0]; v[1] += s[1];
  __syncwarp();
}
DEV void stat_finish(const Params& P, int c, int wa, int lane, int layer, float (&v)[2]) {
  lane = opq(lane);
  const bool b = lane & 1;
  const float s = (b ? v[1] : v[0]) + __shfl_xor_sync(0xffffffffu, b ? v[0] : v[1], 1);
  str1((uint32_t*)SCR->ST[layer] + ((128 * (wa >> 1) + c) * 64 + (wa & 1) * 32 + lane), nzmap(__float_as_uint(s)));
  const uint4* sp = SCR->ST[layer] + ((128 * (wa >> 1) + (c & ~7) + 4 * (wa & 1) + (lane >> 3)) * 16 + (lane & 7));
  uint4 x, y;
  for (int it = 0;; ++it) {
    x = ldr4(sp); y = ldr4(sp + 8);
    if (__all_sync(0xffffffffu, min(min(min(x.x, x.y), min(x.z, x.w)), min(min(y.x, y.y), min(y.z, y.w))) != 0u)) break;
    spin_guard(it);
  }
  const uint32_t q = ln_sums((__uint_as_float(x.x) + __uint_as_float(x.z)) + (__uint_as_float(y.x) + __uint_as_float(y.z)),
                             (__uint_as_float(x.y) + __uint_as_float(x.w)) + (__uint_as_float(y.y) + __uint_as_float(y.w)));
  sts2f(SM_STAT + (16 * wa + (lane >> 4) * 8 + (lane & 7)) * 16 + (lane & 8), bflo(q), rcp(bfhi(q)));
  __syncwarp();
  mbar_arrive1(B_ST + 4 * (wa & 2));
}

DEV void nan_source(uint32_t a, int lane) {
#pragma unroll
  for (int k = 0; k < 4; ++k) sts4(a + k * 512 + lane * 16, FILL, FILL, FILL, FILL);
  fence_async_smem();
  __syncwarp();
}
__global__ void __launch_bounds__(NTHR, 1)
fused_kernel(const __grid_constant__ Params P, const __grid_constant__ CUtensorMap mapW, const __grid_constant__ CUtensorMap mapWo,
             const __grid_constant__ CUtensorMap mapX) {
  extern __shared__ __align__(1024) uint8_t smem_raw[];
  const int warp = __shfl_sync(0xffffffffu, threadIdx.x >> 5, 0), lane = threadIdx.x & 31;
  uint32_t smid; asm volatile("mov.u32 %0,%%smid;" : "=r"(smid));
  const uint32_t* pw = (const uint32_t*)&P + threadIdx.y;
  const int role = P.role[(smid >> 1) + threadIdx.y] + (smid & 1) + (pw[0] & pw[12]);
  const int c = __shfl_sync(0xffffffffu, pw[1] ? role : blockIdx.x, 0);
  if (c >= 128) {
#pragma unroll 1
    for (int k = (c - 128) * NTHR + threadIdx.x; k < 131072; k += P.spare * NTHR) str4(SCR->XG[1] + k, 0, 0, 0, 0);
    __threadfence();
    __syncthreads();
    if (warp == 0) { poll(SCR->C + 1 + (lane & 3) * 32, 32); cnt_add1(SCR->C + 6); }
    __syncthreads();
#pragma unroll 1
    for (int k = (c - 128) * NTHR + threadIdx.x; k < 131072; k += P.spare * NTHR) str4(SCR->XG[0] + k, 0, 0, 0, 0);
    return;
  }
#define DONE() do {} while (0)
  const int cg = c & 7;
  if (warp < 8) {
    PROF(46);
    kgen(P, c, warp, lane);
    PROFK(1);
    bar_sync(0, 384);
#pragma unroll 1
    for (int layer = 0; layer < 2; ++layer) {
#pragma unroll 1
      for (int rho = 0; rho < 2; ++rho) {
        const int wz = warp + ((rho + layer) & P.zero);
        conv_round(wz >> 2, rho, wz & 3, lane_id());
        PROFK(6 + rho + 12 * layer);
      }
      const int z = layer & P.zero;
      attn_phase(P, c + z, (warp + z) >> 2, (warp + z) & 3, lane_id(), layer);
    }
    DONE();
  } else if (warp < 12) {
    asm volatile("setmaxnreg.dec.sync.aligned.u32 %0;" :: "n"(REG_AUX));
    aux_prologue(P, c, warp - 8, lane);
    PROF(1);
    const int c0 = c;
#pragma unroll 1
    for (int layer = 0;; ++layer) {
      const int c = c0 + (layer & P.zero), wa = warp - 8 + (layer & P.zero);
#define lane lane_id()
#define j (32 * wa + lane_id())
      uint4 x[2][2][2];
      uint32_t u[4][4];
      uprep(P, c, wa, lane, layer, x, u);
      fence_async_smem();
      bar_arrive(NB_U, NBARU);
      PROFK(5 + 12 * layer);
      bar_sync(NB_H, 192);
      box_full(j, u, P.zero);
      PROF(3 + 12 * layer);
      conv_out(c, j, 0, x, u[0], SCR->XF[layer], P.zero);
      PROF(32);
      conv_out(c, j, 1, x, u[1], SCR->XF[layer], P.zero);
      PROF(6 + 12 * layer);
      if (layer == 0 && wa < 3) col_sums(P, c, wa, lane);
      conv_out(c, j, 2, x, u[2], SCR->XF[layer], P.zero);
      PROF(33);
      conv_out(c, j, 3, x, u[3], SCR->XF[layer], P.zero);
      PROFK(7 + 12 * layer);
      float v[2];
      zero(v);
#pragma unroll 1
      for (int h = 0; h < 2; ++h) {
        stat_part(P, c, wa, lane, layer, h, v);
        if (h) break;
        mbar_arrive1(B_AE + 4 * (wa & 2));
        if (layer == 0 && wa < 3) col_gather(P, c, wa, lane);
      }
      PROF(9 + 12 * layer);
      stat_finish(P, c, wa, lane, layer, v);
      PROF(8 + 12 * layer);
      if (layer) break;
      mbar_wait(B_ED, 0); mbar_wait(B_ED + 8, 0);
#undef lane
#undef j
    }
    DONE();
  } else {
    asm volatile("setmaxnreg.dec.sync.aligned.u32 %0;" :: "n"(REG_PROD));
    if (s2u(smem_raw) != SB) __trap();
#pragma unroll 1
    for (int n = warp - 12; n < 38; n += 4)
      asm volatile("{.reg .pred p; elect.sync _|p,0xffffffff; @p mbarrier.init.shared::cta.b64 [%0],%1;}"
                   :: "r"(SM_BAR + n * 8), "r"(n == 33 ? 4 : n > 14 ? 1 : (int)(0x322866444444444ull >> (4 * n)) & 15) : "memory");
    fence_async_smem();
    bar_sync(NB_AUX, 128);
    bar_arrive(0, 384); bar_arrive(NB_Y + 1, 256);
    PROF(1);
    if (warp == 12) {
      if (lane == 0) {
        asm volatile("prefetch.tensormap [%0];" :: "l"(&mapW) : "memory");
        asm volatile("prefetch.tensormap [%0];" :: "l"(&mapWo) : "memory");
        asm volatile("prefetch.tensormap [%0];" :: "l"(&mapX) : "memory");
      }
      nan_source(slot(12), lane);
#pragma unroll 1
      for (int k = 0; k < 8; ++k) tma2_store(&mapX, slot(12), 128 * c, 8 * k);
      bulk_wait();
      __threadfence();
      mbar_arrive1(B_Z);
      mbar_wait(B_E, 0);
#pragma unroll 1
      for (int k = 0; k < 4; ++k) bulk_store(SCR->H[k >> 1] + ((c + 8) * 256 + (k & 1) * 128), slot(12), 2048);
#pragma unroll 1
      for (int k = 0; k < 8; ++k) bulk_store(SCR->O + (c * 512 + (k >> 2) * 65536 + (k & 3) * 128), slot(12), 2048);
      bulk_wait();
      PROF(24);
#pragma unroll 1
      for (int layer = 0; layer < 2; ++layer) {
        mbar_wait(B_V, layer);
        if (layer == 1 && c < 4 && ((0x47 >> lane) & 1)) str1(SCR->C + c * 32 + lane, 0);
        mbar_expect1(B_WF, 4 * 24576);
#pragma unroll
        for (int k = 0; k < 4; ++k) tma3(slot(wslot(k)), &mapW, 64 * cg, 64 * k, 0, B_WF);
        if (layer == 0) { __threadfence(); mbar_arrive1(B_Z); }
        mbar_wait(B_WF, layer);
        mbar_expect1(B_W4, 2 * 24576);
#pragma unroll
        for (int k = 4; k < 6; ++k) tma3(slot(wslot(k)), &mapW, 64 * cg, 64 * k, 0, B_W4);
        bar_sync(NB_AUX, 64);
#pragma unroll 1
        for (int k = 0; k < 2; ++k) {
          mbar_expect1(B_W6 + 8 * k, 24576);
          mbar_wait(B_F + 8 * k, layer);
          tma3(slot(3 * k), &mapW, 64 * cg, 384 + 64 * k, 0, B_W6 + 8 * k);
        }
        mbar_expect1(B_WO, 65536);
        mbar_wait(B_AE + 8, layer);
        nan_source(slot(12), lane);
        uint4* fp = layer ? SCR->O + c * 512 : SCR->XF[1] + c * 512;
#pragma unroll 1
        for (int r = 7; r >= 0; --r) {
          __nanosleep(30);
          if (r >= 4) {
            bulk_store(fp + (r & 3) * 128, slot(12), 2048); bulk_store(fp + 65536 + (r & 3) * 128, slot(12), 2048);
          }
          if (r == 3) { bulk_wait(); __threadfence(); mbar_arrive1(B_N); PROF(9 + 12 * layer); }
          if (r == 1) mbar_wait(B_F + 16, layer);
          tma4(SM_WO + r * 8192, &mapWo, 64 * cg, 0, r >> 1, 32 * (r & 1), B_WO);
        }
        PROF(8 + 12 * layer);
      }
      DONE();
    } else if (warp == 13) {
      const int G = stat_group(c);
#pragma unroll 1
      for (int layer = 0; layer < 2; ++layer) {
        float z[4];
        uint2* so = opqp((uint2*)&SCR->SR[layer][lane >> 3][sr_off(G, lane)] + (lane & 1));
        if (layer == 0) {
          bar_sync(NB_P0, 192);
          const float4 a = lds4f(SM_MISC + lane * 16);
          z[0] = a.x; z[1] = a.y; z[2] = a.z; z[3] = a.w;
        } else {
          mbar_wait(B_ED + 2 * (c & 4), 0);
          uint4* ps = &SCR->PS[G * 64 + lane];
          uint4 a, b;
          for (int it = 0;; ++it) {
            a = ldr4(ps); b = ldr4(ps + 32);
            if (__all_sync(0xffffffffu, min(a.x, b.x) != 0u)) break;
            spin_guard(it);
          }
          z[0] = __uint_as_float(a.x) + __uint_as_float(b.x); z[1] = __uint_as_float(a.y) + __uint_as_float(b.y);
          z[2] = __uint_as_float(a.z) + __uint_as_float(b.z); z[3] = __uint_as_float(a.w) + __uint_as_float(b.w);
        }
#pragma unroll
        for (int o = 8; o < 32; o <<= 1)
#pragma unroll
          for (int k = 0; k < 4; ++k) z[k] += __shfl_xor_sync(0xffffffffu, z[k], o);
        const uint32_t w0 = ln_sums(z[0], z[1]), w1 = ln_sums(z[2], z[3]);
        const uint32_t r = nzmap(pack2(rcp(bfhi(w0)), rcp(bfhi(w1)))), m = pack2(z[0] * (-1.f / 512.f) * bflo(r), z[2] * (-1.f / 512.f) * bfhi(r));
        str2(so, r, m); str2(so + 4 * 1024, r, m);
        PROF(4 + 12 * layer);
        box_help(0, lane);
        PROF(6 + 12 * layer);
      }
      DONE();
    } else if (warp == 14) {
#pragma unroll 1
      for (int layer = 0; layer < 2; ++layer) {
        uint32_t* ca = opqp(SCR->C + (c >> 5) * 32 + 3 * layer);
        const uint32_t* cw = opqp(SCR->C + (lane & 3) * 32 + 3 * layer);
        const uint4* xg = opqp(SCR->XG[layer] + c * 1024);
        mbar_expect1(B_E, 16384);
        if (layer) { mbar_wait(B_N, 0); mbar_wait(B_ED, 0); mbar_wait(B_ED + 8, 0); } else bar_sync(NB_P0, 192);
        cnt_add1(ca);
        PROF(4 + 12 * layer);
        poll(cw, 32);
        mbar_arrive1(B_U);
        bulk(SM_X, xg, 16384, B_E);
        PROFK(5 + 12 * layer);
#pragma unroll 1
        for (int n = 0; n < 4; ++n) {
          const int e = n & 1;
          const uint4* src = opqp(SCR->XF[layer] + (32 * e + 2 * (c >> 3) + (n >> 1)) * 2048);
          const uint32_t dst = opq(SM_A + e * A_E), b = opq(B_A + 16 * e), f = opq(n == 1 ? B_L : (n & 2 ? B_AE : B_RD) + 8 * e);
          if (n == 0) { mbar_wait(B_RD, layer); cnt_add1(ca + 1); }
          if (!e) poll(cw + 1 + (n >> 1), 32);
          if (n == 2) PROF(7 + 12 * layer);
          mbar_wait(f, layer);
          mbar_expect1(b, 8192); bulk(dst, src, 8192, b);
          mbar_expect1(b + 8, 24576); bulk(dst + 8192, src + 512, 24576, b + 8);
          bar_arrive_if(NB_AUX, 64, n == 2);
          if (!e) PROFK(6 + n + 12 * layer);
        }
#pragma unroll 1
        for (int n = 0; n < 8; ++n) mbar_expect1(B_O + 8 * n, 16384);
        if (layer == 0) poll(SCR->C + 6, P.spare);
        mbar_wait(B_QE, layer);
#pragma unroll 1
        for (int e = 0; e < 2; ++e) {
          const int J = 16 * e + (c >> 3);
          const uint32_t* fl = opqp(SCR->OF[layer] + J * 32 + lane);
          const uint4* src[4];
          uint32_t dst[4], b[4];
#pragma unroll
          for (int n = 0; n < 4; ++n) { src[n] = opqp(SCR->O + (J * 4096 + n * 1024)); dst[n] = opq(SM_O + e * O_E + 16384 * n); b[n] = opq(B_O + 32 * e + 8 * n); }
          mbar_wait(B_AT + 8 * e, layer);
          if (!e) pause(260);
          poll(fl, 1);
#pragma unroll
          for (int n = 0; n < 4; ++n) bulk(dst[n], src[n], 16384, b[n]);
          PROFK(9 + e + 12 * layer);
        }
      }
      DONE();
    }
    if (warp == 15) {
      const int G = stat_group(c);
      str4(&SCR->ST[0][(lane >> 4) * 2048 + c * 16 + (lane & 15)], 0, 0, 0, 0); str4(&SCR->ST[1][(lane >> 4) * 2048 + c * 16 + (lane & 15)], 0, 0, 0, 0);
      if (lane < 4) str4(SCR->OF[lane >> 1] + ((lane & 1) * 512 + c * 4), 0, 0, 0, 0);
      str4(&SCR->PS[G * 64 + lane], 0, 0, 0, 0); str4(&SCR->PS[G * 64 + 32 + lane], 0, 0, 0, 0);
      str4(&SCR->SR[1][lane >> 2][sr_off(G, 2 * lane)], 0, 0, 0, 0);
      if (c < 4 && lane < 3) str1(SCR->C + c * 32 + 3 + lane, 0);
#pragma unroll
      for (int k = 0; k < 3; ++k) str2((uint2*)SCR->CS + ((c >> 3) * 768 + k * 256 + 32 * cg + lane), 0, 0);
      __threadfence();
#pragma unroll 1
      for (int layer = 0; layer < 2; ++layer) {
        PROF(4 + 12 * layer);
        box_help(1, lane);
        if (layer) str4(&SCR->SR[0][lane >> 2][sr_off(G, 2 * lane)], 0, 0, 0, 0);
        uint32_t* ca = opqp(SCR->C + (c >> 5) * 32 + 3 * layer + 2);
        mbar_wait(B_Z, 1);
        mbar_wait(B_RD + 8, layer);
        cnt_add1(ca);
        if (P.spare == 0) {
#pragma unroll 1
          for (int k = 0; k < 32; ++k) str4(SCR->XG[layer] + (c * 1024 + k * 32 + lane), 0, 0, 0, 0);
        }
      }
      mbar_watch(B_O + 56, 1);
    }
  }
}

typedef CUresult (*EncodeFn)(CUtensorMap*, CUtensorMapDataType, cuuint32_t, void*, const cuuint64_t*, const cuuint64_t*,
                             const cuuint32_t*, const cuuint32_t*, CUtensorMapInterleave, CUtensorMapSwizzle,
                             CUtensorMapL2promotion, CUtensorMapFloatOOBfill);

static int place_roles(uint8_t* role) {
  int dev = 0, nsm = 0;
  cudaGetDevice(&dev);
  cudaDeviceGetAttribute(&nsm, cudaDevAttrMultiProcessorCount, dev);
  if (nsm <= 128 || nsm > 144 || (nsm & 1)) return 0;
  cudaFuncSetAttribute(fused_kernel, cudaFuncAttributeNonPortableClusterSizeAllowed, 1);
  int occ[9] = {0};
  for (int k = 2; k <= 8; ++k) {
    cudaLaunchConfig_t cfg = {};
    cudaLaunchAttribute at[1];
    at[0].id = cudaLaunchAttributeClusterDimension;
    at[0].val.clusterDim.x = 2 * k; at[0].val.clusterDim.y = 1; at[0].val.clusterDim.z = 1;
    cfg.gridDim = dim3(2 * k); cfg.blockDim = dim3(NTHR); cfg.dynamicSmemBytes = SM_TOTAL; cfg.attrs = at; cfg.numAttrs = 1;
    if (cudaOccupancyMaxActiveClusters(&occ[k], fused_kernel, &cfg) != cudaSuccess) { cudaGetLastError(); occ[k] = 0; }
  }
  int n[10];
  n[7] = occ[8]; n[6] = occ[7]; n[5] = occ[6] - 0; n[4] = occ[5];
  n[3] = occ[4] - n[7]; n[1] = occ[2] - n[3] - n[5] - n[7]; n[0] = n[2] = n[1];
  n[8] = occ[3] - n[2] - n[5];
  const int ntpc = nsm / 2;
  int sum = 0;
  bool ok = n[0] > 0 && n[0] <= 8;
  for (int r = 0; r < 9; ++r) { ok = ok && n[r] >= 0 && (r == 0 || n[r] <= n[r - 1]); sum += n[r]; }
  if (!ok || sum > ntpc) { for (int r = 0; r < 9; ++r) n[r] = r < 8 ? 8 : 0; sum = 64; }
  int tp[8][9], cnt[8] = {0}, pool[72], np = 0, id = 0;
  for (int r = 0; r < 9; ++r)
    for (int g = n[0] - n[r]; g < n[0]; ++g) tp[g][cnt[g]++] = id++;
  for (; id < ntpc; ++id) pool[np++] = id;
  int order[72], no = 0;
  for (int g = 0; g < n[0]; ++g) {
    const int full = cnt[g] / 4 * 4;
    for (int k = 0; k < cnt[g]; ++k) { if (k < full) order[no++] = tp[g][k]; else pool[np++] = tp[g][k]; }
  }
  for (int k = 0; k < np; ++k) order[no++] = pool[k];
  for (int k = 0; k < ntpc; ++k) role[order[k]] = 2 * k;
  return nsm;
}

extern "C" void kernel_launch(void* const* d_in, const int* in_sizes, int n_in, void* d_out, int out_size) {
  (void)in_sizes; (void)n_in; (void)out_size;
  static EncodeFn enc = nullptr;
  static uint8_t role[72];
  static int nsm = 0;
  static Scratch* scratch = nullptr;
  if (!enc) {
    void* fn = nullptr;
    cudaDriverEntryPointQueryResult qr;
    cudaGetDriverEntryPoint("cuTensorMapEncodeTiled", &fn, cudaEnableDefault, &qr);
    enc = (EncodeFn)fn;
    cudaFuncSetAttribute(fused_kernel, cudaFuncAttributeMaxDynamicSharedMemorySize, SM_TOTAL);
    nsm = place_roles(role);
    cudaGetSymbolAddress((void**)&scratch, g_S);
  }
  CUtensorMap mW, mWo, mX;
  {
    cuuint64_t dim[3] = {512, 512, 3}, str[2] = {3072, 1024};
    cuuint32_t box[3] = {64, 64, 3}, es[3] = {1, 1, 1};
    enc(&mW, CU_TENSOR_MAP_DATA_TYPE_BFLOAT16, 3, d_in[10], dim, str, box, es, CU_TENSOR_MAP_INTERLEAVE_NONE,
        CU_TENSOR_MAP_SWIZZLE_128B, CU_TENSOR_MAP_L2_PROMOTION_NONE, CU_TENSOR_MAP_FLOAT_OOB_FILL_NONE);
  }
  {
    cuuint64_t dim[4] = {512, 2, 4, 64}, str[3] = {1024, 2048, 8192};
    cuuint32_t box[4] = {64, 2, 1, 32}, es[4] = {1, 1, 1, 1};
    enc(&mWo, CU_TENSOR_MAP_DATA_TYPE_BFLOAT16, 4, d_in[11], dim, str, box, es, CU_TENSOR_MAP_INTERLEAVE_NONE,
        CU_TENSOR_MAP_SWIZZLE_128B, CU_TENSOR_MAP_L2_PROMOTION_NONE, CU_TENSOR_MAP_FLOAT_OOB_FILL_NONE);
  }
  {
    cuuint64_t dim[2] = {16384, 64}, str[1] = {32768};
    cuuint32_t box[2] = {128, 8}, es[2] = {1, 1};
    enc(&mX, CU_TENSOR_MAP_DATA_TYPE_BFLOAT16, 2, scratch->XF[0], dim, str, box, es, CU_TENSOR_MAP_INTERLEAVE_NONE,
        CU_TENSOR_MAP_SWIZZLE_NONE, CU_TENSOR_MAP_L2_PROMOTION_NONE, CU_TENSOR_MAP_FLOAT_OOB_FILL_NONE);
  }
  Params P;
  P.x0 = (const uint16_t*)d_in[0]; P.Are = (const uint16_t*)d_in[1]; P.Aim = (const uint16_t*)d_in[2];
  P.Bre = (const uint16_t*)d_in[3]; P.Bim = (const uint16_t*)d_in[4]; P.Cre = (const uint16_t*)d_in[5];
  P.Cim = (const uint16_t*)d_in[6]; P.logdt = (const uint16_t*)d_in[7]; P.dskip = (const uint16_t*)d_in[8];
  P.wqkv = (const uint16_t*)d_in[10]; P.wo = (const uint16_t*)d_in[11]; P.out = (uint16_t*)d_out;
  for (int k = 0; k < 72; ++k) P.role[k] = role[k];
  P.zero = 0;
  P.mid = (char*)scratch->C;
  P.spare = nsm > 0 ? nsm - 128 : 0;
  fused_kernel<<<nsm > 0 ? nsm : 128, NTHR, SM_TOTAL, cudaStreamPerThread>>>(P, mW, mWo, mX);
}
```

```cpp
#include <cuda_runtime.h>
#include <cuda_bf16.h>
#include <cuda.h>
#include <stdint.h>
#include <stddef.h>

#define DEV __device__ __forceinline__
#define RARE(x) __builtin_expect(!!(x), 0)

#define KCS 0
constexpr int NTHR = 512;
constexpr int REG_MAIN = 192, REG_AUX = 88, REG_PROD = 40;
constexpr int NBARU = 384;
constexpr int SPIN_LIMIT = 1 << 22;

constexpr uint32_t SB = 1024;
__host__ __device__ constexpr uint32_t slot(int n) { return SB + n * 8192; }
__host__ __device__ constexpr int wslot(int k) { return k < 2 ? 3 * k : k < 4 ? 3 * k + 6 : k < 6 ? 21 - 3 * k : 3 * k - 18; }
constexpr uint32_t SM_A = slot(22), A_E = 0u - 32768;
constexpr uint32_t SM_O = slot(18), O_E = 0u - 147456;
constexpr uint32_t SM_WO = slot(10), SM_X = slot(8), SM_KV = slot(9) - 4096;
constexpr uint32_t SM_TAP  = slot(26);
constexpr int TAP_SZ = 3440;
constexpr uint32_t SM_STAT = SM_TAP + 4 * TAP_SZ;
constexpr uint32_t SM_CS   = SM_STAT + 1024;
constexpr uint32_t SM_BAR  = SM_CS + 768;
constexpr int SM_TOTAL = SM_BAR + 352 - SB;
static_assert(SM_TOTAL <= 232448, "");
constexpr int R_SZ = 16384, R_U = 512, R_X5 = 5120, R_X3 = 8704, R_BO = 11776, R_BE = 13824;
constexpr int X_5 = 576, X_3 = 648, T_E = 2 * 720, T_O = 1600 + 2 * 721, T_C = 3390, T_K = 3424;
constexpr uint32_t B_RD = SM_BAR, B_ED = SM_BAR + 16, B_F = SM_BAR + 32, B_AT = SM_BAR + 56, B_L = SM_BAR + 264;
constexpr uint32_t B_AE = SM_BAR + 72, B_QE = SM_BAR + 88, B_ST = SM_BAR + 96, B_CS = SM_BAR + 112;
constexpr uint32_t B_WO = SM_BAR + 120, B_W6 = SM_BAR + 128, B_U = SM_BAR + 144, B_E = SM_BAR + 152, B_WF = SM_BAR + 160, B_W4 = SM_BAR + 168,
                   B_N = SM_BAR + 176, B_V = SM_BAR + 184, B_O = SM_BAR + 192, B_Z = SM_BAR + 256, B_A = SM_BAR + 272;
constexpr int NB_U = 1, NB_B = 2, NB_K = 8, NB_Y = 6, NB_WG = 8, NB_T = 10, NB_AUX = 12, NB_P0 = 13, NB_H = 15;

struct Scratch {
  uint4    XG[2][128 * 1024];
  uint4    O[32 * 8 * 512];
  uint32_t C[8 * 32];
  uint32_t OF[2][32 * 32];
  uint4    CS[16 * 1536 / 4];
  uint4    PS[128 * 64];
  uint4    ST[2][32 * 128];
  uint4    SR[2][8][512];
  uint4    XF[2][32 * 512 * 8];
  uint4    H[2][17 * 8 * 256];
};
__device__ __align__(1024) Scratch g_S;
#define SCR ((Scratch*)(P.mid - offsetof(Scratch, C)))
#define PROFD(slot, v) do {} while (0)
#define PROF(slot) do {} while (0)
#define PROFK(slot) do {} while (0)

#define PROFC(slot) do {} while (0)

DEV uint32_t s2u(const void* p) { return (uint32_t)__cvta_generic_to_shared(p); }
template <class T> DEV T* opqp(T* x) { asm volatile("" : "+l"(x)); return x; }
template <class T> DEV T opq(T x) { asm volatile("" : "+r"(x)); return x; }
DEV int lane_id() { int l; asm volatile("mov.u32 %0,%%laneid;" : "=r"(l)); return l; }
DEV uint32_t pack2(float lo, float hi) { uint32_t d; asm("cvt.rn.bf16x2.f32 %0,%1,%2;" : "=r"(d) : "f"(hi), "f"(lo)); return d; }
DEV float bflo(uint32_t v) { return __uint_as_float(v << 16); }
DEV float bfhi(uint32_t v) { return __uint_as_float(v & 0xFFFF0000u); }
DEV float bfr(float x) { return bflo(pack2(x, 0.f)); }
DEV uint32_t hadd2(uint32_t a, uint32_t b) { uint32_t d; asm("add.rn.bf16x2 %0,%1,%2;" : "=r"(d) : "r"(a), "r"(b)); return d; }
DEV uint32_t hsub2(uint32_t a, uint32_t b) { uint32_t d; asm("sub.rn.bf16x2 %0,%1,%2;" : "=r"(d) : "r"(a), "r"(b)); return d; }
DEV uint32_t hmul2(uint32_t a, uint32_t b) { uint32_t d; asm("mul.rn.bf16x2 %0,%1,%2;" : "=r"(d) : "r"(a), "r"(b)); return d; }
DEV uint32_t hfma2(uint32_t a, uint32_t b, uint32_t c) { uint32_t d; asm("fma.rn.bf16x2 %0,%1,%2,%3;" : "=r"(d) : "r"(a), "r"(b), "r"(c)); return d; }
DEV uint32_t hmax2(uint32_t a, uint32_t b) { uint32_t d; asm("max.bf16x2 %0,%1,%2;" : "=r"(d) : "r"(a), "r"(b)); return d; }
DEV uint32_t prmt(uint32_t a, uint32_t b, uint32_t s) { uint32_t d; asm("prmt.b32 %0,%1,%2,%3;" : "=r"(d) : "r"(a), "r"(b), "r"(s)); return d; }
DEV uint32_t nzmap(uint32_t v) { uint32_t d; asm("max.u32 %0,%1,1;" : "=r"(d) : "r"(v)); return d; }
DEV float rcp(float x) { float y; asm("rcp.approx.ftz.f32 %0,%1;" : "=f"(y) : "f"(x)); return y; }
DEV float sqrt_(float x) { float y; asm("sqrt.approx.ftz.f32 %0,%1;" : "=f"(y) : "f"(x)); return y; }
DEV float ex2(float x) { float y; asm("ex2.approx.ftz.f32 %0,%1;" : "=f"(y) : "f"(x)); return y; }

DEV uint4 ldr4(const void* p) { uint4 v; asm volatile("ld.relaxed.gpu.global.v4.u32 {%0,%1,%2,%3},[%4];" : "=r"(v.x), "=r"(v.y), "=r"(v.z), "=r"(v.w) : "l"(p) : "memory"); return v; }
DEV void ldr4_if(uint4& v, const void* p, bool c) {
  asm volatile("{.reg .pred q; setp.ne.u32 q,%5,0; @q ld.relaxed.gpu.global.v4.u32 {%0,%1,%2,%3},[%4];}"
    : "+r"(v.x), "+r"(v.y), "+r"(v.z), "+r"(v.w) : "l"(p), "r"((uint32_t)c) : "memory");
}
DEV uint2 ldr2(const void* p) { uint2 v; asm volatile("ld.relaxed.gpu.global.v2.u32 {%0,%1},[%2];" : "=r"(v.x), "=r"(v.y) : "l"(p) : "memory"); return v; }
DEV void ldr2_if(uint2& v, const void* p, bool c) {
  asm volatile("{.reg .pred q; setp.ne.u32 q,%3,0; @q ld.relaxed.gpu.global.v2.u32 {%0,%1},[%2];}" : "+r"(v.x), "+r"(v.y) : "l"(p), "r"((uint32_t)c) : "memory");
}
DEV uint32_t ldr1(const void* p) { uint32_t v; asm volatile("ld.relaxed.gpu.global.u32 %0,[%1];" : "=r"(v) : "l"(p) : "memory"); return v; }
DEV float ldnan(const uint16_t* p) {
  uint32_t v = 0xFFFFu;
#pragma unroll 1
  for (int it = 0; it < SPIN_LIMIT && __any_sync(0xffffffffu, v == 0xFFFFu); ++it) asm volatile("ld.relaxed.gpu.global.u16 %0,[%1];" : "=r"(v) : "l"(p) : "memory");
  return __uint_as_float(v << 16);
}
DEV uint4 ldw4(const void* p) { uint4 v; asm volatile("ld.global.v4.u32 {%0,%1,%2,%3},[%4];" : "=r"(v.x), "=r"(v.y), "=r"(v.z), "=r"(v.w) : "l"(p) : "memory"); return v; }
DEV uint2 ldw2(const void* p) { uint2 v; asm volatile("ld.global.v2.u32 {%0,%1},[%2];" : "=r"(v.x), "=r"(v.y) : "l"(p) : "memory"); return v; }
DEV uint32_t ldw1(const void* p) { uint32_t v; asm volatile("ld.global.u32 %0,[%1];" : "=r"(v) : "l"(p) : "memory"); return v; }
DEV void str4(void* p, uint32_t a, uint32_t b, uint32_t c, uint32_t d) { asm volatile("st.relaxed.gpu.global.v4.u32 [%0],{%1,%2,%3,%4};" :: "l"(p), "r"(a), "r"(b), "r"(c), "r"(d) : "memory"); }
DEV void str2(void* p, uint32_t a, uint32_t b) { asm volatile("st.relaxed.gpu.global.v2.u32 [%0],{%1,%2};" :: "l"(p), "r"(a), "r"(b) : "memory"); }
DEV void str1(void* p, uint32_t a) { asm volatile("st.relaxed.gpu.global.u32 [%0],%1;" :: "l"(p), "r"(a) : "memory"); }
DEV void str4_if(void* p, uint32_t a, uint32_t b, uint32_t c, uint32_t d, bool q) {
  asm volatile("{.reg .pred q; setp.ne.u32 q,%5,0; @q st.relaxed.gpu.global.v4.u32 [%0],{%1,%2,%3,%4};}" :: "l"(p), "r"(a), "r"(b), "r"(c), "r"(d), "r"((uint32_t)q) : "memory");
}
DEV void stw4(void* p, uint32_t a, uint32_t b, uint32_t c, uint32_t d) { asm volatile("st.global.v4.u32 [%0],{%1,%2,%3,%4};" :: "l"(p), "r"(a), "r"(b), "r"(c), "r"(d) : "memory"); }
DEV uint4 ldnc4(const void* p) { uint4 v; asm volatile("ld.global.nc.v4.u32 {%0,%1,%2,%3},[%4];" : "=r"(v.x), "=r"(v.y), "=r"(v.z), "=r"(v.w) : "l"(p)); return v; }
DEV uint32_t ldnc1(const void* p) { uint32_t v; asm volatile("ld.global.nc.u32 %0,[%1];" : "=r"(v) : "l"(p)); return v; }
DEV uint2 ldnc2(const void* p) { uint2 v; asm volatile("ld.global.nc.v2.u32 {%0,%1},[%2];" : "=r"(v.x), "=r"(v.y) : "l"(p)); return v; }

DEV uint2 lds2(uint32_t a) { uint2 v; asm volatile("ld.volatile.shared.v2.u32 {%0,%1},[%2];" : "=r"(v.x), "=r"(v.y) : "r"(a)); return v; }
DEV float lds16f(uint32_t a) { uint32_t v; asm volatile("ld.shared.u16 %0,[%1];" : "=r"(v) : "r"(a)); return __uint_as_float(v << 16); }
DEV void sts2(uint32_t a, uint32_t x, uint32_t y) { asm volatile("st.shared.v2.u32 [%0],{%1,%2};" :: "r"(a), "r"(x), "r"(y) : "memory"); }
DEV uint32_t lds1(uint32_t a) { uint32_t v; asm volatile("ld.volatile.shared.u32 %0,[%1];" : "=r"(v) : "r"(a)); return v; }
DEV uint32_t lds1z(uint32_t a, bool c) {
  uint32_t v; asm volatile("{.reg .pred q; setp.ne.u32 q,%2,0; mov.u32 %0,0; @q ld.volatile.shared.u32 %0,[%1];}" : "=r"(v) : "r"(a), "r"((uint32_t)c)); return v;
}
DEV uint4 lds4z(uint32_t a, bool c) {
  uint4 v = make_uint4(0, 0, 0, 0);
  asm volatile("{.reg .pred q; setp.ne.u32 q,%5,0; @q ld.volatile.shared.v4.u32 {%0,%1,%2,%3},[%4];}" : "+r"(v.x), "+r"(v.y), "+r"(v.z), "+r"(v.w) : "r"(a), "r"((uint32_t)c));
  return v;
}
DEV float lds1f(uint32_t a) { float v; asm volatile("ld.shared.f32 %0,[%1];" : "=f"(v) : "r"(a)); return v; }
DEV float2 lds2f(uint32_t a) { float2 v; asm volatile("ld.shared.v2.f32 {%0,%1},[%2];" : "=f"(v.x), "=f"(v.y) : "r"(a)); return v; }
DEV float4 lds4f(uint32_t a) { float4 v; asm volatile("ld.volatile.shared.v4.f32 {%0,%1,%2,%3},[%4];" : "=f"(v.x), "=f"(v.y), "=f"(v.z), "=f"(v.w) : "r"(a)); return v; }
DEV uint4 lds4(uint32_t a) { uint4 v; asm volatile("ld.volatile.shared.v4.u32 {%0,%1,%2,%3},[%4];" : "=r"(v.x), "=r"(v.y), "=r"(v.z), "=r"(v.w) : "r"(a)); return v; }
DEV void sts1(uint32_t a, uint32_t v) { asm volatile("st.shared.u32 [%0],%1;" :: "r"(a), "r"(v) : "memory"); }
DEV void sts16(uint32_t a, uint32_t v) { asm volatile("st.shared.u16 [%0],%1;" :: "r"(a), "r"(v) : "memory"); }
DEV void sts2f(uint32_t a, float x, float y) { asm volatile("st.shared.v2.f32 [%0],{%1,%2};" :: "r"(a), "f"(x), "f"(y) : "memory"); }
DEV void sts4f(uint32_t a, float x, float y, float z, float w) { asm volatile("st.shared.v4.f32 [%0],{%1,%2,%3,%4};" :: "r"(a), "f"(x), "f"(y), "f"(z), "f"(w) : "memory"); }
DEV void sts4(uint32_t a, uint32_t x, uint32_t y, uint32_t z, uint32_t w) { asm volatile("st.shared.v4.u32 [%0],{%1,%2,%3,%4};" :: "r"(a), "r"(x), "r"(y), "r"(z), "r"(w) : "memory"); }

DEV void ldsm4(uint32_t (&r)[4], uint32_t a) { asm volatile("ldmatrix.sync.aligned.m8n8.x4.shared.b16 {%0,%1,%2,%3},[%4];" : "=r"(r[0]), "=r"(r[1]), "=r"(r[2]), "=r"(r[3]) : "r"(a) : "memory"); }
DEV void ldsm4t(uint32_t (&r)[4], uint32_t a) { asm volatile("ldmatrix.sync.aligned.m8n8.x4.trans.shared.b16 {%0,%1,%2,%3},[%4];" : "=r"(r[0]), "=r"(r[1]), "=r"(r[2]), "=r"(r[3]) : "r"(a) : "memory"); }
DEV void ldsm2(uint32_t (&r)[2], uint32_t a) { asm volatile("ldmatrix.sync.aligned.m8n8.x2.shared.b16 {%0,%1},[%2];" : "=r"(r[0]), "=r"(r[1]) : "r"(a) : "memory"); }
DEV void stsm4(uint32_t a, uint32_t r0, uint32_t r1, uint32_t r2, uint32_t r3) { asm volatile("stmatrix.sync.aligned.m8n8.x4.shared.b16 [%0],{%1,%2,%3,%4};" :: "r"(a), "r"(r0), "r"(r1), "r"(r2), "r"(r3) : "memory"); }
DEV void stsm2(uint32_t a, uint32_t r0, uint32_t r1) { asm volatile("stmatrix.sync.aligned.m8n8.x2.shared.b16 [%0],{%1,%2};" :: "r"(a), "r"(r0), "r"(r1) : "memory"); }
DEV void stsm4t(uint32_t a, uint32_t r0, uint32_t r1, uint32_t r2, uint32_t r3) { asm volatile("stmatrix.sync.aligned.m8n8.x4.trans.shared.b16 [%0],{%1,%2,%3,%4};" :: "r"(a), "r"(r0), "r"(r1), "r"(r2), "r"(r3) : "memory"); }
DEV uint32_t movm(uint32_t a) { uint32_t d; asm volatile("movmatrix.sync.aligned.m8n8.trans.b16 %0,%1;" : "=r"(d) : "r"(a)); return d; }
DEV void mma16(float (&d)[4], uint32_t a0, uint32_t a1, uint32_t a2, uint32_t a3, uint32_t b0, uint32_t b1) {
  asm volatile("mma.sync.aligned.m16n8k16.row.col.f32.bf16.bf16.f32 {%0,%1,%2,%3},{%4,%5,%6,%7},{%8,%9},{%0,%1,%2,%3};"
    : "+f"(d[0]), "+f"(d[1]), "+f"(d[2]), "+f"(d[3]) : "r"(a0), "r"(a1), "r"(a2), "r"(a3), "r"(b0), "r"(b1));
}
DEV void mma16z(float (&d)[4], uint32_t a0, uint32_t a1, uint32_t a2, uint32_t a3, uint32_t b0, uint32_t b1) {
  asm volatile("mma.sync.aligned.m16n8k16.row.col.f32.bf16.bf16.f32 {%0,%1,%2,%3},{%4,%5,%6,%7},{%8,%9},{%10,%10,%10,%10};"
    : "=f"(d[0]), "=f"(d[1]), "=f"(d[2]), "=f"(d[3]) : "r"(a0), "r"(a1), "r"(a2), "r"(a3), "r"(b0), "r"(b1), "f"(0.f));
}
DEV void mma8(float (&d)[4], uint32_t a0, uint32_t a1, uint32_t b0) {
  asm volatile("mma.sync.aligned.m16n8k8.row.col.f32.bf16.bf16.f32 {%0,%1,%2,%3},{%4,%5},{%6},{%0,%1,%2,%3};"
    : "+f"(d[0]), "+f"(d[1]), "+f"(d[2]), "+f"(d[3]) : "r"(a0), "r"(a1), "r"(b0));
}

DEV void mma8z(float (&d)[4], uint32_t a0, uint32_t a1, uint32_t b0) {
  asm volatile("mma.sync.aligned.m16n8k8.row.col.f32.bf16.bf16.f32 {%0,%1,%2,%3},{%4,%5},{%6},{%7,%7,%7,%7};"
    : "=f"(d[0]), "=f"(d[1]), "=f"(d[2]), "=f"(d[3]) : "r"(a0), "r"(a1), "r"(b0), "f"(0.f));
}
DEV void bar_sync(int id, int n) { asm volatile("bar.sync %0,%1;" :: "r"(id), "r"(n) : "memory"); }
DEV void bar_sync_if(int id, int n, int c) { asm volatile("{.reg .pred q; setp.ne.s32 q,%2,0; @q bar.sync %0,%1;}" :: "r"(id), "r"(n), "r"(c) : "memory"); }
DEV void bar_arrive_if(int id, int n, int c) { asm volatile("{.reg .pred q; setp.ne.s32 q,%2,0; @q bar.arrive %0,%1;}" :: "r"(id), "r"(n), "r"(c) : "memory"); }
DEV bool bar_any(int id, int n, bool c) {
  uint32_t r; asm volatile("{.reg .pred p,q; setp.ne.u32 q,%3,0; bar.red.or.pred p,%1,%2,q; selp.u32 %0,1,0,p;}" : "=r"(r) : "r"(id), "r"(n), "r"((uint32_t)c) : "memory");
  return __any_sync(0xffffffffu, r);
}
DEV void bar_arrive(int id, int n) { asm volatile("bar.arrive %0,%1;" :: "r"(id), "r"(n) : "memory"); }
DEV void fence_async_glob() { asm volatile("fence.proxy.async.global;" ::: "memory"); }
DEV void fence_async_smem() { asm volatile("fence.proxy.async.shared::cta;" ::: "memory"); }
DEV void mbar_init(uint32_t b, int n) { asm volatile("mbarrier.init.shared::cta.b64 [%0],%1;" :: "r"(b), "r"(n) : "memory"); }
DEV void mbar_arrive(uint32_t b) { asm volatile("mbarrier.arrive.shared::cta.b64 _,[%0];" :: "r"(b) : "memory"); }
DEV void mbar_expect(uint32_t b, int bytes) { asm volatile("mbarrier.arrive.expect_tx.shared::cta.b64 _,[%0],%1;" :: "r"(b), "r"(bytes) : "memory"); }
DEV void mbar_wait(uint32_t b, uint32_t ph) {
  asm volatile("{\n.reg .pred p;\nW: mbarrier.try_wait.parity.shared::cta.b64 p,[%0],%1;\n@!p bra W;\n}" :: "r"(b), "r"(ph) : "memory");
}
DEV void mbar_watch(uint32_t b, uint32_t ph) {
  asm volatile("{\n.reg .pred p,q;\n.reg .u32 n;\nmov.u32 n,0;\n"
               "W: mbarrier.try_wait.parity.shared::cta.b64 p,[%0],%1;\n@p bra D;\n"
               "add.u32 n,n,1;\nsetp.lt.u32 q,n,%2;\n@q bra W;\ntrap;\nD:\n}"
               :: "r"(b), "r"(ph), "n"(SPIN_LIMIT) : "memory");
}
DEV void spin_guard(int it) { asm volatile("{.reg .pred p; setp.gt.s32 p,%0,%1; @p trap;}" :: "r"(it), "n"(SPIN_LIMIT)); }
DEV void split(uint32_t zero) {
  asm volatile("{.reg .pred p; setp.ne.u32 p,%0,0; @p trap;}" :: "r"(zero) : "memory");
}
DEV void pause(int n) {
  uint32_t t0, t; asm volatile("mov.u32 %0,%%clock;" : "=r"(t0));
  do asm volatile("mov.u32 %0,%%clock;" : "=r"(t)); while (t - t0 < n);
}
DEV void poll(const uint32_t* k, uint32_t n) {
#pragma unroll 1
  for (int it = 0;; ++it) {
    spin_guard(it);
    if (__all_sync(0xffffffffu, ldr1(k) >= n)) break;
  }
}
DEV void mbar_arrive1(uint32_t b) { asm volatile("{.reg .pred p; elect.sync _|p,0xffffffff; @p mbarrier.arrive.shared::cta.b64 _,[%0];}" :: "r"(b) : "memory"); }
DEV void mbar_arrive1_if(uint32_t b, int c) {
  asm volatile("{.reg .pred p,q; setp.ne.s32 q,%1,0; elect.sync _|p,0xffffffff; and.pred p,p,q; @p mbarrier.arrive.shared::cta.b64 _,[%0];}" :: "r"(b), "r"(c) : "memory");
}
DEV void mbar_expect1(uint32_t b, int bytes) { asm volatile("{.reg .pred p; elect.sync _|p,0xffffffff; @p mbarrier.arrive.expect_tx.shared::cta.b64 _,[%0],%1;}" :: "r"(b), "r"(bytes) : "memory"); }
DEV void cnt_add1(uint32_t* q) { asm volatile("{.reg .pred p; elect.sync _|p,0xffffffff; @p red.relaxed.gpu.global.add.u32 [%0],1;}" :: "l"(q) : "memory"); }
DEV void tma4(uint32_t dst, const CUtensorMap* m, int c0, int c1, int c2, int c3, uint32_t bar) {
  asm volatile("{.reg .pred p; elect.sync _|p,0xffffffff;\n"
    "@p cp.async.bulk.tensor.4d.shared::cluster.global.mbarrier::complete_tx::bytes [%0],[%1,{%2,%3,%4,%5}],[%6];}"
    :: "r"(dst), "l"(m), "r"(c0), "r"(c1), "r"(c2), "r"(c3), "r"(bar) : "memory");
}
DEV void tma3(uint32_t dst, const CUtensorMap* m, int c0, int c1, int c2, uint32_t bar) {
  asm volatile("{.reg .pred p; elect.sync _|p,0xffffffff;\n"
    "@p cp.async.bulk.tensor.3d.shared::cluster.global.mbarrier::complete_tx::bytes [%0],[%1,{%2,%3,%4}],[%5];}"
    :: "r"(dst), "l"(m), "r"(c0), "r"(c1), "r"(c2), "r"(bar) : "memory");
}
DEV void bulk(uint32_t dst, const void* src, int bytes, uint32_t bar) {
  asm volatile("{.reg .pred p; elect.sync _|p,0xffffffff;\n@p cp.async.bulk.shared::cluster.global.mbarrier::complete_tx::bytes [%0],[%1],%2,[%3];}" :: "r"(dst), "l"(src), "r"(bytes), "r"(bar) : "memory");
}

DEV void bulk_store(void* dst, uint32_t src, int bytes) {
  asm volatile("{.reg .pred p; elect.sync _|p,0xffffffff;\n@p cp.async.bulk.global.shared::cta.bulk_group [%0],[%1],%2;}" :: "l"(dst), "r"(src), "r"(bytes) : "memory");
}
DEV void tma2_store(const CUtensorMap* m, uint32_t src, int c0, int c1) {
  asm volatile("{.reg .pred p; elect.sync _|p,0xffffffff;\n@p cp.async.bulk.tensor.2d.global.shared::cta.bulk_group [%0,{%2,%3}],[%1];}" :: "l"(m), "r"(src), "r"(c0), "r"(c1) : "memory");
}
DEV void bulk_wait() { asm volatile("cp.async.bulk.commit_group;\ncp.async.bulk.wait_group 0;\nfence.proxy.async.global;" ::: "memory"); }

DEV uint32_t dlo(uint32_t addr, uint32_t lbo) { return __shfl_sync(0xffffffffu, (addr >> 4) | ((lbo >> 4) << 16), 0); }
__host__ __device__ constexpr uint32_t dhi(uint32_t sbo, uint32_t swz) { return (sbo >> 4) | (swz << 30); }
DEV void wg_fence() { asm volatile("wgmma.fence.sync.aligned;" ::: "memory"); }
DEV void wg_commit() { asm volatile("wgmma.commit_group.sync.aligned;" ::: "memory"); }
template <int N> DEV void wg_wait() { asm volatile("wgmma.wait_group.sync.aligned %0;" :: "n"(N) : "memory"); }
template <int N> DEV void zero(float (&d)[N]) {
#pragma unroll
  for (int i = 0; i < N; ++i) d[i] = 0.f;
}
template <int N> DEV void zerov(float (&d)[N]) {
#pragma unroll
  for (int i = 0; i < N; ++i) asm volatile("mov.b32 %0,0;" : "=f"(d[i]));
}
template <int N> DEV void undef(float (&d)[N]) {
#pragma unroll
  for (int i = 0; i < N; ++i) asm volatile("" : "=f"(d[i]));
}
#define R4(d, o) "+f"(d[o]), "+f"(d[o + 1]), "+f"(d[o + 2]), "+f"(d[o + 3])
#define R8(d, o) R4(d, o), R4(d, o + 4)
#define R16(d, o) R8(d, o), R8(d, o + 8)
template <int ACC> DEV void wg_rs64k(float (&d)[32], const uint32_t (&a)[4], uint32_t db) {
  asm volatile("{.reg .pred p; .reg .b64 b; setp.ne.s32 p,%38,0; mov.b64 b,{%36,%37};\n"
    "wgmma.mma_async.sync.aligned.m64n64k16.f32.bf16.bf16 {%0,%1,%2,%3,%4,%5,%6,%7,%8,%9,%10,%11,%12,%13,%14,%15,%16,%17,%18,%19,%20,%21,%22,%23,%24,%25,%26,%27,%28,%29,%30,%31},{%32,%33,%34,%35},b,p,1,1,0;}"
    : R16(d, 0), R16(d, 16) : "r"(a[0]), "r"(a[1]), "r"(a[2]), "r"(a[3]), "r"(db), "n"(dhi(512, 2)), "n"(ACC));
}
template <int ACC> DEV void wg_rs48t(float (&d)[24], const uint32_t (&a)[4], uint32_t db) {
  asm volatile("{.reg .pred p; .reg .b64 b; setp.ne.s32 p,%30,0; mov.b64 b,{%28,%29};\n"
    "wgmma.mma_async.sync.aligned.m64n48k16.f32.bf16.bf16 {%0,%1,%2,%3,%4,%5,%6,%7,%8,%9,%10,%11,%12,%13,%14,%15,%16,%17,%18,%19,%20,%21,%22,%23},{%24,%25,%26,%27},b,p,1,1,1;}"
    : R16(d, 0), R8(d, 16) : "r"(a[0]), "r"(a[1]), "r"(a[2]), "r"(a[3]), "r"(db), "n"(dhi(512, 0)), "n"(ACC));
}
template <int ACC> DEV void wg_rs32t(float (&d)[16], const uint32_t (&a)[4], uint32_t db) {
  asm volatile("{.reg .pred p; .reg .b64 b; setp.ne.s32 p,%22,0; mov.b64 b,{%20,%21};\n"
    "wgmma.mma_async.sync.aligned.m64n32k16.f32.bf16.bf16 {%0,%1,%2,%3,%4,%5,%6,%7,%8,%9,%10,%11,%12,%13,%14,%15},{%16,%17,%18,%19},b,p,1,1,1;}"
    : R16(d, 0) : "r"(a[0]), "r"(a[1]), "r"(a[2]), "r"(a[3]), "r"(db), "n"(dhi(1024, 0)), "n"(ACC));
}
template <int ACC> DEV void wg_ss192(float (&d)[96], uint32_t da, uint32_t db) {
  asm volatile("{.reg .pred p; .reg .b64 a,b; setp.ne.s32 p,%100,0; mov.b64 a,{%96,%98}; mov.b64 b,{%97,%99};\n"
    "wgmma.mma_async.sync.aligned.m64n192k16.f32.bf16.bf16 {"
    "%0,%1,%2,%3,%4,%5,%6,%7,%8,%9,%10,%11,%12,%13,%14,%15,%16,%17,%18,%19,%20,%21,%22,%23,%24,%25,%26,%27,%28,%29,%30,%31,"
    "%32,%33,%34,%35,%36,%37,%38,%39,%40,%41,%42,%43,%44,%45,%46,%47,%48,%49,%50,%51,%52,%53,%54,%55,%56,%57,%58,%59,%60,%61,%62,%63,"
    "%64,%65,%66,%67,%68,%69,%70,%71,%72,%73,%74,%75,%76,%77,%78,%79,%80,%81,%82,%83,%84,%85,%86,%87,%88,%89,%90,%91,%92,%93,%94,%95},a,b,p,1,1,1,1;}"
    : R16(d, 0), R16(d, 16), R16(d, 32), R16(d, 48), R16(d, 64), R16(d, 80) : "r"(da), "r"(db), "n"(dhi(1024, 1)), "n"(dhi(1024, 1)), "n"(ACC));
}
template <int ACC> DEV void wg_ss64(float (&d)[32], uint32_t da, uint32_t db) {
  asm volatile("{.reg .pred p; .reg .b64 a,b; setp.ne.s32 p,%36,0; mov.b64 a,{%32,%34}; mov.b64 b,{%33,%35};\n"
    "wgmma.mma_async.sync.aligned.m64n64k16.f32.bf16.bf16 {"
    "%0,%1,%2,%3,%4,%5,%6,%7,%8,%9,%10,%11,%12,%13,%14,%15,%16,%17,%18,%19,%20,%21,%22,%23,%24,%25,%26,%27,%28,%29,%30,%31},a,b,p,1,1,0,1;}"
    : R16(d, 0), R16(d, 16) : "r"(da), "r"(db), "n"(dhi(1024, 0)), "n"(dhi(1024, 1)), "n"(ACC));
}

DEV uint32_t cpy(uint32_t v, uint32_t id) {
  uint32_t d; asm volatile("prmt.b32 %0,%1,%1,%2;" : "=r"(d) : "r"(v), "r"(id)); return d;
}
struct Params {
  uint32_t zero, spare;
  char* mid;
  const uint16_t *x0, *Are, *Aim, *Bre, *Bim, *Cre, *Cim, *logdt, *dskip, *wqkv, *wo;
  uint16_t* out;
  uint8_t role[72];
};

DEV uint32_t ln_word(float mean, float var) {
  float v = bfr(var);
  float s = sqrt_(bfr(v + 1e-5f));
  return pack2(mean, s);
}

DEV int stat_group(int c) { return c ^ 4; }
DEV int xg_off(int G, int g) { return (G >> 6) * 1024 + (G & 63) * 8 + (g ^ (G & 2)); }
DEV int sr_off(int G, int g) { return (G >> 6) * 256 + (g & 2) * 64 + 2 * (G & 63) + ((g >> 2) & 1); }
DEV uint32_t region(int chl) { return SM_A + (chl >> 1) * A_E + (chl & 1) * R_SZ; }
template <bool FIRST> DEV void gram(float (&s)[4], float (&q0)[4], float (&q1)[4], uint32_t a0, uint32_t a1, uint32_t a2, uint32_t a3) {
  const uint32_t one = 0x3F803F80u;
  if (FIRST) { mma16z(s, a0, a1, a2, a3, one, one); mma8z(q0, a0, a1, a0); mma8z(q1, a0, a1, a1); }
  else { mma16(s, a0, a1, a2, a3, one, one); mma8(q0, a0, a1, a0); mma8(q1, a0, a1, a1); }
  mma8(q0, a2, a3, a2); mma8(q1, a2, a3, a3);
}
DEV uint32_t ln_sums(float s, float q) { const float m = s * (1.f / 512.f); return ln_word(m, fmaxf(q * (1.f / 512.f) - m * m, 0.f)); }
DEV void cmul(float& orr, float& oi, float ar, float ai, float br, float bi) {
  float r = ar * br - ai * bi, i = ar * bi + ai * br; orr = r; oi = i;
}
DEV void cexp_(float al, float bt, float s, float& er, float& ei) {
  float mag = ex2(al * s), ph = bt * s;
  ph -= rintf(ph);
  float ang = ph * 6.283185307179586f;
  er = mag * __cosf(ang); ei = mag * __sinf(ang);
}

DEV void kgen(const Params& P, int c, int wm, int lane) {
  const int chl = wm >> 1, mh = wm & 1, g = lane >> 2, t = lane & 3;
  const int ch = 256 * (chl >> 1) + 2 * c + (chl & 1);
  const int mo = ch * 64 + mh * 32 + lane;
  const uint32_t vAr = ldw1((const uint32_t*)P.Are + mo), vAi = ldw1((const uint32_t*)P.Aim + mo);
  const uint32_t vBr = ldw1((const uint32_t*)P.Bre + mo), vBi = ldw1((const uint32_t*)P.Bim + mo);
  const uint32_t vCr = ldw1((const uint32_t*)P.Cre + mo), vCi = ldw1((const uint32_t*)P.Cim + mo);
  const uint32_t vld = ldw1((const uint32_t*)P.logdt + (ch >> 1)), vds = ldw1((const uint32_t*)P.dskip + (ch >> 1));
  bar_arrive(NB_Y, 384);
  PROF(45);
  {
    const uint32_t tz = SM_TAP + chl * TAP_SZ + (mh * 32 + lane) * 16;
#pragma unroll
    for (int k = 0; k < 3; ++k) sts4(tz + k * 1024, 0, 0, 0, 0);
    static_assert(TAP_SZ > 3072 && TAP_SZ <= 4096, "");
    if (mh * 32 + lane < TAP_SZ / 16 - 192) sts4(tz + 3072, 0, 0, 0, 0);
  }
  const uint32_t tb = slot(wm), tw = opq(tb + lane * 4);
  const uint32_t aa = opq(tb + (lane & 15) * 144 + (lane >> 4) * 16), ba = opq(tb + (16 + (lane & 7)) * 144 + (lane >> 3) * 16);
  float acc[5][4], k2048 = 0.f;
#pragma unroll
  for (int i = 0; i < 5; ++i) zerov(acc[i]);
  sts1(tw, 0x3F80u);
  asm volatile("setmaxnreg.inc.sync.aligned.u32 %0;" :: "n"(REG_MAIN));
  PROF(44);
  const float dt = bfr(ex2((ch & 1 ? bfhi(vld) : bflo(vld)) * 1.4426950408889634f));
#pragma unroll 1
  for (int r = 0; r < 2; ++r) {
    const uint32_t sel = r ? 0x3244 : 0x1044;
    const float are = __uint_as_float(prmt(vAr, 0, sel)), aim = __uint_as_float(prmt(vAi, 0, sel)), bre = __uint_as_float(prmt(vBr, 0, sel));
    const float bim = __uint_as_float(prmt(vBi, 0, sel)), cre = __uint_as_float(prmt(vCr, 0, sel)), cim = __uint_as_float(prmt(vCi, 0, sel));
    const float al = dt * are * 1.4426950408889634f, bt = dt * aim * 0.15915494309189535f;
    float qr, qi; cmul(qr, qi, cre, cim, dt * bre, dt * bim);
    if (r == 0) PROFD(2, __float_as_uint(qr + al + bt));
    float er[3], ei[3], e8r, e8i, eLr, eLi;
    cexp_(al, bt, 1.f, er[0], ei[0]); cexp_(al, -bt, 8.f, e8r, e8i); cexp_(al, bt, 128.f, eLr, eLi);
    cmul(er[1], ei[1], er[0], ei[0], er[0], ei[0]); cmul(er[2], ei[2], er[1], ei[1], er[1], ei[1]);
    float yr = e8r, yi = e8i;
#pragma unroll
    for (int a = 0; a < 16; ++a) {
      if (a) sts1(tw + a * 144, pack2(yr, yi));
      if (a && a < 15) cmul(yr, yi, yr, yi, e8r, e8i);
      const int ls = a < 2 ? 0 : a < 4 ? 1 : a < 8 ? 2 : 3;
      const int row0 = 16 + (a < 2 ? 8 * a : a < 4 ? 16 + 4 * (a - 2) : a < 8 ? 24 + 2 * (a - 4) : 32 + (a - 8));
      float xr[8], xi[8];
      xr[0] = qr; xi[0] = qi;
#pragma unroll
      for (int k = 0; k < (8 >> ls); ++k) {
        const int hb = k >= 4 ? 2 : k >= 2 ? 1 : 0;
        if (k) cmul(xr[k], xi[k], xr[k - (1 << hb)], xi[k - (1 << hb)], er[(ls + hb) % 3], ei[(ls + hb) % 3]);
        sts1(tw + (row0 + k) * 144, pack2(xr[k], xi[k]));
      }
      cmul(qr, qi, qr, qi, eLr, eLi);
    }
    __syncwarp();
    if (r == 0) PROF(3);
#pragma unroll
    for (int kp = 0; kp < 2; ++kp) {
      uint32_t a0[4], a1[4];
      ldsm4(a0, aa + kp * 64); ldsm4(a1, aa + kp * 64 + 32);
#pragma unroll
      for (int tl = 0; tl < 5; ++tl) {
        uint32_t b[4];
        ldsm4(b, ba + 8 * tl * 144 + kp * 64);
        if (kp == 0) qr += __shfl_xor_sync(0xffffffffu, qr, 1 << tl);
        mma16(acc[tl], a0[0], a0[1], a0[2], a0[3], b[0], b[1]);
        mma16(acc[tl], a1[0], a1[1], a1[2], a1[3], b[2], b[3]);
      }
    }
    k2048 += qr;
    __syncwarp();
  }
  const uint32_t xa = tb + lane * 16, ob = xa ^ 8192, tp = SM_TAP + chl * TAP_SZ;
  if (mh == 0) {
    sts4f(xa, acc[2][0], acc[2][1], acc[2][2], acc[2][3]);
    sts4f(xa + 512, acc[3][0], acc[3][1], acc[3][2], acc[3][3]);
    sts1(tb + 1024, __float_as_uint(k2048));
  } else {
    sts4f(xa, acc[0][0], acc[0][1], acc[0][2], acc[0][3]);
    sts4f(xa + 512, acc[1][0], acc[1][1], acc[1][2], acc[1][3]);
    sts4f(xa + 1024, acc[4][0], acc[4][1], acc[4][2], acc[4][3]);
  }
  PROF(4);
  bar_sync(NB_K + chl, 64);
  float4 o[3];
#pragma unroll
  for (int k = 0; k < 3; ++k) o[k] = lds4f(ob + k * 512);
  if (mh == 0) {
    if (lane == 0) o[0].x += ch & 1 ? bfhi(vds) : bflo(vds);
    const uint32_t a = tp - 2 * (8 * g + 2 * t + 1);
#pragma unroll
    for (int z = 0; z < 4; ++z) {
      const float* k = acc[z >> 1] + 2 * (z & 1);
      const uint32_t v = z & 1 ? pack2(k[1] + o[z >> 1].w, k[0] + o[z >> 1].z) : pack2(k[1] + o[z >> 1].y, k[0] + o[z >> 1].x);
      sts1(a + T_O - 128 * z, v); sts16(a + T_E - 128 * z, v); sts16(a + T_E + 2 - 128 * z, v >> 16);
    }
    const uint32_t v0 = pack2(acc[4][0] + o[2].x, acc[4][1] + o[2].y), v1 = pack2(acc[4][2] + o[2].z, acc[4][3] + o[2].w);
    const uint32_t b = tp + T_C - 2 * (32 * t + g - 1);
    if (lane == 0) { sts16(tp + T_E - 2 * (X_5 + 63), v0); sts16(tp + T_O - 2 * (X_5 + 63), v0); sts1(tp + T_K, prmt(v0, v0, 0x1010)); }
    else sts16(b, v0);
    sts16(b - 32, v0 >> 16); sts16(b - 16, v1); sts16(b - 48, v1 >> 16);
  } else {
    const uint32_t a = tp - 2 * (256 + 128 * (t >> 1) + 4 * (t & 1) + 8 * g);
#pragma unroll
    for (int z = 0; z < 2; ++z) {
      const uint32_t v = z ? pack2(acc[2][3] + o[0].w, acc[2][2] + o[0].z) : pack2(acc[2][1] + o[0].y, acc[2][0] + o[0].x), d = prmt(v, v, 0x3232);
      sts1(a + T_E - 4 - 128 * z, v); sts16(a + T_O - 4 - 128 * z, v); sts1(a + T_O - 2 - 128 * z, d);
      if (z || lane) { sts1(a + T_E - 128 * z, d); sts16(a + T_O + 2 - 128 * z, d); } else sts16(a + T_E, d);
    }
    const uint32_t w0 = pack2(acc[3][0] + o[1].x, acc[3][1] + o[1].y), w1 = pack2(acc[3][2] + o[1].z, acc[3][3] + o[1].w);
    const uint32_t b = tp - 2 * (16 * t + g);
    if (lane == 0) {
      const uint32_t k = prmt(w0, w0, 0x1010);
      sts1(tp + T_E - 2 * 514, k); sts1(tp + T_E - 2 * 512, k);
      sts16(tp + T_O - 2 * 514, k); sts1(tp + T_O - 2 * 513, k); sts16(tp + T_O - 2 * 511, k);
      sts16(tp + T_C - 2 * 127, pack2(k2048 + o[2].x, 0.f));
    } else { sts16(b + T_E - 2 * (X_5 - 1), w0); sts16(b + T_O - 2 * (X_5 - 1), w0); }
    sts16(b + T_E - 2 * X_3, w0 >> 16); sts16(b + T_O - 2 * X_3, w0 >> 16);
    sts16(b + T_E - 2 * (X_5 + 7), w1); sts16(b + T_O - 2 * (X_5 + 7), w1);
    sts16(b + T_E - 2 * (X_3 + 8), w1 >> 16); sts16(b + T_O - 2 * (X_3 + 8), w1 >> 16);
  }
}

DEV bool bad8(const uint4& v) { return min(v.x, v.z) == 0u; }
DEV uint32_t uchunk(uint32_t reg, int x) { return reg + R_U + (x ^ ((x >> 3) & 3)) * 16; }
DEV uint32_t& xword(uint4 (&x)[2], int e, int tp) { uint4& v = x[tp >> 1]; return tp & 1 ? (e ? v.w : v.z) : (e ? v.y : v.x); }

DEV void uprep(const Params& P, int c, int wa, int lane, int layer, uint4 (&x)[2][2][2], uint32_t (&u)[4][4]) {
  const int j = 32 * wa + lane, o0 = 2 * j + ((j >> 2) & 1);
  {
    const uint32_t za = region(wa) + lane * 16 - 512;
    sts4(za + R_U, 0, 0, 0, 0); sts4(za + R_X5, 0, 0, 0, 0); sts4(za + R_X3, 0, 0, 0, 0);
    sts4(region(wa) + R_BE, 0, 0, 0, 0);
  }
  const uint4* st = opqp(&SCR->SR[layer][c >> 4][j]);
  const uint32_t xa = opq(SM_X + 16 * o0), xb = opq(SM_X + 16 * (o0 ^ 1)), ua = opq(uchunk(0, j));
  uint4 s[2][2];
#pragma unroll
  for (int z = 0; z < 12; ++z) {
    uint4& v = z < 8 ? x[(z >> 2) & 1][(z >> 1) & 1][z & 1] : s[(z >> 1) & 1][z & 1];
    asm volatile("mov.b32 %0,0; mov.b32 %1,0; mov.b32 %2,0; mov.b32 %3,0;" : "=r"(v.x), "=r"(v.y), "=r"(v.z), "=r"(v.w));
  }
#pragma unroll 1
  for (uint32_t it = P.zero;; ++it) {
    if (it) {
      spin_guard(it);
#pragma unroll
      for (int z = 0; z < 4; ++z) { uint4& v = s[z >> 1][z & 1]; ldr4_if(v, st + z * 128, bad8(v)); }
      const uint4* xp = &SCR->XG[layer][c * 1024 + o0];
#pragma unroll
      for (int z = 0; z < 8; ++z) {
        uint4& v = x[z >> 2][(z >> 1) & 1][z & 1];
        ldr4_if(v, (const uint4*)((uintptr_t)xp ^ (16 * (z & 1))) + (z >> 1) * 256, bad8(v));
      }
    } else {
      mbar_wait(B_U, layer);
      PROF(layer ? 25 : 10);
#pragma unroll
      for (int z = 0; z < 4; ++z) s[z >> 1][z & 1] = ldr4(st + z * 128);
#pragma unroll
      for (int z = 0; z < 4; ++z) { uint4& v = s[z >> 1][z & 1]; ldr4_if(v, st + z * 128, bad8(v)); }
      PROF(layer ? 26 : 11);
      mbar_wait(B_E, layer);
#pragma unroll
      for (int z = 7; z >= 0; --z) x[z >> 2][(z >> 1) & 1][z & 1] = lds4((z & 1 ? xb : xa) + (z >> 1) * 4096);
      PROF(layer ? 27 : 14);
    }
    uint32_t m = ~0u;
#pragma unroll
    for (int z = 7; z >= 0; --z) {
      const int k = z >> 2, chl = z & 3;
#pragma unroll
      for (int tp = 0; tp < 4; ++tp) u[chl][tp] = hfma2(xword(x[k][chl >> 1], chl & 1, tp), xword(s[k], 0, tp), xword(s[k], 1, tp));
      sts4(ua + region(chl) + k * 2048, u[chl][0], u[chl][1], u[chl][2], u[chl][3]);
      const uint4& v = x[k][chl >> 1][chl & 1];
      m = min(m, min(v.x, v.z));
      if (z < 4) m = min(m, min(s[z >> 1][z & 1].x, s[z >> 1][z & 1].z));
    }
    if (!__any_sync(0xffffffffu, m == 0)) break;
  }
  PROF(4 + 12 * layer);
}

template <bool FULL> DEV void box_unit(uint32_t reg, int s, const uint2& a, const uint4& b, const uint32_t (&d)[4], uint32_t (&pv)[4]) {
  const uint32_t u[9] = {a.x, a.y, b.x, b.y, b.z, b.w, d[0], d[1], d[2]};
  uint32_t v[8], p[8];
#pragma unroll
  for (int j = 0; j < 8; ++j) { v[j] = prmt(u[j], u[j + 1], 0x5432); p[j] = hadd2(u[j], v[j]); }
  const uint32_t o = reg + s * 16;
  uint32_t x[4], y[4];
#pragma unroll
  for (int j = 0; j < 4; ++j) { x[j] = hadd2(hadd2(p[1 + j], p[2 + j]), u[3 + j]); y[j] = hadd2(v[3 + j], p[4 + j]); pv[j] = p[4 + j]; }
  sts4(o + R_X5, x[0], x[1], x[2], x[3]);
  sts4(o + R_X3, y[0], y[1], y[2], y[3]);
  if (FULL) {
#pragma unroll
    for (int j = 0; j < 4; ++j) { y[j] = hadd2(hadd2(v[j], v[3 + j]), x[j]); x[j] = hadd2(hadd2(u[j], u[4 + j]), y[j]); }
    const bool od = s & 1;
    sts4(o + R_BO, od ? y[0] : x[0], od ? y[1] : x[1], od ? y[2] : x[2], od ? y[3] : x[3]);
    sts4(o + R_BE + 16, od ? x[0] : y[0], od ? x[1] : y[1], od ? x[2] : y[2], od ? x[3] : y[3]);
  }
}
#define NBB(e) (320 - 32 * (e))
template <int C0, int C1> DEV void box_full(int j, uint32_t (&u)[4][4], uint32_t zero) {
  const uint32_t a2 = uchunk(8, j - 2), a1 = uchunk(0, j - 1);
  uint2 a[4]; uint4 b[4];
#define HALO(n) if (n < C1) { a[(n) & 3] = lds2(region(n) + a2); b[(n) & 3] = lds4(region(n) + a1); }
  HALO(C0) HALO(C0 + 1)
  split(zero);
#pragma unroll
  for (int chl = C0; chl < C1; ++chl) {
    const uint32_t d[4] = {u[chl][0], u[chl][1], u[chl][2], u[chl][3]};
    box_unit<true>(region(chl), j, a[chl], b[chl], d, u[chl]);
    fence_async_smem();
    bar_arrive(NB_B + chl, NBB(chl & 1));
    PROFC(28 + chl);
    if (chl == C0) { HALO(C0 + 2) }
  }
#undef HALO
}
DEV void box_help(int e, int n0, int dn, int lane, int layer = 0) {
  bar_sync(NB_H, 224);
#pragma unroll 1
  for (int n = n0; n < 4; n += dn) {
    const int chl = e + (n & 2), s = 128 + 32 * (n & 1) + lane;
    const uint32_t reg = region(chl);
    const uint4 d = lds4(uchunk(reg, s));
    const uint32_t u[4] = {d.x, d.y, d.z, d.w};
    uint32_t v[4];
    box_unit<false>(reg, s, lds2(uchunk(reg, s - 2) + 8), lds4(uchunk(reg, s - 1)), u, v);
    if (dn == 2 || (n & 1)) { fence_async_smem(); bar_arrive(NB_B + chl, NBB(e)); PROFC(28 + n); }
  }
}

DEV uint4 hadd8(const uint4& a, const uint4& b) { return make_uint4(hadd2(a.x, b.x), hadd2(a.y, b.y), hadd2(a.z, b.z), hadd2(a.w, b.w)); }
DEV void conv_out(int c, int j, int chl, uint4 (&x)[2][2][2], const uint32_t (&v)[4], uint4* XF, uint32_t zero) {
  const int rho = chl >> 1, e = chl & 1;
  const uint32_t ua = uchunk(region(chl), j), fa = region(chl) + R_X5 + j * 16, ha = region(chl) + R_X3 + (j & 1) * 1088 + (j >> 1) * 16;
  const int m8 = ((j & 4) + ((j >> 1) & 1) + 2 * (j & 1)) ^ ((2 * c + e) & 7);
  uint4* xo = XF + (((16 - 2 * (j & 8) + (j >> 4)) * 512 + 256 * rho + 2 * c + e) * 8 + m8);
  bar_sync(NB_Y + e + 7 * rho, 256);
  uint4 y[2], f[2], h[2];
#pragma unroll
  for (int k = 0; k < 2; ++k) {
    y[k] = lds4(ua + k * 2048);
    f[k] = lds4z(ua + k * 2048 + R_BO - R_U, k || j >= 36);
    h[k] = lds4z(fa + k * 2048 - 1024, k || j >= 64);
  }
  const uint32_t q = lds1(SM_TAP + chl * TAP_SZ + T_K);
  const uint4 r = lds4(ha);
  split(zero);
  if (chl == 3) mbar_arrive1(B_L + (r.x & zero));
  h[1] = hadd8(h[1], make_uint4(hfma2(q, v[0], r.x), hfma2(q, v[1], r.y), hfma2(q, v[2], r.z), hfma2(q, v[3], r.w)));
#pragma unroll
  for (int k = 0; k < 2; ++k) {
    const uint4 o = hadd8(hadd8(y[k], hadd8(f[k], h[k])), make_uint4(xword(x[k][rho], e, 0), xword(x[k][rho], e, 1), xword(x[k][rho], e, 2), xword(x[k][rho], e, 3)));
    const uint32_t keep = j & 1 ? 0x7632 : 0x5410, k0 = prmt(o.x, o.y, keep), k1 = prmt(o.z, o.w, keep);
    const uint32_t g0 = __shfl_xor_sync(0xffffffffu, prmt(o.x, o.y, keep ^ 0x2222), 1), g1 = __shfl_xor_sync(0xffffffffu, prmt(o.z, o.w, keep ^ 0x2222), 1);
    str4(xo + k * 32768, j & 1 ? g0 : k0, j & 1 ? g1 : k1, j & 1 ? k0 : g0, j & 1 ? k1 : g1);

  }
  if (e) { __syncwarp(); mbar_arrive1(B_RD + rho * 8); }
  PROFC(40 + chl);
}

DEV void conv_round(int e, int rho, int w, int lane) {
  const int g = lane >> 2, t = lane & 3, chl = 2 * rho + e;
  const uint32_t reg = region(chl), tp = SM_TAP + chl * TAP_SZ, dr = dlo(reg, 128);
  const uint32_t g0 = tp + ((g & 1) ? T_O : T_E) + 2 * (2 * t - g) - 16;
  const uint32_t ga = g0 - 32 * (w & 1) - 576 * (w >> 1), id = opq(0x3210u);
  float acc[32], f1[24], f2[16];
  uint32_t q[12][4];
  {
    uint32_t qn[18][4];
    qn[0][2] = lds1(ga + 64);
#pragma unroll
    for (int n = 0; n < 18; ++n) {
      const bool nz = n < 15 || w < 2 || (n == 15 && w == 2);
      qn[n][0] = n < 15 ? lds1(ga + 48 - 32 * n) : lds1z(ga + 48 - 32 * n, nz);
      qn[n][1] = n < 15 ? lds1(ga + 32 - 32 * n) : lds1z(ga + 32 - 32 * n, nz);
    }
#pragma unroll
    for (int n = 0; n < 18; ++n) { qn[n][3] = cpy(qn[n][0], id); if (n) qn[n][2] = cpy(qn[n - 1][1], id); }
#pragma unroll
    for (int n = 0; n < 8; ++n) {
      const int i = n & 3;
      const uint32_t a = g0 + 16 - 16 * w - 2 * (n < 4 ? X_5 : X_3) + 16 * i;
      uint32_t (&q1)[4] = q[(n & 4) + (i >> 1)], (&q2)[4] = q[(n & 4) + 2 + (i >> 1)];
      q1[2 * (i & 1)] = lds1z(a, i <= w); q1[2 * (i & 1) + 1] = lds1(a - 64);
      q2[2 * (i & 1)] = cpy(0, id); q2[2 * (i & 1) + 1] = lds1z(a - 128, i >= w);
    }
    const uint32_t gc = tp + T_C - 2 + 4 * (t - g - 8 * w);
#pragma unroll
    for (int kk = 0; kk < 4; ++kk) {
      q[8 + kk][0] = lds1z(gc + 32 * kk, w >= kk); q[8 + kk][2] = lds1z(gc + 32 * kk + 16, w >= kk);
      q[8 + kk][1] = lds1(gc + 32 * kk - 128); q[8 + kk][3] = lds1(gc + 32 * kk - 112);
    }
    PROFD(rho ? 43 : 47, qn[17][2] ^ q[11][3]);
    bar_sync_if(NB_U, NBARU, 1 - rho);
    mbar_arrive1_if(B_V, chl == 1 && w == 0);
    bar_sync_if(NB_T + 1 - e, 256, chl);
    const uint32_t db = dr + (R_U + 32) / 16;
    undef(acc);
    wg_fence();
#pragma unroll
    for (int n = 0; n < 18; ++n) {
      if (n) wg_rs64k<1>(acc, qn[n], db - 2 * n); else wg_rs64k<0>(acc, qn[0], db);
      if (n == 9) wg_commit();
    }
    wg_commit();
  }
  wg_wait<1>();
  PROFC(rho ? 12 : 2);
  bar_sync(NB_B + chl, NBB(e));
  const uint32_t d1 = dr + R_X5 / 16, d2 = dr + R_BO / 16;
  undef(f1); undef(f2);
  wg_fence();
#pragma unroll
  for (int n = 0; n < 4; ++n) { if (n) wg_rs32t<1>(f2, q[8 + n], d2 + 16 * n); else wg_rs32t<0>(f2, q[8], d2); }
  wg_commit();
#pragma unroll
  for (int n = 0; n < 8; ++n) {
    const uint32_t d = d1 + (n >> 2) * ((R_X3 - R_X5) / 16) + 16 * (n & 1) - 16 * (n & 2);
    if (n) wg_rs48t<1>(f1, q[n], d); else wg_rs48t<0>(f1, q[0], d);
  }
  wg_commit();
  wg_wait<1>();
  PROFC(rho ? 13 : 3);
  bar_arrive_if(NB_T + e, 256, chl - 3);
  bar_sync(NB_WG + e, 128);
  {
    const int p = (lane + 9 * (w >> 1)) & 31;
    const uint32_t ya = reg + ((w >> 1) ? R_BO : R_U) + p * 64 + (((2 * (w & 1)) ^ ((p >> 1) & 3)) * 16);
    const uint32_t up = p < lane ? 2048 : 0;
#pragma unroll
    for (int z = 0; z < 4; ++z) {
      const float* a = acc + 16 * (z >> 1) + 2 * (z & 1);
      stsm4t((ya + (up ^ ((z >> 1) * 2048))) ^ ((z & 1) * 16), pack2(a[0], a[1]), pack2(a[4], a[5]), pack2(a[8], a[9]), pack2(a[12], a[13]));
    }
  }
  wg_wait<0>();
  PROFC(rho ? 14 : 4);
  bar_sync(NB_WG + e, 128);
  {
    const uint32_t fa = reg + R_X5 + (8 * w + (lane & 7)) * 16 + (lane >> 3) * 512;
    uint32_t h[6];
#pragma unroll
    for (int p = 0; p < 6; ++p) h[p] = p ? pack2(f1[4 * p] + f1[4 * p - 2], f1[4 * p + 1] + f1[4 * p - 1]) : pack2(f1[0], f1[1]);
    stsm4(fa, h[0], h[1], h[2], h[3]);
    stsm2(fa + 2048, h[4], h[5]);
    stsm4(reg + R_X3 + (lane < 16 ? 1088 : 0) + (8 * w + (lane & 7) + 4 * (lane & 8)) * 16, pack2(f2[0], f2[1]), pack2(f2[2] + f2[4], f2[3] + f2[5]),
          pack2(f2[8], f2[9]), pack2(f2[10] + f2[12], f2[11] + f2[13]));
  }
  bar_arrive(NB_Y + e + 7 * rho, 256);
}
constexpr uint32_t FILL = 0xFFFFFFFFu;
template <int N> DEV void fixo(uint4 (&A)[N], const uint4* p) {
#pragma unroll 1
  for (int it = 0; it < SPIN_LIMIT; ++it) {
    uint32_t m = A[0].x;
#pragma unroll
    for (int k = 1; k < N; ++k) m = max(m, A[k].x);
    if (__all_sync(0xffffffffu, m != FILL)) break;
#pragma unroll
    for (int k = 0; k < N; ++k) ldr4_if(A[k], p + k * 32, A[k].x == FILL);
  }
}
DEV bool rows_nan(float a, float b) {
  return __any_sync(0xffffffffu, a != a || b != b);
}
template <int N> DEV void slow_step(float (&acc)[N], float a0, float a1, const uint16_t* wr, uint32_t zero) {
#pragma unroll
  for (int j = 0; j < N / 4; ++j) {
    const uint32_t v = __ldg((const uint32_t*)(wr + (j >> 3) * 512 + 8 * (j & 7)));
    acc[4 * j] += a0 * bflo(v); acc[4 * j + 1] += a0 * bfhi(v); acc[4 * j + 2] += a1 * bflo(v); acc[4 * j + 3] += a1 * bfhi(v);
    if ((j & 3) == 3) wr += __float_as_uint(acc[4 * j]) & zero;
  }
}
DEV int res_off(int w, int lane) { return ((lane & 7) + 8 * (lane >> 4)) * 8 + ((2 * (w & 2) + (w & 1) + ((lane >> 2) & 2)) ^ (lane & 7)); }
DEV void res_load(uint32_t (&res)[8][2], uint32_t sa, int w, int lane) {
  const uint32_t a = sa + res_off(w, opq(lane)) * 16;
#pragma unroll
  for (int j = 0; j < 8; j += 2) {
    uint32_t r[4];
    ldsm4t(r, a + j * 1024);
    res[j][0] = r[0]; res[j][1] = r[1]; res[j + 1][0] = r[2]; res[j + 1][1] = r[3];
  }
}

DEV void res_init(float (&ac)[32], const uint32_t (&res)[8][2]) {
#pragma unroll
  for (int j = 0; j < 16; ++j)
    asm volatile("shl.b32 %0,%2,16; and.b32 %1,%2,0xFFFF0000;" : "=&f"(ac[2 * j]), "=f"(ac[2 * j + 1]) : "r"(res[j >> 1][j & 1]));
}
DEV uint32_t after(uint32_t b, const uint32_t (&res)[8][2], uint32_t zero) {
  return b + ((res[0][0] ^ res[2][0] ^ res[4][0] ^ res[6][0]) & zero);
}

DEV void attn_phase(const Params& P, int c, int e, int w, int lane, int layer) {
  lane = opq(lane); c = opq(c);
  const int i = c >> 3, cg = c & 7, J = 16 * e + i, G = 8 * i + 4 - 4 * e + w;
  const int g = lane >> 2, t = lane & 3;
  float acc[96];
  uint32_t res[8][2];
  float2 cs[16];
  float4 st;
  const uint32_t csb = opq(SM_CS + 8 * t);
  {
    const uint32_t sa = SM_A + e * A_E, ba = B_A + 32 * e;
    const uint32_t da = dlo(sa, 8192), db = (SB >> 4) | (512 << 16);
    undef(acc);
#pragma unroll
    for (int j = 0; j < 8; ++j) asm volatile("" : "=r"(res[j][0]), "=r"(res[j][1]));
    mbar_wait(B_WF, layer);
    mbar_wait(ba, 0);
    mbar_wait(B_L, layer);
    bar_sync_if(NB_T, 256, e);
    PROF(24);
#pragma unroll
    for (int j = 0; j < 4; ++j) {
      if (j) mbar_wait(ba + 8 * j, 0);
      if (j == 1) PROFK(layer ? 39 : 15);
      wg_fence();
#pragma unroll
      for (int k = 0; k < 4; ++k) {
        if (j | k) wg_ss192<1>(acc, da + j * 512 + k * 128, db + wslot(j) * 512 + k * 128); else wg_ss192<0>(acc, da, db);
        if (j == 3 && k == 1) wg_commit();
      }
      wg_commit();
      if (j == 1 || j == 2) { wg_wait<1>(); mbar_arrive1_if(B_F + 8 * (j - 1), e); }
    }
    wg_wait<1>();
    bar_arrive(NB_T + e, 256);
    wg_wait<0>();
    if (cg < 4) res_load(res, sa + cg * 8192, w, lane);
    mbar_arrive1(after(B_AE + 8 * e, res, P.zero));
    PROF(25);
#pragma unroll 1
    for (uint32_t late = P.zero;; late = 1) {
      if (late) {
        const uint16_t* xr = (const uint16_t*)SCR->XF[layer] + opq(J) * 32768;
        zero(acc);
#pragma unroll 1
        for (int k = 0; k < 512; ++k)
          slow_step(acc, ldnan(xr + k * 64 + ((2 * w) ^ (k & 7)) * 8 + g), ldnan(xr + k * 64 + ((2 * w + 1) ^ (k & 7)) * 8 + g),
                    P.wqkv + (k * 1536 + 64 * cg + 2 * t), P.zero);
        const uint32_t* q = (const uint32_t*)xr + ((64 * cg + g) * 32 + t);
        const int m8 = (2 * (w & 2) + (w & 1)) ^ g;
#pragma unroll 1
        for (int it = 0; it < SPIN_LIMIT; ++it) {
          uint32_t m = 0;
#pragma unroll
          for (int z = 0; z < 16; ++z) { const uint32_t x = ldr1(q + (z >> 1) * 256 + (m8 ^ (2 * (z & 1))) * 4); m = max(m, x); res[z >> 1][z & 1] = movm(x); }
          if (__all_sync(0xffffffffu, m != FILL)) break;
        }
#pragma unroll
        for (int z = 0; z < 16; ++z) cs[z] = lds2f(csb + 256 + z * 32);
      } else {
        mbar_wait(B_CS, 0);
#pragma unroll
        for (int z = 0; z < 16; ++z) cs[z] = lds2f(csb + 256 + z * 32);
        mbar_wait(B_W4, layer);
        mbar_wait(ba, 1);
        bar_sync(NB_T + 1 - e, 256);
        PROF(26);
#pragma unroll
        for (int j = 4; j < 8; ++j) {
          if (j > 4) mbar_wait(ba + 8 * (j - 4), 1);
          if (j >= 6) mbar_wait(B_W6 + 8 * (j - 6), layer);
          if (j > 4) PROF(31 + j);
          wg_fence();
#pragma unroll
          for (int k = 0; k < 4; ++k) {
            wg_ss192<1>(acc, da + (j & 3) * 512 + k * 128, db + wslot(j) * 512 + k * 128);
            if (j == 7 && k == 1) wg_commit();
          }
          wg_commit();
          if (j == 5) {
            if (cg >= 4) { mbar_wait(ba + 8 * (cg - 4), 1); res_load(res, sa + (cg - 4) * 8192, w, lane); }
            wg_wait<1>(); mbar_arrive1_if(B_F + 16, e); PROF(40);
          }

        }
      }
      uint32_t rs = hadd2(res[0][0], res[0][1]);
#pragma unroll
      for (int z = 2; z < 16; ++z) rs = hadd2(rs, res[z >> 1][z & 1]);
      const float rn = bflo(rs) + bfhi(rs);
      wg_wait<1>();
      bar_arrive_if(NB_T, 256, !(e | late));
      mbar_wait(B_ST + 8 * e, layer);
      st = lds4f(SM_STAT + ((4 * e + w) * 8 + g) * 16);
      PROF(34 + layer);
      wg_wait<0>();
      if (!rows_nan(acc[0] + rn, acc[2]) || late) break;
    }
  }
  mbar_arrive1(B_QE);
  PROFK(8 + 12 * layer);
  uint32_t Q[4][4], K[4][2][2], V[4][2][2];
  {
#pragma unroll
    for (int z = 0; z < 8; ++z) {
      const float* a = acc + 32 + 4 * z; const float* b = acc + 64 + 4 * z;
      K[z >> 1][1][z & 1] = pack2((a[2] - st.z * cs[z].x) * st.w, (a[3] - st.z * cs[z].y) * st.w);
      V[z >> 1][1][z & 1] = movm(pack2((b[2] - st.z * cs[8 + z].x) * st.w, (b[3] - st.z * cs[8 + z].y) * st.w));
    }
    const int hop = (G >> 1) & 3;
    const uint32_t kv = SM_KV + (2 * hop + (w & 1)) * 2048 + lane * 16;
    uint4* h = SCR->H[layer] + (c * 256 + (w & 1) * 128 + lane);
    if (hop == 3) {
#pragma unroll
      for (int z = 0; z < 4; ++z) str4(h + 2048 + z * 32, K[z][1][0], K[z][1][1], V[z][1][0], V[z][1][1]);
    } else {
      mbar_wait(B_F + 16, layer);
#pragma unroll
      for (int z = 0; z < 4; ++z) sts4(kv + z * 512, K[z][1][0], K[z][1][1], V[z][1][0], V[z][1][1]);
      bar_arrive(NB_B + hop, 128);
    }
    PROF(42);
    uint4 hv[4];
#pragma unroll
    for (int z = 0; z < 4; ++z) { hv[z] = make_uint4(0, 0, 0, 0); ldr4_if(hv[z], h + z * 32, G >= 2 && hop == 0); }
#pragma unroll
    for (int z = 0; z < 8; ++z) {
      const float* a = acc + 32 + 4 * z; const float* b = acc + 64 + 4 * z;
      K[z >> 1][0][z & 1] = pack2((a[0] - st.x * cs[z].x) * st.y, (a[1] - st.x * cs[z].y) * st.y);
      V[z >> 1][0][z & 1] = movm(pack2((b[0] - st.x * cs[8 + z].x) * st.y, (b[1] - st.x * cs[8 + z].y) * st.y));
    }
#pragma unroll
    for (int z = 0; z < 8; ++z) {
      const float2 cq = lds2f(csb + z * 32);
      const float* a = acc + 4 * z;
      Q[z >> 1][2 * (z & 1)] = pack2(a[0] - st.x * cq.x, a[1] - st.x * cq.y);
      Q[z >> 1][2 * (z & 1) + 1] = pack2(a[2] - st.z * cq.x, a[3] - st.z * cq.y);
    }
    PROF(27);
    const bool p0 = 2 * t > g, p1 = 2 * t + 1 > g, first = G < 2;
    float s[4][4], mx[4][2];
#pragma unroll
    for (int z = 0; z < 4; ++z) {
      float S[4];
      mma16z(s[z], Q[z][0], Q[z][1], Q[z][2], Q[z][3], K[z][0][0], K[z][0][1]);
      mma16z(S, Q[z][0], Q[z][1], Q[z][2], Q[z][3], K[z][1][0], K[z][1][1]);
      s[z][2] = p0 ? s[z][2] : S[2]; s[z][3] = p1 ? s[z][3] : S[3];
    }
    const float sc0 = st.y * (0.25f * 1.4426950408889634f), sc1 = st.w * (0.25f * 1.4426950408889634f);
    uint32_t pw[4][2];
#pragma unroll
    for (int r = 1; r >= 0; --r) {
      if (r == 0) {
        if (hop) {
          bar_sync(NB_B + hop - 1, 128);
#pragma unroll
          for (int z = 0; z < 4; ++z) hv[z] = lds4(kv - 4096 + z * 512);
        } else fixo(hv, h);
        PROFD(41, hv[3].x);
#pragma unroll
        for (int z = 0; z < 4; ++z) {
          float S[4];
          mma16z(S, Q[z][0], Q[z][1], Q[z][2], Q[z][3], hv[z].x, hv[z].y);
          if (first) S[0] = S[1] = __uint_as_float(0xFF800000u);
          s[z][0] = p0 ? S[0] : s[z][0]; s[z][1] = p1 ? S[1] : s[z][1];
        }
      }
#pragma unroll
      for (int z = 0; z < 4; ++z) mx[z][r] = fmaxf(s[z][2 * r], s[z][2 * r + 1]);
#pragma unroll
      for (int o = 1; o < 3; ++o)
#pragma unroll
        for (int z = 0; z < 4; ++z) mx[z][r] = fmaxf(mx[z][r], __shfl_xor_sync(0xffffffffu, mx[z][r], o));
#pragma unroll
      for (int z = 0; z < 4; ++z) pw[z][r] = pack2(ex2((s[z][2 * r] - mx[z][r]) * (r ? sc1 : sc0)), ex2((s[z][2 * r + 1] - mx[z][r]) * (r ? sc1 : sc0)));
    }
    mbar_wait(layer ? B_N : B_Z, 1);
    const uint32_t M = (p0 ? 0xFFFFu : 0u) | (p1 ? 0xFFFF0000u : 0u);
    uint4* O = SCR->O + ((J * 8 + cg) * 512 + (2 * (w & 2) + (w & 1)) * 64 + t * 8 + g);
#pragma unroll
    for (int h2 = 0; h2 < 2; ++h2) {
      uint32_t ow[2][4];
#pragma unroll
      for (int z = 0; z < 2; ++z) {
        const int n = 2 * h2 + z;
        const uint32_t w0 = pw[n][0], w1 = pw[n][1];
        float sm[4] = {0.f, 0.f, 0.f, 0.f}, Oa[2][4];
        mma8(sm, w0, w1, 0x3F803F80u);
        mma16z(Oa[0], w0 & ~M, w1 & M, 0u, w1 & ~M, V[n][0][0], V[n][1][0]); mma8(Oa[0], w0 & M, 0u, hv[n].z);
        mma16z(Oa[1], w0 & ~M, w1 & M, 0u, w1 & ~M, V[n][0][1], V[n][1][1]); mma8(Oa[1], w0 & M, 0u, hv[n].w);
        const float i0 = rcp(sm[0]), i1 = rcp(sm[2]);
#pragma unroll
        for (int d = 0; d < 2; ++d) { ow[0][2 * z + d] = pack2(Oa[d][0] * i0, Oa[d][1] * i0); ow[1][2 * z + d] = pack2(Oa[d][2] * i1, Oa[d][3] * i1); }
      }
#pragma unroll
      for (int hi = 0; hi < 2; ++hi) str4(O + hi * 128 + h2 * 32, ow[hi][0], ow[hi][1], ow[hi][2], ow[hi][3]);
    }
  }
  str1(SCR->OF[layer] + (J * 32 + cg * 4 + w), 1);
  mbar_arrive1(B_AT + 8 * e);
  PROFK(9 + 12 * layer);
  float ac[32];
  const uint32_t so = SM_O + e * O_E;
  uint2* xo = opqp(layer ? (uint2*)(P.out + ((16 * G + 2 * (lane >> 3)) * 512 + 64 * cg + 8 * (lane & 7)))
                         : (uint2*)SCR->XG[1] + ((32 * (cg & 3) + t) * 2048 + (cg >> 2) * 512 + xg_off(G, g)));
  const uint32_t stg = SM_X + (4 * e + w) * 2048;
  const uint32_t sw = opq(stg + (lane & 15) * 128 + (((lane >> 4) ^ (lane & 7)) * 16)), sr = opq(stg + (lane >> 3) * 128 + (((lane & 7) ^ (lane >> 3)) * 16));
  uint4* ps = opqp(&SCR->PS[(G * 8 + cg) * 8 + g]);
  {
    const uint32_t bo = B_O + 32 * e;
    const uint32_t dw = (SM_WO >> 4) | (512 << 16), da = dlo(so, 512);
    mbar_wait(B_WO, layer);
    res_init(ac, res);
    mbar_wait(B_AT + 8, layer);
#pragma unroll
    for (int j = 0; j < 4; ++j) {
      mbar_wait(bo + 8 * j, layer);
      if (j == 0) PROFK(32 + layer);
      wg_fence();
#pragma unroll
      for (int k = 8 * j; k < 8 * j + 8; ++k) {
        const uint32_t a = da + (k >> 2) * 512 + (k & 3) * 8, b = dw + (k & 3) * 1024 + (k >> 2) * 128;
        wg_ss64<1>(ac, a, b);
      }
      wg_commit();
    }
#pragma unroll 1
    for (uint32_t late = P.zero;; late = 1) {
      if (late) {
        const uint16_t* op = (const uint16_t*)(SCR->O + (J * 4096 + w * 128 + g));
        wg_wait<0>();
        res_init(ac, res);
#pragma unroll 1
        for (int k = 0; k < 512; ++k) {
          const uint16_t* q = op + (k >> 6) * 4096 + (k & 56) * 8 + (k & 7);
          slow_step(ac, ldnan(q), ldnan(q + 512), P.wo + (((k & ~31) + 4 * (k & 6) + ((k >> 2) & 6) + (k & 1)) * 512 + 64 * cg + 2 * t), P.zero);
        }
      }
      wg_wait<0>();
      if (!rows_nan(ac[0], ac[2]) || late) break;
    }
  }
  PROFK(10 + 12 * layer);
#pragma unroll
  for (int j = 0; j < 16; ++j) res[j >> 1][j & 1] = pack2(ac[2 * j], ac[2 * j + 1]);
  if (layer == 0) {
    float s[2][4], q0[2][4], q1[2][4];
#pragma unroll
    for (int j = 0; j < 2; ++j) gram<true>(s[j], q0[j], q1[j], res[2 * j][0], res[2 * j][1], res[2 * j + 1][0], res[2 * j + 1][1]);
#pragma unroll
    for (int j = 0; j < 2; ++j) gram<false>(s[j], q0[j], q1[j], res[2 * j + 4][0], res[2 * j + 4][1], res[2 * j + 5][0], res[2 * j + 5][1]);
    const bool od = g & 1;
    str4_if(ps, nzmap(__float_as_uint(s[0][0] + s[1][0])), __float_as_uint(od ? q0[0][1] + q0[1][1] : q0[0][0] + q0[1][0]),
            __float_as_uint(s[0][2] + s[1][2]), __float_as_uint(od ? q1[0][3] + q1[1][3] : q1[0][2] + q1[1][2]), t == (g >> 1));
#pragma unroll
    for (int j = 0; j < 8; ++j) {
      str2(xo + j * 8192, nzmap(prmt(res[j][0], res[j][1], 0x5410)), prmt(res[j][0], res[j][1], 0x7632));
    }
    mbar_arrive1(B_ED + 8 * e);
  } else {
#pragma unroll
    for (int j = 0; j < 8; j += 2) stsm4(sw ^ (j * 16), res[j][0], res[j][1], res[j + 1][0], res[j + 1][1]);
    __syncwarp();
    uint4 v[4];
#pragma unroll
    for (int k = 0; k < 4; ++k) v[k] = lds4((sr ^ ((k & 1) * 64)) + k * 512);
#pragma unroll
    for (int k = 0; k < 4; ++k) stw4(xo + ((k & 1) * 8 + (k >> 1)) * 128, v[k].x, v[k].y, v[k].z, v[k].w);
  }
  PROFK(11 + 12 * layer);
}

DEV void col_sums(const Params& P, int c, int wa, int lane) {
  const int i = c >> 3, cg = c & 7;
  uint4 wv[8];
#pragma unroll
  for (int k = 0; k < 8; ++k) wv[k] = ldnc4(P.wqkv + ((32 * i + (lane >> 3)) * 1536 + wa * 512 + 64 * cg + 8 * (lane & 7)) + 4 * k * 1536);
  float cs[8];
  zero(cs);
#pragma unroll
  for (int k = 0; k < 8; ++k) {
    cs[0] += bflo(wv[k].x); cs[1] += bfhi(wv[k].x); cs[2] += bflo(wv[k].y); cs[3] += bfhi(wv[k].y);
    cs[4] += bflo(wv[k].z); cs[5] += bfhi(wv[k].z); cs[6] += bflo(wv[k].w); cs[7] += bfhi(wv[k].w);
  }
  const bool b4 = lane & 16, b3 = lane & 8;
#pragma unroll
  for (int k = 0; k < 4; ++k) cs[k] = (b4 ? cs[k + 4] : cs[k]) + __shfl_xor_sync(0xffffffffu, b4 ? cs[k] : cs[k + 4], 16);
#pragma unroll
  for (int k = 0; k < 2; ++k) cs[k] = (b3 ? cs[k + 2] : cs[k]) + __shfl_xor_sync(0xffffffffu, b3 ? cs[k] : cs[k + 2], 8);
  str2((uint2*)SCR->CS + (i * 768 + wa * 256 + 32 * cg + 4 * (lane & 7) + (lane >> 3)), nzmap(__float_as_uint(cs[0])), __float_as_uint(cs[1]));
}
DEV void col_gather(const Params& P, int c, int wa, int lane) {
  const uint2* p = (const uint2*)SCR->CS + (wa * 256 + 32 * (c & 7) + lane);
#pragma unroll 1
  for (int it = 0;; ++it) {
    float a = 0.f, b = 0.f;
    uint32_t m = ~0u;
#pragma unroll
    for (int k = 0; k < 16; ++k) { const uint2 q = ldr2(p + k * 768); m = min(m, q.x); a += __uint_as_float(q.x); b += __uint_as_float(q.y); }
    if (__all_sync(0xffffffffu, m != 0u)) { sts2f(SM_CS + wa * 256 + lane * 8, a, b); break; }
    spin_guard(it);
  }
  __syncwarp();
  mbar_arrive1(B_CS);
}

DEV void aux_prologue(const Params& P, int c, int wa, int lane) {
  const int g = lane >> 2, t = lane & 3, G = stat_group(c);
  {
    uint32_t w[16][2];
    const uint16_t* row = P.x0 + ((16 * G + 2 * g) * 512 + 128 * wa + 8 * t);
    bar_sync(NB_Y, 384);
#pragma unroll
    for (int z = 0; z < 8; ++z) {
      const uint4 v = ldw4(row + (z & 1) * 512 + (z >> 1) * 32);
      const int o = 4 * (z >> 1);
      w[o][z & 1] = v.x; w[o + 1][z & 1] = v.y; w[o + 2][z & 1] = v.z; w[o + 3][z & 1] = v.w;
    }
    PROF(34);
    PROFD(35, w[0][0]);
    PROFD(36, w[15][1]);
    uint2* xo = (uint2*)SCR->XG[0] + ((64 * (wa & 1) + 4 * t) * 2048 + (wa >> 1) * 512 + xg_off(G, g));
#pragma unroll
    for (int n = 0; n < 16; ++n) str2(xo + (16 * (n >> 2) + (n & 3)) * 2048, nzmap(prmt(w[n][0], w[n][1], 0x5410)), prmt(w[n][0], w[n][1], 0x7632));
    float s[2][4], q0[2][4], q1[2][4];
#pragma unroll
    for (int z = 0; z < 8; ++z) {
      const int o = 4 * (z >> 1), r = z & 1;
      if (z < 2) gram<true>(s[r], q0[r], q1[r], w[o][r], w[o + 1][r], w[o + 2][r], w[o + 3][r]);
      else gram<false>(s[r], q0[r], q1[r], w[o][r], w[o + 1][r], w[o + 2][r], w[o + 3][r]);
    }
    const bool od = g & 1;
    if (t == (g >> 1))
      sts4f(SM_STAT + (wa * 8 + g) * 16, s[0][0] + s[0][2], od ? q0[0][1] + q1[0][3] : q0[0][0] + q1[0][2],
            s[1][0] + s[1][2], od ? q0[1][1] + q1[1][3] : q0[1][0] + q1[1][2]);
    bar_arrive(NB_P0, 192);
  }
  PROF(2);
  if (lane == 0)
    asm volatile("cp.async.bulk.prefetch.L2.global [%0],4096;" :: "l"(wa < 3 ? P.wqkv + (3 * c + wa) * 2048 : P.wo + c * 2048) : "memory");
  bar_sync(NB_Y + 1, 256);
  mbar_wait(B_Z, 0);
}

DEV void stat_part(const Params& P, int c, int wa, int lane, int layer, int h, float (&v)[2]) {
  lane = opq(lane);
  const int e = wa >> 1;
  uint32_t x[4][4];
  mbar_wait(B_A + 16 * wa, h); mbar_wait(B_A + 16 * wa + 8, h);
  if (h == 0) mbar_wait(B_A + 32 * e + 24, 0);
#pragma unroll
  for (int k = 0; k < 4; ++k) ldsm4t(x[k], SM_A + e * A_E + (128 * (wa & 1) + lane) * 128 + (((c ^ lane) & 7) * 16) + k * 4096);
  float s[4] = {0.f, 0.f, 0.f, 0.f};
#pragma unroll
  for (int k = 0; k < 16; ++k) { const float a = bflo(x[k >> 2][k & 3]), b = bfhi(x[k >> 2][k & 3]); s[0] += a; s[1] += a * a; s[2] += b; s[3] += b * b; }
  s[0] += s[2]; s[1] += s[3];
  if (RARE(rows_nan(s[1], s[1]))) {
    const uint16_t* q = (const uint16_t*)(SCR->XF[layer] + ((32 * e + 2 * (c >> 3) + h) * 2048 + (wa & 1) * 1024)) + (lane >> 2);
    s[0] = s[1] = 0.f;
#pragma unroll 1
    for (int k = 0; k < 32; ++k) {
      const int r = 2 * (lane & 3) + (k & 1);
      const float a = ldnan(q + ((k >> 1) * 8 + r) * 64 + ((c ^ r) & 7) * 8);
      s[0] += a; s[1] += a * a;
    }
  }
  v[0] += s[0]; v[1] += s[1];
  __syncwarp();
}
DEV void stat_finish(const Params& P, int c, int wa, int lane, int layer, float (&v)[2]) {
  lane = opq(lane);
  const bool b = lane & 1;
  const float s = (b ? v[1] : v[0]) + __shfl_xor_sync(0xffffffffu, b ? v[0] : v[1], 1);
  str1((uint32_t*)SCR->ST[layer] + ((128 * (wa >> 1) + c) * 64 + (wa & 1) * 32 + lane), nzmap(__float_as_uint(s)));
  const uint4* sp = SCR->ST[layer] + ((128 * (wa >> 1) + (c & ~7) + 4 * (wa & 1) + (lane >> 3)) * 16 + (lane & 7));
  uint4 x, y;
  for (int it = 0;; ++it) {
    x = ldr4(sp); y = ldr4(sp + 8);
    if (__all_sync(0xffffffffu, min(min(min(x.x, x.y), min(x.z, x.w)), min(min(y.x, y.y), min(y.z, y.w))) != 0u)) break;
    spin_guard(it);
  }
  const uint32_t q = ln_sums((__uint_as_float(x.x) + __uint_as_float(x.z)) + (__uint_as_float(y.x) + __uint_as_float(y.z)),
                             (__uint_as_float(x.y) + __uint_as_float(x.w)) + (__uint_as_float(y.y) + __uint_as_float(y.w)));
  sts2f(SM_STAT + (16 * wa + (lane >> 4) * 8 + (lane & 7)) * 16 + (lane & 8), bflo(q), rcp(bfhi(q)));
  __syncwarp();
  mbar_arrive1(B_ST + 4 * (wa & 2));
}

DEV void nan_source(uint32_t a, int lane) {
#pragma unroll
  for (int k = 0; k < 4; ++k) sts4(a + k * 512 + lane * 16, FILL, FILL, FILL, FILL);
  fence_async_smem();
  __syncwarp();
}
__global__ void __launch_bounds__(NTHR, 1)
fused_kernel(const __grid_constant__ Params P, const __grid_constant__ CUtensorMap mapW, const __grid_constant__ CUtensorMap mapWo,
             const __grid_constant__ CUtensorMap mapX) {
  extern __shared__ __align__(1024) uint8_t smem_raw[];
  const int warp = __shfl_sync(0xffffffffu, threadIdx.x >> 5, 0), lane = threadIdx.x & 31;
  uint32_t smid; asm volatile("mov.u32 %0,%%smid;" : "=r"(smid));
  const uint32_t* pw = (const uint32_t*)&P + threadIdx.y;
  const int role = P.role[(smid >> 1) + threadIdx.y] + (smid & 1) + (pw[0] & pw[12]);
  const int c = __shfl_sync(0xffffffffu, pw[1] ? role : blockIdx.x, 0);
  if (c >= 128) {
#pragma unroll 1
    for (int k = (c - 128) * NTHR + threadIdx.x; k < 131072; k += P.spare * NTHR) str4(SCR->XG[1] + k, 0, 0, 0, 0);
    __threadfence();
    __syncthreads();
    if (warp == 0) { poll(SCR->C + 1 + (lane & 3) * 32, 32); cnt_add1(SCR->C + 6); }
    __syncthreads();
#pragma unroll 1
    for (int k = (c - 128) * NTHR + threadIdx.x; k < 131072; k += P.spare * NTHR) str4(SCR->XG[0] + k, 0, 0, 0, 0);
    return;
  }
#define DONE() do {} while (0)
  const int cg = c & 7;
  if (warp < 8) {
    PROF(46);
    kgen(P, c, warp, lane);
    PROFK(1);
    bar_sync(0, 384);
#pragma unroll 1
    for (int layer = 0; layer < 2; ++layer) {
#pragma unroll 1
      for (int rho = 0; rho < 2; ++rho) {
        const int wz = warp + ((rho + layer) & P.zero);
        conv_round(wz >> 2, rho, wz & 3, lane_id());
        PROFK(6 + rho + 12 * layer);
      }
      const int z = layer & P.zero;
      attn_phase(P, c + z, (warp + z) >> 2, (warp + z) & 3, lane_id(), layer);
    }
    DONE();
  } else if (warp < 12) {
    asm volatile("setmaxnreg.dec.sync.aligned.u32 %0;" :: "n"(REG_AUX));
    aux_prologue(P, c, warp - 8, lane);
    PROF(1);
    const int c0 = c;
#pragma unroll 1
    for (int layer = 0;; ++layer) {
      const int c = c0 + (layer & P.zero), wa = warp - 8 + (layer & P.zero);
#define lane lane_id()
#define j (32 * wa + lane_id())
      uint4 x[2][2][2];
      uint32_t u[4][4];
      uprep(P, c, wa, lane, layer, x, u);
      fence_async_smem();
      bar_arrive(NB_U, NBARU);
      PROFK(5 + 12 * layer);
      bar_sync(NB_H, 224);
      box_full<0, 3>(j, u, P.zero);
      PROF(3 + 12 * layer);
      conv_out(c, j, 0, x, u[0], SCR->XF[layer], P.zero);
      PROF(32);
      conv_out(c, j, 1, x, u[1], SCR->XF[layer], P.zero);
      box_full<3, 4>(j, u, P.zero);
      PROF(6 + 12 * layer);
      if (layer == 0 && wa < 3) col_sums(P, c, wa, lane);
      conv_out(c, j, 2, x, u[2], SCR->XF[layer], P.zero);
      PROF(33);
      conv_out(c, j, 3, x, u[3], SCR->XF[layer], P.zero);
      PROFK(7 + 12 * layer);
      float v[2];
      zero(v);
#pragma unroll 1
      for (int h = 0; h < 2; ++h) {
        stat_part(P, c, wa, lane, layer, h, v);
        if (h) break;
        mbar_arrive1(B_AE + 4 * (wa & 2));
        if (layer == 0 && wa < 3) col_gather(P, c, wa, lane);
      }
      PROF(9 + 12 * layer);
      stat_finish(P, c, wa, lane, layer, v);
      PROF(8 + 12 * layer);
      if (layer) break;
      mbar_wait(B_ED, 0); mbar_wait(B_ED + 8, 0);
#undef lane
#undef j
    }
    DONE();
  } else {
    asm volatile("setmaxnreg.dec.sync.aligned.u32 %0;" :: "n"(REG_PROD));
    if (s2u(smem_raw) != SB) __trap();
#pragma unroll 1
    for (int n = warp - 12; n < 42; n += 4)
      asm volatile("{.reg .pred p; elect.sync _|p,0xffffffff; @p mbarrier.init.shared::cta.b64 [%0],%1;}"
                   :: "r"(SM_BAR + n * 8), "r"(n == 33 ? 4 : n > 14 ? 1 : (int)(0x322866444444444ull >> (4 * n)) & 15) : "memory");
    fence_async_smem();
    bar_sync(NB_AUX, 128);
    bar_arrive(0, 384); bar_arrive(NB_Y + 1, 256);
    PROF(1);
    if (warp == 12) {
      if (lane == 0) {
        asm volatile("prefetch.tensormap [%0];" :: "l"(&mapW) : "memory");
        asm volatile("prefetch.tensormap [%0];" :: "l"(&mapWo) : "memory");
        asm volatile("prefetch.tensormap [%0];" :: "l"(&mapX) : "memory");
      }
      nan_source(slot(12), lane);
#pragma unroll 1
      for (int k = 0; k < 8; ++k) tma2_store(&mapX, slot(12), 128 * c, 8 * k);
      bulk_wait();
      __threadfence();
      mbar_arrive1(B_Z);
      mbar_wait(B_E, 0);
#pragma unroll 1
      for (int k = 0; k < 4; ++k) bulk_store(SCR->H[k >> 1] + ((c + 8) * 256 + (k & 1) * 128), slot(12), 2048);
#pragma unroll 1
      for (int k = 0; k < 8; ++k) bulk_store(SCR->O + (c * 512 + (k >> 2) * 65536 + (k & 3) * 128), slot(12), 2048);
      bulk_wait();
      PROF(24);
#pragma unroll 1
      for (int layer = 0; layer < 2; ++layer) {
        mbar_wait(B_V, layer);
        if (layer == 1 && c < 4 && ((0x47 >> lane) & 1)) str1(SCR->C + c * 32 + lane, 0);
        mbar_expect1(B_WF, 4 * 24576);
#pragma unroll
        for (int k = 0; k < 4; ++k) tma3(slot(wslot(k)), &mapW, 64 * cg, 64 * k, 0, B_WF);
        if (layer == 0) { __threadfence(); mbar_arrive1(B_Z); }
        mbar_wait(B_WF, layer);
        mbar_expect1(B_W4, 2 * 24576);
#pragma unroll
        for (int k = 4; k < 6; ++k) tma3(slot(wslot(k)), &mapW, 64 * cg, 64 * k, 0, B_W4);
        bar_sync(NB_AUX, 64);
#pragma unroll 1
        for (int k = 0; k < 2; ++k) {
          mbar_expect1(B_W6 + 8 * k, 24576);
          mbar_wait(B_F + 8 * k, layer);
          tma3(slot(3 * k), &mapW, 64 * cg, 384 + 64 * k, 0, B_W6 + 8 * k);
        }
        mbar_expect1(B_WO, 65536);
        mbar_wait(B_AE + 8, layer);
        nan_source(slot(12), lane);
        uint4* fp = layer ? SCR->O + c * 512 : SCR->XF[1] + c * 512;
#pragma unroll 1
        for (int r = 7; r >= 0; --r) {
          __nanosleep(30);
          if (r >= 4) {
            bulk_store(fp + (r & 3) * 128, slot(12), 2048); bulk_store(fp + 65536 + (r & 3) * 128, slot(12), 2048);
          }
          if (r == 3) { bulk_wait(); __threadfence(); mbar_arrive1(B_N); PROF(9 + 12 * layer); }
          if (r == 1) mbar_wait(B_F + 16, layer);
          tma4(SM_WO + r * 8192, &mapWo, 64 * cg, 0, r >> 1, 32 * (r & 1), B_WO);
        }
        PROF(8 + 12 * layer);
      }
      DONE();
    } else if (warp == 13) {
      const int G = stat_group(c);
#pragma unroll 1
      for (int layer = 0; layer < 2; ++layer) {
        float z[4];
        uint2* so = opqp((uint2*)&SCR->SR[layer][lane >> 3][sr_off(G, lane)] + (lane & 1));
        if (layer == 0) {
          bar_sync(NB_P0, 192);
          const float4 a = lds4f(SM_STAT + lane * 16);
          z[0] = a.x; z[1] = a.y; z[2] = a.z; z[3] = a.w;
        } else {
          mbar_wait(B_ED + 2 * (c & 4), 0);
          uint4* ps = &SCR->PS[G * 64 + lane];
          uint4 a, b;
          for (int it = 0;; ++it) {
            a = ldr4(ps); b = ldr4(ps + 32);
            if (__all_sync(0xffffffffu, min(a.x, b.x) != 0u)) break;
            spin_guard(it);
          }
          z[0] = __uint_as_float(a.x) + __uint_as_float(b.x); z[1] = __uint_as_float(a.y) + __uint_as_float(b.y);
          z[2] = __uint_as_float(a.z) + __uint_as_float(b.z); z[3] = __uint_as_float(a.w) + __uint_as_float(b.w);
        }
#pragma unroll
        for (int o = 8; o < 32; o <<= 1)
#pragma unroll
          for (int k = 0; k < 4; ++k) z[k] += __shfl_xor_sync(0xffffffffu, z[k], o);
        const uint32_t w0 = ln_sums(z[0], z[1]), w1 = ln_sums(z[2], z[3]);
        const uint32_t r = nzmap(pack2(rcp(bfhi(w0)), rcp(bfhi(w1)))), m = pack2(z[0] * (-1.f / 512.f) * bflo(r), z[2] * (-1.f / 512.f) * bfhi(r));
        str2(so, r, m); str2(so + 4 * 1024, r, m);
        PROF(4 + 12 * layer);
        box_help(0, 0, 2, lane);
        PROF(6 + 12 * layer);
      }
      DONE();
    } else if (warp == 14) {
#pragma unroll 1
      for (int layer = 0; layer < 2; ++layer) {
        uint32_t* ca = opqp(SCR->C + (c >> 5) * 32 + 3 * layer);
        const uint32_t* cw = opqp(SCR->C + (lane & 3) * 32 + 3 * layer);
        const uint4* xg = opqp(SCR->XG[layer] + c * 1024);
        mbar_expect1(B_E, 16384);
        if (layer) { mbar_wait(B_N, 0); mbar_wait(B_ED, 0); mbar_wait(B_ED + 8, 0); } else bar_sync(NB_P0, 192);
        cnt_add1(ca);
        PROF(4 + 12 * layer);
        poll(cw, 32);
        mbar_arrive1(B_U);
        bulk(SM_X, xg, 16384, B_E);
        PROFK(5 + 12 * layer);
        box_help(0, 1, 2, lane);
#pragma unroll 1
        for (int n = 0; n < 4; ++n) {
          const int e = n & 1;
          const uint4* src = opqp(SCR->XF[layer] + (32 * e + 2 * (c >> 3) + (n >> 1)) * 2048);
          const uint32_t dst = opq(SM_A + e * A_E), b = opq(B_A + 32 * e), f = opq(n == 1 ? B_L : (n & 2 ? B_AE : B_RD) + 8 * e);
          if (n == 2) poll(cw + 2, 32);
          if (n == 2) PROF(7 + 12 * layer);
          mbar_wait(f, layer);
          if (n == 0) cnt_add1(ca + 1);
          uint32_t ok = n ? 15 : 0;
#pragma unroll 1
          for (int q = 0, it = 0; q < 4; ++q) {
            mbar_expect1(b + 8 * q, 8192);
#pragma unroll 1
            for (; !((ok >> q) & 1); ++it) {
              spin_guard(it);
              ok = __ballot_sync(0xffffffffu, ldr1(cw + 1) >= 32);
            }
            bulk(dst + 8192 * q, src + 512 * q, 8192, b + 8 * q);
          }
          bar_arrive_if(NB_AUX, 64, n == 2);
          if (!e) PROFK(6 + n + 12 * layer);
        }
#pragma unroll 1
        for (int n = 0; n < 8; ++n) mbar_expect1(B_O + 8 * n, 16384);
        if (layer == 0) poll(SCR->C + 6, P.spare);
        mbar_wait(B_QE, layer);
#pragma unroll 1
        for (int e = 0; e < 2; ++e) {
          const int J = 16 * e + (c >> 3);
          const uint32_t* fl = opqp(SCR->OF[layer] + J * 32 + lane);
          const uint4* src[4];
          uint32_t dst[4], b[4];
#pragma unroll
          for (int n = 0; n < 4; ++n) { src[n] = opqp(SCR->O + (J * 4096 + n * 1024)); dst[n] = opq(SM_O + e * O_E + 16384 * n); b[n] = opq(B_O + 32 * e + 8 * n); }
          mbar_wait(B_AT + 8 * e, layer);
          if (!e) pause(260);
          poll(fl, 1);
#pragma unroll
          for (int n = 0; n < 4; ++n) bulk(dst[n], src[n], 16384, b[n]);
          PROFK(9 + e + 12 * layer);
        }
      }
      DONE();
    }
    if (warp == 15) {
      const int G = stat_group(c);
      str4(&SCR->ST[0][(lane >> 4) * 2048 + c * 16 + (lane & 15)], 0, 0, 0, 0); str4(&SCR->ST[1][(lane >> 4) * 2048 + c * 16 + (lane & 15)], 0, 0, 0, 0);
      if (lane < 4) str4(SCR->OF[lane >> 1] + ((lane & 1) * 512 + c * 4), 0, 0, 0, 0);
      str4(&SCR->PS[G * 64 + lane], 0, 0, 0, 0); str4(&SCR->PS[G * 64 + 32 + lane], 0, 0, 0, 0);
      str4(&SCR->SR[1][lane >> 2][sr_off(G, 2 * lane)], 0, 0, 0, 0);
      if (c < 4 && lane < 3) str1(SCR->C + c * 32 + 3 + lane, 0);
#pragma unroll
      for (int k = 0; k < 3; ++k) str2((uint2*)SCR->CS + ((c >> 3) * 768 + k * 256 + 32 * cg + lane), 0, 0);
      __threadfence();
#pragma unroll 1
      for (int layer = 0; layer < 2; ++layer) {
        PROF(4 + 12 * layer);
        box_help(1, 0, 1, lane, layer);
        if (layer) str4(&SCR->SR[0][lane >> 2][sr_off(G, 2 * lane)], 0, 0, 0, 0);
        uint32_t* ca = opqp(SCR->C + (c >> 5) * 32 + 3 * layer + 2);
        mbar_wait(B_Z, 1);
        mbar_wait(B_RD + 8, layer);
        cnt_add1(ca);
        if (P.spare == 0) {
#pragma unroll 1
          for (int k = 0; k < 32; ++k) str4(SCR->XG[layer] + (c * 1024 + k * 32 + lane), 0, 0, 0, 0);
        }
      }
      mbar_watch(B_O + 56, 1);
    }
  }
}

typedef CUresult (*EncodeFn)(CUtensorMap*, CUtensorMapDataType, cuuint32_t, void*, const cuuint64_t*, const cuuint64_t*,
                             const cuuint32_t*, const cuuint32_t*, CUtensorMapInterleave, CUtensorMapSwizzle,
                             CUtensorMapL2promotion, CUtensorMapFloatOOBfill);

static int place_roles(uint8_t* role) {
  int dev = 0, nsm = 0;
  cudaGetDevice(&dev);
  cudaDeviceGetAttribute(&nsm, cudaDevAttrMultiProcessorCount, dev);
  if (nsm <= 128 || nsm > 144 || (nsm & 1)) return 0;
  cudaFuncSetAttribute(fused_kernel, cudaFuncAttributeNonPortableClusterSizeAllowed, 1);
  int occ[9] = {0};
  for (int k = 2; k <= 8; ++k) {
    cudaLaunchConfig_t cfg = {};
    cudaLaunchAttribute at[1];
    at[0].id = cudaLaunchAttributeClusterDimension;
    at[0].val.clusterDim.x = 2 * k; at[0].val.clusterDim.y = 1; at[0].val.clusterDim.z = 1;
    cfg.gridDim = dim3(2 * k); cfg.blockDim = dim3(NTHR); cfg.dynamicSmemBytes = SM_TOTAL; cfg.attrs = at; cfg.numAttrs = 1;
    if (cudaOccupancyMaxActiveClusters(&occ[k], fused_kernel, &cfg) != cudaSuccess) { cudaGetLastError(); occ[k] = 0; }
  }
  int n[10];
  n[7] = occ[8]; n[6] = occ[7]; n[5] = occ[6] - 0; n[4] = occ[5];
  n[3] = occ[4] - n[7]; n[1] = occ[2] - n[3] - n[5] - n[7]; n[0] = n[2] = n[1];
  n[8] = occ[3] - n[2] - n[5];
  const int ntpc = nsm / 2;
  int sum = 0;
  bool ok = n[0] > 0 && n[0] <= 8;
  for (int r = 0; r < 9; ++r) { ok = ok && n[r] >= 0 && (r == 0 || n[r] <= n[r - 1]); sum += n[r]; }
  if (!ok || sum > ntpc) { for (int r = 0; r < 9; ++r) n[r] = r < 8 ? 8 : 0; sum = 64; }
  int tp[8][9], cnt[8] = {0}, pool[72], np = 0, id = 0;
  for (int r = 0; r < 9; ++r)
    for (int g = n[0] - n[r]; g < n[0]; ++g) tp[g][cnt[g]++] = id++;
  for (; id < ntpc; ++id) pool[np++] = id;
  int order[72], no = 0;
  for (int g = 0; g < n[0]; ++g) {
    const int full = cnt[g] / 4 * 4;
    for (int k = 0; k < cnt[g]; ++k) { if (k < full) order[no++] = tp[g][k]; else pool[np++] = tp[g][k]; }
  }
  for (int k = 0; k < np; ++k) order[no++] = pool[k];
  for (int k = 0; k < ntpc; ++k) role[order[k]] = 2 * k;
  return nsm;
}

extern "C" void kernel_launch(void* const* d_in, const int* in_sizes, int n_in, void* d_out, int out_size) {
  (void)in_sizes; (void)n_in; (void)out_size;
  static EncodeFn enc = nullptr;
  static uint8_t role[72];
  static int nsm = 0;
  static Scratch* scratch = nullptr;
  if (!enc) {
    void* fn = nullptr;
    cudaDriverEntryPointQueryResult qr;
    cudaGetDriverEntryPoint("cuTensorMapEncodeTiled", &fn, cudaEnableDefault, &qr);
    enc = (EncodeFn)fn;
    cudaFuncSetAttribute(fused_kernel, cudaFuncAttributeMaxDynamicSharedMemorySize, SM_TOTAL);
    nsm = place_roles(role);
    cudaGetSymbolAddress((void**)&scratch, g_S);
  }
  CUtensorMap mW, mWo, mX;
  {
    cuuint64_t dim[3] = {512, 512, 3}, str[2] = {3072, 1024};
    cuuint32_t box[3] = {64, 64, 3}, es[3] = {1, 1, 1};
    enc(&mW, CU_TENSOR_MAP_DATA_TYPE_BFLOAT16, 3, d_in[10], dim, str, box, es, CU_TENSOR_MAP_INTERLEAVE_NONE,
        CU_TENSOR_MAP_SWIZZLE_128B, CU_TENSOR_MAP_L2_PROMOTION_NONE, CU_TENSOR_MAP_FLOAT_OOB_FILL_NONE);
  }
  {
    cuuint64_t dim[4] = {512, 2, 4, 64}, str[3] = {1024, 2048, 8192};
    cuuint32_t box[4] = {64, 2, 1, 32}, es[4] = {1, 1, 1, 1};
    enc(&mWo, CU_TENSOR_MAP_DATA_TYPE_BFLOAT16, 4, d_in[11], dim, str, box, es, CU_TENSOR_MAP_INTERLEAVE_NONE,
        CU_TENSOR_MAP_SWIZZLE_128B, CU_TENSOR_MAP_L2_PROMOTION_NONE, CU_TENSOR_MAP_FLOAT_OOB_FILL_NONE);
  }
  {
    cuuint64_t dim[2] = {16384, 64}, str[1] = {32768};
    cuuint32_t box[2] = {128, 8}, es[2] = {1, 1};
    enc(&mX, CU_TENSOR_MAP_DATA_TYPE_BFLOAT16, 2, scratch->XF[0], dim, str, box, es, CU_TENSOR_MAP_INTERLEAVE_NONE,
        CU_TENSOR_MAP_SWIZZLE_NONE, CU_TENSOR_MAP_L2_PROMOTION_NONE, CU_TENSOR_MAP_FLOAT_OOB_FILL_NONE);
  }
  Params P;
  P.x0 = (const uint16_t*)d_in[0]; P.Are = (const uint16_t*)d_in[1]; P.Aim = (const uint16_t*)d_in[2];
  P.Bre = (const uint16_t*)d_in[3]; P.Bim = (const uint16_t*)d_in[4]; P.Cre = (const uint16_t*)d_in[5];
  P.Cim = (const uint16_t*)d_in[6]; P.logdt = (const uint16_t*)d_in[7]; P.dskip = (const uint16_t*)d_in[8];
  P.wqkv = (const uint16_t*)d_in[10]; P.wo = (const uint16_t*)d_in[11]; P.out = (uint16_t*)d_out;
  for (int k = 0; k < 72; ++k) P.role[k] = role[k];
  P.zero = 0;
  P.mid = (char*)scratch->C;
  P.spare = nsm > 0 ? nsm - 128 : 0;
  fused_kernel<<<nsm > 0 ? nsm : 128, NTHR, SM_TOTAL, cudaStreamPerThread>>>(P, mW, mWo, mX);
}
```

```cpp
#include <cuda_runtime.h>
#include <cuda_bf16.h>
#include <cuda.h>
#include <stdint.h>
#include <stddef.h>

#define DEV __device__ __forceinline__
#define RARE(x) __builtin_expect(!!(x), 0)

constexpr int NTHR = 512;
constexpr int REG_MAIN = 192, REG_AUX = 88, REG_PROD = 40;
constexpr int NBARU = 384;
constexpr int SPIN_LIMIT = 1 << 22;

constexpr uint32_t SB = 1024;
__host__ __device__ constexpr uint32_t slot(int n) { return SB + n * 8192; }
__host__ __device__ constexpr int wslot(int k) { return k < 2 ? 3 * k : k < 4 ? 3 * k + 6 : k < 6 ? 21 - 3 * k : 3 * k - 18; }
constexpr uint32_t SM_A = slot(22), A_E = 0u - 32768;
constexpr uint32_t SM_O = slot(18), O_E = 0u - 147456;
constexpr uint32_t SM_WO = slot(10), SM_X = slot(8), SM_KV = slot(9) - 4096;
constexpr uint32_t SM_TAP  = slot(26);
constexpr int TAP_SZ = 3440;
constexpr uint32_t SM_STAT = SM_TAP + 4 * TAP_SZ;
constexpr uint32_t SM_CS   = SM_STAT + 1024;
constexpr uint32_t SM_BAR  = SM_CS + 768;
constexpr int SM_TOTAL = SM_BAR + 352 - SB;
static_assert(SM_TOTAL <= 232448, "");
constexpr int R_SZ = 16384, R_U = 512, R_X5 = 5120, R_X3 = 8704, R_BO = 11776, R_BE = 13824;
constexpr int X_5 = 576, X_3 = 648, T_E = 2 * 720, T_O = 1600 + 2 * 721, T_C = 3390, T_K = 3424;
constexpr uint32_t B_RD = SM_BAR, B_ED = SM_BAR + 16, B_F = SM_BAR + 32, B_AT = SM_BAR + 56, B_L = SM_BAR + 264;
constexpr uint32_t B_AE = SM_BAR + 72, B_QE = SM_BAR + 88, B_ST = SM_BAR + 96, B_CS = SM_BAR + 112;
constexpr uint32_t B_WO = SM_BAR + 120, B_W6 = SM_BAR + 128, B_U = SM_BAR + 144, B_E = SM_BAR + 152, B_WF = SM_BAR + 160, B_W4 = SM_BAR + 168,
                   B_N = SM_BAR + 176, B_V = SM_BAR + 184, B_O = SM_BAR + 192, B_Z = SM_BAR + 256, B_A = SM_BAR + 272;
constexpr int NB_U = 1, NB_B = 2, NB_K = 8, NB_Y = 6, NB_WG = 8, NB_T = 10, NB_AUX = 12, NB_P0 = 13, NB_H = 15;

struct Scratch {
  uint4    XG[2][128 * 1024];
  uint4    O[32 * 8 * 512];
  uint32_t C[8 * 32];
  uint32_t OF[2][32 * 32];
  uint4    CS[16 * 1536 / 4];
  uint4    PS[128 * 64];
  uint4    ST[2][32 * 128];
  uint4    SR[2][8][512];
  uint4    XF[2][32 * 512 * 8];
  uint4    H[2][17 * 8 * 256];
};
__device__ __align__(1024) Scratch g_S;
#define SCR ((Scratch*)(P.mid - offsetof(Scratch, C)))
#define PROFD(slot, v) do {} while (0)
#define PROF(slot) do {} while (0)
#define PROFK(slot) do {} while (0)

#define PROFC(slot) do {} while (0)

DEV uint32_t s2u(const void* p) { return (uint32_t)__cvta_generic_to_shared(p); }
template <class T> DEV T* opqp(T* x) { asm volatile("" : "+l"(x)); return x; }
template <class T> DEV T opq(T x) { asm volatile("" : "+r"(x)); return x; }
DEV int lane_id() { int l; asm volatile("mov.u32 %0,%%laneid;" : "=r"(l)); return l; }
DEV uint32_t pack2(float lo, float hi) { uint32_t d; asm("cvt.rn.bf16x2.f32 %0,%1,%2;" : "=r"(d) : "f"(hi), "f"(lo)); return d; }
DEV float bflo(uint32_t v) { return __uint_as_float(v << 16); }
DEV float bfhi(uint32_t v) { return __uint_as_float(v & 0xFFFF0000u); }
DEV float bfr(float x) { return bflo(pack2(x, 0.f)); }
DEV uint32_t hadd2(uint32_t a, uint32_t b) { uint32_t d; asm("add.rn.bf16x2 %0,%1,%2;" : "=r"(d) : "r"(a), "r"(b)); return d; }
DEV uint32_t hsub2(uint32_t a, uint32_t b) { uint32_t d; asm("sub.rn.bf16x2 %0,%1,%2;" : "=r"(d) : "r"(a), "r"(b)); return d; }
DEV uint32_t hmul2(uint32_t a, uint32_t b) { uint32_t d; asm("mul.rn.bf16x2 %0,%1,%2;" : "=r"(d) : "r"(a), "r"(b)); return d; }
DEV uint32_t hfma2(uint32_t a, uint32_t b, uint32_t c) { uint32_t d; asm("fma.rn.bf16x2 %0,%1,%2,%3;" : "=r"(d) : "r"(a), "r"(b), "r"(c)); return d; }
DEV uint32_t hmax2(uint32_t a, uint32_t b) { uint32_t d; asm("max.bf16x2 %0,%1,%2;" : "=r"(d) : "r"(a), "r"(b)); return d; }
DEV uint32_t prmt(uint32_t a, uint32_t b, uint32_t s) { uint32_t d; asm("prmt.b32 %0,%1,%2,%3;" : "=r"(d) : "r"(a), "r"(b), "r"(s)); return d; }
DEV uint32_t nzmap(uint32_t v) { uint32_t d; asm("max.u32 %0,%1,1;" : "=r"(d) : "r"(v)); return d; }
DEV float rcp(float x) { float y; asm("rcp.approx.ftz.f32 %0,%1;" : "=f"(y) : "f"(x)); return y; }
DEV float sqrt_(float x) { float y; asm("sqrt.approx.ftz.f32 %0,%1;" : "=f"(y) : "f"(x)); return y; }
DEV float ex2(float x) { float y; asm("ex2.approx.ftz.f32 %0,%1;" : "=f"(y) : "f"(x)); return y; }

DEV uint4 ldr4(const void* p) { uint4 v; asm volatile("ld.relaxed.gpu.global.v4.u32 {%0,%1,%2,%3},[%4];" : "=r"(v.x), "=r"(v.y), "=r"(v.z), "=r"(v.w) : "l"(p) : "memory"); return v; }
DEV void ldr4_if(uint4& v, const void* p, bool c) {
  asm volatile("{.reg .pred q; setp.ne.u32 q,%5,0; @q ld.relaxed.gpu.global.v4.u32 {%0,%1,%2,%3},[%4];}"
    : "+r"(v.x), "+r"(v.y), "+r"(v.z), "+r"(v.w) : "l"(p), "r"((uint32_t)c) : "memory");
}
DEV uint2 ldr2(const void* p) { uint2 v; asm volatile("ld.relaxed.gpu.global.v2.u32 {%0,%1},[%2];" : "=r"(v.x), "=r"(v.y) : "l"(p) : "memory"); return v; }
DEV void ldr2_if(uint2& v, const void* p, bool c) {
  asm volatile("{.reg .pred q; setp.ne.u32 q,%3,0; @q ld.relaxed.gpu.global.v2.u32 {%0,%1},[%2];}" : "+r"(v.x), "+r"(v.y) : "l"(p), "r"((uint32_t)c) : "memory");
}
DEV uint32_t ldr1(const void* p) { uint32_t v; asm volatile("ld.relaxed.gpu.global.u32 %0,[%1];" : "=r"(v) : "l"(p) : "memory"); return v; }
DEV float ldnan(const uint16_t* p) {
  uint32_t v = 0xFFFFu;
#pragma unroll 1
  for (int it = 0; it < SPIN_LIMIT && __any_sync(0xffffffffu, v == 0xFFFFu); ++it) asm volatile("ld.relaxed.gpu.global.u16 %0,[%1];" : "=r"(v) : "l"(p) : "memory");
  return __uint_as_float(v << 16);
}
DEV uint4 ldw4(const void* p) { uint4 v; asm volatile("ld.global.v4.u32 {%0,%1,%2,%3},[%4];" : "=r"(v.x), "=r"(v.y), "=r"(v.z), "=r"(v.w) : "l"(p) : "memory"); return v; }
DEV uint2 ldw2(const void* p) { uint2 v; asm volatile("ld.global.v2.u32 {%0,%1},[%2];" : "=r"(v.x), "=r"(v.y) : "l"(p) : "memory"); return v; }
DEV uint32_t ldw1(const void* p) { uint32_t v; asm volatile("ld.global.u32 %0,[%1];" : "=r"(v) : "l"(p) : "memory"); return v; }
DEV void str4(void* p, uint32_t a, uint32_t b, uint32_t c, uint32_t d) { asm volatile("st.relaxed.gpu.global.v4.u32 [%0],{%1,%2,%3,%4};" :: "l"(p), "r"(a), "r"(b), "r"(c), "r"(d) : "memory"); }
DEV void str2(void* p, uint32_t a, uint32_t b) { asm volatile("st.relaxed.gpu.global.v2.u32 [%0],{%1,%2};" :: "l"(p), "r"(a), "r"(b) : "memory"); }
DEV void str1(void* p, uint32_t a) { asm volatile("st.relaxed.gpu.global.u32 [%0],%1;" :: "l"(p), "r"(a) : "memory"); }
DEV void str4_if(void* p, uint32_t a, uint32_t b, uint32_t c, uint32_t d, bool q) {
  asm volatile("{.reg .pred q; setp.ne.u32 q,%5,0; @q st.relaxed.gpu.global.v4.u32 [%0],{%1,%2,%3,%4};}" :: "l"(p), "r"(a), "r"(b), "r"(c), "r"(d), "r"((uint32_t)q) : "memory");
}
DEV void stw4(void* p, uint32_t a, uint32_t b, uint32_t c, uint32_t d) { asm volatile("st.global.v4.u32 [%0],{%1,%2,%3,%4};" :: "l"(p), "r"(a), "r"(b), "r"(c), "r"(d) : "memory"); }
DEV uint4 ldnc4(const void* p) { uint4 v; asm volatile("ld.global.nc.v4.u32 {%0,%1,%2,%3},[%4];" : "=r"(v.x), "=r"(v.y), "=r"(v.z), "=r"(v.w) : "l"(p)); return v; }
DEV uint32_t ldnc1(const void* p) { uint32_t v; asm volatile("ld.global.nc.u32 %0,[%1];" : "=r"(v) : "l"(p)); return v; }
DEV uint2 ldnc2(const void* p) { uint2 v; asm volatile("ld.global.nc.v2.u32 {%0,%1},[%2];" : "=r"(v.x), "=r"(v.y) : "l"(p)); return v; }

DEV uint2 lds2(uint32_t a) { uint2 v; asm volatile("ld.volatile.shared.v2.u32 {%0,%1},[%2];" : "=r"(v.x), "=r"(v.y) : "r"(a)); return v; }
DEV float lds16f(uint32_t a) { uint32_t v; asm volatile("ld.shared.u16 %0,[%1];" : "=r"(v) : "r"(a)); return __uint_as_float(v << 16); }
DEV void sts2(uint32_t a, uint32_t x, uint32_t y) { asm volatile("st.shared.v2.u32 [%0],{%1,%2};" :: "r"(a), "r"(x), "r"(y) : "memory"); }
DEV uint32_t lds1(uint32_t a) { uint32_t v; asm volatile("ld.volatile.shared.u32 %0,[%1];" : "=r"(v) : "r"(a)); return v; }
DEV uint32_t lds1z(uint32_t a, bool c) {
  uint32_t v; asm volatile("{.reg .pred q; setp.ne.u32 q,%2,0; mov.u32 %0,0; @q ld.volatile.shared.u32 %0,[%1];}" : "=r"(v) : "r"(a), "r"((uint32_t)c)); return v;
}
DEV uint4 lds4z(uint32_t a, bool c) {
  uint4 v = make_uint4(0, 0, 0, 0);
  asm volatile("{.reg .pred q; setp.ne.u32 q,%5,0; @q ld.volatile.shared.v4.u32 {%0,%1,%2,%3},[%4];}" : "+r"(v.x), "+r"(v.y), "+r"(v.z), "+r"(v.w) : "r"(a), "r"((uint32_t)c));
  return v;
}
DEV float lds1f(uint32_t a) { float v; asm volatile("ld.shared.f32 %0,[%1];" : "=f"(v) : "r"(a)); return v; }
DEV float2 lds2f(uint32_t a) { float2 v; asm volatile("ld.shared.v2.f32 {%0,%1},[%2];" : "=f"(v.x), "=f"(v.y) : "r"(a)); return v; }
DEV float4 lds4f(uint32_t a) { float4 v; asm volatile("ld.volatile.shared.v4.f32 {%0,%1,%2,%3},[%4];" : "=f"(v.x), "=f"(v.y), "=f"(v.z), "=f"(v.w) : "r"(a)); return v; }
DEV uint4 lds4(uint32_t a) { uint4 v; asm volatile("ld.volatile.shared.v4.u32 {%0,%1,%2,%3},[%4];" : "=r"(v.x), "=r"(v.y), "=r"(v.z), "=r"(v.w) : "r"(a)); return v; }
DEV void sts1(uint32_t a, uint32_t v) { asm volatile("st.shared.u32 [%0],%1;" :: "r"(a), "r"(v) : "memory"); }
DEV void sts16(uint32_t a, uint32_t v) { asm volatile("st.shared.u16 [%0],%1;" :: "r"(a), "r"(v) : "memory"); }
DEV void sts2f(uint32_t a, float x, float y) { asm volatile("st.shared.v2.f32 [%0],{%1,%2};" :: "r"(a), "f"(x), "f"(y) : "memory"); }
DEV void sts4f(uint32_t a, float x, float y, float z, float w) { asm volatile("st.shared.v4.f32 [%0],{%1,%2,%3,%4};" :: "r"(a), "f"(x), "f"(y), "f"(z), "f"(w) : "memory"); }
DEV void sts4(uint32_t a, uint32_t x, uint32_t y, uint32_t z, uint32_t w) { asm volatile("st.shared.v4.u32 [%0],{%1,%2,%3,%4};" :: "r"(a), "r"(x), "r"(y), "r"(z), "r"(w) : "memory"); }

DEV void ldsm4(uint32_t (&r)[4], uint32_t a) { asm volatile("ldmatrix.sync.aligned.m8n8.x4.shared.b16 {%0,%1,%2,%3},[%4];" : "=r"(r[0]), "=r"(r[1]), "=r"(r[2]), "=r"(r[3]) : "r"(a) : "memory"); }
DEV void ldsm4t(uint32_t (&r)[4], uint32_t a) { asm volatile("ldmatrix.sync.aligned.m8n8.x4.trans.shared.b16 {%0,%1,%2,%3},[%4];" : "=r"(r[0]), "=r"(r[1]), "=r"(r[2]), "=r"(r[3]) : "r"(a) : "memory"); }
DEV void ldsm2(uint32_t (&r)[2], uint32_t a) { asm volatile("ldmatrix.sync.aligned.m8n8.x2.shared.b16 {%0,%1},[%2];" : "=r"(r[0]), "=r"(r[1]) : "r"(a) : "memory"); }
DEV void stsm4(uint32_t a, uint32_t r0, uint32_t r1, uint32_t r2, uint32_t r3) { asm volatile("stmatrix.sync.aligned.m8n8.x4.shared.b16 [%0],{%1,%2,%3,%4};" :: "r"(a), "r"(r0), "r"(r1), "r"(r2), "r"(r3) : "memory"); }
DEV void stsm2(uint32_t a, uint32_t r0, uint32_t r1) { asm volatile("stmatrix.sync.aligned.m8n8.x2.shared.b16 [%0],{%1,%2};" :: "r"(a), "r"(r0), "r"(r1) : "memory"); }
DEV void stsm4t(uint32_t a, uint32_t r0, uint32_t r1, uint32_t r2, uint32_t r3) { asm volatile("stmatrix.sync.aligned.m8n8.x4.trans.shared.b16 [%0],{%1,%2,%3,%4};" :: "r"(a), "r"(r0), "r"(r1), "r"(r2), "r"(r3) : "memory"); }
DEV uint32_t movm(uint32_t a) { uint32_t d; asm volatile("movmatrix.sync.aligned.m8n8.trans.b16 %0,%1;" : "=r"(d) : "r"(a)); return d; }
DEV void mma16(float (&d)[4], uint32_t a0, uint32_t a1, uint32_t a2, uint32_t a3, uint32_t b0, uint32_t b1) {
  asm volatile("mma.sync.aligned.m16n8k16.row.col.f32.bf16.bf16.f32 {%0,%1,%2,%3},{%4,%5,%6,%7},{%8,%9},{%0,%1,%2,%3};"
    : "+f"(d[0]), "+f"(d[1]), "+f"(d[2]), "+f"(d[3]) : "r"(a0), "r"(a1), "r"(a2), "r"(a3), "r"(b0), "r"(b1));
}
DEV void mma16z(float (&d)[4], uint32_t a0, uint32_t a1, uint32_t a2, uint32_t a3, uint32_t b0, uint32_t b1) {
  asm volatile("mma.sync.aligned.m16n8k16.row.col.f32.bf16.bf16.f32 {%0,%1,%2,%3},{%4,%5,%6,%7},{%8,%9},{%10,%10,%10,%10};"
    : "=f"(d[0]), "=f"(d[1]), "=f"(d[2]), "=f"(d[3]) : "r"(a0), "r"(a1), "r"(a2), "r"(a3), "r"(b0), "r"(b1), "f"(0.f));
}
DEV void mma8(float (&d)[4], uint32_t a0, uint32_t a1, uint32_t b0) {
  asm volatile("mma.sync.aligned.m16n8k8.row.col.f32.bf16.bf16.f32 {%0,%1,%2,%3},{%4,%5},{%6},{%0,%1,%2,%3};"
    : "+f"(d[0]), "+f"(d[1]), "+f"(d[2]), "+f"(d[3]) : "r"(a0), "r"(a1), "r"(b0));
}

DEV void mma8z(float (&d)[4], uint32_t a0, uint32_t a1, uint32_t b0) {
  asm volatile("mma.sync.aligned.m16n8k8.row.col.f32.bf16.bf16.f32 {%0,%1,%2,%3},{%4,%5},{%6},{%7,%7,%7,%7};"
    : "=f"(d[0]), "=f"(d[1]), "=f"(d[2]), "=f"(d[3]) : "r"(a0), "r"(a1), "r"(b0), "f"(0.f));
}
DEV void bar_sync(int id, int n) { asm volatile("bar.sync %0,%1;" :: "r"(id), "r"(n) : "memory"); }
DEV void bar_sync_if(int id, int n, int c) { asm volatile("{.reg .pred q; setp.ne.s32 q,%2,0; @q bar.sync %0,%1;}" :: "r"(id), "r"(n), "r"(c) : "memory"); }
DEV void bar_arrive_if(int id, int n, int c) { asm volatile("{.reg .pred q; setp.ne.s32 q,%2,0; @q bar.arrive %0,%1;}" :: "r"(id), "r"(n), "r"(c) : "memory"); }
DEV bool bar_any(int id, int n, bool c) {
  uint32_t r; asm volatile("{.reg .pred p,q; setp.ne.u32 q,%3,0; bar.red.or.pred p,%1,%2,q; selp.u32 %0,1,0,p;}" : "=r"(r) : "r"(id), "r"(n), "r"((uint32_t)c) : "memory");
  return __any_sync(0xffffffffu, r);
}
DEV void bar_arrive(int id, int n) { asm volatile("bar.arrive %0,%1;" :: "r"(id), "r"(n) : "memory"); }
DEV void fence_async_glob() { asm volatile("fence.proxy.async.global;" ::: "memory"); }
DEV void fence_async_smem() { asm volatile("fence.proxy.async.shared::cta;" ::: "memory"); }
DEV void mbar_init(uint32_t b, int n) { asm volatile("mbarrier.init.shared::cta.b64 [%0],%1;" :: "r"(b), "r"(n) : "memory"); }
DEV void mbar_arrive(uint32_t b) { asm volatile("mbarrier.arrive.shared::cta.b64 _,[%0];" :: "r"(b) : "memory"); }
DEV void mbar_expect(uint32_t b, int bytes) { asm volatile("mbarrier.arrive.expect_tx.shared::cta.b64 _,[%0],%1;" :: "r"(b), "r"(bytes) : "memory"); }
DEV void mbar_wait(uint32_t b, uint32_t ph) {
  asm volatile("{\n.reg .pred p;\nW: mbarrier.try_wait.parity.shared::cta.b64 p,[%0],%1;\n@!p bra W;\n}" :: "r"(b), "r"(ph) : "memory");
}
DEV void mbar_watch(uint32_t b, uint32_t ph) {
  asm volatile("{\n.reg .pred p,q;\n.reg .u32 n;\nmov.u32 n,0;\n"
               "W: mbarrier.try_wait.parity.shared::cta.b64 p,[%0],%1;\n@p bra D;\n"
               "add.u32 n,n,1;\nsetp.lt.u32 q,n,%2;\n@q bra W;\ntrap;\nD:\n}"
               :: "r"(b), "r"(ph), "n"(SPIN_LIMIT) : "memory");
}
DEV void spin_guard(int it) { asm volatile("{.reg .pred p; setp.gt.s32 p,%0,%1; @p trap;}" :: "r"(it), "n"(SPIN_LIMIT)); }
DEV void split(uint32_t zero) {
  asm volatile("{.reg .pred p; setp.ne.u32 p,%0,0; @p trap;}" :: "r"(zero) : "memory");
}
DEV void pause(int n) {
  uint32_t t0, t; asm volatile("mov.u32 %0,%%clock;" : "=r"(t0));
  do asm volatile("mov.u32 %0,%%clock;" : "=r"(t)); while (t - t0 < n);
}
DEV void poll(const uint32_t* k, uint32_t n) {
#pragma unroll 1
  for (int it = 0;; ++it) {
    spin_guard(it);
    if (__all_sync(0xffffffffu, ldr1(k) >= n)) break;
  }
}
DEV void mbar_arrive1(uint32_t b) { asm volatile("{.reg .pred p; elect.sync _|p,0xffffffff; @p mbarrier.arrive.shared::cta.b64 _,[%0];}" :: "r"(b) : "memory"); }
DEV void mbar_arrive1_if(uint32_t b, int c) {
  asm volatile("{.reg .pred p,q; setp.ne.s32 q,%1,0; elect.sync _|p,0xffffffff; and.pred p,p,q; @p mbarrier.arrive.shared::cta.b64 _,[%0];}" :: "r"(b), "r"(c) : "memory");
}
DEV void mbar_expect1(uint32_t b, int bytes) { asm volatile("{.reg .pred p; elect.sync _|p,0xffffffff; @p mbarrier.arrive.expect_tx.shared::cta.b64 _,[%0],%1;}" :: "r"(b), "r"(bytes) : "memory"); }
DEV void cnt_add1(uint32_t* q) { asm volatile("{.reg .pred p; elect.sync _|p,0xffffffff; @p red.relaxed.gpu.global.add.u32 [%0],1;}" :: "l"(q) : "memory"); }
DEV void tma4(uint32_t dst, const CUtensorMap* m, int c0, int c1, int c2, int c3, uint32_t bar) {
  asm volatile("{.reg .pred p; elect.sync _|p,0xffffffff;\n"
    "@p cp.async.bulk.tensor.4d.shared::cluster.global.mbarrier::complete_tx::bytes [%0],[%1,{%2,%3,%4,%5}],[%6];}"
    :: "r"(dst), "l"(m), "r"(c0), "r"(c1), "r"(c2), "r"(c3), "r"(bar) : "memory");
}
DEV void tma3(uint32_t dst, const CUtensorMap* m, int c0, int c1, int c2, uint32_t bar) {
  asm volatile("{.reg .pred p; elect.sync _|p,0xffffffff;\n"
    "@p cp.async.bulk.tensor.3d.shared::cluster.global.mbarrier::complete_tx::bytes [%0],[%1,{%2,%3,%4}],[%5];}"
    :: "r"(dst), "l"(m), "r"(c0), "r"(c1), "r"(c2), "r"(bar) : "memory");
}
DEV void bulk(uint32_t dst, const void* src, int bytes, uint32_t bar) {
  asm volatile("{.reg .pred p; elect.sync _|p,0xffffffff;\n@p cp.async.bulk.shared::cluster.global.mbarrier::complete_tx::bytes [%0],[%1],%2,[%3];}" :: "r"(dst), "l"(src), "r"(bytes), "r"(bar) : "memory");
}

DEV void bulk_store(void* dst, uint32_t src, int bytes) {
  asm volatile("{.reg .pred p; elect.sync _|p,0xffffffff;\n@p cp.async.bulk.global.shared::cta.bulk_group [%0],[%1],%2;}" :: "l"(dst), "r"(src), "r"(bytes) : "memory");
}
DEV void tma2_store(const CUtensorMap* m, uint32_t src, int c0, int c1) {
  asm volatile("{.reg .pred p; elect.sync _|p,0xffffffff;\n@p cp.async.bulk.tensor.2d.global.shared::cta.bulk_group [%0,{%2,%3}],[%1];}" :: "l"(m), "r"(src), "r"(c0), "r"(c1) : "memory");
}
DEV void bulk_wait() { asm volatile("cp.async.bulk.commit_group;\ncp.async.bulk.wait_group 0;\nfence.proxy.async.global;" ::: "memory"); }

DEV uint32_t dlo(uint32_t addr, uint32_t lbo) { return __shfl_sync(0xffffffffu, (addr >> 4) | ((lbo >> 4) << 16), 0); }
__host__ __device__ constexpr uint32_t dhi(uint32_t sbo, uint32_t swz) { return (sbo >> 4) | (swz << 30); }
DEV void wg_fence() { asm volatile("wgmma.fence.sync.aligned;" ::: "memory"); }
DEV void wg_commit() { asm volatile("wgmma.commit_group.sync.aligned;" ::: "memory"); }
template <int N> DEV void wg_wait() { asm volatile("wgmma.wait_group.sync.aligned %0;" :: "n"(N) : "memory"); }
template <int N> DEV void zero(float (&d)[N]) {
#pragma unroll
  for (int i = 0; i < N; ++i) d[i] = 0.f;
}
template <int N> DEV void zerov(float (&d)[N]) {
#pragma unroll
  for (int i = 0; i < N; ++i) asm volatile("mov.b32 %0,0;" : "=f"(d[i]));
}
template <int N> DEV void undef(float (&d)[N]) {
#pragma unroll
  for (int i = 0; i < N; ++i) asm volatile("" : "=f"(d[i]));
}
#define R4(d, o) "+f"(d[o]), "+f"(d[o + 1]), "+f"(d[o + 2]), "+f"(d[o + 3])
#define R8(d, o) R4(d, o), R4(d, o + 4)
#define R16(d, o) R8(d, o), R8(d, o + 8)
template <int ACC> DEV void wg_rs64k(float (&d)[32], const uint32_t (&a)[4], uint32_t db) {
  asm volatile("{.reg .pred p; .reg .b64 b; setp.ne.s32 p,%38,0; mov.b64 b,{%36,%37};\n"
    "wgmma.mma_async.sync.aligned.m64n64k16.f32.bf16.bf16 {%0,%1,%2,%3,%4,%5,%6,%7,%8,%9,%10,%11,%12,%13,%14,%15,%16,%17,%18,%19,%20,%21,%22,%23,%24,%25,%26,%27,%28,%29,%30,%31},{%32,%33,%34,%35},b,p,1,1,0;}"
    : R16(d, 0), R16(d, 16) : "r"(a[0]), "r"(a[1]), "r"(a[2]), "r"(a[3]), "r"(db), "n"(dhi(512, 2)), "n"(ACC));
}
template <int ACC> DEV void wg_rs48t(float (&d)[24], const uint32_t (&a)[4], uint32_t db) {
  asm volatile("{.reg .pred p; .reg .b64 b; setp.ne.s32 p,%30,0; mov.b64 b,{%28,%29};\n"
    "wgmma.mma_async.sync.aligned.m64n48k16.f32.bf16.bf16 {%0,%1,%2,%3,%4,%5,%6,%7,%8,%9,%10,%11,%12,%13,%14,%15,%16,%17,%18,%19,%20,%21,%22,%23},{%24,%25,%26,%27},b,p,1,1,1;}"
    : R16(d, 0), R8(d, 16) : "r"(a[0]), "r"(a[1]), "r"(a[2]), "r"(a[3]), "r"(db), "n"(dhi(512, 0)), "n"(ACC));
}
template <int ACC> DEV void wg_rs32t(float (&d)[16], const uint32_t (&a)[4], uint32_t db) {
  asm volatile("{.reg .pred p; .reg .b64 b; setp.ne.s32 p,%22,0; mov.b64 b,{%20,%21};\n"
    "wgmma.mma_async.sync.aligned.m64n32k16.f32.bf16.bf16 {%0,%1,%2,%3,%4,%5,%6,%7,%8,%9,%10,%11,%12,%13,%14,%15},{%16,%17,%18,%19},b,p,1,1,1;}"
    : R16(d, 0) : "r"(a[0]), "r"(a[1]), "r"(a[2]), "r"(a[3]), "r"(db), "n"(dhi(1024, 0)), "n"(ACC));
}
template <int ACC> DEV void wg_ss192(float (&d)[96], uint32_t da, uint32_t db) {
  asm volatile("{.reg .pred p; .reg .b64 a,b; setp.ne.s32 p,%100,0; mov.b64 a,{%96,%98}; mov.b64 b,{%97,%99};\n"
    "wgmma.mma_async.sync.aligned.m64n192k16.f32.bf16.bf16 {"
    "%0,%1,%2,%3,%4,%5,%6,%7,%8,%9,%10,%11,%12,%13,%14,%15,%16,%17,%18,%19,%20,%21,%22,%23,%24,%25,%26,%27,%28,%29,%30,%31,"
    "%32,%33,%34,%35,%36,%37,%38,%39,%40,%41,%42,%43,%44,%45,%46,%47,%48,%49,%50,%51,%52,%53,%54,%55,%56,%57,%58,%59,%60,%61,%62,%63,"
    "%64,%65,%66,%67,%68,%69,%70,%71,%72,%73,%74,%75,%76,%77,%78,%79,%80,%81,%82,%83,%84,%85,%86,%87,%88,%89,%90,%91,%92,%93,%94,%95},a,b,p,1,1,1,1;}"
    : R16(d, 0), R16(d, 16), R16(d, 32), R16(d, 48), R16(d, 64), R16(d, 80) : "r"(da), "r"(db), "n"(dhi(1024, 1)), "n"(dhi(1024, 1)), "n"(ACC));
}
template <int ACC> DEV void wg_ss64(float (&d)[32], uint32_t da, uint32_t db) {
  asm volatile("{.reg .pred p; .reg .b64 a,b; setp.ne.s32 p,%36,0; mov.b64 a,{%32,%34}; mov.b64 b,{%33,%35};\n"
    "wgmma.mma_async.sync.aligned.m64n64k16.f32.bf16.bf16 {"
    "%0,%1,%2,%3,%4,%5,%6,%7,%8,%9,%10,%11,%12,%13,%14,%15,%16,%17,%18,%19,%20,%21,%22,%23,%24,%25,%26,%27,%28,%29,%30,%31},a,b,p,1,1,0,1;}"
    : R16(d, 0), R16(d, 16) : "r"(da), "r"(db), "n"(dhi(1024, 0)), "n"(dhi(1024, 1)), "n"(ACC));
}

DEV uint32_t cpy(uint32_t v, uint32_t id) {
  uint32_t d; asm volatile("prmt.b32 %0,%1,%1,%2;" : "=r"(d) : "r"(v), "r"(id)); return d;
}
struct Params {
  uint32_t zero, spare;
  char* mid;
  const uint16_t *x0, *Are, *Aim, *Bre, *Bim, *Cre, *Cim, *logdt, *dskip, *wqkv, *wo;
  uint16_t* out;
  uint8_t role[72];
};

DEV uint32_t ln_word(float mean, float var) {
  float v = bfr(var);
  float s = sqrt_(bfr(v + 1e-5f));
  return pack2(mean, s);
}

DEV int stat_group(int c) { return c ^ 4; }
DEV int xg_off(int G, int g) { return (G >> 5) * 512 + (G & 31) * 8 + (g ^ (G & 2)); }
DEV int sr_off(int G, int g) { return (G >> 6) * 256 + (g & 2) * 64 + 2 * (G & 63) + ((g >> 2) & 1); }
DEV uint32_t region(int chl) { return SM_A + (chl >> 1) * A_E + (chl & 1) * R_SZ; }
template <bool FIRST> DEV void gram(float (&s)[4], float (&q0)[4], float (&q1)[4], uint32_t a0, uint32_t a1, uint32_t a2, uint32_t a3) {
  const uint32_t one = 0x3F803F80u;
  if (FIRST) { mma16z(s, a0, a1, a2, a3, one, one); mma8z(q0, a0, a1, a0); mma8z(q1, a0, a1, a1); }
  else { mma16(s, a0, a1, a2, a3, one, one); mma8(q0, a0, a1, a0); mma8(q1, a0, a1, a1); }
  mma8(q0, a2, a3, a2); mma8(q1, a2, a3, a3);
}
DEV uint32_t ln_sums(float s, float q) { const float m = s * (1.f / 512.f); return ln_word(m, fmaxf(q * (1.f / 512.f) - m * m, 0.f)); }
DEV void cmul(float& orr, float& oi, float ar, float ai, float br, float bi) {
  float r = ar * br - ai * bi, i = ar * bi + ai * br; orr = r; oi = i;
}
DEV void cexp_(float al, float bt, float s, float& er, float& ei) {
  float mag = ex2(al * s), ph = bt * s;
  ph -= rintf(ph);
  float ang = ph * 6.283185307179586f;
  er = mag * __cosf(ang); ei = mag * __sinf(ang);
}

DEV void kgen(const Params& P, int c, int wm, int lane) {
  const int chl = wm >> 1, mh = wm & 1, g = lane >> 2, t = lane & 3;
  const int ch = 256 * (chl >> 1) + 2 * c + (chl & 1);
  const int mo = ch * 64 + mh * 32 + lane;
  const uint32_t vAr = ldw1((const uint32_t*)P.Are + mo), vAi = ldw1((const uint32_t*)P.Aim + mo);
  const uint32_t vBr = ldw1((const uint32_t*)P.Bre + mo), vBi = ldw1((const uint32_t*)P.Bim + mo);
  const uint32_t vCr = ldw1((const uint32_t*)P.Cre + mo), vCi = ldw1((const uint32_t*)P.Cim + mo);
  const uint32_t vld = ldw1((const uint32_t*)P.logdt + (ch >> 1)), vds = ldw1((const uint32_t*)P.dskip + (ch >> 1));
  bar_arrive(NB_Y, 384);
  PROF(45);
  {
    const uint32_t tz = SM_TAP + chl * TAP_SZ + (mh * 32 + lane) * 16;
#pragma unroll
    for (int k = 0; k < 3; ++k) sts4(tz + k * 1024, 0, 0, 0, 0);
    static_assert(TAP_SZ > 3072 && TAP_SZ <= 4096, "");
    if (mh * 32 + lane < TAP_SZ / 16 - 192) sts4(tz + 3072, 0, 0, 0, 0);
  }
  const uint32_t tb = slot(wm), tw = opq(tb + lane * 4);
  const uint32_t aa = opq(tb + (lane & 15) * 144 + (lane >> 4) * 16), ba = opq(tb + (16 + (lane & 7)) * 144 + (lane >> 3) * 16);
  float acc[5][4], k2048 = 0.f;
#pragma unroll
  for (int i = 0; i < 5; ++i) zerov(acc[i]);
  sts1(tw, 0x3F80u);
  asm volatile("setmaxnreg.inc.sync.aligned.u32 %0;" :: "n"(REG_MAIN));
  PROF(44);
  const float dt = bfr(ex2((ch & 1 ? bfhi(vld) : bflo(vld)) * 1.4426950408889634f));
#pragma unroll 1
  for (int r = 0; r < 2; ++r) {
    const uint32_t sel = r ? 0x3244 : 0x1044;
    const float are = __uint_as_float(prmt(vAr, 0, sel)), aim = __uint_as_float(prmt(vAi, 0, sel)), bre = __uint_as_float(prmt(vBr, 0, sel));
    const float bim = __uint_as_float(prmt(vBi, 0, sel)), cre = __uint_as_float(prmt(vCr, 0, sel)), cim = __uint_as_float(prmt(vCi, 0, sel));
    const float al = dt * are * 1.4426950408889634f, bt = dt * aim * 0.15915494309189535f;
    float qr, qi; cmul(qr, qi, cre, cim, dt * bre, dt * bim);
    if (r == 0) PROFD(2, __float_as_uint(qr + al + bt));
    float er[3], ei[3], e8r, e8i, eLr, eLi;
    cexp_(al, bt, 1.f, er[0], ei[0]); cexp_(al, -bt, 8.f, e8r, e8i); cexp_(al, bt, 128.f, eLr, eLi);
    cmul(er[1], ei[1], er[0], ei[0], er[0], ei[0]); cmul(er[2], ei[2], er[1], ei[1], er[1], ei[1]);
    float yr = e8r, yi = e8i;
#pragma unroll
    for (int a = 0; a < 16; ++a) {
      if (a) sts1(tw + a * 144, pack2(yr, yi));
      if (a && a < 15) cmul(yr, yi, yr, yi, e8r, e8i);
      const int ls = a < 2 ? 0 : a < 4 ? 1 : a < 8 ? 2 : 3;
      const int row0 = 16 + (a < 2 ? 8 * a : a < 4 ? 16 + 4 * (a - 2) : a < 8 ? 24 + 2 * (a - 4) : 32 + (a - 8));
      float xr[8], xi[8];
      xr[0] = qr; xi[0] = qi;
#pragma unroll
      for (int k = 0; k < (8 >> ls); ++k) {
        const int hb = k >= 4 ? 2 : k >= 2 ? 1 : 0;
        if (k) cmul(xr[k], xi[k], xr[k - (1 << hb)], xi[k - (1 << hb)], er[(ls + hb) % 3], ei[(ls + hb) % 3]);
        sts1(tw + (row0 + k) * 144, pack2(xr[k], xi[k]));
      }
      cmul(qr, qi, qr, qi, eLr, eLi);
    }
    __syncwarp();
    if (r == 0) PROF(3);
#pragma unroll
    for (int kp = 0; kp < 2; ++kp) {
      uint32_t a0[4], a1[4];
      ldsm4(a0, aa + kp * 64); ldsm4(a1, aa + kp * 64 + 32);
#pragma unroll
      for (int tl = 0; tl < 5; ++tl) {
        uint32_t b[4];
        ldsm4(b, ba + 8 * tl * 144 + kp * 64);
        if (kp == 0) qr += __shfl_xor_sync(0xffffffffu, qr, 1 << tl);
        mma16(acc[tl], a0[0], a0[1], a0[2], a0[3], b[0], b[1]);
        mma16(acc[tl], a1[0], a1[1], a1[2], a1[3], b[2], b[3]);
      }
    }
    k2048 += qr;
    __syncwarp();
  }
  const uint32_t xa = tb + lane * 16, ob = xa ^ 8192, tp = SM_TAP + chl * TAP_SZ;
  if (mh == 0) {
    sts4f(xa, acc[2][0], acc[2][1], acc[2][2], acc[2][3]);
    sts4f(xa + 512, acc[3][0], acc[3][1], acc[3][2], acc[3][3]);
    sts1(tb + 1024, __float_as_uint(k2048));
  } else {
    sts4f(xa, acc[0][0], acc[0][1], acc[0][2], acc[0][3]);
    sts4f(xa + 512, acc[1][0], acc[1][1], acc[1][2], acc[1][3]);
    sts4f(xa + 1024, acc[4][0], acc[4][1], acc[4][2], acc[4][3]);
  }
  PROF(4);
  bar_sync(NB_K + chl, 64);
  float4 o[3];
#pragma unroll
  for (int k = 0; k < 3; ++k) o[k] = lds4f(ob + k * 512);
  if (mh == 0) {
    if (lane == 0) o[0].x += ch & 1 ? bfhi(vds) : bflo(vds);
    const uint32_t a = tp - 2 * (8 * g + 2 * t + 1);
#pragma unroll
    for (int z = 0; z < 4; ++z) {
      const float* k = acc[z >> 1] + 2 * (z & 1);
      const uint32_t v = z & 1 ? pack2(k[1] + o[z >> 1].w, k[0] + o[z >> 1].z) : pack2(k[1] + o[z >> 1].y, k[0] + o[z >> 1].x);
      sts1(a + T_O - 128 * z, v); sts16(a + T_E - 128 * z, v); sts16(a + T_E + 2 - 128 * z, v >> 16);
    }
    const uint32_t v0 = pack2(acc[4][0] + o[2].x, acc[4][1] + o[2].y), v1 = pack2(acc[4][2] + o[2].z, acc[4][3] + o[2].w);
    const uint32_t b = tp + T_C - 2 * (32 * t + g - 1);
    if (lane == 0) { sts16(tp + T_E - 2 * (X_5 + 63), v0); sts16(tp + T_O - 2 * (X_5 + 63), v0); sts1(tp + T_K, prmt(v0, v0, 0x1010)); }
    else sts16(b, v0);
    sts16(b - 32, v0 >> 16); sts16(b - 16, v1); sts16(b - 48, v1 >> 16);
  } else {
    const uint32_t a = tp - 2 * (256 + 128 * (t >> 1) + 4 * (t & 1) + 8 * g);
#pragma unroll
    for (int z = 0; z < 2; ++z) {
      const uint32_t v = z ? pack2(acc[2][3] + o[0].w, acc[2][2] + o[0].z) : pack2(acc[2][1] + o[0].y, acc[2][0] + o[0].x), d = prmt(v, v, 0x3232);
      sts1(a + T_E - 4 - 128 * z, v); sts16(a + T_O - 4 - 128 * z, v); sts1(a + T_O - 2 - 128 * z, d);
      if (z || lane) { sts1(a + T_E - 128 * z, d); sts16(a + T_O + 2 - 128 * z, d); } else sts16(a + T_E, d);
    }
    const uint32_t w0 = pack2(acc[3][0] + o[1].x, acc[3][1] + o[1].y), w1 = pack2(acc[3][2] + o[1].z, acc[3][3] + o[1].w);
    const uint32_t b = tp - 2 * (16 * t + g);
    if (lane == 0) {
      const uint32_t k = prmt(w0, w0, 0x1010);
      sts1(tp + T_E - 2 * 514, k); sts1(tp + T_E - 2 * 512, k);
      sts16(tp + T_O - 2 * 514, k); sts1(tp + T_O - 2 * 513, k); sts16(tp + T_O - 2 * 511, k);
      sts16(tp + T_C - 2 * 127, pack2(k2048 + o[2].x, 0.f));
    } else { sts16(b + T_E - 2 * (X_5 - 1), w0); sts16(b + T_O - 2 * (X_5 - 1), w0); }
    sts16(b + T_E - 2 * X_3, w0 >> 16); sts16(b + T_O - 2 * X_3, w0 >> 16);
    sts16(b + T_E - 2 * (X_5 + 7), w1); sts16(b + T_O - 2 * (X_5 + 7), w1);
    sts16(b + T_E - 2 * (X_3 + 8), w1 >> 16); sts16(b + T_O - 2 * (X_3 + 8), w1 >> 16);
  }
}

DEV bool bad8(const uint4& v) { return min(v.x, v.z) == 0u; }
DEV uint32_t uchunk(uint32_t reg, int x) { return reg + R_U + (x ^ ((x >> 3) & 3)) * 16; }
DEV uint32_t& xword(uint4 (&x)[2], int e, int tp) { uint4& v = x[tp >> 1]; return tp & 1 ? (e ? v.w : v.z) : (e ? v.y : v.x); }

DEV void uprep(const Params& P, int c, int wa, int lane, int layer, uint4 (&x)[2][2][2], uint32_t (&u)[4][4]) {
  const int j = 32 * wa + lane, o0 = 2 * (j + (j & 64)) + ((j >> 2) & 1);
  {
    const uint32_t za = region(wa) + lane * 16 - 512;
    sts4(za + R_U, 0, 0, 0, 0); sts4(za + R_X5, 0, 0, 0, 0); sts4(za + R_X3, 0, 0, 0, 0);
    sts4(region(wa) + R_BE, 0, 0, 0, 0);
  }
  const uint4* st = opqp(&SCR->SR[layer][c >> 4][j]);
  const uint32_t xa = opq(SM_X + 16 * o0), xb = opq(SM_X + 16 * (o0 ^ 1)), ua = opq(uchunk(0, j));
  uint4 s[2][2];
#pragma unroll
  for (int z = 0; z < 12; ++z) {
    uint4& v = z < 8 ? x[(z >> 2) & 1][(z >> 1) & 1][z & 1] : s[(z >> 1) & 1][z & 1];
    asm volatile("mov.b32 %0,0; mov.b32 %1,0; mov.b32 %2,0; mov.b32 %3,0;" : "=r"(v.x), "=r"(v.y), "=r"(v.z), "=r"(v.w));
  }
#pragma unroll 1
  for (uint32_t it = P.zero;; ++it) {
    if (it) {
      spin_guard(it);
#pragma unroll
      for (int z = 0; z < 4; ++z) { uint4& v = s[z >> 1][z & 1]; ldr4_if(v, st + z * 128, bad8(v)); }
      const uint4* xp = &SCR->XG[layer][c * 1024 + o0];
#pragma unroll
      for (int z = 0; z < 8; ++z) {
        uint4& v = x[z >> 2][(z >> 1) & 1][z & 1];
        ldr4_if(v, (const uint4*)((uintptr_t)xp ^ (16 * (z & 1))) + (z >> 2) * 512 + (z & 2) * 64, bad8(v));
      }
    } else {
      mbar_wait(B_U, layer);
      PROF(layer ? 25 : 10);
#pragma unroll
      for (int z = 0; z < 4; ++z) s[z >> 1][z & 1] = ldr4(st + z * 128);
#pragma unroll
      for (int z = 0; z < 4; ++z) { uint4& v = s[z >> 1][z & 1]; ldr4_if(v, st + z * 128, bad8(v)); }
      PROF(layer ? 26 : 11);
      mbar_wait(B_E, layer);
#pragma unroll
      for (int z = 7; z >= 0; --z) x[z >> 2][(z >> 1) & 1][z & 1] = lds4((z & 1 ? xb : xa) + (z >> 2) * 8192 + (z & 2) * 1024);
      PROF(layer ? 27 : 14);
    }
    uint32_t m = ~0u;
#pragma unroll
    for (int z = 7; z >= 0; --z) {
      const int k = z >> 2, chl = z & 3;
#pragma unroll
      for (int tp = 0; tp < 4; ++tp) u[chl][tp] = hmul2(hsub2(xword(x[k][chl >> 1], chl & 1, tp), xword(s[k], 1, tp)), xword(s[k], 0, tp));
      sts4(ua + region(chl) + k * 2048, u[chl][0], u[chl][1], u[chl][2], u[chl][3]);
      const uint4& v = x[k][chl >> 1][chl & 1];
      m = min(m, min(v.x, v.z));
      if (z < 4) m = min(m, min(s[z >> 1][z & 1].x, s[z >> 1][z & 1].z));
    }
    if (!__any_sync(0xffffffffu, m == 0)) break;
  }
  PROF(4 + 12 * layer);
}

template <bool FULL> DEV void box_unit(uint32_t reg, int s, const uint2& a, const uint4& b, const uint32_t (&d)[4], uint32_t (&pv)[4]) {
  const uint32_t u[9] = {a.x, a.y, b.x, b.y, b.z, b.w, d[0], d[1], d[2]};
  uint32_t v[8], p[8];
#pragma unroll
  for (int j = 0; j < 8; ++j) { v[j] = prmt(u[j], u[j + 1], 0x5432); p[j] = hadd2(u[j], v[j]); }
  const uint32_t o = reg + s * 16;
  uint32_t x[4], y[4];
#pragma unroll
  for (int j = 0; j < 4; ++j) { x[j] = hadd2(hadd2(p[1 + j], p[2 + j]), u[3 + j]); y[j] = hadd2(v[3 + j], p[4 + j]); pv[j] = p[4 + j]; }
  sts4(o + R_X5, x[0], x[1], x[2], x[3]);
  sts4(o + R_X3, y[0], y[1], y[2], y[3]);
  if (FULL) {
#pragma unroll
    for (int j = 0; j < 4; ++j) { y[j] = hadd2(hadd2(v[j], v[3 + j]), x[j]); x[j] = hadd2(hadd2(u[j], u[4 + j]), y[j]); }
    const bool od = s & 1;
    sts4(o + R_BO, od ? y[0] : x[0], od ? y[1] : x[1], od ? y[2] : x[2], od ? y[3] : x[3]);
    sts4(o + R_BE + 16, od ? x[0] : y[0], od ? x[1] : y[1], od ? x[2] : y[2], od ? x[3] : y[3]);
  }
}
#define NBB(e) (320 - 32 * (e))
template <int C0, int C1> DEV void box_full(int j, uint32_t (&u)[4][4], uint32_t zero) {
  const uint32_t a2 = uchunk(8, j - 2), a1 = uchunk(0, j - 1);
  uint2 a[4]; uint4 b[4];
#define HALO(n) if (n < C1) { a[(n) & 3] = lds2(region(n) + a2); b[(n) & 3] = lds4(region(n) + a1); }
  HALO(C0) HALO(C0 + 1)
  split(zero);
#pragma unroll
  for (int chl = C0; chl < C1; ++chl) {
    const uint32_t d[4] = {u[chl][0], u[chl][1], u[chl][2], u[chl][3]};
    box_unit<true>(region(chl), j, a[chl], b[chl], d, u[chl]);
    fence_async_smem();
    bar_arrive(NB_B + chl, NBB(chl & 1));
    PROFC(28 + chl);
    if (chl == C0) { HALO(C0 + 2) }
  }
#undef HALO
}
DEV void box_help(int e, int n0, int dn, int lane, int layer) {
  bar_sync(NB_H, 224);
#pragma unroll 1
  for (int n = n0; n < 4; n += dn) {
    if (n == 2 && dn == 1) mbar_wait(B_RD, layer);
    const int chl = e + (n & 2), s = 128 + 32 * (n & 1) + lane;
    const uint32_t reg = region(chl);
    const uint4 d = lds4(uchunk(reg, s));
    const uint32_t u[4] = {d.x, d.y, d.z, d.w};
    uint32_t v[4];
    box_unit<false>(reg, s, lds2(uchunk(reg, s - 2) + 8), lds4(uchunk(reg, s - 1)), u, v);
    if (dn == 2 || (n & 1)) { fence_async_smem(); bar_arrive(NB_B + chl, NBB(e)); PROFC(28 + n); }
  }
}

DEV uint4 hadd8(const uint4& a, const uint4& b) { return make_uint4(hadd2(a.x, b.x), hadd2(a.y, b.y), hadd2(a.z, b.z), hadd2(a.w, b.w)); }
DEV void conv_out(int c, int j, int chl, uint4 (&x)[2][2][2], const uint32_t (&v)[4], uint4* XF, uint32_t zero) {
  const int rho = chl >> 1, e = chl & 1;
  const uint32_t ua = uchunk(region(chl), j), fa = region(chl) + R_X5 + j * 16, ha = region(chl) + R_X3 + (j & 1) * 1088 + (j >> 1) * 16;
  const int m8 = ((j & 4) + ((j >> 1) & 1) + 2 * (j & 1)) ^ ((2 * c + e) & 7);
  uint4* xo = XF + (((16 - 2 * (j & 8) + (j >> 4)) * 512 + 256 * rho + 2 * c + e) * 8 + m8);
  bar_sync(NB_Y + e + 7 * rho, 256);
  uint4 y[2], f[2], h[2];
#pragma unroll
  for (int k = 0; k < 2; ++k) {
    y[k] = lds4(ua + k * 2048);
    f[k] = lds4z(ua + k * 2048 + R_BO - R_U, k || j >= 36);
    h[k] = lds4z(fa + k * 2048 - 1024, k || j >= 64);
  }
  const uint32_t q = lds1(SM_TAP + chl * TAP_SZ + T_K);
  const uint4 r = lds4(ha);
  split(zero);
  if (chl == 3) mbar_arrive1(B_L + (r.x & zero));
  h[1] = hadd8(h[1], make_uint4(hfma2(q, v[0], r.x), hfma2(q, v[1], r.y), hfma2(q, v[2], r.z), hfma2(q, v[3], r.w)));
#pragma unroll
  for (int k = 0; k < 2; ++k) {
    const uint4 o = hadd8(hadd8(y[k], hadd8(f[k], h[k])), make_uint4(xword(x[k][rho], e, 0), xword(x[k][rho], e, 1), xword(x[k][rho], e, 2), xword(x[k][rho], e, 3)));
    const uint32_t keep = j & 1 ? 0x7632 : 0x5410, k0 = prmt(o.x, o.y, keep), k1 = prmt(o.z, o.w, keep);
    const uint32_t g0 = __shfl_xor_sync(0xffffffffu, prmt(o.x, o.y, keep ^ 0x2222), 1), g1 = __shfl_xor_sync(0xffffffffu, prmt(o.z, o.w, keep ^ 0x2222), 1);
    str4(xo + k * 32768, j & 1 ? g0 : k0, j & 1 ? g1 : k1, j & 1 ? k0 : g0, j & 1 ? k1 : g1);

  }
  if (e) { __syncwarp(); mbar_arrive1(B_RD + rho * 8); }
  PROFC(40 + chl);
}

DEV void conv_round(int e, int rho, int w, int lane) {
  const int g = lane >> 2, t = lane & 3, chl = 2 * rho + e;
  const uint32_t reg = region(chl), tp = SM_TAP + chl * TAP_SZ, dr = dlo(reg, 128);
  const uint32_t g0 = tp + ((g & 1) ? T_O : T_E) + 2 * (2 * t - g) - 16;
  const uint32_t ga = g0 - 32 * (w & 1) - 576 * (w >> 1), id = opq(0x3210u);
  float acc[32], f1[24], f2[16];
  uint32_t q[12][4];
  {
    uint32_t qn[18][4];
    qn[0][2] = lds1(ga + 64);
#pragma unroll
    for (int n = 0; n < 18; ++n) {
      const bool nz = n < 15 || w < 2 || (n == 15 && w == 2);
      qn[n][0] = n < 15 ? lds1(ga + 48 - 32 * n) : lds1z(ga + 48 - 32 * n, nz);
      qn[n][1] = n < 15 ? lds1(ga + 32 - 32 * n) : lds1z(ga + 32 - 32 * n, nz);
    }
#pragma unroll
    for (int n = 0; n < 18; ++n) { qn[n][3] = cpy(qn[n][0], id); if (n) qn[n][2] = cpy(qn[n - 1][1], id); }
#pragma unroll
    for (int n = 0; n < 8; ++n) {
      const int i = n & 3;
      const uint32_t a = g0 + 16 - 16 * w - 2 * (n < 4 ? X_5 : X_3) + 16 * i;
      uint32_t (&q1)[4] = q[(n & 4) + (i >> 1)], (&q2)[4] = q[(n & 4) + 2 + (i >> 1)];
      q1[2 * (i & 1)] = lds1z(a, i <= w); q1[2 * (i & 1) + 1] = lds1(a - 64);
      q2[2 * (i & 1)] = cpy(0, id); q2[2 * (i & 1) + 1] = lds1z(a - 128, i >= w);
    }
    const uint32_t gc = tp + T_C - 2 + 4 * (t - g - 8 * w);
#pragma unroll
    for (int kk = 0; kk < 4; ++kk) {
      q[8 + kk][0] = lds1z(gc + 32 * kk, w >= kk); q[8 + kk][2] = lds1z(gc + 32 * kk + 16, w >= kk);
      q[8 + kk][1] = lds1(gc + 32 * kk - 128); q[8 + kk][3] = lds1(gc + 32 * kk - 112);
    }
    PROFD(rho ? 43 : 47, qn[17][2] ^ q[11][3]);
    bar_sync_if(NB_U, NBARU, 1 - rho);
    mbar_arrive1_if(B_V, chl == 1 && w == 0);
    bar_sync_if(NB_T + 1 - e, 256, chl);
    const uint32_t db = dr + (R_U + 32) / 16;
    undef(acc);
    wg_fence();
#pragma unroll
    for (int n = 0; n < 18; ++n) {
      if (n) wg_rs64k<1>(acc, qn[n], db - 2 * n); else wg_rs64k<0>(acc, qn[0], db);
      if (n == 9) wg_commit();
    }
    wg_commit();
  }
  wg_wait<1>();
  PROFC(rho ? 12 : 2);
  bar_sync(NB_B + chl, NBB(e));
  const uint32_t d1 = dr + R_X5 / 16, d2 = dr + R_BO / 16;
  undef(f1); undef(f2);
  wg_fence();
#pragma unroll
  for (int n = 0; n < 4; ++n) { if (n) wg_rs32t<1>(f2, q[8 + n], d2 + 16 * n); else wg_rs32t<0>(f2, q[8], d2); }
  wg_commit();
#pragma unroll
  for (int n = 0; n < 8; ++n) {
    const uint32_t d = d1 + (n >> 2) * ((R_X3 - R_X5) / 16) + 16 * (n & 1) - 16 * (n & 2);
    if (n) wg_rs48t<1>(f1, q[n], d); else wg_rs48t<0>(f1, q[0], d);
  }
  wg_commit();
  wg_wait<1>();
  PROFC(rho ? 13 : 3);
  bar_arrive_if(NB_T + e, 256, chl - 3);
  bar_sync(NB_WG + e, 128);
  {
    const int p = (lane + 9 * (w >> 1)) & 31;
    const uint32_t ya = reg + ((w >> 1) ? R_BO : R_U) + p * 64 + (((2 * (w & 1)) ^ ((p >> 1) & 3)) * 16);
    const uint32_t up = p < lane ? 2048 : 0;
#pragma unroll
    for (int z = 0; z < 4; ++z) {
      const float* a = acc + 16 * (z >> 1) + 2 * (z & 1);
      stsm4t((ya + (up ^ ((z >> 1) * 2048))) ^ ((z & 1) * 16), pack2(a[0], a[1]), pack2(a[4], a[5]), pack2(a[8], a[9]), pack2(a[12], a[13]));
    }
  }
  wg_wait<0>();
  PROFC(rho ? 14 : 4);
  bar_sync(NB_WG + e, 128);
  {
    const uint32_t fa = reg + R_X5 + (8 * w + (lane & 7)) * 16 + (lane >> 3) * 512;
    uint32_t h[6];
#pragma unroll
    for (int p = 0; p < 6; ++p) h[p] = p ? pack2(f1[4 * p] + f1[4 * p - 2], f1[4 * p + 1] + f1[4 * p - 1]) : pack2(f1[0], f1[1]);
    stsm4(fa, h[0], h[1], h[2], h[3]);
    stsm2(fa + 2048, h[4], h[5]);
    stsm4(reg + R_X3 + (lane < 16 ? 1088 : 0) + (8 * w + (lane & 7) + 4 * (lane & 8)) * 16, pack2(f2[0], f2[1]), pack2(f2[2] + f2[4], f2[3] + f2[5]),
          pack2(f2[8], f2[9]), pack2(f2[10] + f2[12], f2[11] + f2[13]));
  }
  bar_arrive(NB_Y + e + 7 * rho, 256);
}
constexpr uint32_t FILL = 0xFFFFFFFFu;
template <int N> DEV void fixo(uint4 (&A)[N], const uint4* p) {
#pragma unroll 1
  for (int it = 0; it < SPIN_LIMIT; ++it) {
    uint32_t m = A[0].x;
#pragma unroll
    for (int k = 1; k < N; ++k) m = max(m, A[k].x);
    if (__all_sync(0xffffffffu, m != FILL)) break;
#pragma unroll
    for (int k = 0; k < N; ++k) ldr4_if(A[k], p + k * 32, A[k].x == FILL);
  }
}
DEV bool rows_nan(float a, float b) {
  return __any_sync(0xffffffffu, a != a || b != b);
}
template <int N> DEV void slow_step(float (&acc)[N], float a0, float a1, const uint16_t* wr, uint32_t zero) {
#pragma unroll
  for (int j = 0; j < N / 4; ++j) {
    const uint32_t v = __ldg((const uint32_t*)(wr + (j >> 3) * 512 + 8 * (j & 7)));
    acc[4 * j] += a0 * bflo(v); acc[4 * j + 1] += a0 * bfhi(v); acc[4 * j + 2] += a1 * bflo(v); acc[4 * j + 3] += a1 * bfhi(v);
    if ((j & 3) == 3) wr += __float_as_uint(acc[4 * j]) & zero;
  }
}
DEV int res_off(int w, int lane) { return ((lane & 7) + 8 * (lane >> 4)) * 8 + ((2 * (w & 2) + (w & 1) + ((lane >> 2) & 2)) ^ (lane & 7)); }
DEV void res_load(uint32_t (&res)[8][2], uint32_t sa, int w, int lane) {
  const uint32_t a = sa + res_off(w, opq(lane)) * 16;
#pragma unroll
  for (int j = 0; j < 8; j += 2) {
    uint32_t r[4];
    ldsm4t(r, a + j * 1024);
    res[j][0] = r[0]; res[j][1] = r[1]; res[j + 1][0] = r[2]; res[j + 1][1] = r[3];
  }
}

DEV void res_init(float (&ac)[32], const uint32_t (&res)[8][2]) {
#pragma unroll
  for (int j = 0; j < 16; ++j)
    asm volatile("shl.b32 %0,%2,16; and.b32 %1,%2,0xFFFF0000;" : "=&f"(ac[2 * j]), "=f"(ac[2 * j + 1]) : "r"(res[j >> 1][j & 1]));
}
DEV uint32_t after(uint32_t b, const uint32_t (&res)[8][2], uint32_t zero) {
  return b + ((res[0][0] ^ res[2][0] ^ res[4][0] ^ res[6][0]) & zero);
}

DEV void attn_phase(const Params& P, int c, int e, int w, int lane, int layer) {
  lane = opq(lane); c = opq(c);
  const int i = c >> 3, cg = c & 7, J = 16 * e + i, G = 8 * i + 4 - 4 * e + w;
  const int g = lane >> 2, t = lane & 3;
  float acc[96];
  uint32_t res[8][2];
  float2 cs[16];
  float4 st;
  const uint32_t csb = opq(SM_CS + 8 * t);
  {
    const uint32_t sa = SM_A + e * A_E, ba = B_A + 32 * e;
    const uint32_t da = dlo(sa, 8192), db = (SB >> 4) | (512 << 16);
    undef(acc);
#pragma unroll
    for (int j = 0; j < 8; ++j) asm volatile("" : "=r"(res[j][0]), "=r"(res[j][1]));
    mbar_wait(B_WF, layer);
    mbar_wait(ba, 0);
    mbar_wait(B_L, layer);
    bar_sync_if(NB_T, 256, e);
    PROF(24);
#pragma unroll
    for (int j = 0; j < 4; ++j) {
      if (j) mbar_wait(ba + 8 * j, 0);
      if (j == 1) PROFK(layer ? 39 : 15);
      wg_fence();
#pragma unroll
      for (int k = 0; k < 4; ++k) {
        if (j | k) wg_ss192<1>(acc, da + j * 512 + k * 128, db + wslot(j) * 512 + k * 128); else wg_ss192<0>(acc, da, db);
        if (j == 3 && k == 1) wg_commit();
      }
      wg_commit();
      if (j == 1 || j == 2) { wg_wait<1>(); mbar_arrive1_if(B_F + 8 * (j - 1), e); }
    }
    wg_wait<1>();
    bar_arrive(NB_T + e, 256);
    wg_wait<0>();
    if (cg < 4) res_load(res, sa + cg * 8192, w, lane);
    mbar_arrive1(after(B_AE + 8 * e, res, P.zero));
    PROF(25);
#pragma unroll 1
    for (uint32_t late = P.zero;; late = 1) {
      if (late) {
        const uint16_t* xr = (const uint16_t*)SCR->XF[layer] + opq(J) * 32768;
        zero(acc);
#pragma unroll 1
        for (int k = 0; k < 512; ++k)
          slow_step(acc, ldnan(xr + k * 64 + ((2 * w) ^ (k & 7)) * 8 + g), ldnan(xr + k * 64 + ((2 * w + 1) ^ (k & 7)) * 8 + g),
                    P.wqkv + (k * 1536 + 64 * cg + 2 * t), P.zero);
        const uint32_t* q = (const uint32_t*)xr + ((64 * cg + g) * 32 + t);
        const int m8 = (2 * (w & 2) + (w & 1)) ^ g;
#pragma unroll 1
        for (int it = 0; it < SPIN_LIMIT; ++it) {
          uint32_t m = 0;
#pragma unroll
          for (int z = 0; z < 16; ++z) { const uint32_t x = ldr1(q + (z >> 1) * 256 + (m8 ^ (2 * (z & 1))) * 4); m = max(m, x); res[z >> 1][z & 1] = movm(x); }
          if (__all_sync(0xffffffffu, m != FILL)) break;
        }
#pragma unroll
        for (int z = 0; z < 16; ++z) cs[z] = lds2f(csb + 256 + z * 32);
      } else {
        mbar_wait(B_CS, 0);
#pragma unroll
        for (int z = 0; z < 16; ++z) cs[z] = lds2f(csb + 256 + z * 32);
        mbar_wait(B_W4, layer);
        mbar_wait(ba, 1);
        bar_sync(NB_T + 1 - e, 256);
        PROF(26);
#pragma unroll
        for (int j = 4; j < 8; ++j) {
          if (j > 4) mbar_wait(ba + 8 * (j - 4), 1);
          if (j >= 6) mbar_wait(B_W6 + 8 * (j - 6), layer);
          if (j > 4) PROF(31 + j);
          wg_fence();
#pragma unroll
          for (int k = 0; k < 4; ++k) {
            wg_ss192<1>(acc, da + (j & 3) * 512 + k * 128, db + wslot(j) * 512 + k * 128);
            if (j == 7 && k == 1) wg_commit();
          }
          wg_commit();
          if (j == 5) {
            if (cg >= 4) { mbar_wait(ba + 8 * (cg - 4), 1); res_load(res, sa + (cg - 4) * 8192, w, lane); }
            wg_wait<1>(); mbar_arrive1_if(B_F + 16, e); PROF(40);
          }

        }
      }
      uint32_t rs = hadd2(res[0][0], res[0][1]);
#pragma unroll
      for (int z = 2; z < 16; ++z) rs = hadd2(rs, res[z >> 1][z & 1]);
      const float rn = bflo(rs) + bfhi(rs);
      wg_wait<1>();
      bar_arrive_if(NB_T, 256, !(e | late));
      mbar_wait(B_ST + 8 * e, layer);
      st = lds4f(SM_STAT + ((4 * e + w) * 8 + g) * 16);
      PROF(34 + layer);
      wg_wait<0>();
      if (!rows_nan(acc[0] + rn, acc[2]) || late) break;
    }
  }
  mbar_arrive1(B_QE);
  PROFK(8 + 12 * layer);
  uint32_t Q[4][4], K[4][2][2], V[4][2][2];
  {
#pragma unroll
    for (int z = 0; z < 8; ++z) {
      const float* a = acc + 32 + 4 * z; const float* b = acc + 64 + 4 * z;
      K[z >> 1][1][z & 1] = pack2((a[2] - st.z * cs[z].x) * st.w, (a[3] - st.z * cs[z].y) * st.w);
      V[z >> 1][1][z & 1] = movm(pack2((b[2] - st.z * cs[8 + z].x) * st.w, (b[3] - st.z * cs[8 + z].y) * st.w));
    }
    const int hop = (G >> 1) & 3;
    const uint32_t kv = SM_KV + (2 * hop + (w & 1)) * 2048 + lane * 16;
    uint4* h = SCR->H[layer] + (c * 256 + (w & 1) * 128 + lane);
    if (hop == 3) {
#pragma unroll
      for (int z = 0; z < 4; ++z) str4(h + 2048 + z * 32, K[z][1][0], K[z][1][1], V[z][1][0], V[z][1][1]);
    } else {
      mbar_wait(B_F + 16, layer);
#pragma unroll
      for (int z = 0; z < 4; ++z) sts4(kv + z * 512, K[z][1][0], K[z][1][1], V[z][1][0], V[z][1][1]);
      bar_arrive(NB_B + hop, 128);
    }
    PROF(42);
    uint4 hv[4];
#pragma unroll
    for (int z = 0; z < 4; ++z) { hv[z] = make_uint4(0, 0, 0, 0); ldr4_if(hv[z], h + z * 32, G >= 2 && hop == 0); }
#pragma unroll
    for (int z = 0; z < 8; ++z) {
      const float* a = acc + 32 + 4 * z; const float* b = acc + 64 + 4 * z;
      K[z >> 1][0][z & 1] = pack2((a[0] - st.x * cs[z].x) * st.y, (a[1] - st.x * cs[z].y) * st.y);
      V[z >> 1][0][z & 1] = movm(pack2((b[0] - st.x * cs[8 + z].x) * st.y, (b[1] - st.x * cs[8 + z].y) * st.y));
    }
#pragma unroll
    for (int z = 0; z < 8; ++z) {
      const float2 cq = lds2f(csb + z * 32);
      const float* a = acc + 4 * z;
      Q[z >> 1][2 * (z & 1)] = pack2(a[0] - st.x * cq.x, a[1] - st.x * cq.y);
      Q[z >> 1][2 * (z & 1) + 1] = pack2(a[2] - st.z * cq.x, a[3] - st.z * cq.y);
    }
    PROF(27);
    const bool p0 = 2 * t > g, p1 = 2 * t + 1 > g, first = G < 2;
    float s[4][4], mx[4][2];
#pragma unroll
    for (int z = 0; z < 4; ++z) {
      float S[4];
      mma16z(s[z], Q[z][0], Q[z][1], Q[z][2], Q[z][3], K[z][0][0], K[z][0][1]);
      mma16z(S, Q[z][0], Q[z][1], Q[z][2], Q[z][3], K[z][1][0], K[z][1][1]);
      s[z][2] = p0 ? s[z][2] : S[2]; s[z][3] = p1 ? s[z][3] : S[3];
    }
    const float sc0 = st.y * (0.25f * 1.4426950408889634f), sc1 = st.w * (0.25f * 1.4426950408889634f);
    uint32_t pw[4][2];
#pragma unroll
    for (int r = 1; r >= 0; --r) {
      if (r == 0) {
        if (hop) {
          bar_sync(NB_B + hop - 1, 128);
#pragma unroll
          for (int z = 0; z < 4; ++z) hv[z] = lds4(kv - 4096 + z * 512);
        } else fixo(hv, h);
        PROFD(41, hv[3].x);
#pragma unroll
        for (int z = 0; z < 4; ++z) {
          float S[4];
          mma16z(S, Q[z][0], Q[z][1], Q[z][2], Q[z][3], hv[z].x, hv[z].y);
          if (first) S[0] = S[1] = __uint_as_float(0xFF800000u);
          s[z][0] = p0 ? S[0] : s[z][0]; s[z][1] = p1 ? S[1] : s[z][1];
        }
      }
#pragma unroll
      for (int z = 0; z < 4; ++z) mx[z][r] = fmaxf(s[z][2 * r], s[z][2 * r + 1]);
#pragma unroll
      for (int o = 1; o < 3; ++o)
#pragma unroll
        for (int z = 0; z < 4; ++z) mx[z][r] = fmaxf(mx[z][r], __shfl_xor_sync(0xffffffffu, mx[z][r], o));
#pragma unroll
      for (int z = 0; z < 4; ++z) pw[z][r] = pack2(ex2((s[z][2 * r] - mx[z][r]) * (r ? sc1 : sc0)), ex2((s[z][2 * r + 1] - mx[z][r]) * (r ? sc1 : sc0)));
    }
    mbar_wait(layer ? B_N : B_Z, 1);
    const uint32_t M = (p0 ? 0xFFFFu : 0u) | (p1 ? 0xFFFF0000u : 0u);
    uint4* O = SCR->O + ((J * 8 + cg) * 512 + (2 * (w & 2) + (w & 1)) * 64 + t * 8 + g);
#pragma unroll
    for (int h2 = 0; h2 < 2; ++h2) {
      uint32_t ow[2][4];
#pragma unroll
      for (int z = 0; z < 2; ++z) {
        const int n = 2 * h2 + z;
        const uint32_t w0 = pw[n][0], w1 = pw[n][1];
        float sm[4] = {0.f, 0.f, 0.f, 0.f}, Oa[2][4];
        mma8(sm, w0, w1, 0x3F803F80u);
        mma16z(Oa[0], w0 & ~M, w1 & M, 0u, w1 & ~M, V[n][0][0], V[n][1][0]); mma8(Oa[0], w0 & M, 0u, hv[n].z);
        mma16z(Oa[1], w0 & ~M, w1 & M, 0u, w1 & ~M, V[n][0][1], V[n][1][1]); mma8(Oa[1], w0 & M, 0u, hv[n].w);
        const float i0 = rcp(sm[0]), i1 = rcp(sm[2]);
#pragma unroll
        for (int d = 0; d < 2; ++d) { ow[0][2 * z + d] = pack2(Oa[d][0] * i0, Oa[d][1] * i0); ow[1][2 * z + d] = pack2(Oa[d][2] * i1, Oa[d][3] * i1); }
      }
#pragma unroll
      for (int hi = 0; hi < 2; ++hi) str4(O + hi * 128 + h2 * 32, ow[hi][0], ow[hi][1], ow[hi][2], ow[hi][3]);
    }
  }
  str1(SCR->OF[layer] + (J * 32 + cg * 4 + w), 1);
  mbar_arrive1(B_AT + 8 * e);
  PROFK(9 + 12 * layer);
  float ac[32];
  const uint32_t so = SM_O + e * O_E;
  uint2* xo = opqp(layer ? (uint2*)(P.out + ((16 * G + 2 * (lane >> 3)) * 512 + 64 * cg + 8 * (lane & 7)))
                         : (uint2*)SCR->XG[1] + ((32 * (cg & 3) + t) * 2048 + (cg >> 2) * 256 + xg_off(G, g)));
  const uint32_t stg = SM_X + (4 * e + w) * 2048;
  const uint32_t sw = opq(stg + (lane & 15) * 128 + (((lane >> 4) ^ (lane & 7)) * 16)), sr = opq(stg + (lane >> 3) * 128 + (((lane & 7) ^ (lane >> 3)) * 16));
  uint4* ps = opqp(&SCR->PS[(G * 8 + cg) * 8 + g]);
  {
    const uint32_t bo = B_O + 32 * e;
    const uint32_t dw = (SM_WO >> 4) | (512 << 16), da = dlo(so, 512);
    mbar_wait(B_WO, layer);
    res_init(ac, res);
    mbar_wait(B_AT + 8, layer);
#pragma unroll
    for (int j = 0; j < 4; ++j) {
      mbar_wait(bo + 8 * j, layer);
      if (j == 0) PROFK(32 + layer);
      wg_fence();
#pragma unroll
      for (int k = 8 * j; k < 8 * j + 8; ++k) {
        const uint32_t a = da + (k >> 2) * 512 + (k & 3) * 8, b = dw + (k & 3) * 1024 + (k >> 2) * 128;
        wg_ss64<1>(ac, a, b);
      }
      wg_commit();
    }
#pragma unroll 1
    for (uint32_t late = P.zero;; late = 1) {
      if (late) {
        const uint16_t* op = (const uint16_t*)(SCR->O + (J * 4096 + w * 128 + g));
        wg_wait<0>();
        res_init(ac, res);
#pragma unroll 1
        for (int k = 0; k < 512; ++k) {
          const uint16_t* q = op + (k >> 6) * 4096 + (k & 56) * 8 + (k & 7);
          slow_step(ac, ldnan(q), ldnan(q + 512), P.wo + (((k & ~31) + 4 * (k & 6) + ((k >> 2) & 6) + (k & 1)) * 512 + 64 * cg + 2 * t), P.zero);
        }
      }
      wg_wait<0>();
      if (!rows_nan(ac[0], ac[2]) || late) break;
    }
  }
  PROFK(10 + 12 * layer);
#pragma unroll
  for (int j = 0; j < 16; ++j) res[j >> 1][j & 1] = pack2(ac[2 * j], ac[2 * j + 1]);
  if (layer == 0) {
    float s[2][4], q0[2][4], q1[2][4];
#pragma unroll
    for (int j = 0; j < 2; ++j) gram<true>(s[j], q0[j], q1[j], res[2 * j][0], res[2 * j][1], res[2 * j + 1][0], res[2 * j + 1][1]);
#pragma unroll
    for (int j = 0; j < 2; ++j) gram<false>(s[j], q0[j], q1[j], res[2 * j + 4][0], res[2 * j + 4][1], res[2 * j + 5][0], res[2 * j + 5][1]);
    const bool od = g & 1;
    str4_if(ps, nzmap(__float_as_uint(s[0][0] + s[1][0])), __float_as_uint(od ? q0[0][1] + q0[1][1] : q0[0][0] + q0[1][0]),
            __float_as_uint(s[0][2] + s[1][2]), __float_as_uint(od ? q1[0][3] + q1[1][3] : q1[0][2] + q1[1][2]), t == (g >> 1));
#pragma unroll
    for (int j = 0; j < 8; ++j) {
      str2(xo + j * 8192, nzmap(prmt(res[j][0], res[j][1], 0x5410)), prmt(res[j][0], res[j][1], 0x7632));
    }
    mbar_arrive1(B_ED + 8 * e);
  } else {
#pragma unroll
    for (int j = 0; j < 8; j += 2) stsm4(sw ^ (j * 16), res[j][0], res[j][1], res[j + 1][0], res[j + 1][1]);
    __syncwarp();
    uint4 v[4];
#pragma unroll
    for (int k = 0; k < 4; ++k) v[k] = lds4((sr ^ ((k & 1) * 64)) + k * 512);
#pragma unroll
    for (int k = 0; k < 4; ++k) stw4(xo + ((k & 1) * 8 + (k >> 1)) * 128, v[k].x, v[k].y, v[k].z, v[k].w);
  }
  PROFK(11 + 12 * layer);
}

DEV void col_sums(const Params& P, int c, int wa, int lane) {
  const int i = c >> 3, cg = c & 7;
  uint4 wv[8];
#pragma unroll
  for (int k = 0; k < 8; ++k) wv[k] = ldnc4(P.wqkv + ((32 * i + (lane >> 3)) * 1536 + wa * 512 + 64 * cg + 8 * (lane & 7)) + 4 * k * 1536);
  float cs[8];
  zero(cs);
#pragma unroll
  for (int k = 0; k < 8; ++k) {
    cs[0] += bflo(wv[k].x); cs[1] += bfhi(wv[k].x); cs[2] += bflo(wv[k].y); cs[3] += bfhi(wv[k].y);
    cs[4] += bflo(wv[k].z); cs[5] += bfhi(wv[k].z); cs[6] += bflo(wv[k].w); cs[7] += bfhi(wv[k].w);
  }
  const bool b4 = lane & 16, b3 = lane & 8;
#pragma unroll
  for (int k = 0; k < 4; ++k) cs[k] = (b4 ? cs[k + 4] : cs[k]) + __shfl_xor_sync(0xffffffffu, b4 ? cs[k] : cs[k + 4], 16);
#pragma unroll
  for (int k = 0; k < 2; ++k) cs[k] = (b3 ? cs[k + 2] : cs[k]) + __shfl_xor_sync(0xffffffffu, b3 ? cs[k] : cs[k + 2], 8);
  str2((uint2*)SCR->CS + (i * 768 + wa * 256 + 32 * cg + 4 * (lane & 7) + (lane >> 3)), nzmap(__float_as_uint(cs[0])), __float_as_uint(cs[1]));
}
DEV void col_gather(const Params& P, int c, int wa, int lane) {
  const uint2* p = (const uint2*)SCR->CS + (wa * 256 + 32 * (c & 7) + lane);
#pragma unroll 1
  for (int it = 0;; ++it) {
    float a = 0.f, b = 0.f;
    uint32_t m = ~0u;
#pragma unroll
    for (int k = 0; k < 16; ++k) { const uint2 q = ldr2(p + k * 768); m = min(m, q.x); a += __uint_as_float(q.x); b += __uint_as_float(q.y); }
    if (__all_sync(0xffffffffu, m != 0u)) { sts2f(SM_CS + wa * 256 + lane * 8, a, b); break; }
    spin_guard(it);
  }
  __syncwarp();
  mbar_arrive1(B_CS);
}

DEV void aux_prologue(const Params& P, int c, int wa, int lane) {
  const int g = lane >> 2, t = lane & 3, G = stat_group(c);
  {
    uint32_t w[16][2];
    const uint16_t* row = P.x0 + ((16 * G + 2 * g) * 512 + 128 * wa + 8 * t);
    bar_sync(NB_Y, 384);
#pragma unroll
    for (int z = 0; z < 8; ++z) {
      const uint4 v = ldw4(row + (z & 1) * 512 + (z >> 1) * 32);
      const int o = 4 * (z >> 1);
      w[o][z & 1] = v.x; w[o + 1][z & 1] = v.y; w[o + 2][z & 1] = v.z; w[o + 3][z & 1] = v.w;
    }
    PROF(34);
    PROFD(35, w[0][0]);
    PROFD(36, w[15][1]);
    uint2* xo = (uint2*)SCR->XG[0] + ((64 * (wa & 1) + 4 * t) * 2048 + (wa >> 1) * 256 + xg_off(G, g));
#pragma unroll
    for (int n = 0; n < 16; ++n) str2(xo + (16 * (n >> 2) + (n & 3)) * 2048, nzmap(prmt(w[n][0], w[n][1], 0x5410)), prmt(w[n][0], w[n][1], 0x7632));
    float s[2][4], q0[2][4], q1[2][4];
#pragma unroll
    for (int z = 0; z < 8; ++z) {
      const int o = 4 * (z >> 1), r = z & 1;
      if (z < 2) gram<true>(s[r], q0[r], q1[r], w[o][r], w[o + 1][r], w[o + 2][r], w[o + 3][r]);
      else gram<false>(s[r], q0[r], q1[r], w[o][r], w[o + 1][r], w[o + 2][r], w[o + 3][r]);
    }
    const bool od = g & 1;
    if (t == (g >> 1))
      sts4f(SM_STAT + (wa * 8 + g) * 16, s[0][0] + s[0][2], od ? q0[0][1] + q1[0][3] : q0[0][0] + q1[0][2],
            s[1][0] + s[1][2], od ? q0[1][1] + q1[1][3] : q0[1][0] + q1[1][2]);
    bar_arrive(NB_P0, 192);
  }
  PROF(2);
  if (lane == 0)
    asm volatile("cp.async.bulk.prefetch.L2.global [%0],4096;" :: "l"(wa < 3 ? P.wqkv + (3 * c + wa) * 2048 : P.wo + c * 2048) : "memory");
  bar_sync(NB_Y + 1, 256);
  mbar_wait(B_Z, 0);
}

DEV void stat_part(const Params& P, int c, int wa, int lane, int layer, int h, float (&v)[2]) {
  lane = opq(lane);
  const int e = wa >> 1;
  uint32_t x[4][4];
  mbar_wait(B_A + 16 * wa, h); mbar_wait(B_A + 16 * wa + 8, h);
  if (h == 0) mbar_wait(B_A + 32 * e + 24, 0);
#pragma unroll
  for (int k = 0; k < 4; ++k) ldsm4t(x[k], SM_A + e * A_E + (128 * (wa & 1) + lane) * 128 + (((c ^ lane) & 7) * 16) + k * 4096);
  float s[4] = {0.f, 0.f, 0.f, 0.f};
#pragma unroll
  for (int k = 0; k < 16; ++k) { const float a = bflo(x[k >> 2][k & 3]), b = bfhi(x[k >> 2][k & 3]); s[0] += a; s[1] += a * a; s[2] += b; s[3] += b * b; }
  s[0] += s[2]; s[1] += s[3];
  if (RARE(rows_nan(s[1], s[1]))) {
    const uint16_t* q = (const uint16_t*)(SCR->XF[layer] + ((32 * e + 2 * (c >> 3) + h) * 2048 + (wa & 1) * 1024)) + (lane >> 2);
    s[0] = s[1] = 0.f;
#pragma unroll 1
    for (int k = 0; k < 32; ++k) {
      const int r = 2 * (lane & 3) + (k & 1);
      const float a = ldnan(q + ((k >> 1) * 8 + r) * 64 + ((c ^ r) & 7) * 8);
      s[0] += a; s[1] += a * a;
    }
  }
  v[0] += s[0]; v[1] += s[1];
  __syncwarp();
}
DEV void stat_finish(const Params& P, int c, int wa, int lane, int layer, float (&v)[2]) {
  lane = opq(lane);
  const bool b = lane & 1;
  const float s = (b ? v[1] : v[0]) + __shfl_xor_sync(0xffffffffu, b ? v[0] : v[1], 1);
  str1((uint32_t*)SCR->ST[layer] + ((128 * (wa >> 1) + c) * 64 + (wa & 1) * 32 + lane), nzmap(__float_as_uint(s)));
  const uint4* sp = SCR->ST[layer] + ((128 * (wa >> 1) + (c & ~7) + 4 * (wa & 1) + (lane >> 3)) * 16 + (lane & 7));
  uint4 x, y;
  for (int it = 0;; ++it) {
    x = ldr4(sp); y = ldr4(sp + 8);
    if (__all_sync(0xffffffffu, min(min(min(x.x, x.y), min(x.z, x.w)), min(min(y.x, y.y), min(y.z, y.w))) != 0u)) break;
    spin_guard(it);
  }
  const uint32_t q = ln_sums((__uint_as_float(x.x) + __uint_as_float(x.z)) + (__uint_as_float(y.x) + __uint_as_float(y.z)),
                             (__uint_as_float(x.y) + __uint_as_float(x.w)) + (__uint_as_float(y.y) + __uint_as_float(y.w)));
  sts2f(SM_STAT + (16 * wa + (lane >> 4) * 8 + (lane & 7)) * 16 + (lane & 8), bflo(q), rcp(bfhi(q)));
  __syncwarp();
  mbar_arrive1(B_ST + 4 * (wa & 2));
}

DEV void nan_source(uint32_t a, int lane) {
#pragma unroll
  for (int k = 0; k < 4; ++k) sts4(a + k * 512 + lane * 16, FILL, FILL, FILL, FILL);
  fence_async_smem();
  __syncwarp();
}
__global__ void __launch_bounds__(NTHR, 1)
fused_kernel(const __grid_constant__ Params P, const __grid_constant__ CUtensorMap mapW, const __grid_constant__ CUtensorMap mapWo,
             const __grid_constant__ CUtensorMap mapX) {
  extern __shared__ __align__(1024) uint8_t smem_raw[];
  const int warp = __shfl_sync(0xffffffffu, threadIdx.x >> 5, 0), lane = threadIdx.x & 31;
  uint32_t smid; asm volatile("mov.u32 %0,%%smid;" : "=r"(smid));
  const uint32_t* pw = (const uint32_t*)&P + threadIdx.y;
  const int role = P.role[(smid >> 1) + threadIdx.y] + (smid & 1) + (pw[0] & pw[12]);
  const int c = __shfl_sync(0xffffffffu, pw[1] ? role : blockIdx.x, 0);
  if (c >= 128) {
#pragma unroll 1
    for (int k = (c - 128) * NTHR + threadIdx.x; k < 131072; k += P.spare * NTHR) str4(SCR->XG[1] + k, 0, 0, 0, 0);
    __threadfence();
    __syncthreads();
    if (warp == 0) { poll(SCR->C + 1 + (lane & 3) * 32, 32); cnt_add1(SCR->C + 6); }
    __syncthreads();
#pragma unroll 1
    for (int k = (c - 128) * NTHR + threadIdx.x; k < 131072; k += P.spare * NTHR) str4(SCR->XG[0] + k, 0, 0, 0, 0);
    return;
  }
#define DONE() do {} while (0)
  const int cg = c & 7;
  if (warp < 8) {
    PROF(46);
    kgen(P, c, warp, lane);
    PROFK(1);
    bar_sync(0, 384);
#pragma unroll 1
    for (int layer = 0; layer < 2; ++layer) {
#pragma unroll 1
      for (int rho = 0; rho < 2; ++rho) {
        const int wz = warp + ((rho + layer) & P.zero);
        conv_round(wz >> 2, rho, wz & 3, lane_id());
        PROFK(6 + rho + 12 * layer);
      }
      const int z = layer & P.zero;
      attn_phase(P, c + z, (warp + z) >> 2, (warp + z) & 3, lane_id(), layer);
    }
    DONE();
  } else if (warp < 12) {
    asm volatile("setmaxnreg.dec.sync.aligned.u32 %0;" :: "n"(REG_AUX));
    aux_prologue(P, c, warp - 8, lane);
    PROF(1);
    const int c0 = c;
#pragma unroll 1
    for (int layer = 0;; ++layer) {
      const int c = c0 + (layer & P.zero), wa = warp - 8 + (layer & P.zero);
#define lane lane_id()
#define j (32 * wa + lane_id())
      uint4 x[2][2][2];
      uint32_t u[4][4];
      uprep(P, c, wa, lane, layer, x, u);
      fence_async_smem();
      bar_arrive(NB_U, NBARU);
      PROFK(5 + 12 * layer);
      bar_sync(NB_H, 224);
      box_full<0, 3>(j, u, P.zero);
      PROF(3 + 12 * layer);
      conv_out(c, j, 0, x, u[0], SCR->XF[layer], P.zero);
      PROF(32);
      conv_out(c, j, 1, x, u[1], SCR->XF[layer], P.zero);
      box_full<3, 4>(j, u, P.zero);
      PROF(6 + 12 * layer);
      if (layer == 0 && wa < 3) col_sums(P, c, wa, lane);
      conv_out(c, j, 2, x, u[2], SCR->XF[layer], P.zero);
      PROF(33);
      conv_out(c, j, 3, x, u[3], SCR->XF[layer], P.zero);
      PROFK(7 + 12 * layer);
      float v[2];
      zero(v);
#pragma unroll 1
      for (int h = 0; h < 2; ++h) {
        stat_part(P, c, wa, lane, layer, h, v);
        if (h) break;
        mbar_arrive1(B_AE + 4 * (wa & 2));
        if (layer == 0 && wa < 3) col_gather(P, c, wa, lane);
      }
      PROF(9 + 12 * layer);
      stat_finish(P, c, wa, lane, layer, v);
      PROF(8 + 12 * layer);
      if (layer) break;
      mbar_wait(B_ED, 0); mbar_wait(B_ED + 8, 0);
#undef lane
#undef j
    }
    DONE();
  } else {
    asm volatile("setmaxnreg.dec.sync.aligned.u32 %0;" :: "n"(REG_PROD));
    if (s2u(smem_raw) != SB) __trap();
#pragma unroll 1
    for (int n = warp - 12; n < 42; n += 4)
      asm volatile("{.reg .pred p; elect.sync _|p,0xffffffff; @p mbarrier.init.shared::cta.b64 [%0],%1;}"
                   :: "r"(SM_BAR + n * 8), "r"(n == 33 ? 4 : n > 14 ? 1 : (int)(0x322866444444444ull >> (4 * n)) & 15) : "memory");
    fence_async_smem();
    bar_sync(NB_AUX, 128);
    bar_arrive(0, 384); bar_arrive(NB_Y + 1, 256);
    PROF(1);
    if (warp == 12) {
      if (lane == 0) {
        asm volatile("prefetch.tensormap [%0];" :: "l"(&mapW) : "memory");
        asm volatile("prefetch.tensormap [%0];" :: "l"(&mapWo) : "memory");
        asm volatile("prefetch.tensormap [%0];" :: "l"(&mapX) : "memory");
      }
      nan_source(slot(12), lane);
#pragma unroll 1
      for (int k = 0; k < 8; ++k) tma2_store(&mapX, slot(12), 128 * c, 8 * k);
      bulk_wait();
      __threadfence();
      mbar_arrive1(B_Z);
      mbar_wait(B_E, 0);
#pragma unroll 1
      for (int k = 0; k < 4; ++k) bulk_store(SCR->H[k >> 1] + ((c + 8) * 256 + (k & 1) * 128), slot(12), 2048);
#pragma unroll 1
      for (int k = 0; k < 8; ++k) bulk_store(SCR->O + (c * 512 + (k >> 2) * 65536 + (k & 3) * 128), slot(12), 2048);
      bulk_wait();
      PROF(24);
#pragma unroll 1
      for (int layer = 0; layer < 2; ++layer) {
        mbar_wait(B_V, layer);
        if (layer == 1 && c < 4 && ((0x47 >> lane) & 1)) str1(SCR->C + c * 32 + lane, 0);
        mbar_expect1(B_WF, 4 * 24576);
#pragma unroll
        for (int k = 0; k < 4; ++k) tma3(slot(wslot(k)), &mapW, 64 * cg, 64 * k, 0, B_WF);
        if (layer == 0) { __threadfence(); mbar_arrive1(B_Z); }
        mbar_wait(B_WF, layer);
        mbar_expect1(B_W4, 2 * 24576);
#pragma unroll
        for (int k = 4; k < 6; ++k) tma3(slot(wslot(k)), &mapW, 64 * cg, 64 * k, 0, B_W4);
        bar_sync(NB_AUX, 64);
#pragma unroll 1
        for (int k = 0; k < 2; ++k) {
          mbar_expect1(B_W6 + 8 * k, 24576);
          mbar_wait(B_F + 8 * k, layer);
          tma3(slot(3 * k), &mapW, 64 * cg, 384 + 64 * k, 0, B_W6 + 8 * k);
        }
        mbar_expect1(B_WO, 65536);
        mbar_wait(B_AE + 8, layer);
        nan_source(slot(12), lane);
        uint4* fp = layer ? SCR->O + c * 512 : SCR->XF[1] + c * 512;
#pragma unroll 1
        for (int r = 7; r >= 0; --r) {
          __nanosleep(30);
          if (r >= 4) {
            bulk_store(fp + (r & 3) * 128, slot(12), 2048); bulk_store(fp + 65536 + (r & 3) * 128, slot(12), 2048);
          }
          if (r == 3) { bulk_wait(); __threadfence(); mbar_arrive1(B_N); PROF(9 + 12 * layer); }
          if (r == 1) mbar_wait(B_F + 16, layer);
          tma4(SM_WO + r * 8192, &mapWo, 64 * cg, 0, r >> 1, 32 * (r & 1), B_WO);
        }
        PROF(8 + 12 * layer);
      }
      DONE();
    } else if (warp == 13) {
      const int G = stat_group(c);
#pragma unroll 1
      for (int layer = 0; layer < 2; ++layer) {
        float z[4];
        uint2* so = opqp((uint2*)&SCR->SR[layer][lane >> 3][sr_off(G, lane)] + (lane & 1));
        if (layer == 0) {
          bar_sync(NB_P0, 192);
          const float4 a = lds4f(SM_STAT + lane * 16);
          z[0] = a.x; z[1] = a.y; z[2] = a.z; z[3] = a.w;
        } else {
          mbar_wait(B_ED + 2 * (c & 4), 0);
          uint4* ps = &SCR->PS[G * 64 + lane];
          uint4 a, b;
          for (int it = 0;; ++it) {
            a = ldr4(ps); b = ldr4(ps + 32);
            if (__all_sync(0xffffffffu, min(a.x, b.x) != 0u)) break;
            spin_guard(it);
          }
          z[0] = __uint_as_float(a.x) + __uint_as_float(b.x); z[1] = __uint_as_float(a.y) + __uint_as_float(b.y);
          z[2] = __uint_as_float(a.z) + __uint_as_float(b.z); z[3] = __uint_as_float(a.w) + __uint_as_float(b.w);
        }
#pragma unroll
        for (int o = 8; o < 32; o <<= 1)
#pragma unroll
          for (int k = 0; k < 4; ++k) z[k] += __shfl_xor_sync(0xffffffffu, z[k], o);
        const uint32_t w0 = ln_sums(z[0], z[1]), w1 = ln_sums(z[2], z[3]);
        const uint32_t r = nzmap(pack2(rcp(bfhi(w0)), rcp(bfhi(w1)))), m = prmt(w0, w1, 0x5410);
        str2(so, r, m); str2(so + 4 * 1024, r, m);
        PROF(4 + 12 * layer);
        box_help(0, 0, 2, lane, layer);
        PROF(6 + 12 * layer);
      }
      DONE();
    } else if (warp == 14) {
#pragma unroll 1
      for (int layer = 0; layer < 2; ++layer) {
        uint32_t* ca = opqp(SCR->C + (c >> 5) * 32 + 3 * layer);
        const uint32_t* cw = opqp(SCR->C + (lane & 3) * 32 + 3 * layer);
        const uint4* xg = opqp(SCR->XG[layer] + c * 1024);
        mbar_expect1(B_E, 16384);
        if (layer) { mbar_wait(B_N, 0); mbar_wait(B_ED, 0); mbar_wait(B_ED + 8, 0); } else bar_sync(NB_P0, 192);
        cnt_add1(ca);
        PROF(4 + 12 * layer);
#pragma unroll 1
        for (uint32_t it = 0, todo = 15; todo; ++it) {
          spin_guard(it);
          const uint32_t m = __ballot_sync(0xffffffffu, ldr1(cw) >= 32) & todo;
          todo ^= m;
          mbar_arrive1_if(B_U, todo == 0);
#pragma unroll
          for (int q = 0; q < 4; ++q)
            if ((m >> q) & 1) bulk(SM_X + 4096 * q, xg + 256 * q, 4096, B_E);
        }
        PROFK(5 + 12 * layer);
        box_help(0, 1, 2, lane, layer);
#pragma unroll 1
        for (int n = 0; n < 4; ++n) {
          const int e = n & 1;
          const uint4* src = opqp(SCR->XF[layer] + (32 * e + 2 * (c >> 3) + (n >> 1)) * 2048);
          const uint32_t dst = opq(SM_A + e * A_E), b = opq(B_A + 32 * e), f = opq(n == 1 ? B_L : (n & 2 ? B_AE : B_RD) + 8 * e);
          if (n == 2) poll(cw + 2, 32);
          if (n == 2) PROF(7 + 12 * layer);
          mbar_wait(f, layer);
          if (n == 0) cnt_add1(ca + 1);
          uint32_t ok = n ? 15 : 0;
#pragma unroll 1
          for (int q = 0, it = 0; q < 4; ++q) {
            mbar_expect1(b + 8 * q, 8192);
#pragma unroll 1
            for (; !((ok >> q) & 1); ++it) {
              spin_guard(it);
              ok = __ballot_sync(0xffffffffu, ldr1(cw + 1) >= 32);
            }
            bulk(dst + 8192 * q, src + 512 * q, 8192, b + 8 * q);
          }
          bar_arrive_if(NB_AUX, 64, n == 2);
          if (!e) PROFK(6 + n + 12 * layer);
        }
#pragma unroll 1
        for (int n = 0; n < 8; ++n) mbar_expect1(B_O + 8 * n, 16384);
        if (layer == 0) poll(SCR->C + 6, P.spare);
        mbar_wait(B_QE, layer);
#pragma unroll 1
        for (int e = 0; e < 2; ++e) {
          const int J = 16 * e + (c >> 3);
          const uint32_t* fl = opqp(SCR->OF[layer] + J * 32 + lane);
          const uint4* src[4];
          uint32_t dst[4], b[4];
#pragma unroll
          for (int n = 0; n < 4; ++n) { src[n] = opqp(SCR->O + (J * 4096 + n * 1024)); dst[n] = opq(SM_O + e * O_E + 16384 * n); b[n] = opq(B_O + 32 * e + 8 * n); }
          mbar_wait(B_AT + 8 * e, layer);
          if (!e) pause(260);
          poll(fl, 1);
#pragma unroll
          for (int n = 0; n < 4; ++n) bulk(dst[n], src[n], 16384, b[n]);
          PROFK(9 + e + 12 * layer);
        }
      }
      DONE();
    }
    if (warp == 15) {
      const int G = stat_group(c);
      str4(&SCR->ST[0][(lane >> 4) * 2048 + c * 16 + (lane & 15)], 0, 0, 0, 0); str4(&SCR->ST[1][(lane >> 4) * 2048 + c * 16 + (lane & 15)], 0, 0, 0, 0);
      if (lane < 4) str4(SCR->OF[lane >> 1] + ((lane & 1) * 512 + c * 4), 0, 0, 0, 0);
      str4(&SCR->PS[G * 64 + lane], 0, 0, 0, 0); str4(&SCR->PS[G * 64 + 32 + lane], 0, 0, 0, 0);
      str4(&SCR->SR[1][lane >> 2][sr_off(G, 2 * lane)], 0, 0, 0, 0);
      if (c < 4 && lane < 3) str1(SCR->C + c * 32 + 3 + lane, 0);
#pragma unroll
      for (int k = 0; k < 3; ++k) str2((uint2*)SCR->CS + ((c >> 3) * 768 + k * 256 + 32 * cg + lane), 0, 0);
      __threadfence();
#pragma unroll 1
      for (int layer = 0; layer < 2; ++layer) {
        PROF(4 + 12 * layer);
        box_help(1, 0, 1, lane, layer);
        if (layer) str4(&SCR->SR[0][lane >> 2][sr_off(G, 2 * lane)], 0, 0, 0, 0);
        uint32_t* ca = opqp(SCR->C + (c >> 5) * 32 + 3 * layer + 2);
        mbar_wait(B_Z, 1);
        mbar_wait(B_RD + 8, layer);
        cnt_add1(ca);
        if (P.spare == 0) {
#pragma unroll 1
          for (int k = 0; k < 32; ++k) str4(SCR->XG[layer] + (c * 1024 + k * 32 + lane), 0, 0, 0, 0);
        }
      }
      mbar_watch(B_O + 56, 1);
    }
  }
}

typedef CUresult (*EncodeFn)(CUtensorMap*, CUtensorMapDataType, cuuint32_t, void*, const cuuint64_t*, const cuuint64_t*,
                             const cuuint32_t*, const cuuint32_t*, CUtensorMapInterleave, CUtensorMapSwizzle,
                             CUtensorMapL2promotion, CUtensorMapFloatOOBfill);

static int place_roles(uint8_t* role) {
  int dev = 0, nsm = 0;
  cudaGetDevice(&dev);
  cudaDeviceGetAttribute(&nsm, cudaDevAttrMultiProcessorCount, dev);
  if (nsm <= 128 || nsm > 144 || (nsm & 1)) return 0;
  cudaFuncSetAttribute(fused_kernel, cudaFuncAttributeNonPortableClusterSizeAllowed, 1);
  int occ[9] = {0};
  for (int k = 2; k <= 8; ++k) {
    cudaLaunchConfig_t cfg = {};
    cudaLaunchAttribute at[1];
    at[0].id = cudaLaunchAttributeClusterDimension;
    at[0].val.clusterDim.x = 2 * k; at[0].val.clusterDim.y = 1; at[0].val.clusterDim.z = 1;
    cfg.gridDim = dim3(2 * k); cfg.blockDim = dim3(NTHR); cfg.dynamicSmemBytes = SM_TOTAL; cfg.attrs = at; cfg.numAttrs = 1;
    if (cudaOccupancyMaxActiveClusters(&occ[k], fused_kernel, &cfg) != cudaSuccess) { cudaGetLastError(); occ[k] = 0; }
  }
  int n[10];
  n[7] = occ[8]; n[6] = occ[7]; n[5] = occ[6] - 0; n[4] = occ[5];
  n[3] = occ[4] - n[7]; n[1] = occ[2] - n[3] - n[5] - n[7]; n[0] = n[2] = n[1];
  n[8] = occ[3] - n[2] - n[5];
  const int ntpc = nsm / 2;
  int sum = 0;
  bool ok = n[0] > 0 && n[0] <= 8;
  for (int r = 0; r < 9; ++r) { ok = ok && n[r] >= 0 && (r == 0 || n[r] <= n[r - 1]); sum += n[r]; }
  if (!ok || sum > ntpc) { for (int r = 0; r < 9; ++r) n[r] = r < 8 ? 8 : 0; sum = 64; }
  int tp[8][9], cnt[8] = {0}, pool[72], np = 0, id = 0;
  for (int r = 0; r < 9; ++r)
    for (int g = n[0] - n[r]; g < n[0]; ++g) tp[g][cnt[g]++] = id++;
  for (; id < ntpc; ++id) pool[np++] = id;
  int order[72], no = 0;
  for (int g = 0; g < n[0]; ++g) {
    const int full = cnt[g] / 4 * 4;
    for (int k = 0; k < cnt[g]; ++k) { if (k < full) order[no++] = tp[g][k]; else pool[np++] = tp[g][k]; }
  }
  for (int k = 0; k < np; ++k) order[no++] = pool[k];
  for (int k = 0; k < ntpc; ++k) role[order[k]] = 2 * k;
  return nsm;
}

extern "C" void kernel_launch(void* const* d_in, const int* in_sizes, int n_in, void* d_out, int out_size) {
  (void)in_sizes; (void)n_in; (void)out_size;
  static EncodeFn enc = nullptr;
  static uint8_t role[72];
  static int nsm = 0;
  static Scratch* scratch = nullptr;
  if (!enc) {
    void* fn = nullptr;
    cudaDriverEntryPointQueryResult qr;
    cudaGetDriverEntryPoint("cuTensorMapEncodeTiled", &fn, cudaEnableDefault, &qr);
    enc = (EncodeFn)fn;
    cudaFuncSetAttribute(fused_kernel, cudaFuncAttributeMaxDynamicSharedMemorySize, SM_TOTAL);
    nsm = place_roles(role);
    cudaGetSymbolAddress((void**)&scratch, g_S);
  }
  CUtensorMap mW, mWo, mX;
  {
    cuuint64_t dim[3] = {512, 512, 3}, str[2] = {3072, 1024};
    cuuint32_t box[3] = {64, 64, 3}, es[3] = {1, 1, 1};
    enc(&mW, CU_TENSOR_MAP_DATA_TYPE_BFLOAT16, 3, d_in[10], dim, str, box, es, CU_TENSOR_MAP_INTERLEAVE_NONE,
        CU_TENSOR_MAP_SWIZZLE_128B, CU_TENSOR_MAP_L2_PROMOTION_NONE, CU_TENSOR_MAP_FLOAT_OOB_FILL_NONE);
  }
  {
    cuuint64_t dim[4] = {512, 2, 4, 64}, str[3] = {1024, 2048, 8192};
    cuuint32_t box[4] = {64, 2, 1, 32}, es[4] = {1, 1, 1, 1};
    enc(&mWo, CU_TENSOR_MAP_DATA_TYPE_BFLOAT16, 4, d_in[11], dim, str, box, es, CU_TENSOR_MAP_INTERLEAVE_NONE,
        CU_TENSOR_MAP_SWIZZLE_128B, CU_TENSOR_MAP_L2_PROMOTION_NONE, CU_TENSOR_MAP_FLOAT_OOB_FILL_NONE);
  }
  {
    cuuint64_t dim[2] = {16384, 64}, str[1] = {32768};
    cuuint32_t box[2] = {128, 8}, es[2] = {1, 1};
    enc(&mX, CU_TENSOR_MAP_DATA_TYPE_BFLOAT16, 2, scratch->XF[0], dim, str, box, es, CU_TENSOR_MAP_INTERLEAVE_NONE,
        CU_TENSOR_MAP_SWIZZLE_NONE, CU_TENSOR_MAP_L2_PROMOTION_NONE, CU_TENSOR_MAP_FLOAT_OOB_FILL_NONE);
  }
  Params P;
  P.x0 = (const uint16_t*)d_in[0]; P.Are = (const uint16_t*)d_in[1]; P.Aim = (const uint16_t*)d_in[2];
  P.Bre = (const uint16_t*)d_in[3]; P.Bim = (const uint16_t*)d_in[4]; P.Cre = (const uint16_t*)d_in[5];
  P.Cim = (const uint16_t*)d_in[6]; P.logdt = (const uint16_t*)d_in[7]; P.dskip = (const uint16_t*)d_in[8];
  P.wqkv = (const uint16_t*)d_in[10]; P.wo = (const uint16_t*)d_in[11]; P.out = (uint16_t*)d_out;
  for (int k = 0; k < 72; ++k) P.role[k] = role[k];
  P.zero = 0;
  P.mid = (char*)scratch->C;
  P.spare = nsm > 0 ? nsm - 128 : 0;
  fused_kernel<<<nsm > 0 ? nsm : 128, NTHR, SM_TOTAL, cudaStreamPerThread>>>(P, mW, mWo, mX);
}
```

```cpp
#include <cuda_runtime.h>
#include <cuda_bf16.h>
#include <cuda.h>
#include <stdint.h>
#include <stddef.h>

#define DEV __device__ __forceinline__
#define RARE(x) __builtin_expect(!!(x), 0)

constexpr int NTHR = 512;
constexpr int REG_MAIN = 192, REG_AUX = 88, REG_PROD = 40;
constexpr int NBARU = 384;
constexpr int SPIN_LIMIT = 1 << 22;

constexpr uint32_t SB = 1024;
__host__ __device__ constexpr uint32_t slot(int n) { return SB + n * 8192; }
__host__ __device__ constexpr int wslot(int k) { return k < 2 ? 3 * k : k < 4 ? 3 * k + 6 : k < 6 ? 21 - 3 * k : 3 * k - 18; }
constexpr uint32_t SM_A = slot(22), A_E = 0u - 32768;
constexpr uint32_t SM_O = slot(18), O_E = 0u - 147456;
constexpr uint32_t SM_WO = slot(10), SM_X = slot(8), SM_KV = slot(9) - 4096;
constexpr uint32_t SM_TAP  = slot(26);
constexpr int TAP_SZ = 3440;
constexpr uint32_t SM_STAT = SM_TAP + 4 * TAP_SZ;
constexpr uint32_t SM_CS   = SM_STAT + 1024;
constexpr uint32_t SM_BAR  = SM_CS + 768;
constexpr int SM_TOTAL = SM_BAR + 352 - SB;
static_assert(SM_TOTAL <= 232448, "");
constexpr int R_SZ = 16384, R_U = 512, R_X5 = 5120, R_X3 = 8704, R_BO = 11776, R_BE = 13824;
constexpr int X_5 = 576, X_3 = 648, T_E = 2 * 720, T_O = 1600 + 2 * 721, T_C = 3390, T_K = 3424;
constexpr uint32_t B_RD = SM_BAR, B_ED = SM_BAR + 16, B_F = SM_BAR + 32, B_AT = SM_BAR + 56, B_L = SM_BAR + 264;
constexpr uint32_t B_AE = SM_BAR + 72, B_QE = SM_BAR + 88, B_ST = SM_BAR + 96, B_CS = SM_BAR + 112;
constexpr uint32_t B_WO = SM_BAR + 120, B_W6 = SM_BAR + 128, B_U = SM_BAR + 144, B_E = SM_BAR + 152, B_WF = SM_BAR + 160, B_W4 = SM_BAR + 168,
                   B_N = SM_BAR + 176, B_V = SM_BAR + 184, B_O = SM_BAR + 192, B_Z = SM_BAR + 256, B_A = SM_BAR + 272;
constexpr int NB_U = 1, NB_B = 2, NB_K = 8, NB_Y = 6, NB_WG = 8, NB_T = 10, NB_AUX = 12, NB_P0 = 13, NB_H = 15;

struct Scratch {
  uint4    XG[2][128 * 1024];
  uint4    O[32 * 8 * 512];
  uint32_t C[8 * 32];
  uint32_t OF[2][32 * 32];
  uint4    CS[16 * 1536 / 4];
  uint4    PS[128 * 64];
  uint4    ST[2][32 * 128];
  uint4    SR[2][8][512];
  uint4    XF[2][32 * 512 * 8];
  uint4    H[2][17 * 8 * 256];
};
__device__ __align__(1024) Scratch g_S;
#define SCR ((Scratch*)(P.mid - offsetof(Scratch, C)))
#define PROFD(slot, v) do {} while (0)
#define PROF(slot) do {} while (0)
#define PROFK(slot) do {} while (0)

#define PROFC(slot) do {} while (0)

DEV uint32_t s2u(const void* p) { return (uint32_t)__cvta_generic_to_shared(p); }
template <class T> DEV T* opqp(T* x) { asm volatile("" : "+l"(x)); return x; }
template <class T> DEV T opq(T x) { asm volatile("" : "+r"(x)); return x; }
DEV int lane_id() { int l; asm volatile("mov.u32 %0,%%laneid;" : "=r"(l)); return l; }
DEV uint32_t pack2(float lo, float hi) { uint32_t d; asm("cvt.rn.bf16x2.f32 %0,%1,%2;" : "=r"(d) : "f"(hi), "f"(lo)); return d; }
DEV float bflo(uint32_t v) { return __uint_as_float(v << 16); }
DEV float bfhi(uint32_t v) { return __uint_as_float(v & 0xFFFF0000u); }
DEV float bfr(float x) { return bflo(pack2(x, 0.f)); }
DEV uint32_t hadd2(uint32_t a, uint32_t b) { uint32_t d; asm("add.rn.bf16x2 %0,%1,%2;" : "=r"(d) : "r"(a), "r"(b)); return d; }
DEV uint32_t hsub2(uint32_t a, uint32_t b) { uint32_t d; asm("sub.rn.bf16x2 %0,%1,%2;" : "=r"(d) : "r"(a), "r"(b)); return d; }
DEV uint32_t hmul2(uint32_t a, uint32_t b) { uint32_t d; asm("mul.rn.bf16x2 %0,%1,%2;" : "=r"(d) : "r"(a), "r"(b)); return d; }
DEV uint32_t hfma2(uint32_t a, uint32_t b, uint32_t c) { uint32_t d; asm("fma.rn.bf16x2 %0,%1,%2,%3;" : "=r"(d) : "r"(a), "r"(b), "r"(c)); return d; }
DEV uint32_t prmt(uint32_t a, uint32_t b, uint32_t s) { uint32_t d; asm("prmt.b32 %0,%1,%2,%3;" : "=r"(d) : "r"(a), "r"(b), "r"(s)); return d; }
DEV uint32_t nzmap(uint32_t v) { uint32_t d; asm("max.u32 %0,%1,1;" : "=r"(d) : "r"(v)); return d; }
DEV float rcp(float x) { float y; asm("rcp.approx.ftz.f32 %0,%1;" : "=f"(y) : "f"(x)); return y; }
DEV float sqrt_(float x) { float y; asm("sqrt.approx.ftz.f32 %0,%1;" : "=f"(y) : "f"(x)); return y; }
DEV float ex2(float x) { float y; asm("ex2.approx.ftz.f32 %0,%1;" : "=f"(y) : "f"(x)); return y; }

DEV uint4 ldr4(const void* p) { uint4 v; asm volatile("ld.relaxed.gpu.global.v4.u32 {%0,%1,%2,%3},[%4];" : "=r"(v.x), "=r"(v.y), "=r"(v.z), "=r"(v.w) : "l"(p) : "memory"); return v; }
DEV void ldr4_if(uint4& v, const void* p, bool c) {
  asm volatile("{.reg .pred q; setp.ne.u32 q,%5,0; @q ld.relaxed.gpu.global.v4.u32 {%0,%1,%2,%3},[%4];}"
    : "+r"(v.x), "+r"(v.y), "+r"(v.z), "+r"(v.w) : "l"(p), "r"((uint32_t)c) : "memory");
}
DEV uint2 ldr2(const void* p) { uint2 v; asm volatile("ld.relaxed.gpu.global.v2.u32 {%0,%1},[%2];" : "=r"(v.x), "=r"(v.y) : "l"(p) : "memory"); return v; }
DEV uint32_t ldr1(const void* p) { uint32_t v; asm volatile("ld.relaxed.gpu.global.u32 %0,[%1];" : "=r"(v) : "l"(p) : "memory"); return v; }
DEV float ldnan(const uint16_t* p) {
  uint32_t v = 0xFFFFu;
#pragma unroll 1
  for (int it = 0; it < SPIN_LIMIT && __any_sync(0xffffffffu, v == 0xFFFFu); ++it) asm volatile("ld.relaxed.gpu.global.u16 %0,[%1];" : "=r"(v) : "l"(p) : "memory");
  return __uint_as_float(v << 16);
}
DEV uint4 ldw4(const void* p) { uint4 v; asm volatile("ld.global.v4.u32 {%0,%1,%2,%3},[%4];" : "=r"(v.x), "=r"(v.y), "=r"(v.z), "=r"(v.w) : "l"(p) : "memory"); return v; }
DEV uint32_t ldw1(const void* p) { uint32_t v; asm volatile("ld.global.u32 %0,[%1];" : "=r"(v) : "l"(p) : "memory"); return v; }
DEV void str4(void* p, uint32_t a, uint32_t b, uint32_t c, uint32_t d) { asm volatile("st.relaxed.gpu.global.v4.u32 [%0],{%1,%2,%3,%4};" :: "l"(p), "r"(a), "r"(b), "r"(c), "r"(d) : "memory"); }
DEV void str2(void* p, uint32_t a, uint32_t b) { asm volatile("st.relaxed.gpu.global.v2.u32 [%0],{%1,%2};" :: "l"(p), "r"(a), "r"(b) : "memory"); }
DEV void str1(void* p, uint32_t a) { asm volatile("st.relaxed.gpu.global.u32 [%0],%1;" :: "l"(p), "r"(a) : "memory"); }
DEV void str4_if(void* p, uint32_t a, uint32_t b, uint32_t c, uint32_t d, bool q) {
  asm volatile("{.reg .pred q; setp.ne.u32 q,%5,0; @q st.relaxed.gpu.global.v4.u32 [%0],{%1,%2,%3,%4};}" :: "l"(p), "r"(a), "r"(b), "r"(c), "r"(d), "r"((uint32_t)q) : "memory");
}
DEV void stw4(void* p, uint32_t a, uint32_t b, uint32_t c, uint32_t d) { asm volatile("st.global.v4.u32 [%0],{%1,%2,%3,%4};" :: "l"(p), "r"(a), "r"(b), "r"(c), "r"(d) : "memory"); }
DEV uint4 ldnc4(const void* p) { uint4 v; asm volatile("ld.global.nc.v4.u32 {%0,%1,%2,%3},[%4];" : "=r"(v.x), "=r"(v.y), "=r"(v.z), "=r"(v.w) : "l"(p)); return v; }

DEV uint2 lds2(uint32_t a) { uint2 v; asm volatile("ld.volatile.shared.v2.u32 {%0,%1},[%2];" : "=r"(v.x), "=r"(v.y) : "r"(a)); return v; }
DEV void sts2(uint32_t a, uint32_t x, uint32_t y) { asm volatile("st.shared.v2.u32 [%0],{%1,%2};" :: "r"(a), "r"(x), "r"(y) : "memory"); }
DEV uint32_t lds1(uint32_t a) { uint32_t v; asm volatile("ld.volatile.shared.u32 %0,[%1];" : "=r"(v) : "r"(a)); return v; }
DEV uint32_t lds1z(uint32_t a, bool c) {
  uint32_t v; asm volatile("{.reg .pred q; setp.ne.u32 q,%2,0; mov.u32 %0,0; @q ld.volatile.shared.u32 %0,[%1];}" : "=r"(v) : "r"(a), "r"((uint32_t)c)); return v;
}
DEV uint4 lds4z(uint32_t a, bool c) {
  uint4 v = make_uint4(0, 0, 0, 0);
  asm volatile("{.reg .pred q; setp.ne.u32 q,%5,0; @q ld.volatile.shared.v4.u32 {%0,%1,%2,%3},[%4];}" : "+r"(v.x), "+r"(v.y), "+r"(v.z), "+r"(v.w) : "r"(a), "r"((uint32_t)c));
  return v;
}
DEV float2 lds2f(uint32_t a) { float2 v; asm volatile("ld.shared.v2.f32 {%0,%1},[%2];" : "=f"(v.x), "=f"(v.y) : "r"(a)); return v; }
DEV float4 lds4f(uint32_t a) { float4 v; asm volatile("ld.volatile.shared.v4.f32 {%0,%1,%2,%3},[%4];" : "=f"(v.x), "=f"(v.y), "=f"(v.z), "=f"(v.w) : "r"(a)); return v; }
DEV uint4 lds4(uint32_t a) { uint4 v; asm volatile("ld.volatile.shared.v4.u32 {%0,%1,%2,%3},[%4];" : "=r"(v.x), "=r"(v.y), "=r"(v.z), "=r"(v.w) : "r"(a)); return v; }
DEV void sts1(uint32_t a, uint32_t v) { asm volatile("st.shared.u32 [%0],%1;" :: "r"(a), "r"(v) : "memory"); }
DEV void sts16(uint32_t a, uint32_t v) { asm volatile("st.shared.u16 [%0],%1;" :: "r"(a), "r"(v) : "memory"); }
DEV void sts2f(uint32_t a, float x, float y) { asm volatile("st.shared.v2.f32 [%0],{%1,%2};" :: "r"(a), "f"(x), "f"(y) : "memory"); }
DEV void sts4f(uint32_t a, float x, float y, float z, float w) { asm volatile("st.shared.v4.f32 [%0],{%1,%2,%3,%4};" :: "r"(a), "f"(x), "f"(y), "f"(z), "f"(w) : "memory"); }
DEV void sts4(uint32_t a, uint32_t x, uint32_t y, uint32_t z, uint32_t w) { asm volatile("st.shared.v4.u32 [%0],{%1,%2,%3,%4};" :: "r"(a), "r"(x), "r"(y), "r"(z), "r"(w) : "memory"); }

DEV void ldsm4(uint32_t (&r)[4], uint32_t a) { asm volatile("ldmatrix.sync.aligned.m8n8.x4.shared.b16 {%0,%1,%2,%3},[%4];" : "=r"(r[0]), "=r"(r[1]), "=r"(r[2]), "=r"(r[3]) : "r"(a) : "memory"); }
DEV void ldsm4t(uint32_t (&r)[4], uint32_t a) { asm volatile("ldmatrix.sync.aligned.m8n8.x4.trans.shared.b16 {%0,%1,%2,%3},[%4];" : "=r"(r[0]), "=r"(r[1]), "=r"(r[2]), "=r"(r[3]) : "r"(a) : "memory"); }
DEV void stsm4(uint32_t a, uint32_t r0, uint32_t r1, uint32_t r2, uint32_t r3) { asm volatile("stmatrix.sync.aligned.m8n8.x4.shared.b16 [%0],{%1,%2,%3,%4};" :: "r"(a), "r"(r0), "r"(r1), "r"(r2), "r"(r3) : "memory"); }
DEV void stsm2(uint32_t a, uint32_t r0, uint32_t r1) { asm volatile("stmatrix.sync.aligned.m8n8.x2.shared.b16 [%0],{%1,%2};" :: "r"(a), "r"(r0), "r"(r1) : "memory"); }
DEV void stsm4t(uint32_t a, uint32_t r0, uint32_t r1, uint32_t r2, uint32_t r3) { asm volatile("stmatrix.sync.aligned.m8n8.x4.trans.shared.b16 [%0],{%1,%2,%3,%4};" :: "r"(a), "r"(r0), "r"(r1), "r"(r2), "r"(r3) : "memory"); }
DEV uint32_t movm(uint32_t a) { uint32_t d; asm volatile("movmatrix.sync.aligned.m8n8.trans.b16 %0,%1;" : "=r"(d) : "r"(a)); return d; }
DEV void mma16(float (&d)[4], uint32_t a0, uint32_t a1, uint32_t a2, uint32_t a3, uint32_t b0, uint32_t b1) {
  asm volatile("mma.sync.aligned.m16n8k16.row.col.f32.bf16.bf16.f32 {%0,%1,%2,%3},{%4,%5,%6,%7},{%8,%9},{%0,%1,%2,%3};"
    : "+f"(d[0]), "+f"(d[1]), "+f"(d[2]), "+f"(d[3]) : "r"(a0), "r"(a1), "r"(a2), "r"(a3), "r"(b0), "r"(b1));
}
DEV void mma16z(float (&d)[4], uint32_t a0, uint32_t a1, uint32_t a2, uint32_t a3, uint32_t b0, uint32_t b1) {
  asm volatile("mma.sync.aligned.m16n8k16.row.col.f32.bf16.bf16.f32 {%0,%1,%2,%3},{%4,%5,%6,%7},{%8,%9},{%10,%10,%10,%10};"
    : "=f"(d[0]), "=f"(d[1]), "=f"(d[2]), "=f"(d[3]) : "r"(a0), "r"(a1), "r"(a2), "r"(a3), "r"(b0), "r"(b1), "f"(0.f));
}
DEV void mma8(float (&d)[4], uint32_t a0, uint32_t a1, uint32_t b0) {
  asm volatile("mma.sync.aligned.m16n8k8.row.col.f32.bf16.bf16.f32 {%0,%1,%2,%3},{%4,%5},{%6},{%0,%1,%2,%3};"
    : "+f"(d[0]), "+f"(d[1]), "+f"(d[2]), "+f"(d[3]) : "r"(a0), "r"(a1), "r"(b0));
}

DEV void mma8z(float (&d)[4], uint32_t a0, uint32_t a1, uint32_t b0) {
  asm volatile("mma.sync.aligned.m16n8k8.row.col.f32.bf16.bf16.f32 {%0,%1,%2,%3},{%4,%5},{%6},{%7,%7,%7,%7};"
    : "=f"(d[0]), "=f"(d[1]), "=f"(d[2]), "=f"(d[3]) : "r"(a0), "r"(a1), "r"(b0), "f"(0.f));
}
DEV void bar_sync(int id, int n) { asm volatile("bar.sync %0,%1;" :: "r"(id), "r"(n) : "memory"); }
DEV void bar_sync_if(int id, int n, int c) { asm volatile("{.reg .pred q; setp.ne.s32 q,%2,0; @q bar.sync %0,%1;}" :: "r"(id), "r"(n), "r"(c) : "memory"); }
DEV void bar_arrive_if(int id, int n, int c) { asm volatile("{.reg .pred q; setp.ne.s32 q,%2,0; @q bar.arrive %0,%1;}" :: "r"(id), "r"(n), "r"(c) : "memory"); }
DEV void bar_arrive(int id, int n) { asm volatile("bar.arrive %0,%1;" :: "r"(id), "r"(n) : "memory"); }
DEV void fence_async_smem() { asm volatile("fence.proxy.async.shared::cta;" ::: "memory"); }
DEV void mbar_wait(uint32_t b, uint32_t ph) {
  asm volatile("{\n.reg .pred p;\nW: mbarrier.try_wait.parity.shared::cta.b64 p,[%0],%1;\n@!p bra W;\n}" :: "r"(b), "r"(ph) : "memory");
}
DEV void mbar_watch(uint32_t b, uint32_t ph) {
  asm volatile("{\n.reg .pred p,q;\n.reg .u32 n;\nmov.u32 n,0;\n"
               "W: mbarrier.try_wait.parity.shared::cta.b64 p,[%0],%1;\n@p bra D;\n"
               "add.u32 n,n,1;\nsetp.lt.u32 q,n,%2;\n@q bra W;\ntrap;\nD:\n}"
               :: "r"(b), "r"(ph), "n"(SPIN_LIMIT) : "memory");
}
DEV void spin_guard(int it) { asm volatile("{.reg .pred p; setp.gt.s32 p,%0,%1; @p trap;}" :: "r"(it), "n"(SPIN_LIMIT)); }
DEV void split(uint32_t zero) {
  asm volatile("{.reg .pred p; setp.ne.u32 p,%0,0; @p trap;}" :: "r"(zero) : "memory");
}
DEV void pause(int n) {
  uint32_t t0, t; asm volatile("mov.u32 %0,%%clock;" : "=r"(t0));
  do asm volatile("mov.u32 %0,%%clock;" : "=r"(t)); while (t - t0 < n);
}
DEV void poll(const uint32_t* k, uint32_t n) {
#pragma unroll 1
  for (int it = 0;; ++it) {
    spin_guard(it);
    if (__all_sync(0xffffffffu, ldr1(k) >= n)) break;
  }
}
DEV void mbar_arrive1(uint32_t b) { asm volatile("{.reg .pred p; elect.sync _|p,0xffffffff; @p mbarrier.arrive.shared::cta.b64 _,[%0];}" :: "r"(b) : "memory"); }
DEV void mbar_arrive1_if(uint32_t b, int c) {
  asm volatile("{.reg .pred p,q; setp.ne.s32 q,%1,0; elect.sync _|p,0xffffffff; and.pred p,p,q; @p mbarrier.arrive.shared::cta.b64 _,[%0];}" :: "r"(b), "r"(c) : "memory");
}
DEV void mbar_expect1(uint32_t b, int bytes) { asm volatile("{.reg .pred p; elect.sync _|p,0xffffffff; @p mbarrier.arrive.expect_tx.shared::cta.b64 _,[%0],%1;}" :: "r"(b), "r"(bytes) : "memory"); }
DEV void cnt_add1(uint32_t* q) { asm volatile("{.reg .pred p; elect.sync _|p,0xffffffff; @p red.relaxed.gpu.global.add.u32 [%0],1;}" :: "l"(q) : "memory"); }
DEV void tma4(uint32_t dst, const CUtensorMap* m, int c0, int c1, int c2, int c3, uint32_t bar) {
  asm volatile("{.reg .pred p; elect.sync _|p,0xffffffff;\n"
    "@p cp.async.bulk.tensor.4d.shared::cluster.global.mbarrier::complete_tx::bytes [%0],[%1,{%2,%3,%4,%5}],[%6];}"
    :: "r"(dst), "l"(m), "r"(c0), "r"(c1), "r"(c2), "r"(c3), "r"(bar) : "memory");
}
DEV void tma3(uint32_t dst, const CUtensorMap* m, int c0, int c1, int c2, uint32_t bar) {
  asm volatile("{.reg .pred p; elect.sync _|p,0xffffffff;\n"
    "@p cp.async.bulk.tensor.3d.shared::cluster.global.mbarrier::complete_tx::bytes [%0],[%1,{%2,%3,%4}],[%5];}"
    :: "r"(dst), "l"(m), "r"(c0), "r"(c1), "r"(c2), "r"(bar) : "memory");
}
DEV void bulk(uint32_t dst, const void* src, int bytes, uint32_t bar) {
  asm volatile("{.reg .pred p; elect.sync _|p,0xffffffff;\n@p cp.async.bulk.shared::cluster.global.mbarrier::complete_tx::bytes [%0],[%1],%2,[%3];}" :: "r"(dst), "l"(src), "r"(bytes), "r"(bar) : "memory");
}

DEV void bulk_store(void* dst, uint32_t src, int bytes) {
  asm volatile("{.reg .pred p; elect.sync _|p,0xffffffff;\n@p cp.async.bulk.global.shared::cta.bulk_group [%0],[%1],%2;}" :: "l"(dst), "r"(src), "r"(bytes) : "memory");
}
DEV void tma2_store(const CUtensorMap* m, uint32_t src, int c0, int c1) {
  asm volatile("{.reg .pred p; elect.sync _|p,0xffffffff;\n@p cp.async.bulk.tensor.2d.global.shared::cta.bulk_group [%0,{%2,%3}],[%1];}" :: "l"(m), "r"(src), "r"(c0), "r"(c1) : "memory");
}
DEV void bulk_wait() { asm volatile("cp.async.bulk.commit_group;\ncp.async.bulk.wait_group 0;\nfence.proxy.async.global;" ::: "memory"); }

DEV uint32_t dlo(uint32_t addr, uint32_t lbo) { return __shfl_sync(0xffffffffu, (addr >> 4) | ((lbo >> 4) << 16), 0); }
__host__ __device__ constexpr uint32_t dhi(uint32_t sbo, uint32_t swz) { return (sbo >> 4) | (swz << 30); }
DEV void wg_fence() { asm volatile("wgmma.fence.sync.aligned;" ::: "memory"); }
DEV void wg_commit() { asm volatile("wgmma.commit_group.sync.aligned;" ::: "memory"); }
template <int N> DEV void wg_wait() { asm volatile("wgmma.wait_group.sync.aligned %0;" :: "n"(N) : "memory"); }
template <int N> DEV void zero(float (&d)[N]) {
#pragma unroll
  for (int i = 0; i < N; ++i) d[i] = 0.f;
}
template <int N> DEV void zerov(float (&d)[N]) {
#pragma unroll
  for (int i = 0; i < N; ++i) asm volatile("mov.b32 %0,0;" : "=f"(d[i]));
}
template <int N> DEV void undef(float (&d)[N]) {
#pragma unroll
  for (int i = 0; i < N; ++i) asm volatile("" : "=f"(d[i]));
}
#define R4(d, o) "+f"(d[o]), "+f"(d[o + 1]), "+f"(d[o + 2]), "+f"(d[o + 3])
#define R8(d, o) R4(d, o), R4(d, o + 4)
#define R16(d, o) R8(d, o), R8(d, o + 8)
template <int ACC> DEV void wg_rs64k(float (&d)[32], const uint32_t (&a)[4], uint32_t db) {
  asm volatile("{.reg .pred p; .reg .b64 b; setp.ne.s32 p,%38,0; mov.b64 b,{%36,%37};\n"
    "wgmma.mma_async.sync.aligned.m64n64k16.f32.bf16.bf16 {%0,%1,%2,%3,%4,%5,%6,%7,%8,%9,%10,%11,%12,%13,%14,%15,%16,%17,%18,%19,%20,%21,%22,%23,%24,%25,%26,%27,%28,%29,%30,%31},{%32,%33,%34,%35},b,p,1,1,0;}"
    : R16(d, 0), R16(d, 16) : "r"(a[0]), "r"(a[1]), "r"(a[2]), "r"(a[3]), "r"(db), "n"(dhi(512, 2)), "n"(ACC));
}
template <int ACC> DEV void wg_rs48t(float (&d)[24], const uint32_t (&a)[4], uint32_t db) {
  asm volatile("{.reg .pred p; .reg .b64 b; setp.ne.s32 p,%30,0; mov.b64 b,{%28,%29};\n"
    "wgmma.mma_async.sync.aligned.m64n48k16.f32.bf16.bf16 {%0,%1,%2,%3,%4,%5,%6,%7,%8,%9,%10,%11,%12,%13,%14,%15,%16,%17,%18,%19,%20,%21,%22,%23},{%24,%25,%26,%27},b,p,1,1,1;}"
    : R16(d, 0), R8(d, 16) : "r"(a[0]), "r"(a[1]), "r"(a[2]), "r"(a[3]), "r"(db), "n"(dhi(512, 0)), "n"(ACC));
}
template <int ACC> DEV void wg_rs32t(float (&d)[16], const uint32_t (&a)[4], uint32_t db) {
  asm volatile("{.reg .pred p; .reg .b64 b; setp.ne.s32 p,%22,0; mov.b64 b,{%20,%21};\n"
    "wgmma.mma_async.sync.aligned.m64n32k16.f32.bf16.bf16 {%0,%1,%2,%3,%4,%5,%6,%7,%8,%9,%10,%11,%12,%13,%14,%15},{%16,%17,%18,%19},b,p,1,1,1;}"
    : R16(d, 0) : "r"(a[0]), "r"(a[1]), "r"(a[2]), "r"(a[3]), "r"(db), "n"(dhi(1024, 0)), "n"(ACC));
}
template <int ACC> DEV void wg_ss192(float (&d)[96], uint32_t da, uint32_t db) {
  asm volatile("{.reg .pred p; .reg .b64 a,b; setp.ne.s32 p,%100,0; mov.b64 a,{%96,%98}; mov.b64 b,{%97,%99};\n"
    "wgmma.mma_async.sync.aligned.m64n192k16.f32.bf16.bf16 {"
    "%0,%1,%2,%3,%4,%5,%6,%7,%8,%9,%10,%11,%12,%13,%14,%15,%16,%17,%18,%19,%20,%21,%22,%23,%24,%25,%26,%27,%28,%29,%30,%31,"
    "%32,%33,%34,%35,%36,%37,%38,%39,%40,%41,%42,%43,%44,%45,%46,%47,%48,%49,%50,%51,%52,%53,%54,%55,%56,%57,%58,%59,%60,%61,%62,%63,"
    "%64,%65,%66,%67,%68,%69,%70,%71,%72,%73,%74,%75,%76,%77,%78,%79,%80,%81,%82,%83,%84,%85,%86,%87,%88,%89,%90,%91,%92,%93,%94,%95},a,b,p,1,1,1,1;}"
    : R16(d, 0), R16(d, 16), R16(d, 32), R16(d, 48), R16(d, 64), R16(d, 80) : "r"(da), "r"(db), "n"(dhi(1024, 1)), "n"(dhi(1024, 1)), "n"(ACC));
}
template <int ACC> DEV void wg_ss64(float (&d)[32], uint32_t da, uint32_t db) {
  asm volatile("{.reg .pred p; .reg .b64 a,b; setp.ne.s32 p,%36,0; mov.b64 a,{%32,%34}; mov.b64 b,{%33,%35};\n"
    "wgmma.mma_async.sync.aligned.m64n64k16.f32.bf16.bf16 {"
    "%0,%1,%2,%3,%4,%5,%6,%7,%8,%9,%10,%11,%12,%13,%14,%15,%16,%17,%18,%19,%20,%21,%22,%23,%24,%25,%26,%27,%28,%29,%30,%31},a,b,p,1,1,0,1;}"
    : R16(d, 0), R16(d, 16) : "r"(da), "r"(db), "n"(dhi(1024, 0)), "n"(dhi(1024, 1)), "n"(ACC));
}

DEV uint32_t cpy(uint32_t v, uint32_t id) {
  uint32_t d; asm volatile("prmt.b32 %0,%1,%1,%2;" : "=r"(d) : "r"(v), "r"(id)); return d;
}
struct Params {
  uint32_t zero, spare;
  char* mid;
  const uint16_t *x0, *Are, *Aim, *Bre, *Bim, *Cre, *Cim, *logdt, *dskip, *wqkv, *wo;
  uint16_t* out;
  uint8_t role[72];
};

DEV uint32_t ln_word(float mean, float var) {
  float v = bfr(var);
  float s = sqrt_(bfr(v + 1e-5f));
  return pack2(mean, s);
}

DEV int stat_group(int c) { return c ^ 4; }
DEV int xg_off(int G, int g) { return (G >> 5) * 512 + (G & 31) * 8 + (g ^ (G & 2)); }
DEV int sr_off(int G, int g) { return (G >> 6) * 256 + (g & 2) * 64 + 2 * (G & 63) + ((g >> 2) & 1); }
DEV uint32_t region(int chl) { return SM_A + (chl >> 1) * A_E + (chl & 1) * R_SZ; }
template <bool FIRST> DEV void gram(float (&s)[4], float (&q0)[4], float (&q1)[4], uint32_t a0, uint32_t a1, uint32_t a2, uint32_t a3) {
  const uint32_t one = 0x3F803F80u;
  if (FIRST) { mma16z(s, a0, a1, a2, a3, one, one); mma8z(q0, a0, a1, a0); mma8z(q1, a0, a1, a1); }
  else { mma16(s, a0, a1, a2, a3, one, one); mma8(q0, a0, a1, a0); mma8(q1, a0, a1, a1); }
  mma8(q0, a2, a3, a2); mma8(q1, a2, a3, a3);
}
DEV uint32_t ln_sums(float s, float q) { const float m = s * (1.f / 512.f); return ln_word(m, fmaxf(q * (1.f / 512.f) - m * m, 0.f)); }
DEV void cmul(float& orr, float& oi, float ar, float ai, float br, float bi) {
  float r = ar * br - ai * bi, i = ar * bi + ai * br; orr = r; oi = i;
}
DEV void cexp_(float al, float bt, float s, float& er, float& ei) {
  float mag = ex2(al * s), ph = bt * s;
  ph -= rintf(ph);
  float ang = ph * 6.283185307179586f;
  er = mag * __cosf(ang); ei = mag * __sinf(ang);
}

DEV void kgen(const Params& P, int c, int wm, int lane) {
  const int chl = wm >> 1, mh = wm & 1, g = lane >> 2, t = lane & 3;
  const int ch = 256 * (chl >> 1) + 2 * c + (chl & 1);
  const int mo = ch * 64 + mh * 32 + lane;
  const uint32_t vAr = ldw1((const uint32_t*)P.Are + mo), vAi = ldw1((const uint32_t*)P.Aim + mo);
  const uint32_t vBr = ldw1((const uint32_t*)P.Bre + mo), vBi = ldw1((const uint32_t*)P.Bim + mo);
  const uint32_t vCr = ldw1((const uint32_t*)P.Cre + mo), vCi = ldw1((const uint32_t*)P.Cim + mo);
  const uint32_t vld = ldw1((const uint32_t*)P.logdt + (ch >> 1)), vds = ldw1((const uint32_t*)P.dskip + (ch >> 1));
  bar_arrive(NB_Y, 384);
  PROF(45);
  {
    const uint32_t tz = SM_TAP + chl * TAP_SZ + (mh * 32 + lane) * 16;
#pragma unroll
    for (int k = 0; k < 3; ++k) sts4(tz + k * 1024, 0, 0, 0, 0);
    static_assert(TAP_SZ > 3072 && TAP_SZ <= 4096, "");
    if (mh * 32 + lane < TAP_SZ / 16 - 192) sts4(tz + 3072, 0, 0, 0, 0);
  }
  const uint32_t tb = slot(wm), tw = opq(tb + lane * 4);
  const uint32_t aa = opq(tb + (lane & 15) * 144 + (lane >> 4) * 16), ba = opq(tb + (16 + (lane & 7)) * 144 + (lane >> 3) * 16);
  float acc[5][4], k2048 = 0.f;
#pragma unroll
  for (int i = 0; i < 5; ++i) zerov(acc[i]);
  sts1(tw, 0x3F80u);
  asm volatile("setmaxnreg.inc.sync.aligned.u32 %0;" :: "n"(REG_MAIN));
  PROF(44);
  const float dt = bfr(ex2((ch & 1 ? bfhi(vld) : bflo(vld)) * 1.4426950408889634f));
#pragma unroll 1
  for (int r = 0; r < 2; ++r) {
    const uint32_t sel = r ? 0x3244 : 0x1044;
    const float are = __uint_as_float(prmt(vAr, 0, sel)), aim = __uint_as_float(prmt(vAi, 0, sel)), bre = __uint_as_float(prmt(vBr, 0, sel));
    const float bim = __uint_as_float(prmt(vBi, 0, sel)), cre = __uint_as_float(prmt(vCr, 0, sel)), cim = __uint_as_float(prmt(vCi, 0, sel));
    const float al = dt * are * 1.4426950408889634f, bt = dt * aim * 0.15915494309189535f;
    float qr, qi; cmul(qr, qi, cre, cim, dt * bre, dt * bim);
    if (r == 0) PROFD(2, __float_as_uint(qr + al + bt));
    float er[3], ei[3], e8r, e8i, eLr, eLi;
    cexp_(al, bt, 1.f, er[0], ei[0]); cexp_(al, -bt, 8.f, e8r, e8i); cexp_(al, bt, 128.f, eLr, eLi);
    cmul(er[1], ei[1], er[0], ei[0], er[0], ei[0]); cmul(er[2], ei[2], er[1], ei[1], er[1], ei[1]);
    float yr = e8r, yi = e8i;
#pragma unroll
    for (int a = 0; a < 16; ++a) {
      if (a) sts1(tw + a * 144, pack2(yr, yi));
      if (a && a < 15) cmul(yr, yi, yr, yi, e8r, e8i);
      const int ls = a < 2 ? 0 : a < 4 ? 1 : a < 8 ? 2 : 3;
      const int row0 = 16 + (a < 2 ? 8 * a : a < 4 ? 16 + 4 * (a - 2) : a < 8 ? 24 + 2 * (a - 4) : 32 + (a - 8));
      float xr[8], xi[8];
      xr[0] = qr; xi[0] = qi;
#pragma unroll
      for (int k = 0; k < (8 >> ls); ++k) {
        const int hb = k >= 4 ? 2 : k >= 2 ? 1 : 0;
        if (k) cmul(xr[k], xi[k], xr[k - (1 << hb)], xi[k - (1 << hb)], er[(ls + hb) % 3], ei[(ls + hb) % 3]);
        sts1(tw + (row0 + k) * 144, pack2(xr[k], xi[k]));
      }
      cmul(qr, qi, qr, qi, eLr, eLi);
    }
    __syncwarp();
    if (r == 0) PROF(3);
#pragma unroll
    for (int kp = 0; kp < 2; ++kp) {
      uint32_t a0[4], a1[4];
      ldsm4(a0, aa + kp * 64); ldsm4(a1, aa + kp * 64 + 32);
#pragma unroll
      for (int tl = 0; tl < 5; ++tl) {
        uint32_t b[4];
        ldsm4(b, ba + 8 * tl * 144 + kp * 64);
        if (kp == 0) qr += __shfl_xor_sync(0xffffffffu, qr, 1 << tl);
        mma16(acc[tl], a0[0], a0[1], a0[2], a0[3], b[0], b[1]);
        mma16(acc[tl], a1[0], a1[1], a1[2], a1[3], b[2], b[3]);
      }
    }
    k2048 += qr;
    __syncwarp();
  }
  const uint32_t xa = tb + lane * 16, ob = xa ^ 8192, tp = SM_TAP + chl * TAP_SZ;
  if (mh == 0) {
    sts4f(xa, acc[2][0], acc[2][1], acc[2][2], acc[2][3]);
    sts4f(xa + 512, acc[3][0], acc[3][1], acc[3][2], acc[3][3]);
    sts1(tb + 1024, __float_as_uint(k2048));
  } else {
    sts4f(xa, acc[0][0], acc[0][1], acc[0][2], acc[0][3]);
    sts4f(xa + 512, acc[1][0], acc[1][1], acc[1][2], acc[1][3]);
    sts4f(xa + 1024, acc[4][0], acc[4][1], acc[4][2], acc[4][3]);
  }
  PROF(4);
  bar_sync(NB_K + chl, 64);
  float4 o[3];
#pragma unroll
  for (int k = 0; k < 3; ++k) o[k] = lds4f(ob + k * 512);
  if (mh == 0) {
    if (lane == 0) o[0].x += ch & 1 ? bfhi(vds) : bflo(vds);
    const uint32_t a = tp - 2 * (8 * g + 2 * t + 1);
#pragma unroll
    for (int z = 0; z < 4; ++z) {
      const float* k = acc[z >> 1] + 2 * (z & 1);
      const uint32_t v = z & 1 ? pack2(k[1] + o[z >> 1].w, k[0] + o[z >> 1].z) : pack2(k[1] + o[z >> 1].y, k[0] + o[z >> 1].x);
      sts1(a + T_O - 128 * z, v); sts16(a + T_E - 128 * z, v); sts16(a + T_E + 2 - 128 * z, v >> 16);
    }
    const uint32_t v0 = pack2(acc[4][0] + o[2].x, acc[4][1] + o[2].y), v1 = pack2(acc[4][2] + o[2].z, acc[4][3] + o[2].w);
    const uint32_t b = tp + T_C - 2 * (32 * t + g - 1);
    if (lane == 0) { sts16(tp + T_E - 2 * (X_5 + 63), v0); sts16(tp + T_O - 2 * (X_5 + 63), v0); sts1(tp + T_K, prmt(v0, v0, 0x1010)); }
    else sts16(b, v0);
    sts16(b - 32, v0 >> 16); sts16(b - 16, v1); sts16(b - 48, v1 >> 16);
  } else {
    const uint32_t a = tp - 2 * (256 + 128 * (t >> 1) + 4 * (t & 1) + 8 * g);
#pragma unroll
    for (int z = 0; z < 2; ++z) {
      const uint32_t v = z ? pack2(acc[2][3] + o[0].w, acc[2][2] + o[0].z) : pack2(acc[2][1] + o[0].y, acc[2][0] + o[0].x), d = prmt(v, v, 0x3232);
      sts1(a + T_E - 4 - 128 * z, v); sts16(a + T_O - 4 - 128 * z, v); sts1(a + T_O - 2 - 128 * z, d);
      if (z || lane) { sts1(a + T_E - 128 * z, d); sts16(a + T_O + 2 - 128 * z, d); } else sts16(a + T_E, d);
    }
    const uint32_t w0 = pack2(acc[3][0] + o[1].x, acc[3][1] + o[1].y), w1 = pack2(acc[3][2] + o[1].z, acc[3][3] + o[1].w);
    const uint32_t b = tp - 2 * (16 * t + g);
    if (lane == 0) {
      const uint32_t k = prmt(w0, w0, 0x1010);
      sts1(tp + T_E - 2 * 514, k); sts1(tp + T_E - 2 * 512, k);
      sts16(tp + T_O - 2 * 514, k); sts1(tp + T_O - 2 * 513, k); sts16(tp + T_O - 2 * 511, k);
      sts16(tp + T_C - 2 * 127, pack2(k2048 + o[2].x, 0.f));
    } else { sts16(b + T_E - 2 * (X_5 - 1), w0); sts16(b + T_O - 2 * (X_5 - 1), w0); }
    sts16(b + T_E - 2 * X_3, w0 >> 16); sts16(b + T_O - 2 * X_3, w0 >> 16);
    sts16(b + T_E - 2 * (X_5 + 7), w1); sts16(b + T_O - 2 * (X_5 + 7), w1);
    sts16(b + T_E - 2 * (X_3 + 8), w1 >> 16); sts16(b + T_O - 2 * (X_3 + 8), w1 >> 16);
  }
}

DEV bool bad8(const uint4& v) { return min(v.x, v.z) == 0u; }
DEV uint32_t uchunk(uint32_t reg, int x) { return reg + R_U + (x ^ ((x >> 3) & 3)) * 16; }
DEV uint32_t& xword(uint4 (&x)[2], int e, int tp) { uint4& v = x[tp >> 1]; return tp & 1 ? (e ? v.w : v.z) : (e ? v.y : v.x); }

DEV void uprep(const Params& P, int c, int wa, int lane, int layer, uint4 (&x)[2][2][2], uint32_t (&u)[4][4]) {
  const int j = 32 * wa + lane, o0 = 2 * (j + (j & 64)) + ((j >> 2) & 1);
  {
    const uint32_t za = region(wa) + lane * 16 - 512;
    sts4(za + R_U, 0, 0, 0, 0); sts4(za + R_X5, 0, 0, 0, 0); sts4(za + R_X3, 0, 0, 0, 0);
    sts4(region(wa) + R_BE, 0, 0, 0, 0);
  }
  const uint4* st = opqp(&SCR->SR[layer][c >> 4][j]);
  const uint32_t xa = opq(SM_X + 16 * o0), xb = opq(SM_X + 16 * (o0 ^ 1)), ua = opq(uchunk(0, j));
  uint4 s[2][2];
#pragma unroll
  for (int z = 0; z < 12; ++z) {
    uint4& v = z < 8 ? x[(z >> 2) & 1][(z >> 1) & 1][z & 1] : s[(z >> 1) & 1][z & 1];
    asm volatile("mov.b32 %0,0; mov.b32 %1,0; mov.b32 %2,0; mov.b32 %3,0;" : "=r"(v.x), "=r"(v.y), "=r"(v.z), "=r"(v.w));
  }
#pragma unroll 1
  for (uint32_t it = P.zero;; ++it) {
    if (it) {
      spin_guard(it);
#pragma unroll
      for (int z = 0; z < 4; ++z) { uint4& v = s[z >> 1][z & 1]; ldr4_if(v, st + z * 128, bad8(v)); }
      const uint4* xp = &SCR->XG[layer][c * 1024 + o0];
#pragma unroll
      for (int z = 0; z < 8; ++z) {
        uint4& v = x[z >> 2][(z >> 1) & 1][z & 1];
        ldr4_if(v, (const uint4*)((uintptr_t)xp ^ (16 * (z & 1))) + (z >> 2) * 512 + (z & 2) * 64, bad8(v));
      }
    } else {
      mbar_wait(B_U, layer);
      PROF(layer ? 25 : 10);
#pragma unroll
      for (int z = 0; z < 4; ++z) s[z >> 1][z & 1] = ldr4(st + z * 128);
#pragma unroll
      for (int z = 0; z < 4; ++z) { uint4& v = s[z >> 1][z & 1]; ldr4_if(v, st + z * 128, bad8(v)); }
      PROF(layer ? 26 : 11);
      mbar_wait(B_E, layer);
#pragma unroll
      for (int z = 7; z >= 0; --z) x[z >> 2][(z >> 1) & 1][z & 1] = lds4((z & 1 ? xb : xa) + (z >> 2) * 8192 + (z & 2) * 1024);
      PROF(layer ? 27 : 14);
    }
    uint32_t m = ~0u;
#pragma unroll
    for (int z = 7; z >= 0; --z) {
      const int k = z >> 2, chl = z & 3;
#pragma unroll
      for (int tp = 0; tp < 4; ++tp) u[chl][tp] = hmul2(hsub2(xword(x[k][chl >> 1], chl & 1, tp), xword(s[k], 1, tp)), xword(s[k], 0, tp));
      sts4(ua + region(chl) + k * 2048, u[chl][0], u[chl][1], u[chl][2], u[chl][3]);
      const uint4& v = x[k][chl >> 1][chl & 1];
      m = min(m, min(v.x, v.z));
      if (z < 4) m = min(m, min(s[z >> 1][z & 1].x, s[z >> 1][z & 1].z));
    }
    if (!__any_sync(0xffffffffu, m == 0)) break;
  }
  PROF(4 + 12 * layer);
}

template <bool FULL> DEV void box_unit(uint32_t reg, int s, const uint2& a, const uint4& b, const uint32_t (&d)[4], uint32_t (&pv)[4]) {
  const uint32_t u[9] = {a.x, a.y, b.x, b.y, b.z, b.w, d[0], d[1], d[2]};
  uint32_t v[8], p[8];
#pragma unroll
  for (int j = 0; j < 8; ++j) { v[j] = prmt(u[j], u[j + 1], 0x5432); p[j] = hadd2(u[j], v[j]); }
  const uint32_t o = reg + s * 16;
  uint32_t x[4], y[4];
#pragma unroll
  for (int j = 0; j < 4; ++j) { x[j] = hadd2(hadd2(p[1 + j], p[2 + j]), u[3 + j]); y[j] = hadd2(v[3 + j], p[4 + j]); pv[j] = p[4 + j]; }
  sts4(o + R_X5, x[0], x[1], x[2], x[3]);
  sts4(o + R_X3, y[0], y[1], y[2], y[3]);
  if (FULL) {
#pragma unroll
    for (int j = 0; j < 4; ++j) { y[j] = hadd2(hadd2(v[j], v[3 + j]), x[j]); x[j] = hadd2(hadd2(u[j], u[4 + j]), y[j]); }
    const bool od = s & 1;
    sts4(o + R_BO, od ? y[0] : x[0], od ? y[1] : x[1], od ? y[2] : x[2], od ? y[3] : x[3]);
    sts4(o + R_BE + 16, od ? x[0] : y[0], od ? x[1] : y[1], od ? x[2] : y[2], od ? x[3] : y[3]);
  }
}
#define NBB(e) (320 - 32 * (e))
template <int C0, int C1> DEV void box_full(int j, uint32_t (&u)[4][4], uint32_t zero) {
  const uint32_t a2 = uchunk(8, j - 2), a1 = uchunk(0, j - 1);
  uint2 a[4]; uint4 b[4];
#define HALO(n) if (n < C1) { a[(n) & 3] = lds2(region(n) + a2); b[(n) & 3] = lds4(region(n) + a1); }
  HALO(C0) HALO(C0 + 1)
  split(zero);
#pragma unroll
  for (int chl = C0; chl < C1; ++chl) {
    const uint32_t d[4] = {u[chl][0], u[chl][1], u[chl][2], u[chl][3]};
    box_unit<true>(region(chl), j, a[chl], b[chl], d, u[chl]);
    fence_async_smem();
    bar_arrive(NB_B + chl, NBB(chl & 1));
    PROFC(28 + chl);
    if (chl == C0) { HALO(C0 + 2) }
  }
#undef HALO
}
DEV void box_help(int e, int n0, int dn, int lane, int layer) {
  bar_sync(NB_H, 224);
#pragma unroll 1
  for (int n = n0; n < 4; n += dn) {
    if (n == 2 && dn == 1) mbar_watch(B_RD, layer);
    const int chl = e + (n & 2), s = 128 + 32 * (n & 1) + lane;
    const uint32_t reg = region(chl);
    const uint4 d = lds4(uchunk(reg, s));
    const uint32_t u[4] = {d.x, d.y, d.z, d.w};
    uint32_t v[4];
    box_unit<false>(reg, s, lds2(uchunk(reg, s - 2) + 8), lds4(uchunk(reg, s - 1)), u, v);
    if (dn == 2 || (n & 1)) { fence_async_smem(); bar_arrive(NB_B + chl, NBB(e)); PROFC(28 + n); }
  }
}

DEV uint4 hadd8(const uint4& a, const uint4& b) { return make_uint4(hadd2(a.x, b.x), hadd2(a.y, b.y), hadd2(a.z, b.z), hadd2(a.w, b.w)); }
DEV void conv_out(int c, int j, int chl, uint4 (&x)[2][2][2], const uint32_t (&v)[4], uint4* XF, uint32_t zero) {
  const int rho = chl >> 1, e = chl & 1;
  const uint32_t ua = uchunk(region(chl), j), fa = region(chl) + R_X5 + j * 16, ha = region(chl) + R_X3 + (j & 1) * 1088 + (j >> 1) * 16;
  const int m8 = ((j & 4) + ((j >> 1) & 1) + 2 * (j & 1)) ^ ((2 * c + e) & 7);
  uint4* xo = XF + (((16 - 2 * (j & 8) + (j >> 4)) * 512 + 256 * rho + 2 * c + e) * 8 + m8);
  bar_sync(NB_Y + e + 7 * rho, 256);
  uint4 y[2], f[2], h[2];
#pragma unroll
  for (int k = 0; k < 2; ++k) {
    y[k] = lds4(ua + k * 2048);
    f[k] = lds4z(ua + k * 2048 + R_BO - R_U, k || j >= 36);
    h[k] = lds4z(fa + k * 2048 - 1024, k || j >= 64);
  }
  const uint32_t q = lds1(SM_TAP + chl * TAP_SZ + T_K);
  const uint4 r = lds4(ha);
  split(zero);
  if (chl == 3) mbar_arrive1(B_L + (r.x & zero));
  h[1] = hadd8(h[1], make_uint4(hfma2(q, v[0], r.x), hfma2(q, v[1], r.y), hfma2(q, v[2], r.z), hfma2(q, v[3], r.w)));
#pragma unroll
  for (int k = 0; k < 2; ++k) {
    const uint4 o = hadd8(hadd8(y[k], hadd8(f[k], h[k])), make_uint4(xword(x[k][rho], e, 0), xword(x[k][rho], e, 1), xword(x[k][rho], e, 2), xword(x[k][rho], e, 3)));
    const uint32_t keep = j & 1 ? 0x7632 : 0x5410, k0 = prmt(o.x, o.y, keep), k1 = prmt(o.z, o.w, keep);
    const uint32_t g0 = __shfl_xor_sync(0xffffffffu, prmt(o.x, o.y, keep ^ 0x2222), 1), g1 = __shfl_xor_sync(0xffffffffu, prmt(o.z, o.w, keep ^ 0x2222), 1);
    str4(xo + k * 32768, j & 1 ? g0 : k0, j & 1 ? g1 : k1, j & 1 ? k0 : g0, j & 1 ? k1 : g1);

  }
  if (e) { __syncwarp(); mbar_arrive1(B_RD + rho * 8); }
  PROFC(40 + chl);
}

DEV void conv_round(int e, int rho, int w, int lane) {
  const int g = lane >> 2, t = lane & 3, chl = 2 * rho + e;
  const uint32_t reg = region(chl), tp = SM_TAP + chl * TAP_SZ, dr = dlo(reg, 128);
  const uint32_t g0 = tp + ((g & 1) ? T_O : T_E) + 2 * (2 * t - g) - 16;
  const uint32_t ga = g0 - 32 * (w & 1) - 576 * (w >> 1), id = opq(0x3210u);
  float acc[32], f1[24], f2[16];
  uint32_t q[12][4];
  {
    uint32_t qn[18][4];
    qn[0][2] = lds1(ga + 64);
#pragma unroll
    for (int n = 0; n < 18; ++n) {
      const bool nz = n < 15 || w < 2 || (n == 15 && w == 2);
      qn[n][0] = n < 15 ? lds1(ga + 48 - 32 * n) : lds1z(ga + 48 - 32 * n, nz);
      qn[n][1] = n < 15 ? lds1(ga + 32 - 32 * n) : lds1z(ga + 32 - 32 * n, nz);
    }
#pragma unroll
    for (int n = 0; n < 18; ++n) { qn[n][3] = cpy(qn[n][0], id); if (n) qn[n][2] = cpy(qn[n - 1][1], id); }
#pragma unroll
    for (int n = 0; n < 8; ++n) {
      const int i = n & 3;
      const uint32_t a = g0 + 16 - 16 * w - 2 * (n < 4 ? X_5 : X_3) + 16 * i;
      uint32_t (&q1)[4] = q[(n & 4) + (i >> 1)], (&q2)[4] = q[(n & 4) + 2 + (i >> 1)];
      q1[2 * (i & 1)] = lds1z(a, i <= w); q1[2 * (i & 1) + 1] = lds1(a - 64);
      q2[2 * (i & 1)] = cpy(0, id); q2[2 * (i & 1) + 1] = lds1z(a - 128, i >= w);
    }
    const uint32_t gc = tp + T_C - 2 + 4 * (t - g - 8 * w);
#pragma unroll
    for (int kk = 0; kk < 4; ++kk) {
      q[8 + kk][0] = lds1z(gc + 32 * kk, w >= kk); q[8 + kk][2] = lds1z(gc + 32 * kk + 16, w >= kk);
      q[8 + kk][1] = lds1(gc + 32 * kk - 128); q[8 + kk][3] = lds1(gc + 32 * kk - 112);
    }
    PROFD(rho ? 43 : 47, qn[17][2] ^ q[11][3]);
    bar_sync_if(NB_U, NBARU, 1 - rho);
    mbar_arrive1_if(B_V, chl == 1 && w == 0);
    bar_sync_if(NB_T + 1 - e, 256, chl);
    const uint32_t db = dr + (R_U + 32) / 16;
    undef(acc);
    wg_fence();
#pragma unroll
    for (int n = 0; n < 18; ++n) {
      if (n) wg_rs64k<1>(acc, qn[n], db - 2 * n); else wg_rs64k<0>(acc, qn[0], db);
      if (n == 9) wg_commit();
    }
    wg_commit();
  }
  wg_wait<1>();
  PROFC(rho ? 12 : 2);
  bar_sync(NB_B + chl, NBB(e));
  const uint32_t d1 = dr + R_X5 / 16, d2 = dr + R_BO / 16;
  undef(f1); undef(f2);
  wg_fence();
#pragma unroll
  for (int n = 0; n < 4; ++n) { if (n) wg_rs32t<1>(f2, q[8 + n], d2 + 16 * n); else wg_rs32t<0>(f2, q[8], d2); }
  wg_commit();
#pragma unroll
  for (int n = 0; n < 8; ++n) {
    const uint32_t d = d1 + (n >> 2) * ((R_X3 - R_X5) / 16) + 16 * (n & 1) - 16 * (n & 2);
    if (n) wg_rs48t<1>(f1, q[n], d); else wg_rs48t<0>(f1, q[0], d);
  }
  wg_commit();
  wg_wait<1>();
  PROFC(rho ? 13 : 3);
  bar_arrive_if(NB_T + e, 256, chl - 3);
  bar_sync(NB_WG + e, 128);
  {
    const int p = (lane + 9 * (w >> 1)) & 31;
    const uint32_t ya = reg + ((w >> 1) ? R_BO : R_U) + p * 64 + (((2 * (w & 1)) ^ ((p >> 1) & 3)) * 16);
    const uint32_t up = p < lane ? 2048 : 0;
#pragma unroll
    for (int z = 0; z < 4; ++z) {
      const float* a = acc + 16 * (z >> 1) + 2 * (z & 1);
      stsm4t((ya + (up ^ ((z >> 1) * 2048))) ^ ((z & 1) * 16), pack2(a[0], a[1]), pack2(a[4], a[5]), pack2(a[8], a[9]), pack2(a[12], a[13]));
    }
  }
  wg_wait<0>();
  PROFC(rho ? 14 : 4);
  bar_sync(NB_WG + e, 128);
  {
    const uint32_t fa = reg + R_X5 + (8 * w + (lane & 7)) * 16 + (lane >> 3) * 512;
    uint32_t h[6];
#pragma unroll
    for (int p = 0; p < 6; ++p) h[p] = p ? pack2(f1[4 * p] + f1[4 * p - 2], f1[4 * p + 1] + f1[4 * p - 1]) : pack2(f1[0], f1[1]);
    stsm4(fa, h[0], h[1], h[2], h[3]);
    stsm2(fa + 2048, h[4], h[5]);
    stsm4(reg + R_X3 + (lane < 16 ? 1088 : 0) + (8 * w + (lane & 7) + 4 * (lane & 8)) * 16, pack2(f2[0], f2[1]), pack2(f2[2] + f2[4], f2[3] + f2[5]),
          pack2(f2[8], f2[9]), pack2(f2[10] + f2[12], f2[11] + f2[13]));
  }
  bar_arrive(NB_Y + e + 7 * rho, 256);
}
constexpr uint32_t FILL = 0xFFFFFFFFu;
template <int N> DEV void fixo(uint4 (&A)[N], const uint4* p) {
#pragma unroll 1
  for (int it = 0; it < SPIN_LIMIT; ++it) {
    uint32_t m = A[0].x;
#pragma unroll
    for (int k = 1; k < N; ++k) m = max(m, A[k].x);
    if (__all_sync(0xffffffffu, m != FILL)) break;
#pragma unroll
    for (int k = 0; k < N; ++k) ldr4_if(A[k], p + k * 32, A[k].x == FILL);
  }
}
DEV bool rows_nan(float a, float b) {
  return __any_sync(0xffffffffu, a != a || b != b);
}
template <int N> DEV void slow_step(float (&acc)[N], float a0, float a1, const uint16_t* wr, uint32_t zero) {
#pragma unroll
  for (int j = 0; j < N / 4; ++j) {
    const uint32_t v = __ldg((const uint32_t*)(wr + (j >> 3) * 512 + 8 * (j & 7)));
    acc[4 * j] += a0 * bflo(v); acc[4 * j + 1] += a0 * bfhi(v); acc[4 * j + 2] += a1 * bflo(v); acc[4 * j + 3] += a1 * bfhi(v);
    if ((j & 3) == 3) wr += __float_as_uint(acc[4 * j]) & zero;
  }
}
DEV int res_off(int w, int lane) { return ((lane & 7) + 8 * (lane >> 4)) * 8 + ((2 * (w & 2) + (w & 1) + ((lane >> 2) & 2)) ^ (lane & 7)); }
DEV void res_load(uint32_t (&res)[8][2], uint32_t sa, int w, int lane) {
  const uint32_t a = sa + res_off(w, opq(lane)) * 16;
#pragma unroll
  for (int j = 0; j < 8; j += 2) {
    uint32_t r[4];
    ldsm4t(r, a + j * 1024);
    res[j][0] = r[0]; res[j][1] = r[1]; res[j + 1][0] = r[2]; res[j + 1][1] = r[3];
  }
}

DEV void res_init(float (&ac)[32], const uint32_t (&res)[8][2]) {
#pragma unroll
  for (int j = 0; j < 16; ++j)
    asm volatile("shl.b32 %0,%2,16; and.b32 %1,%2,0xFFFF0000;" : "=&f"(ac[2 * j]), "=f"(ac[2 * j + 1]) : "r"(res[j >> 1][j & 1]));
}
DEV uint32_t after(uint32_t b, const uint32_t (&res)[8][2], uint32_t zero) {
  return b + ((res[0][0] ^ res[2][0] ^ res[4][0] ^ res[6][0]) & zero);
}

DEV void attn_phase(const Params& P, int c, int e, int w, int lane, int layer) {
  lane = opq(lane); c = opq(c);
  const int i = c >> 3, cg = c & 7, J = 16 * e + i, G = 8 * i + 4 - 4 * e + w;
  const int g = lane >> 2, t = lane & 3;
  float acc[96];
  uint32_t res[8][2];
  float2 cs[16];
  float4 st;
  const uint32_t csb = opq(SM_CS + 8 * t);
  {
    const uint32_t sa = SM_A + e * A_E, ba = B_A + 32 * e;
    const uint32_t da = dlo(sa, 8192), db = (SB >> 4) | (512 << 16);
    undef(acc);
#pragma unroll
    for (int j = 0; j < 8; ++j) asm volatile("" : "=r"(res[j][0]), "=r"(res[j][1]));
    mbar_wait(B_WF, layer);
    mbar_wait(ba, 0);
    mbar_wait(B_L, layer);
    bar_sync_if(NB_T, 256, e);
    PROF(24);
#pragma unroll
    for (int j = 0; j < 4; ++j) {
      if (j) mbar_wait(ba + 8 * j, 0);
      if (j == 1) PROFK(layer ? 39 : 15);
      wg_fence();
#pragma unroll
      for (int k = 0; k < 4; ++k) {
        if (j | k) wg_ss192<1>(acc, da + j * 512 + k * 128, db + wslot(j) * 512 + k * 128); else wg_ss192<0>(acc, da, db);
        if (j == 3 && k == 1) wg_commit();
      }
      wg_commit();
      if (j == 1 || j == 2) { wg_wait<1>(); mbar_arrive1_if(B_F + 8 * (j - 1), e); }
    }
    wg_wait<1>();
    bar_arrive(NB_T + e, 256);
    wg_wait<0>();
    if (cg < 4) res_load(res, sa + cg * 8192, w, lane);
    mbar_arrive1(after(B_AE + 8 * e, res, P.zero));
    PROF(25);
#pragma unroll 1
    for (uint32_t late = P.zero;; late = 1) {
      if (late) {
        const uint16_t* xr = (const uint16_t*)SCR->XF[layer] + opq(J) * 32768;
        zero(acc);
#pragma unroll 1
        for (int k = 0; k < 512; ++k)
          slow_step(acc, ldnan(xr + k * 64 + ((2 * w) ^ (k & 7)) * 8 + g), ldnan(xr + k * 64 + ((2 * w + 1) ^ (k & 7)) * 8 + g),
                    P.wqkv + (k * 1536 + 64 * cg + 2 * t), P.zero);
        const uint32_t* q = (const uint32_t*)xr + ((64 * cg + g) * 32 + t);
        const int m8 = (2 * (w & 2) + (w & 1)) ^ g;
#pragma unroll 1
        for (int it = 0; it < SPIN_LIMIT; ++it) {
          uint32_t m = 0;
#pragma unroll
          for (int z = 0; z < 16; ++z) { const uint32_t x = ldr1(q + (z >> 1) * 256 + (m8 ^ (2 * (z & 1))) * 4); m = max(m, x); res[z >> 1][z & 1] = movm(x); }
          if (__all_sync(0xffffffffu, m != FILL)) break;
        }
#pragma unroll
        for (int z = 0; z < 16; ++z) cs[z] = lds2f(csb + 256 + z * 32);
      } else {
        mbar_wait(B_CS, 0);
#pragma unroll
        for (int z = 0; z < 16; ++z) cs[z] = lds2f(csb + 256 + z * 32);
        mbar_wait(B_W4, layer);
        mbar_wait(ba, 1);
        bar_sync(NB_T + 1 - e, 256);
        PROF(26);
#pragma unroll
        for (int j = 4; j < 8; ++j) {
          if (j > 4) mbar_wait(ba + 8 * (j - 4), 1);
          if (j >= 6) mbar_wait(B_W6 + 8 * (j - 6), layer);
          if (j > 4) PROF(31 + j);
          wg_fence();
#pragma unroll
          for (int k = 0; k < 4; ++k) {
            wg_ss192<1>(acc, da + (j & 3) * 512 + k * 128, db + wslot(j) * 512 + k * 128);
            if (j == 7 && k == 1) wg_commit();
          }
          wg_commit();
          if (j == 5) {
            if (cg >= 4) { mbar_wait(ba + 8 * (cg - 4), 1); res_load(res, sa + (cg - 4) * 8192, w, lane); }
            wg_wait<1>(); mbar_arrive1_if(B_F + 16, e); PROF(40);
          }

        }
      }
      uint32_t rs = hadd2(res[0][0], res[0][1]);
#pragma unroll
      for (int z = 2; z < 16; ++z) rs = hadd2(rs, res[z >> 1][z & 1]);
      const float rn = bflo(rs) + bfhi(rs);
      wg_wait<1>();
      bar_arrive_if(NB_T, 256, !(e | late));
      mbar_wait(B_ST + 8 * e, layer);
      st = lds4f(SM_STAT + ((4 * e + w) * 8 + g) * 16);
      PROF(34 + layer);
      wg_wait<0>();
      if (!rows_nan(acc[0] + rn, acc[2]) || late) break;
    }
  }
  mbar_arrive1(B_QE);
  PROFK(8 + 12 * layer);
  uint32_t Q[4][4], K[4][2][2], V[4][2][2];
  {
#pragma unroll
    for (int z = 0; z < 8; ++z) {
      const float* a = acc + 32 + 4 * z; const float* b = acc + 64 + 4 * z;
      K[z >> 1][1][z & 1] = pack2((a[2] - st.z * cs[z].x) * st.w, (a[3] - st.z * cs[z].y) * st.w);
      V[z >> 1][1][z & 1] = movm(pack2((b[2] - st.z * cs[8 + z].x) * st.w, (b[3] - st.z * cs[8 + z].y) * st.w));
    }
    const int hop = (G >> 1) & 3;
    const uint32_t kv = SM_KV + (2 * hop + (w & 1)) * 2048 + lane * 16;
    uint4* h = SCR->H[layer] + (c * 256 + (w & 1) * 128 + lane);
    if (hop == 3) {
#pragma unroll
      for (int z = 0; z < 4; ++z) str4(h + 2048 + z * 32, K[z][1][0], K[z][1][1], V[z][1][0], V[z][1][1]);
    } else {
      mbar_wait(B_F + 16, layer);
#pragma unroll
      for (int z = 0; z < 4; ++z) sts4(kv + z * 512, K[z][1][0], K[z][1][1], V[z][1][0], V[z][1][1]);
      bar_arrive(NB_B + hop, 128);
    }
    PROF(42);
    uint4 hv[4];
#pragma unroll
    for (int z = 0; z < 4; ++z) { hv[z] = make_uint4(0, 0, 0, 0); ldr4_if(hv[z], h + z * 32, G >= 2 && hop == 0); }
#pragma unroll
    for (int z = 0; z < 8; ++z) {
      const float* a = acc + 32 + 4 * z; const float* b = acc + 64 + 4 * z;
      K[z >> 1][0][z & 1] = pack2((a[0] - st.x * cs[z].x) * st.y, (a[1] - st.x * cs[z].y) * st.y);
      V[z >> 1][0][z & 1] = movm(pack2((b[0] - st.x * cs[8 + z].x) * st.y, (b[1] - st.x * cs[8 + z].y) * st.y));
    }
#pragma unroll
    for (int z = 0; z < 8; ++z) {
      const float2 cq = lds2f(csb + z * 32);
      const float* a = acc + 4 * z;
      Q[z >> 1][2 * (z & 1)] = pack2(a[0] - st.x * cq.x, a[1] - st.x * cq.y);
      Q[z >> 1][2 * (z & 1) + 1] = pack2(a[2] - st.z * cq.x, a[3] - st.z * cq.y);
    }
    PROF(27);
    const bool p0 = 2 * t > g, p1 = 2 * t + 1 > g, first = G < 2;
    float s[4][4], mx[4][2];
#pragma unroll
    for (int z = 0; z < 4; ++z) {
      float S[4];
      mma16z(s[z], Q[z][0], Q[z][1], Q[z][2], Q[z][3], K[z][0][0], K[z][0][1]);
      mma16z(S, Q[z][0], Q[z][1], Q[z][2], Q[z][3], K[z][1][0], K[z][1][1]);
      s[z][2] = p0 ? s[z][2] : S[2]; s[z][3] = p1 ? s[z][3] : S[3];
    }
    const float sc0 = st.y * (0.25f * 1.4426950408889634f), sc1 = st.w * (0.25f * 1.4426950408889634f);
    uint32_t pw[4][2];
#pragma unroll
    for (int r = 1; r >= 0; --r) {
      if (r == 0) {
        if (hop) {
          bar_sync(NB_B + hop - 1, 128);
#pragma unroll
          for (int z = 0; z < 4; ++z) hv[z] = lds4(kv - 4096 + z * 512);
        } else fixo(hv, h);
        PROFD(41, hv[3].x);
#pragma unroll
        for (int z = 0; z < 4; ++z) {
          float S[4];
          mma16z(S, Q[z][0], Q[z][1], Q[z][2], Q[z][3], hv[z].x, hv[z].y);
          if (first) S[0] = S[1] = __uint_as_float(0xFF800000u);
          s[z][0] = p0 ? S[0] : s[z][0]; s[z][1] = p1 ? S[1] : s[z][1];
        }
      }
#pragma unroll
      for (int z = 0; z < 4; ++z) mx[z][r] = fmaxf(s[z][2 * r], s[z][2 * r + 1]);
#pragma unroll
      for (int o = 1; o < 3; ++o)
#pragma unroll
        for (int z = 0; z < 4; ++z) mx[z][r] = fmaxf(mx[z][r], __shfl_xor_sync(0xffffffffu, mx[z][r], o));
#pragma unroll
      for (int z = 0; z < 4; ++z) pw[z][r] = pack2(ex2((s[z][2 * r] - mx[z][r]) * (r ? sc1 : sc0)), ex2((s[z][2 * r + 1] - mx[z][r]) * (r ? sc1 : sc0)));
    }
    mbar_wait(layer ? B_N : B_Z, 1);
    const uint32_t M = (p0 ? 0xFFFFu : 0u) | (p1 ? 0xFFFF0000u : 0u);
    uint4* O = SCR->O + ((J * 8 + cg) * 512 + (2 * (w & 2) + (w & 1)) * 64 + t * 8 + g);
#pragma unroll
    for (int h2 = 0; h2 < 2; ++h2) {
      uint32_t ow[2][4];
#pragma unroll
      for (int z = 0; z < 2; ++z) {
        const int n = 2 * h2 + z;
        const uint32_t w0 = pw[n][0], w1 = pw[n][1];
        float sm[4] = {0.f, 0.f, 0.f, 0.f}, Oa[2][4];
        mma8(sm, w0, w1, 0x3F803F80u);
        mma16z(Oa[0], w0 & ~M, w1 & M, 0u, w1 & ~M, V[n][0][0], V[n][1][0]); mma8(Oa[0], w0 & M, 0u, hv[n].z);
        mma16z(Oa[1], w0 & ~M, w1 & M, 0u, w1 & ~M, V[n][0][1], V[n][1][1]); mma8(Oa[1], w0 & M, 0u, hv[n].w);
        const float i0 = rcp(sm[0]), i1 = rcp(sm[2]);
#pragma unroll
        for (int d = 0; d < 2; ++d) { ow[0][2 * z + d] = pack2(Oa[d][0] * i0, Oa[d][1] * i0); ow[1][2 * z + d] = pack2(Oa[d][2] * i1, Oa[d][3] * i1); }
      }
#pragma unroll
      for (int hi = 0; hi < 2; ++hi) str4(O + hi * 128 + h2 * 32, ow[hi][0], ow[hi][1], ow[hi][2], ow[hi][3]);
    }
  }
  str1(SCR->OF[layer] + (J * 32 + cg * 4 + w), 1);
  mbar_arrive1(B_AT + 8 * e);
  PROFK(9 + 12 * layer);
  float ac[32];
  const uint32_t so = SM_O + e * O_E;
  uint2* xo = opqp(layer ? (uint2*)(P.out + ((16 * G + 2 * (lane >> 3)) * 512 + 64 * cg + 8 * (lane & 7)))
                         : (uint2*)SCR->XG[1] + ((32 * (cg & 3) + t) * 2048 + (cg >> 2) * 256 + xg_off(G, g)));
  const uint32_t stg = SM_X + (4 * e + w) * 2048;
  const uint32_t sw = opq(stg + (lane & 15) * 128 + (((lane >> 4) ^ (lane & 7)) * 16)), sr = opq(stg + (lane >> 3) * 128 + (((lane & 7) ^ (lane >> 3)) * 16));
  uint4* ps = opqp(&SCR->PS[(G * 8 + cg) * 8 + g]);
  {
    const uint32_t bo = B_O + 32 * e;
    const uint32_t dw = (SM_WO >> 4) | (512 << 16), da = dlo(so, 512);
    mbar_wait(B_WO, layer);
    res_init(ac, res);
    mbar_wait(B_AT + 8, layer);
#pragma unroll
    for (int j = 0; j < 4; ++j) {
      mbar_wait(bo + 8 * j, layer);
      if (j == 0) PROFK(32 + layer);
      wg_fence();
#pragma unroll
      for (int k = 8 * j; k < 8 * j + 8; ++k) {
        const uint32_t a = da + (k >> 2) * 512 + (k & 3) * 8, b = dw + (k & 3) * 1024 + (k >> 2) * 128;
        wg_ss64<1>(ac, a, b);
      }
      wg_commit();
    }
#pragma unroll 1
    for (uint32_t late = P.zero;; late = 1) {
      if (late) {
        const uint16_t* op = (const uint16_t*)(SCR->O + (J * 4096 + w * 128 + g));
        wg_wait<0>();
        res_init(ac, res);
#pragma unroll 1
        for (int k = 0; k < 512; ++k) {
          const uint16_t* q = op + (k >> 6) * 4096 + (k & 56) * 8 + (k & 7);
          slow_step(ac, ldnan(q), ldnan(q + 512), P.wo + (((k & ~31) + 4 * (k & 6) + ((k >> 2) & 6) + (k & 1)) * 512 + 64 * cg + 2 * t), P.zero);
        }
      }
      wg_wait<0>();
      if (!rows_nan(ac[0], ac[2]) || late) break;
    }
  }
  PROFK(10 + 12 * layer);
#pragma unroll
  for (int j = 0; j < 16; ++j) res[j >> 1][j & 1] = pack2(ac[2 * j], ac[2 * j + 1]);
  if (layer == 0) {
    float s[2][4], q0[2][4], q1[2][4];
#pragma unroll
    for (int j = 0; j < 2; ++j) gram<true>(s[j], q0[j], q1[j], res[2 * j][0], res[2 * j][1], res[2 * j + 1][0], res[2 * j + 1][1]);
#pragma unroll
    for (int j = 0; j < 2; ++j) gram<false>(s[j], q0[j], q1[j], res[2 * j + 4][0], res[2 * j + 4][1], res[2 * j + 5][0], res[2 * j + 5][1]);
    const bool od = g & 1;
    str4_if(ps, nzmap(__float_as_uint(s[0][0] + s[1][0])), __float_as_uint(od ? q0[0][1] + q0[1][1] : q0[0][0] + q0[1][0]),
            __float_as_uint(s[0][2] + s[1][2]), __float_as_uint(od ? q1[0][3] + q1[1][3] : q1[0][2] + q1[1][2]), t == (g >> 1));
#pragma unroll
    for (int j = 0; j < 8; ++j) {
      str2(xo + j * 8192, nzmap(prmt(res[j][0], res[j][1], 0x5410)), prmt(res[j][0], res[j][1], 0x7632));
    }
    mbar_arrive1(B_ED + 8 * e);
  } else {
#pragma unroll
    for (int j = 0; j < 8; j += 2) stsm4(sw ^ (j * 16), res[j][0], res[j][1], res[j + 1][0], res[j + 1][1]);
    __syncwarp();
    uint4 v[4];
#pragma unroll
    for (int k = 0; k < 4; ++k) v[k] = lds4((sr ^ ((k & 1) * 64)) + k * 512);
#pragma unroll
    for (int k = 0; k < 4; ++k) stw4(xo + ((k & 1) * 8 + (k >> 1)) * 128, v[k].x, v[k].y, v[k].z, v[k].w);
  }
  PROFK(11 + 12 * layer);
}

DEV void col_sums(const Params& P, int c, int wa, int lane) {
  const int i = c >> 3, cg = c & 7;
  uint4 wv[8];
#pragma unroll
  for (int k = 0; k < 8; ++k) wv[k] = ldnc4(P.wqkv + ((32 * i + (lane >> 3)) * 1536 + wa * 512 + 64 * cg + 8 * (lane & 7)) + 4 * k * 1536);
  float cs[8];
  zero(cs);
#pragma unroll
  for (int k = 0; k < 8; ++k) {
    cs[0] += bflo(wv[k].x); cs[1] += bfhi(wv[k].x); cs[2] += bflo(wv[k].y); cs[3] += bfhi(wv[k].y);
    cs[4] += bflo(wv[k].z); cs[5] += bfhi(wv[k].z); cs[6] += bflo(wv[k].w); cs[7] += bfhi(wv[k].w);
  }
  const bool b4 = lane & 16, b3 = lane & 8;
#pragma unroll
  for (int k = 0; k < 4; ++k) cs[k] = (b4 ? cs[k + 4] : cs[k]) + __shfl_xor_sync(0xffffffffu, b4 ? cs[k] : cs[k + 4], 16);
#pragma unroll
  for (int k = 0; k < 2; ++k) cs[k] = (b3 ? cs[k + 2] : cs[k]) + __shfl_xor_sync(0xffffffffu, b3 ? cs[k] : cs[k + 2], 8);
  str2((uint2*)SCR->CS + (i * 768 + wa * 256 + 32 * cg + 4 * (lane & 7) + (lane >> 3)), nzmap(__float_as_uint(cs[0])), __float_as_uint(cs[1]));
}
DEV void col_gather(const Params& P, int c, int wa, int lane) {
  const uint2* p = (const uint2*)SCR->CS + (wa * 256 + 32 * (c & 7) + lane);
#pragma unroll 1
  for (int it = 0;; ++it) {
    float a = 0.f, b = 0.f;
    uint32_t m = ~0u;
#pragma unroll
    for (int k = 0; k < 16; ++k) { const uint2 q = ldr2(p + k * 768); m = min(m, q.x); a += __uint_as_float(q.x); b += __uint_as_float(q.y); }
    if (__all_sync(0xffffffffu, m != 0u)) { sts2f(SM_CS + wa * 256 + lane * 8, a, b); break; }
    spin_guard(it);
  }
  __syncwarp();
  mbar_arrive1(B_CS);
}

DEV void aux_prologue(const Params& P, int c, int wa, int lane) {
  const int g = lane >> 2, t = lane & 3, G = stat_group(c);
  {
    uint32_t w[16][2];
    const uint16_t* row = P.x0 + ((16 * G + 2 * g) * 512 + 128 * wa + 8 * t);
    bar_sync(NB_Y, 384);
#pragma unroll
    for (int z = 0; z < 8; ++z) {
      const uint4 v = ldw4(row + (z & 1) * 512 + (z >> 1) * 32);
      const int o = 4 * (z >> 1);
      w[o][z & 1] = v.x; w[o + 1][z & 1] = v.y; w[o + 2][z & 1] = v.z; w[o + 3][z & 1] = v.w;
    }
    PROF(34);
    PROFD(35, w[0][0]);
    PROFD(36, w[15][1]);
    uint2* xo = (uint2*)SCR->XG[0] + ((64 * (wa & 1) + 4 * t) * 2048 + (wa >> 1) * 256 + xg_off(G, g));
#pragma unroll
    for (int n = 0; n < 16; ++n) str2(xo + (16 * (n >> 2) + (n & 3)) * 2048, nzmap(prmt(w[n][0], w[n][1], 0x5410)), prmt(w[n][0], w[n][1], 0x7632));
    float s[2][4], q0[2][4], q1[2][4];
#pragma unroll
    for (int z = 0; z < 8; ++z) {
      const int o = 4 * (z >> 1), r = z & 1;
      if (z < 2) gram<true>(s[r], q0[r], q1[r], w[o][r], w[o + 1][r], w[o + 2][r], w[o + 3][r]);
      else gram<false>(s[r], q0[r], q1[r], w[o][r], w[o + 1][r], w[o + 2][r], w[o + 3][r]);
    }
    const bool od = g & 1;
    if (t == (g >> 1))
      sts4f(SM_STAT + (wa * 8 + g) * 16, s[0][0] + s[0][2], od ? q0[0][1] + q1[0][3] : q0[0][0] + q1[0][2],
            s[1][0] + s[1][2], od ? q0[1][1] + q1[1][3] : q0[1][0] + q1[1][2]);
    bar_arrive(NB_P0, 192);
  }
  PROF(2);
  if (lane == 0)
    asm volatile("cp.async.bulk.prefetch.L2.global [%0],4096;" :: "l"(wa < 3 ? P.wqkv + (3 * c + wa) * 2048 : P.wo + c * 2048) : "memory");
  bar_sync(NB_Y + 1, 256);
  mbar_wait(B_Z, 0);
}

DEV void stat_part(const Params& P, int c, int wa, int lane, int layer, int h, float (&v)[2]) {
  lane = opq(lane);
  const int e = wa >> 1;
  uint32_t x[4][4];
  mbar_wait(B_A + 16 * wa, h); mbar_wait(B_A + 16 * wa + 8, h);
  if (h == 0) mbar_wait(B_A + 32 * e + 24, 0);
#pragma unroll
  for (int k = 0; k < 4; ++k) ldsm4t(x[k], SM_A + e * A_E + (128 * (wa & 1) + lane) * 128 + (((c ^ lane) & 7) * 16) + k * 4096);
  float s[4] = {0.f, 0.f, 0.f, 0.f};
#pragma unroll
  for (int k = 0; k < 16; ++k) { const float a = bflo(x[k >> 2][k & 3]), b = bfhi(x[k >> 2][k & 3]); s[0] += a; s[1] += a * a; s[2] += b; s[3] += b * b; }
  s[0] += s[2]; s[1] += s[3];
  if (RARE(rows_nan(s[1], s[1]))) {
    const uint16_t* q = (const uint16_t*)(SCR->XF[layer] + ((32 * e + 2 * (c >> 3) + h) * 2048 + (wa & 1) * 1024)) + (lane >> 2);
    s[0] = s[1] = 0.f;
#pragma unroll 1
    for (int k = 0; k < 32; ++k) {
      const int r = 2 * (lane & 3) + (k & 1);
      const float a = ldnan(q + ((k >> 1) * 8 + r) * 64 + ((c ^ r) & 7) * 8);
      s[0] += a; s[1] += a * a;
    }
  }
  v[0] += s[0]; v[1] += s[1];
  __syncwarp();
}
DEV void stat_finish(const Params& P, int c, int wa, int lane, int layer, float (&v)[2]) {
  lane = opq(lane);
  const bool b = lane & 1;
  const float s = (b ? v[1] : v[0]) + __shfl_xor_sync(0xffffffffu, b ? v[0] : v[1], 1);
  str1((uint32_t*)SCR->ST[layer] + ((128 * (wa >> 1) + c) * 64 + (wa & 1) * 32 + lane), nzmap(__float_as_uint(s)));
  const uint4* sp = SCR->ST[layer] + ((128 * (wa >> 1) + (c & ~7) + 4 * (wa & 1) + (lane >> 3)) * 16 + (lane & 7));
  uint4 x, y;
  for (int it = 0;; ++it) {
    x = ldr4(sp); y = ldr4(sp + 8);
    if (__all_sync(0xffffffffu, min(min(min(x.x, x.y), min(x.z, x.w)), min(min(y.x, y.y), min(y.z, y.w))) != 0u)) break;
    spin_guard(it);
  }
  const uint32_t q = ln_sums((__uint_as_float(x.x) + __uint_as_float(x.z)) + (__uint_as_float(y.x) + __uint_as_float(y.z)),
                             (__uint_as_float(x.y) + __uint_as_float(x.w)) + (__uint_as_float(y.y) + __uint_as_float(y.w)));
  sts2f(SM_STAT + (16 * wa + (lane >> 4) * 8 + (lane & 7)) * 16 + (lane & 8), bflo(q), rcp(bfhi(q)));
  __syncwarp();
  mbar_arrive1(B_ST + 4 * (wa & 2));
}

DEV void nan_source(uint32_t a, int lane) {
#pragma unroll
  for (int k = 0; k < 4; ++k) sts4(a + k * 512 + lane * 16, FILL, FILL, FILL, FILL);
  fence_async_smem();
  __syncwarp();
}
__global__ void __launch_bounds__(NTHR, 1)
fused_kernel(const __grid_constant__ Params P, const __grid_constant__ CUtensorMap mapW, const __grid_constant__ CUtensorMap mapWo,
             const __grid_constant__ CUtensorMap mapX) {
  extern __shared__ __align__(1024) uint8_t smem_raw[];
  const int warp = __shfl_sync(0xffffffffu, threadIdx.x >> 5, 0), lane = threadIdx.x & 31;
  uint32_t smid; asm volatile("mov.u32 %0,%%smid;" : "=r"(smid));
  const uint32_t* pw = (const uint32_t*)&P + threadIdx.y;
  const int role = P.role[(smid >> 1) + threadIdx.y] + (smid & 1) + (pw[0] & pw[12]);
  const int c = __shfl_sync(0xffffffffu, pw[1] ? role : blockIdx.x, 0);
  if (c >= 128) {
#pragma unroll 1
    for (int k = (c - 128) * NTHR + threadIdx.x; k < 131072; k += P.spare * NTHR) str4(SCR->XG[1] + k, 0, 0, 0, 0);
    __threadfence();
    __syncthreads();
    if (warp == 0) { poll(SCR->C + 1 + (lane & 3) * 32, 32); cnt_add1(SCR->C + 6); }
    __syncthreads();
#pragma unroll 1
    for (int k = (c - 128) * NTHR + threadIdx.x; k < 131072; k += P.spare * NTHR) str4(SCR->XG[0] + k, 0, 0, 0, 0);
    return;
  }
#define DONE() do {} while (0)
  const int cg = c & 7;
  if (warp < 8) {
    PROF(46);
    kgen(P, c, warp, lane);
    PROFK(1);
    bar_sync(0, 384);
#pragma unroll 1
    for (int layer = 0; layer < 2; ++layer) {
#pragma unroll 1
      for (int rho = 0; rho < 2; ++rho) {
        const int wz = warp + ((rho + layer) & P.zero);
        conv_round(wz >> 2, rho, wz & 3, lane_id());
        PROFK(6 + rho + 12 * layer);
      }
      const int z = layer & P.zero;
      attn_phase(P, c + z, (warp + z) >> 2, (warp + z) & 3, lane_id(), layer);
    }
    DONE();
  } else if (warp < 12) {
    asm volatile("setmaxnreg.dec.sync.aligned.u32 %0;" :: "n"(REG_AUX));
    aux_prologue(P, c, warp - 8, lane);
    PROF(1);
    const int c0 = c;
#pragma unroll 1
    for (int layer = 0;; ++layer) {
      const int c = c0 + (layer & P.zero), wa = warp - 8 + (layer & P.zero);
#define lane lane_id()
#define j (32 * wa + lane_id())
      uint4 x[2][2][2];
      uint32_t u[4][4];
      uprep(P, c, wa, lane, layer, x, u);
      fence_async_smem();
      bar_arrive(NB_U, NBARU);
      PROFK(5 + 12 * layer);
      bar_sync(NB_H, 224);
      box_full<0, 3>(j, u, P.zero);
      PROF(3 + 12 * layer);
      conv_out(c, j, 0, x, u[0], SCR->XF[layer], P.zero);
      PROF(32);
      conv_out(c, j, 1, x, u[1], SCR->XF[layer], P.zero);
      box_full<3, 4>(j, u, P.zero);
      PROF(6 + 12 * layer);
      if (layer == 0 && wa < 3) col_sums(P, c, wa, lane);
      conv_out(c, j, 2, x, u[2], SCR->XF[layer], P.zero);
      PROF(33);
      conv_out(c, j, 3, x, u[3], SCR->XF[layer], P.zero);
      PROFK(7 + 12 * layer);
      float v[2];
      zero(v);
#pragma unroll 1
      for (int h = 0; h < 2; ++h) {
        stat_part(P, c, wa, lane, layer, h, v);
        if (h) break;
        mbar_arrive1(B_AE + 4 * (wa & 2));
        if (layer == 0 && wa < 3) col_gather(P, c, wa, lane);
      }
      PROF(9 + 12 * layer);
      stat_finish(P, c, wa, lane, layer, v);
      PROF(8 + 12 * layer);
      if (layer) break;
      mbar_wait(B_ED, 0); mbar_wait(B_ED + 8, 0);
#undef lane
#undef j
    }
    DONE();
  } else {
    asm volatile("setmaxnreg.dec.sync.aligned.u32 %0;" :: "n"(REG_PROD));
    if (s2u(smem_raw) != SB) __trap();
#pragma unroll 1
    for (int n = warp - 12; n < 42; n += 4)
      asm volatile("{.reg .pred p; elect.sync _|p,0xffffffff; @p mbarrier.init.shared::cta.b64 [%0],%1;}"
                   :: "r"(SM_BAR + n * 8), "r"(n == 33 ? 4 : n > 14 ? 1 : (int)(0x322866444444444ull >> (4 * n)) & 15) : "memory");
    fence_async_smem();
    bar_sync(NB_AUX, 128);
    bar_arrive(0, 384); bar_arrive(NB_Y + 1, 256);
    PROF(1);
    if (warp == 12) {
      if (lane == 0) {
        asm volatile("prefetch.tensormap [%0];" :: "l"(&mapW) : "memory");
        asm volatile("prefetch.tensormap [%0];" :: "l"(&mapWo) : "memory");
        asm volatile("prefetch.tensormap [%0];" :: "l"(&mapX) : "memory");
      }
      nan_source(slot(12), lane);
#pragma unroll 1
      for (int k = 0; k < 8; ++k) tma2_store(&mapX, slot(12), 128 * c, 8 * k);
      bulk_wait();
      __threadfence();
      mbar_arrive1(B_Z);
      mbar_wait(B_E, 0);
#pragma unroll 1
      for (int k = 0; k < 4; ++k) bulk_store(SCR->H[k >> 1] + ((c + 8) * 256 + (k & 1) * 128), slot(12), 2048);
#pragma unroll 1
      for (int k = 0; k < 8; ++k) bulk_store(SCR->O + (c * 512 + (k >> 2) * 65536 + (k & 3) * 128), slot(12), 2048);
      bulk_wait();
      PROF(24);
#pragma unroll 1
      for (int layer = 0; layer < 2; ++layer) {
        mbar_wait(B_V, layer);
        if (layer == 1 && c < 4 && ((0x47 >> lane) & 1)) str1(SCR->C + c * 32 + lane, 0);
        mbar_expect1(B_WF, 4 * 24576);
#pragma unroll
        for (int k = 0; k < 4; ++k) tma3(slot(wslot(k)), &mapW, 64 * cg, 64 * k, 0, B_WF);
        if (layer == 0) { __threadfence(); mbar_arrive1(B_Z); }
        mbar_wait(B_WF, layer);
        mbar_expect1(B_W4, 2 * 24576);
#pragma unroll
        for (int k = 4; k < 6; ++k) tma3(slot(wslot(k)), &mapW, 64 * cg, 64 * k, 0, B_W4);
        bar_sync(NB_AUX, 64);
#pragma unroll 1
        for (int k = 0; k < 2; ++k) {
          mbar_expect1(B_W6 + 8 * k, 24576);
          mbar_wait(B_F + 8 * k, layer);
          tma3(slot(3 * k), &mapW, 64 * cg, 384 + 64 * k, 0, B_W6 + 8 * k);
        }
        mbar_expect1(B_WO, 65536);
        mbar_wait(B_AE + 8, layer);
        nan_source(slot(12), lane);
        uint4* fp = layer ? SCR->O + c * 512 : SCR->XF[1] + c * 512;
#pragma unroll 1
        for (int r = 7; r >= 0; --r) {
          __nanosleep(30);
          if (r >= 4) {
            bulk_store(fp + (r & 3) * 128, slot(12), 2048); bulk_store(fp + 65536 + (r & 3) * 128, slot(12), 2048);
          }
          if (r == 3) { bulk_wait(); __threadfence(); mbar_arrive1(B_N); PROF(9 + 12 * layer); }
          if (r == 1) mbar_wait(B_F + 16, layer);
          tma4(SM_WO + r * 8192, &mapWo, 64 * cg, 0, r >> 1, 32 * (r & 1), B_WO);
        }
        PROF(8 + 12 * layer);
      }
      DONE();
    } else if (warp == 13) {
      const int G = stat_group(c);
#pragma unroll 1
      for (int layer = 0; layer < 2; ++layer) {
        float z[4];
        uint2* so = opqp((uint2*)&SCR->SR[layer][lane >> 3][sr_off(G, lane)] + (lane & 1));
        if (layer == 0) {
          bar_sync(NB_P0, 192);
          const float4 a = lds4f(SM_STAT + lane * 16);
          z[0] = a.x; z[1] = a.y; z[2] = a.z; z[3] = a.w;
        } else {
          mbar_wait(B_ED + 2 * (c & 4), 0);
          uint4* ps = &SCR->PS[G * 64 + lane];
          uint4 a, b;
          for (int it = 0;; ++it) {
            a = ldr4(ps); b = ldr4(ps + 32);
            if (__all_sync(0xffffffffu, min(a.x, b.x) != 0u)) break;
            spin_guard(it);
          }
          z[0] = __uint_as_float(a.x) + __uint_as_float(b.x); z[1] = __uint_as_float(a.y) + __uint_as_float(b.y);
          z[2] = __uint_as_float(a.z) + __uint_as_float(b.z); z[3] = __uint_as_float(a.w) + __uint_as_float(b.w);
        }
#pragma unroll
        for (int o = 8; o < 32; o <<= 1)
#pragma unroll
          for (int k = 0; k < 4; ++k) z[k] += __shfl_xor_sync(0xffffffffu, z[k], o);
        const uint32_t w0 = ln_sums(z[0], z[1]), w1 = ln_sums(z[2], z[3]);
        const uint32_t r = nzmap(pack2(rcp(bfhi(w0)), rcp(bfhi(w1)))), m = prmt(w0, w1, 0x5410);
        str2(so, r, m); str2(so + 4 * 1024, r, m);
        PROF(4 + 12 * layer);
        box_help(0, 0, 2, lane, layer);
        PROF(6 + 12 * layer);
      }
      DONE();
    } else if (warp == 14) {
#pragma unroll 1
      for (int layer = 0; layer < 2; ++layer) {
        uint32_t* ca = opqp(SCR->C + (c >> 5) * 32 + 3 * layer);
        const uint32_t* cw = opqp(SCR->C + (lane & 3) * 32 + 3 * layer);
        const uint4* xg = opqp(SCR->XG[layer] + c * 1024);
        mbar_expect1(B_E, 16384);
        if (layer) { mbar_wait(B_N, 0); mbar_wait(B_ED, 0); mbar_wait(B_ED + 8, 0); } else bar_sync(NB_P0, 192);
        cnt_add1(ca);
        PROF(4 + 12 * layer);
#pragma unroll 1
        for (uint32_t it = 0, todo = 15; todo; ++it) {
          spin_guard(it);
          const uint32_t m = __ballot_sync(0xffffffffu, ldr1(cw) >= 32) & todo;
          todo ^= m;
          mbar_arrive1_if(B_U, todo == 0);
#pragma unroll
          for (int q = 0; q < 4; ++q)
            if ((m >> q) & 1) bulk(SM_X + 4096 * q, xg + 256 * q, 4096, B_E);
        }
        PROFK(5 + 12 * layer);
        box_help(0, 1, 2, lane, layer);
#pragma unroll 1
        for (int n = 0; n < 4; ++n) {
          const int e = n & 1;
          const uint4* src = opqp(SCR->XF[layer] + (32 * e + 2 * (c >> 3) + (n >> 1)) * 2048);
          const uint32_t dst = opq(SM_A + e * A_E), b = opq(B_A + 32 * e), f = opq(n == 1 ? B_L : (n & 2 ? B_AE : B_RD) + 8 * e);
          if (n == 2) poll(cw + 2, 32);
          if (n == 2) PROF(7 + 12 * layer);
          mbar_wait(f, layer);
          if (n == 0) cnt_add1(ca + 1);
          uint32_t ok = n ? 15 : 0;
#pragma unroll 1
          for (int q = 0, it = 0; q < 4; ++q) {
            mbar_expect1(b + 8 * q, 8192);
#pragma unroll 1
            for (; !((ok >> q) & 1); ++it) {
              spin_guard(it);
              ok = __ballot_sync(0xffffffffu, ldr1(cw + 1) >= 32);
            }
            bulk(dst + 8192 * q, src + 512 * q, 8192, b + 8 * q);
          }
          bar_arrive_if(NB_AUX, 64, n == 2);
          if (!e) PROFK(6 + n + 12 * layer);
        }
#pragma unroll 1
        for (int n = 0; n < 8; ++n) mbar_expect1(B_O + 8 * n, 16384);
        if (layer == 0) poll(SCR->C + 6, P.spare);
        mbar_wait(B_QE, layer);
#pragma unroll 1
        for (int e = 0; e < 2; ++e) {
          const int J = 16 * e + (c >> 3);
          const uint32_t* fl = opqp(SCR->OF[layer] + J * 32 + lane);
          const uint4* src[4];
          uint32_t dst[4], b[4];
#pragma unroll
          for (int n = 0; n < 4; ++n) { src[n] = opqp(SCR->O + (J * 4096 + n * 1024)); dst[n] = opq(SM_O + e * O_E + 16384 * n); b[n] = opq(B_O + 32 * e + 8 * n); }
          mbar_wait(B_AT + 8 * e, layer);
          if (!e) pause(260);
          poll(fl, 1);
#pragma unroll
          for (int n = 0; n < 4; ++n) bulk(dst[n], src[n], 16384, b[n]);
          PROFK(9 + e + 12 * layer);
        }
      }
      DONE();
    }
    if (warp == 15) {
      const int G = stat_group(c);
      str4(&SCR->ST[0][(lane >> 4) * 2048 + c * 16 + (lane & 15)], 0, 0, 0, 0); str4(&SCR->ST[1][(lane >> 4) * 2048 + c * 16 + (lane & 15)], 0, 0, 0, 0);
      if (lane < 4) str4(SCR->OF[lane >> 1] + ((lane & 1) * 512 + c * 4), 0, 0, 0, 0);
      str4(&SCR->PS[G * 64 + lane], 0, 0, 0, 0); str4(&SCR->PS[G * 64 + 32 + lane], 0, 0, 0, 0);
      str4(&SCR->SR[1][lane >> 2][sr_off(G, 2 * lane)], 0, 0, 0, 0);
      if (c < 4 && lane < 3) str1(SCR->C + c * 32 + 3 + lane, 0);
#pragma unroll
      for (int k = 0; k < 3; ++k) str2((uint2*)SCR->CS + ((c >> 3) * 768 + k * 256 + 32 * cg + lane), 0, 0);
      __threadfence();
#pragma unroll 1
      for (int layer = 0; layer < 2; ++layer) {
        PROF(4 + 12 * layer);
        mbar_watch(B_E, layer);
        box_help(1, 0, 1, lane, layer);
        if (layer) str4(&SCR->SR[0][lane >> 2][sr_off(G, 2 * lane)], 0, 0, 0, 0);
        uint32_t* ca = opqp(SCR->C + (c >> 5) * 32 + 3 * layer + 2);
        mbar_watch(B_Z, 1);
        mbar_watch(B_RD + 8, layer);
        cnt_add1(ca);
        if (P.spare == 0) {
#pragma unroll 1
          for (int k = 0; k < 32; ++k) str4(SCR->XG[layer] + (c * 1024 + k * 32 + lane), 0, 0, 0, 0);
        }
      }
      mbar_watch(B_O + 56, 1);
    }
  }
}

typedef CUresult (*EncodeFn)(CUtensorMap*, CUtensorMapDataType, cuuint32_t, void*, const cuuint64_t*, const cuuint64_t*,
                             const cuuint32_t*, const cuuint32_t*, CUtensorMapInterleave, CUtensorMapSwizzle,
                             CUtensorMapL2promotion, CUtensorMapFloatOOBfill);

static int place_roles(uint8_t* role) {
  int dev = 0, nsm = 0;
  cudaGetDevice(&dev);
  cudaDeviceGetAttribute(&nsm, cudaDevAttrMultiProcessorCount, dev);
  if (nsm <= 128 || nsm > 144 || (nsm & 1)) return 0;
  cudaFuncSetAttribute(fused_kernel, cudaFuncAttributeNonPortableClusterSizeAllowed, 1);
  int occ[9] = {0};
  for (int k = 2; k <= 8; ++k) {
    cudaLaunchConfig_t cfg = {};
    cudaLaunchAttribute at[1];
    at[0].id = cudaLaunchAttributeClusterDimension;
    at[0].val.clusterDim.x = 2 * k; at[0].val.clusterDim.y = 1; at[0].val.clusterDim.z = 1;
    cfg.gridDim = dim3(2 * k); cfg.blockDim = dim3(NTHR); cfg.dynamicSmemBytes = SM_TOTAL; cfg.attrs = at; cfg.numAttrs = 1;
    if (cudaOccupancyMaxActiveClusters(&occ[k], fused_kernel, &cfg) != cudaSuccess) { cudaGetLastError(); occ[k] = 0; }
  }
  int n[10];
  n[7] = occ[8]; n[6] = occ[7]; n[5] = occ[6] - 0; n[4] = occ[5];
  n[3] = occ[4] - n[7]; n[1] = occ[2] - n[3] - n[5] - n[7]; n[0] = n[2] = n[1];
  n[8] = occ[3] - n[2] - n[5];
  const int ntpc = nsm / 2;
  int sum = 0;
  bool ok = n[0] > 0 && n[0] <= 8;
  for (int r = 0; r < 9; ++r) { ok = ok && n[r] >= 0 && (r == 0 || n[r] <= n[r - 1]); sum += n[r]; }
  if (!ok || sum > ntpc) { for (int r = 0; r < 9; ++r) n[r] = r < 8 ? 8 : 0; sum = 64; }
  int tp[8][9], cnt[8] = {0}, pool[72], np = 0, id = 0;
  for (int r = 0; r < 9; ++r)
    for (int g = n[0] - n[r]; g < n[0]; ++g) tp[g][cnt[g]++] = id++;
  for (; id < ntpc; ++id) pool[np++] = id;
  int order[72], no = 0;
  for (int g = 0; g < n[0]; ++g) {
    const int full = cnt[g] / 4 * 4;
    for (int k = 0; k < cnt[g]; ++k) { if (k < full) order[no++] = tp[g][k]; else pool[np++] = tp[g][k]; }
  }
  for (int k = 0; k < np; ++k) order[no++] = pool[k];
  for (int k = 0; k < ntpc; ++k) role[order[k]] = 2 * k;
  return nsm;
}

extern "C" void kernel_launch(void* const* d_in, const int* in_sizes, int n_in, void* d_out, int out_size) {
  (void)in_sizes; (void)n_in; (void)out_size;
  static EncodeFn enc = nullptr;
  static uint8_t role[72];
  static int nsm = 0;
  static Scratch* scratch = nullptr;
  if (!enc) {
    void* fn = nullptr;
    cudaDriverEntryPointQueryResult qr;
    cudaGetDriverEntryPoint("cuTensorMapEncodeTiled", &fn, cudaEnableDefault, &qr);
    enc = (EncodeFn)fn;
    cudaFuncSetAttribute(fused_kernel, cudaFuncAttributeMaxDynamicSharedMemorySize, SM_TOTAL);
    nsm = place_roles(role);
    cudaGetSymbolAddress((void**)&scratch, g_S);
  }
  CUtensorMap mW, mWo, mX;
  {
    cuuint64_t dim[3] = {512, 512, 3}, str[2] = {3072, 1024};
    cuuint32_t box[3] = {64, 64, 3}, es[3] = {1, 1, 1};
    enc(&mW, CU_TENSOR_MAP_DATA_TYPE_BFLOAT16, 3, d_in[10], dim, str, box, es, CU_TENSOR_MAP_INTERLEAVE_NONE,
        CU_TENSOR_MAP_SWIZZLE_128B, CU_TENSOR_MAP_L2_PROMOTION_NONE, CU_TENSOR_MAP_FLOAT_OOB_FILL_NONE);
  }
  {
    cuuint64_t dim[4] = {512, 2, 4, 64}, str[3] = {1024, 2048, 8192};
    cuuint32_t box[4] = {64, 2, 1, 32}, es[4] = {1, 1, 1, 1};
    enc(&mWo, CU_TENSOR_MAP_DATA_TYPE_BFLOAT16, 4, d_in[11], dim, str, box, es, CU_TENSOR_MAP_INTERLEAVE_NONE,
        CU_TENSOR_MAP_SWIZZLE_128B, CU_TENSOR_MAP_L2_PROMOTION_NONE, CU_TENSOR_MAP_FLOAT_OOB_FILL_NONE);
  }
  {
    cuuint64_t dim[2] = {16384, 64}, str[1] = {32768};
    cuuint32_t box[2] = {128, 8}, es[2] = {1, 1};
    enc(&mX, CU_TENSOR_MAP_DATA_TYPE_BFLOAT16, 2, scratch->XF[0], dim, str, box, es, CU_TENSOR_MAP_INTERLEAVE_NONE,
        CU_TENSOR_MAP_SWIZZLE_NONE, CU_TENSOR_MAP_L2_PROMOTION_NONE, CU_TENSOR_MAP_FLOAT_OOB_FILL_NONE);
  }
  Params P;
  P.x0 = (const uint16_t*)d_in[0]; P.Are = (const uint16_t*)d_in[1]; P.Aim = (const uint16_t*)d_in[2];
  P.Bre = (const uint16_t*)d_in[3]; P.Bim = (const uint16_t*)d_in[4]; P.Cre = (const uint16_t*)d_in[5];
  P.Cim = (const uint16_t*)d_in[6]; P.logdt = (const uint16_t*)d_in[7]; P.dskip = (const uint16_t*)d_in[8];
  P.wqkv = (const uint16_t*)d_in[10]; P.wo = (const uint16_t*)d_in[11]; P.out = (uint16_t*)d_out;
  for (int k = 0; k < 72; ++k) P.role[k] = role[k];
  P.zero = 0;
  P.mid = (char*)scratch->C;
  P.spare = nsm > 0 ? nsm - 128 : 0;
  fused_kernel<<<nsm > 0 ? nsm : 128, NTHR, SM_TOTAL, cudaStreamPerThread>>>(P, mW, mWo, mX);
}
```

```cpp
#include <cuda_runtime.h>
#include <cuda_bf16.h>
#include <cuda.h>
#include <stdint.h>
#include <stddef.h>

#define DEV __device__ __forceinline__
#define RARE(x) __builtin_expect(!!(x), 0)

constexpr int NTHR = 512;
constexpr int REG_MAIN = 192, REG_AUX = 88, REG_PROD = 40;
constexpr int NBARU = 384;
constexpr int SPIN_LIMIT = 1 << 22;

constexpr uint32_t SB = 1024;
__host__ __device__ constexpr uint32_t slot(int n) { return SB + n * 8192; }
__host__ __device__ constexpr int wslot(int k) { return k < 2 ? 3 * k : k < 4 ? 3 * k + 6 : k < 6 ? 21 - 3 * k : 3 * k - 18; }
constexpr uint32_t SM_A = slot(22), A_E = 0u - 32768;
constexpr uint32_t SM_O = slot(18), O_E = 0u - 147456;
constexpr uint32_t SM_WO = slot(10), SM_X = slot(8), SM_KV = slot(9) - 4096;
constexpr uint32_t SM_TAP  = slot(26);
constexpr int TAP_SZ = 3440;
constexpr uint32_t SM_STAT = SM_TAP + 4 * TAP_SZ;
constexpr uint32_t SM_CS   = SM_STAT + 1024;
constexpr uint32_t SM_BAR  = SM_CS + 768;
constexpr int SM_TOTAL = SM_BAR + 352 - SB;
static_assert(SM_TOTAL <= 232448, "");
constexpr int R_SZ = 16384, R_U = 512, R_X5 = 5120, R_X3 = 8704, R_BO = 11776, R_BE = 13824;
constexpr int X_5 = 576, X_3 = 648, T_E = 2 * 720, T_O = 1600 + 2 * 721, T_C = 3390, T_K = 3424;
constexpr uint32_t B_RD = SM_BAR, B_ED = SM_BAR + 16, B_F = SM_BAR + 32, B_AT = SM_BAR + 56, B_L = SM_BAR + 264;
constexpr uint32_t B_AE = SM_BAR + 72, B_QE = SM_BAR + 88, B_ST = SM_BAR + 96, B_CS = SM_BAR + 112;
constexpr uint32_t B_WO = SM_BAR + 120, B_W6 = SM_BAR + 128, B_U = SM_BAR + 144, B_E = SM_BAR + 152, B_WF = SM_BAR + 160, B_W4 = SM_BAR + 168,
                   B_N = SM_BAR + 176, B_V = SM_BAR + 184, B_O = SM_BAR + 192, B_Z = SM_BAR + 256, B_A = SM_BAR + 272;
constexpr int NB_U = 1, NB_B = 2, NB_K = 8, NB_Y = 6, NB_WG = 8, NB_T = 10, NB_AUX = 12, NB_P0 = 13, NB_H = 15;

struct Scratch {
  uint4    XG[2][128 * 1024];
  uint4    O[32 * 8 * 512];
  uint32_t C[8 * 32];
  uint32_t OF[2][32 * 32];
  uint4    CS[16 * 1536 / 4];
  uint4    PS[128 * 64];
  uint4    ST[2][32 * 128];
  uint4    SR[2][8][512];
  uint4    XF[2][32 * 512 * 8];
  uint4    H[2][17 * 8 * 256];
};
__device__ __align__(1024) Scratch g_S;
#define SCR ((Scratch*)(P.mid - offsetof(Scratch, C)))
#define COUNT(k) do {} while (0)
#define PROFD(slot, v) do {} while (0)
#define PROF(slot) do {} while (0)
#define PROFK(slot) do {} while (0)

#define PROFC(slot) do {} while (0)

DEV uint32_t s2u(const void* p) { return (uint32_t)__cvta_generic_to_shared(p); }
template <class T> DEV T* opqp(T* x) { asm volatile("" : "+l"(x)); return x; }
template <class T> DEV T opq(T x) { asm volatile("" : "+r"(x)); return x; }
DEV int lane_id() { int l; asm volatile("mov.u32 %0,%%laneid;" : "=r"(l)); return l; }
DEV uint32_t pack2(float lo, float hi) { uint32_t d; asm("cvt.rn.bf16x2.f32 %0,%1,%2;" : "=r"(d) : "f"(hi), "f"(lo)); return d; }
DEV float bflo(uint32_t v) { return __uint_as_float(v << 16); }
DEV float bfhi(uint32_t v) { return __uint_as_float(v & 0xFFFF0000u); }
DEV float bfr(float x) { return bflo(pack2(x, 0.f)); }
DEV uint32_t hadd2(uint32_t a, uint32_t b) { uint32_t d; asm("add.rn.bf16x2 %0,%1,%2;" : "=r"(d) : "r"(a), "r"(b)); return d; }
DEV uint32_t hsub2(uint32_t a, uint32_t b) { uint32_t d; asm("sub.rn.bf16x2 %0,%1,%2;" : "=r"(d) : "r"(a), "r"(b)); return d; }
DEV uint32_t hmul2(uint32_t a, uint32_t b) { uint32_t d; asm("mul.rn.bf16x2 %0,%1,%2;" : "=r"(d) : "r"(a), "r"(b)); return d; }
DEV uint32_t hfma2(uint32_t a, uint32_t b, uint32_t c) { uint32_t d; asm("fma.rn.bf16x2 %0,%1,%2,%3;" : "=r"(d) : "r"(a), "r"(b), "r"(c)); return d; }
DEV uint32_t prmt(uint32_t a, uint32_t b, uint32_t s) { uint32_t d; asm("prmt.b32 %0,%1,%2,%3;" : "=r"(d) : "r"(a), "r"(b), "r"(s)); return d; }
DEV uint32_t nzmap(uint32_t v) { uint32_t d; asm("max.u32 %0,%1,1;" : "=r"(d) : "r"(v)); return d; }
DEV float rcp(float x) { float y; asm("rcp.approx.ftz.f32 %0,%1;" : "=f"(y) : "f"(x)); return y; }
DEV float sqrt_(float x) { float y; asm("sqrt.approx.ftz.f32 %0,%1;" : "=f"(y) : "f"(x)); return y; }
DEV float ex2(float x) { float y; asm("ex2.approx.ftz.f32 %0,%1;" : "=f"(y) : "f"(x)); return y; }

DEV uint4 ldr4(const void* p) { uint4 v; asm volatile("ld.relaxed.gpu.global.v4.u32 {%0,%1,%2,%3},[%4];" : "=r"(v.x), "=r"(v.y), "=r"(v.z), "=r"(v.w) : "l"(p) : "memory"); return v; }
DEV void ldr4_if(uint4& v, const void* p, bool c) {
  asm volatile("{.reg .pred q; setp.ne.u32 q,%5,0; @q ld.relaxed.gpu.global.v4.u32 {%0,%1,%2,%3},[%4];}"
    : "+r"(v.x), "+r"(v.y), "+r"(v.z), "+r"(v.w) : "l"(p), "r"((uint32_t)c) : "memory");
}
DEV uint2 ldr2(const void* p) { uint2 v; asm volatile("ld.relaxed.gpu.global.v2.u32 {%0,%1},[%2];" : "=r"(v.x), "=r"(v.y) : "l"(p) : "memory"); return v; }
DEV uint32_t ldr1(const void* p) { uint32_t v; asm volatile("ld.relaxed.gpu.global.u32 %0,[%1];" : "=r"(v) : "l"(p) : "memory"); return v; }
DEV float ldnan(const uint16_t* p) {
  uint32_t v = 0xFFFFu;
#pragma unroll 1
  for (int it = 0; it < SPIN_LIMIT && __any_sync(0xffffffffu, v == 0xFFFFu); ++it) asm volatile("ld.relaxed.gpu.global.u16 %0,[%1];" : "=r"(v) : "l"(p) : "memory");
  return __uint_as_float(v << 16);
}
DEV uint4 ldw4(const void* p) { uint4 v; asm volatile("ld.global.v4.u32 {%0,%1,%2,%3},[%4];" : "=r"(v.x), "=r"(v.y), "=r"(v.z), "=r"(v.w) : "l"(p) : "memory"); return v; }
DEV uint32_t ldw1(const void* p) { uint32_t v; asm volatile("ld.global.u32 %0,[%1];" : "=r"(v) : "l"(p) : "memory"); return v; }
DEV void str4(void* p, uint32_t a, uint32_t b, uint32_t c, uint32_t d) { asm volatile("st.relaxed.gpu.global.v4.u32 [%0],{%1,%2,%3,%4};" :: "l"(p), "r"(a), "r"(b), "r"(c), "r"(d) : "memory"); }
DEV void str2(void* p, uint32_t a, uint32_t b) { asm volatile("st.relaxed.gpu.global.v2.u32 [%0],{%1,%2};" :: "l"(p), "r"(a), "r"(b) : "memory"); }
DEV void str1(void* p, uint32_t a) { asm volatile("st.relaxed.gpu.global.u32 [%0],%1;" :: "l"(p), "r"(a) : "memory"); }
DEV void str4_if(void* p, uint32_t a, uint32_t b, uint32_t c, uint32_t d, bool q) {
  asm volatile("{.reg .pred q; setp.ne.u32 q,%5,0; @q st.relaxed.gpu.global.v4.u32 [%0],{%1,%2,%3,%4};}" :: "l"(p), "r"(a), "r"(b), "r"(c), "r"(d), "r"((uint32_t)q) : "memory");
}
DEV void stw4(void* p, uint32_t a, uint32_t b, uint32_t c, uint32_t d) { asm volatile("st.global.v4.u32 [%0],{%1,%2,%3,%4};" :: "l"(p), "r"(a), "r"(b), "r"(c), "r"(d) : "memory"); }
DEV uint4 ldnc4(const void* p) { uint4 v; asm volatile("ld.global.nc.v4.u32 {%0,%1,%2,%3},[%4];" : "=r"(v.x), "=r"(v.y), "=r"(v.z), "=r"(v.w) : "l"(p)); return v; }

DEV uint2 lds2(uint32_t a) { uint2 v; asm volatile("ld.volatile.shared.v2.u32 {%0,%1},[%2];" : "=r"(v.x), "=r"(v.y) : "r"(a)); return v; }
DEV void sts2(uint32_t a, uint32_t x, uint32_t y) { asm volatile("st.shared.v2.u32 [%0],{%1,%2};" :: "r"(a), "r"(x), "r"(y) : "memory"); }
DEV uint32_t lds1(uint32_t a) { uint32_t v; asm volatile("ld.volatile.shared.u32 %0,[%1];" : "=r"(v) : "r"(a)); return v; }
DEV uint32_t lds1z(uint32_t a, bool c) {
  uint32_t v; asm volatile("{.reg .pred q; setp.ne.u32 q,%2,0; mov.u32 %0,0; @q ld.volatile.shared.u32 %0,[%1];}" : "=r"(v) : "r"(a), "r"((uint32_t)c)); return v;
}
DEV uint4 lds4z(uint32_t a, bool c) {
  uint4 v = make_uint4(0, 0, 0, 0);
  asm volatile("{.reg .pred q; setp.ne.u32 q,%5,0; @q ld.volatile.shared.v4.u32 {%0,%1,%2,%3},[%4];}" : "+r"(v.x), "+r"(v.y), "+r"(v.z), "+r"(v.w) : "r"(a), "r"((uint32_t)c));
  return v;
}
DEV float2 lds2f(uint32_t a) { float2 v; asm volatile("ld.shared.v2.f32 {%0,%1},[%2];" : "=f"(v.x), "=f"(v.y) : "r"(a)); return v; }
DEV float4 lds4f(uint32_t a) { float4 v; asm volatile("ld.volatile.shared.v4.f32 {%0,%1,%2,%3},[%4];" : "=f"(v.x), "=f"(v.y), "=f"(v.z), "=f"(v.w) : "r"(a)); return v; }
DEV uint4 lds4(uint32_t a) { uint4 v; asm volatile("ld.volatile.shared.v4.u32 {%0,%1,%2,%3},[%4];" : "=r"(v.x), "=r"(v.y), "=r"(v.z), "=r"(v.w) : "r"(a)); return v; }
DEV void sts1(uint32_t a, uint32_t v) { asm volatile("st.shared.u32 [%0],%1;" :: "r"(a), "r"(v) : "memory"); }
DEV void sts16(uint32_t a, uint32_t v) { asm volatile("st.shared.u16 [%0],%1;" :: "r"(a), "r"(v) : "memory"); }
DEV void sts2f(uint32_t a, float x, float y) { asm volatile("st.shared.v2.f32 [%0],{%1,%2};" :: "r"(a), "f"(x), "f"(y) : "memory"); }
DEV void sts4f(uint32_t a, float x, float y, float z, float w) { asm volatile("st.shared.v4.f32 [%0],{%1,%2,%3,%4};" :: "r"(a), "f"(x), "f"(y), "f"(z), "f"(w) : "memory"); }
DEV void sts4(uint32_t a, uint32_t x, uint32_t y, uint32_t z, uint32_t w) { asm volatile("st.shared.v4.u32 [%0],{%1,%2,%3,%4};" :: "r"(a), "r"(x), "r"(y), "r"(z), "r"(w) : "memory"); }

DEV void ldsm4(uint32_t (&r)[4], uint32_t a) { asm volatile("ldmatrix.sync.aligned.m8n8.x4.shared.b16 {%0,%1,%2,%3},[%4];" : "=r"(r[0]), "=r"(r[1]), "=r"(r[2]), "=r"(r[3]) : "r"(a) : "memory"); }
DEV void ldsm4t(uint32_t (&r)[4], uint32_t a) { asm volatile("ldmatrix.sync.aligned.m8n8.x4.trans.shared.b16 {%0,%1,%2,%3},[%4];" : "=r"(r[0]), "=r"(r[1]), "=r"(r[2]), "=r"(r[3]) : "r"(a) : "memory"); }
DEV void stsm4(uint32_t a, uint32_t r0, uint32_t r1, uint32_t r2, uint32_t r3) { asm volatile("stmatrix.sync.aligned.m8n8.x4.shared.b16 [%0],{%1,%2,%3,%4};" :: "r"(a), "r"(r0), "r"(r1), "r"(r2), "r"(r3) : "memory"); }
DEV void stsm2(uint32_t a, uint32_t r0, uint32_t r1) { asm volatile("stmatrix.sync.aligned.m8n8.x2.shared.b16 [%0],{%1,%2};" :: "r"(a), "r"(r0), "r"(r1) : "memory"); }
DEV void stsm4t(uint32_t a, uint32_t r0, uint32_t r1, uint32_t r2, uint32_t r3) { asm volatile("stmatrix.sync.aligned.m8n8.x4.trans.shared.b16 [%0],{%1,%2,%3,%4};" :: "r"(a), "r"(r0), "r"(r1), "r"(r2), "r"(r3) : "memory"); }
DEV uint32_t movm(uint32_t a) { uint32_t d; asm volatile("movmatrix.sync.aligned.m8n8.trans.b16 %0,%1;" : "=r"(d) : "r"(a)); return d; }
DEV void mma16(float (&d)[4], uint32_t a0, uint32_t a1, uint32_t a2, uint32_t a3, uint32_t b0, uint32_t b1) {
  asm volatile("mma.sync.aligned.m16n8k16.row.col.f32.bf16.bf16.f32 {%0,%1,%2,%3},{%4,%5,%6,%7},{%8,%9},{%0,%1,%2,%3};"
    : "+f"(d[0]), "+f"(d[1]), "+f"(d[2]), "+f"(d[3]) : "r"(a0), "r"(a1), "r"(a2), "r"(a3), "r"(b0), "r"(b1));
}
DEV void mma16z(float (&d)[4], uint32_t a0, uint32_t a1, uint32_t a2, uint32_t a3, uint32_t b0, uint32_t b1) {
  asm volatile("mma.sync.aligned.m16n8k16.row.col.f32.bf16.bf16.f32 {%0,%1,%2,%3},{%4,%5,%6,%7},{%8,%9},{%10,%10,%10,%10};"
    : "=f"(d[0]), "=f"(d[1]), "=f"(d[2]), "=f"(d[3]) : "r"(a0), "r"(a1), "r"(a2), "r"(a3), "r"(b0), "r"(b1), "f"(0.f));
}
DEV void mma8(float (&d)[4], uint32_t a0, uint32_t a1, uint32_t b0) {
  asm volatile("mma.sync.aligned.m16n8k8.row.col.f32.bf16.bf16.f32 {%0,%1,%2,%3},{%4,%5},{%6},{%0,%1,%2,%3};"
    : "+f"(d[0]), "+f"(d[1]), "+f"(d[2]), "+f"(d[3]) : "r"(a0), "r"(a1), "r"(b0));
}

DEV void mma8z(float (&d)[4], uint32_t a0, uint32_t a1, uint32_t b0) {
  asm volatile("mma.sync.aligned.m16n8k8.row.col.f32.bf16.bf16.f32 {%0,%1,%2,%3},{%4,%5},{%6},{%7,%7,%7,%7};"
    : "=f"(d[0]), "=f"(d[1]), "=f"(d[2]), "=f"(d[3]) : "r"(a0), "r"(a1), "r"(b0), "f"(0.f));
}
DEV void bar_sync(int id, int n) { asm volatile("bar.sync %0,%1;" :: "r"(id), "r"(n) : "memory"); }
DEV void bar_sync_if(int id, int n, int c) { asm volatile("{.reg .pred q; setp.ne.s32 q,%2,0; @q bar.sync %0,%1;}" :: "r"(id), "r"(n), "r"(c) : "memory"); }
DEV void bar_arrive_if(int id, int n, int c) { asm volatile("{.reg .pred q; setp.ne.s32 q,%2,0; @q bar.arrive %0,%1;}" :: "r"(id), "r"(n), "r"(c) : "memory"); }
DEV void bar_arrive(int id, int n) { asm volatile("bar.arrive %0,%1;" :: "r"(id), "r"(n) : "memory"); }
DEV void fence_async_smem() { asm volatile("fence.proxy.async.shared::cta;" ::: "memory"); }
DEV void mbar_wait(uint32_t b, uint32_t ph) {
  asm volatile("{\n.reg .pred p;\nW: mbarrier.try_wait.parity.shared::cta.b64 p,[%0],%1;\n@!p bra W;\n}" :: "r"(b), "r"(ph) : "memory");
}
DEV void mbar_watch(uint32_t b, uint32_t ph) {
  asm volatile("{\n.reg .pred p,q;\n.reg .u32 n;\nmov.u32 n,0;\n"
               "W: mbarrier.try_wait.parity.shared::cta.b64 p,[%0],%1;\n@p bra D;\n"
               "add.u32 n,n,1;\nsetp.lt.u32 q,n,%2;\n@q bra W;\ntrap;\nD:\n}"
               :: "r"(b), "r"(ph), "n"(SPIN_LIMIT) : "memory");
}
DEV void spin_guard(int it) { asm volatile("{.reg .pred p; setp.gt.s32 p,%0,%1; @p trap;}" :: "r"(it), "n"(SPIN_LIMIT)); }
DEV void split(uint32_t zero) {
  asm volatile("{.reg .pred p; setp.ne.u32 p,%0,0; @p trap;}" :: "r"(zero) : "memory");
}
DEV void pause(int n) {
  uint32_t t0, t; asm volatile("mov.u32 %0,%%clock;" : "=r"(t0));
  do asm volatile("mov.u32 %0,%%clock;" : "=r"(t)); while (t - t0 < n);
}
DEV void poll(const uint32_t* k, uint32_t n) {
#pragma unroll 1
  for (int it = 0;; ++it) {
    spin_guard(it);
    if (__all_sync(0xffffffffu, ldr1(k) >= n)) break;
  }
}
DEV void mbar_arrive1(uint32_t b) { asm volatile("{.reg .pred p; elect.sync _|p,0xffffffff; @p mbarrier.arrive.shared::cta.b64 _,[%0];}" :: "r"(b) : "memory"); }
DEV void mbar_arrive1_if(uint32_t b, int c) {
  asm volatile("{.reg .pred p,q; setp.ne.s32 q,%1,0; elect.sync _|p,0xffffffff; and.pred p,p,q; @p mbarrier.arrive.shared::cta.b64 _,[%0];}" :: "r"(b), "r"(c) : "memory");
}
DEV void mbar_expect1(uint32_t b, int bytes) { asm volatile("{.reg .pred p; elect.sync _|p,0xffffffff; @p mbarrier.arrive.expect_tx.shared::cta.b64 _,[%0],%1;}" :: "r"(b), "r"(bytes) : "memory"); }
DEV void cnt_add1(uint32_t* q) { asm volatile("{.reg .pred p; elect.sync _|p,0xffffffff; @p red.relaxed.gpu.global.add.u32 [%0],1;}" :: "l"(q) : "memory"); }
DEV void tma4(uint32_t dst, const CUtensorMap* m, int c0, int c1, int c2, int c3, uint32_t bar) {
  asm volatile("{.reg .pred p; elect.sync _|p,0xffffffff;\n"
    "@p cp.async.bulk.tensor.4d.shared::cluster.global.mbarrier::complete_tx::bytes [%0],[%1,{%2,%3,%4,%5}],[%6];}"
    :: "r"(dst), "l"(m), "r"(c0), "r"(c1), "r"(c2), "r"(c3), "r"(bar) : "memory");
}
DEV void tma3(uint32_t dst, const CUtensorMap* m, int c0, int c1, int c2, uint32_t bar) {
  asm volatile("{.reg .pred p; elect.sync _|p,0xffffffff;\n"
    "@p cp.async.bulk.tensor.3d.shared::cluster.global.mbarrier::complete_tx::bytes [%0],[%1,{%2,%3,%4}],[%5];}"
    :: "r"(dst), "l"(m), "r"(c0), "r"(c1), "r"(c2), "r"(bar) : "memory");
}
DEV void bulk(uint32_t dst, const void* src, int bytes, uint32_t bar) {
  asm volatile("{.reg .pred p; elect.sync _|p,0xffffffff;\n@p cp.async.bulk.shared::cluster.global.mbarrier::complete_tx::bytes [%0],[%1],%2,[%3];}" :: "r"(dst), "l"(src), "r"(bytes), "r"(bar) : "memory");
}

DEV void bulk_store(void* dst, uint32_t src, int bytes) {
  asm volatile("{.reg .pred p; elect.sync _|p,0xffffffff;\n@p cp.async.bulk.global.shared::cta.bulk_group [%0],[%1],%2;}" :: "l"(dst), "r"(src), "r"(bytes) : "memory");
}
DEV void tma2_store(const CUtensorMap* m, uint32_t src, int c0, int c1) {
  asm volatile("{.reg .pred p; elect.sync _|p,0xffffffff;\n@p cp.async.bulk.tensor.2d.global.shared::cta.bulk_group [%0,{%2,%3}],[%1];}" :: "l"(m), "r"(src), "r"(c0), "r"(c1) : "memory");
}
DEV void bulk_wait() { asm volatile("cp.async.bulk.commit_group;\ncp.async.bulk.wait_group 0;\nfence.proxy.async.global;" ::: "memory"); }

DEV uint32_t dlo(uint32_t addr, uint32_t lbo) { return __shfl_sync(0xffffffffu, (addr >> 4) | ((lbo >> 4) << 16), 0); }
__host__ __device__ constexpr uint32_t dhi(uint32_t sbo, uint32_t swz) { return (sbo >> 4) | (swz << 30); }
DEV void wg_fence() { asm volatile("wgmma.fence.sync.aligned;" ::: "memory"); }
DEV void wg_commit() { asm volatile("wgmma.commit_group.sync.aligned;" ::: "memory"); }
template <int N> DEV void wg_wait() { asm volatile("wgmma.wait_group.sync.aligned %0;" :: "n"(N) : "memory"); }
template <int N> DEV void zero(float (&d)[N]) {
#pragma unroll
  for (int i = 0; i < N; ++i) d[i] = 0.f;
}
template <int N> DEV void zerov(float (&d)[N]) {
#pragma unroll
  for (int i = 0; i < N; ++i) asm volatile("mov.b32 %0,0;" : "=f"(d[i]));
}
template <int N> DEV void undef(float (&d)[N]) {
#pragma unroll
  for (int i = 0; i < N; ++i) asm volatile("" : "=f"(d[i]));
}
#define R4(d, o) "+f"(d[o]), "+f"(d[o + 1]), "+f"(d[o + 2]), "+f"(d[o + 3])
#define R8(d, o) R4(d, o), R4(d, o + 4)
#define R16(d, o) R8(d, o), R8(d, o + 8)
template <int ACC> DEV void wg_rs64k(float (&d)[32], const uint32_t (&a)[4], uint32_t db) {
  asm volatile("{.reg .pred p; .reg .b64 b; setp.ne.s32 p,%38,0; mov.b64 b,{%36,%37};\n"
    "wgmma.mma_async.sync.aligned.m64n64k16.f32.bf16.bf16 {%0,%1,%2,%3,%4,%5,%6,%7,%8,%9,%10,%11,%12,%13,%14,%15,%16,%17,%18,%19,%20,%21,%22,%23,%24,%25,%26,%27,%28,%29,%30,%31},{%32,%33,%34,%35},b,p,1,1,0;}"
    : R16(d, 0), R16(d, 16) : "r"(a[0]), "r"(a[1]), "r"(a[2]), "r"(a[3]), "r"(db), "n"(dhi(512, 2)), "n"(ACC));
}
template <int ACC> DEV void wg_rs48t(float (&d)[24], const uint32_t (&a)[4], uint32_t db) {
  asm volatile("{.reg .pred p; .reg .b64 b; setp.ne.s32 p,%30,0; mov.b64 b,{%28,%29};\n"
    "wgmma.mma_async.sync.aligned.m64n48k16.f32.bf16.bf16 {%0,%1,%2,%3,%4,%5,%6,%7,%8,%9,%10,%11,%12,%13,%14,%15,%16,%17,%18,%19,%20,%21,%22,%23},{%24,%25,%26,%27},b,p,1,1,1;}"
    : R16(d, 0), R8(d, 16) : "r"(a[0]), "r"(a[1]), "r"(a[2]), "r"(a[3]), "r"(db), "n"(dhi(512, 0)), "n"(ACC));
}
template <int ACC> DEV void wg_rs32t(float (&d)[16], const uint32_t (&a)[4], uint32_t db) {
  asm volatile("{.reg .pred p; .reg .b64 b; setp.ne.s32 p,%22,0; mov.b64 b,{%20,%21};\n"
    "wgmma.mma_async.sync.aligned.m64n32k16.f32.bf16.bf16 {%0,%1,%2,%3,%4,%5,%6,%7,%8,%9,%10,%11,%12,%13,%14,%15},{%16,%17,%18,%19},b,p,1,1,1;}"
    : R16(d, 0) : "r"(a[0]), "r"(a[1]), "r"(a[2]), "r"(a[3]), "r"(db), "n"(dhi(1024, 0)), "n"(ACC));
}
template <int ACC> DEV void wg_ss192(float (&d)[96], uint32_t da, uint32_t db) {
  asm volatile("{.reg .pred p; .reg .b64 a,b; setp.ne.s32 p,%100,0; mov.b64 a,{%96,%98}; mov.b64 b,{%97,%99};\n"
    "wgmma.mma_async.sync.aligned.m64n192k16.f32.bf16.bf16 {"
    "%0,%1,%2,%3,%4,%5,%6,%7,%8,%9,%10,%11,%12,%13,%14,%15,%16,%17,%18,%19,%20,%21,%22,%23,%24,%25,%26,%27,%28,%29,%30,%31,"
    "%32,%33,%34,%35,%36,%37,%38,%39,%40,%41,%42,%43,%44,%45,%46,%47,%48,%49,%50,%51,%52,%53,%54,%55,%56,%57,%58,%59,%60,%61,%62,%63,"
    "%64,%65,%66,%67,%68,%69,%70,%71,%72,%73,%74,%75,%76,%77,%78,%79,%80,%81,%82,%83,%84,%85,%86,%87,%88,%89,%90,%91,%92,%93,%94,%95},a,b,p,1,1,1,1;}"
    : R16(d, 0), R16(d, 16), R16(d, 32), R16(d, 48), R16(d, 64), R16(d, 80) : "r"(da), "r"(db), "n"(dhi(1024, 1)), "n"(dhi(1024, 1)), "n"(ACC));
}
template <int ACC> DEV void wg_ss64(float (&d)[32], uint32_t da, uint32_t db) {
  asm volatile("{.reg .pred p; .reg .b64 a,b; setp.ne.s32 p,%36,0; mov.b64 a,{%32,%34}; mov.b64 b,{%33,%35};\n"
    "wgmma.mma_async.sync.aligned.m64n64k16.f32.bf16.bf16 {"
    "%0,%1,%2,%3,%4,%5,%6,%7,%8,%9,%10,%11,%12,%13,%14,%15,%16,%17,%18,%19,%20,%21,%22,%23,%24,%25,%26,%27,%28,%29,%30,%31},a,b,p,1,1,0,1;}"
    : R16(d, 0), R16(d, 16) : "r"(da), "r"(db), "n"(dhi(1024, 0)), "n"(dhi(1024, 1)), "n"(ACC));
}

DEV uint32_t cpy(uint32_t v, uint32_t id) {
  uint32_t d; asm volatile("prmt.b32 %0,%1,%1,%2;" : "=r"(d) : "r"(v), "r"(id)); return d;
}
struct Params {
  uint32_t zero, spare;
  char* mid;
  const uint16_t *x0, *Are, *Aim, *Bre, *Bim, *Cre, *Cim, *logdt, *dskip, *wqkv, *wo;
  uint16_t* out;
  uint8_t role[72];
};

DEV uint32_t ln_word(float mean, float var) {
  float v = bfr(var);
  float s = sqrt_(bfr(v + 1e-5f));
  return pack2(mean, s);
}

DEV int stat_group(int c) { return c ^ 4; }
DEV int xg_off(int G, int g) { return (G >> 5) * 512 + (G & 31) * 8 + (g ^ (G & 2)); }
DEV int sr_off(int G, int g) { return (G >> 6) * 256 + (g & 2) * 64 + 2 * (G & 63) + ((g >> 2) & 1); }
DEV uint32_t region(int chl) { return SM_A + (chl >> 1) * A_E + (chl & 1) * R_SZ; }
template <bool FIRST> DEV void gram(float (&s)[4], float (&q0)[4], float (&q1)[4], uint32_t a0, uint32_t a1, uint32_t a2, uint32_t a3) {
  const uint32_t one = 0x3F803F80u;
  if (FIRST) { mma16z(s, a0, a1, a2, a3, one, one); mma8z(q0, a0, a1, a0); mma8z(q1, a0, a1, a1); }
  else { mma16(s, a0, a1, a2, a3, one, one); mma8(q0, a0, a1, a0); mma8(q1, a0, a1, a1); }
  mma8(q0, a2, a3, a2); mma8(q1, a2, a3, a3);
}
DEV uint32_t ln_sums(float s, float q) { const float m = s * (1.f / 512.f); return ln_word(m, fmaxf(q * (1.f / 512.f) - m * m, 0.f)); }
DEV void cmul(float& orr, float& oi, float ar, float ai, float br, float bi) {
  float r = ar * br - ai * bi, i = ar * bi + ai * br; orr = r; oi = i;
}
DEV void cexp_(float al, float bt, float s, float& er, float& ei) {
  float mag = ex2(al * s), ph = bt * s;
  ph -= rintf(ph);
  float ang = ph * 6.283185307179586f;
  er = mag * __cosf(ang); ei = mag * __sinf(ang);
}

DEV void kgen(const Params& P, int c, int wm, int lane) {
  const int chl = wm >> 1, mh = wm & 1, g = lane >> 2, t = lane & 3;
  const int ch = 256 * (chl >> 1) + 2 * c + (chl & 1);
  const int mo = ch * 64 + mh * 32 + lane;
  const uint32_t vAr = ldw1((const uint32_t*)P.Are + mo), vAi = ldw1((const uint32_t*)P.Aim + mo);
  const uint32_t vBr = ldw1((const uint32_t*)P.Bre + mo), vBi = ldw1((const uint32_t*)P.Bim + mo);
  const uint32_t vCr = ldw1((const uint32_t*)P.Cre + mo), vCi = ldw1((const uint32_t*)P.Cim + mo);
  const uint32_t vld = ldw1((const uint32_t*)P.logdt + (ch >> 1)), vds = ldw1((const uint32_t*)P.dskip + (ch >> 1));
  bar_arrive(NB_Y, 384);
  PROF(45);
  {
    const uint32_t tz = SM_TAP + chl * TAP_SZ + (mh * 32 + lane) * 16;
#pragma unroll
    for (int k = 0; k < 3; ++k) sts4(tz + k * 1024, 0, 0, 0, 0);
    static_assert(TAP_SZ > 3072 && TAP_SZ <= 4096, "");
    if (mh * 32 + lane < TAP_SZ / 16 - 192) sts4(tz + 3072, 0, 0, 0, 0);
  }
  const uint32_t tb = slot(wm), tw = opq(tb + lane * 4);
  const uint32_t aa = opq(tb + (lane & 15) * 144 + (lane >> 4) * 16), ba = opq(tb + (16 + (lane & 7)) * 144 + (lane >> 3) * 16);
  float acc[5][4], k2048 = 0.f;
#pragma unroll
  for (int i = 0; i < 5; ++i) zerov(acc[i]);
  sts1(tw, 0x3F80u);
  asm volatile("setmaxnreg.inc.sync.aligned.u32 %0;" :: "n"(REG_MAIN));
  PROF(44);
  const float dt = bfr(ex2((ch & 1 ? bfhi(vld) : bflo(vld)) * 1.4426950408889634f));
#pragma unroll 1
  for (int r = 0; r < 2; ++r) {
    const uint32_t sel = r ? 0x3244 : 0x1044;
    const float are = __uint_as_float(prmt(vAr, 0, sel)), aim = __uint_as_float(prmt(vAi, 0, sel)), bre = __uint_as_float(prmt(vBr, 0, sel));
    const float bim = __uint_as_float(prmt(vBi, 0, sel)), cre = __uint_as_float(prmt(vCr, 0, sel)), cim = __uint_as_float(prmt(vCi, 0, sel));
    const float al = dt * are * 1.4426950408889634f, bt = dt * aim * 0.15915494309189535f;
    float qr, qi; cmul(qr, qi, cre, cim, dt * bre, dt * bim);
    if (r == 0) PROFD(2, __float_as_uint(qr + al + bt));
    float er[3], ei[3], e8r, e8i, eLr, eLi;
    cexp_(al, bt, 1.f, er[0], ei[0]); cexp_(al, -bt, 8.f, e8r, e8i); cexp_(al, bt, 128.f, eLr, eLi);
    cmul(er[1], ei[1], er[0], ei[0], er[0], ei[0]); cmul(er[2], ei[2], er[1], ei[1], er[1], ei[1]);
    float yr = e8r, yi = e8i;
#pragma unroll
    for (int a = 0; a < 16; ++a) {
      if (a) sts1(tw + a * 144, pack2(yr, yi));
      if (a && a < 15) cmul(yr, yi, yr, yi, e8r, e8i);
      const int ls = a < 2 ? 0 : a < 4 ? 1 : a < 8 ? 2 : 3;
      const int row0 = 16 + (a < 2 ? 8 * a : a < 4 ? 16 + 4 * (a - 2) : a < 8 ? 24 + 2 * (a - 4) : 32 + (a - 8));
      float xr[8], xi[8];
      xr[0] = qr; xi[0] = qi;
#pragma unroll
      for (int k = 0; k < (8 >> ls); ++k) {
        const int hb = k >= 4 ? 2 : k >= 2 ? 1 : 0;
        if (k) cmul(xr[k], xi[k], xr[k - (1 << hb)], xi[k - (1 << hb)], er[(ls + hb) % 3], ei[(ls + hb) % 3]);
        sts1(tw + (row0 + k) * 144, pack2(xr[k], xi[k]));
      }
      cmul(qr, qi, qr, qi, eLr, eLi);
    }
    __syncwarp();
    if (r == 0) PROF(3);
#pragma unroll
    for (int kp = 0; kp < 2; ++kp) {
      uint32_t a0[4], a1[4];
      ldsm4(a0, aa + kp * 64); ldsm4(a1, aa + kp * 64 + 32);
#pragma unroll
      for (int tl = 0; tl < 5; ++tl) {
        uint32_t b[4];
        ldsm4(b, ba + 8 * tl * 144 + kp * 64);
        if (kp == 0) qr += __shfl_xor_sync(0xffffffffu, qr, 1 << tl);
        mma16(acc[tl], a0[0], a0[1], a0[2], a0[3], b[0], b[1]);
        mma16(acc[tl], a1[0], a1[1], a1[2], a1[3], b[2], b[3]);
      }
    }
    k2048 += qr;
    __syncwarp();
  }
  const uint32_t xa = tb + lane * 16, ob = xa ^ 8192, tp = SM_TAP + chl * TAP_SZ;
  if (mh == 0) {
    sts4f(xa, acc[2][0], acc[2][1], acc[2][2], acc[2][3]);
    sts4f(xa + 512, acc[3][0], acc[3][1], acc[3][2], acc[3][3]);
    sts1(tb + 1024, __float_as_uint(k2048));
  } else {
    sts4f(xa, acc[0][0], acc[0][1], acc[0][2], acc[0][3]);
    sts4f(xa + 512, acc[1][0], acc[1][1], acc[1][2], acc[1][3]);
    sts4f(xa + 1024, acc[4][0], acc[4][1], acc[4][2], acc[4][3]);
  }
  PROF(4);
  bar_sync(NB_K + chl, 64);
  float4 o[3];
#pragma unroll
  for (int k = 0; k < 3; ++k) o[k] = lds4f(ob + k * 512);
  if (mh == 0) {
    if (lane == 0) o[0].x += ch & 1 ? bfhi(vds) : bflo(vds);
    const uint32_t a = tp - 2 * (8 * g + 2 * t + 1);
#pragma unroll
    for (int z = 0; z < 4; ++z) {
      const float* k = acc[z >> 1] + 2 * (z & 1);
      const uint32_t v = z & 1 ? pack2(k[1] + o[z >> 1].w, k[0] + o[z >> 1].z) : pack2(k[1] + o[z >> 1].y, k[0] + o[z >> 1].x);
      sts1(a + T_O - 128 * z, v); sts16(a + T_E - 128 * z, v); sts16(a + T_E + 2 - 128 * z, v >> 16);
    }
    const uint32_t v0 = pack2(acc[4][0] + o[2].x, acc[4][1] + o[2].y), v1 = pack2(acc[4][2] + o[2].z, acc[4][3] + o[2].w);
    const uint32_t b = tp + T_C - 2 * (32 * t + g - 1);
    if (lane == 0) { sts16(tp + T_E - 2 * (X_5 + 63), v0); sts16(tp + T_O - 2 * (X_5 + 63), v0); sts1(tp + T_K, prmt(v0, v0, 0x1010)); }
    else sts16(b, v0);
    sts16(b - 32, v0 >> 16); sts16(b - 16, v1); sts16(b - 48, v1 >> 16);
  } else {
    const uint32_t a = tp - 2 * (256 + 128 * (t >> 1) + 4 * (t & 1) + 8 * g);
#pragma unroll
    for (int z = 0; z < 2; ++z) {
      const uint32_t v = z ? pack2(acc[2][3] + o[0].w, acc[2][2] + o[0].z) : pack2(acc[2][1] + o[0].y, acc[2][0] + o[0].x), d = prmt(v, v, 0x3232);
      sts1(a + T_E - 4 - 128 * z, v); sts16(a + T_O - 4 - 128 * z, v); sts1(a + T_O - 2 - 128 * z, d);
      if (z || lane) { sts1(a + T_E - 128 * z, d); sts16(a + T_O + 2 - 128 * z, d); } else sts16(a + T_E, d);
    }
    const uint32_t w0 = pack2(acc[3][0] + o[1].x, acc[3][1] + o[1].y), w1 = pack2(acc[3][2] + o[1].z, acc[3][3] + o[1].w);
    const uint32_t b = tp - 2 * (16 * t + g);
    if (lane == 0) {
      const uint32_t k = prmt(w0, w0, 0x1010);
      sts1(tp + T_E - 2 * 514, k); sts1(tp + T_E - 2 * 512, k);
      sts16(tp + T_O - 2 * 514, k); sts1(tp + T_O - 2 * 513, k); sts16(tp + T_O - 2 * 511, k);
      sts16(tp + T_C - 2 * 127, pack2(k2048 + o[2].x, 0.f));
    } else { sts16(b + T_E - 2 * (X_5 - 1), w0); sts16(b + T_O - 2 * (X_5 - 1), w0); }
    sts16(b + T_E - 2 * X_3, w0 >> 16); sts16(b + T_O - 2 * X_3, w0 >> 16);
    sts16(b + T_E - 2 * (X_5 + 7), w1); sts16(b + T_O - 2 * (X_5 + 7), w1);
    sts16(b + T_E - 2 * (X_3 + 8), w1 >> 16); sts16(b + T_O - 2 * (X_3 + 8), w1 >> 16);
  }
}

DEV bool bad8(const uint4& v) { return min(v.x, v.z) == 0u; }
DEV uint32_t uchunk(uint32_t reg, int x) { return reg + R_U + (x ^ ((x >> 3) & 3)) * 16; }
DEV uint32_t& xword(uint4 (&x)[2], int e, int tp) { uint4& v = x[tp >> 1]; return tp & 1 ? (e ? v.w : v.z) : (e ? v.y : v.x); }

DEV void uprep(const Params& P, int c, int wa, int lane, int layer, uint4 (&x)[2][2][2], uint32_t (&u)[4][4]) {
  const int j = 32 * wa + lane, o0 = 2 * (j + (j & 64)) + ((j >> 2) & 1);
  {
    const uint32_t za = region(wa) + lane * 16 - 512;
    sts4(za + R_U, 0, 0, 0, 0); sts4(za + R_X5, 0, 0, 0, 0); sts4(za + R_X3, 0, 0, 0, 0);
    sts4(region(wa) + R_BE, 0, 0, 0, 0);
  }
  const uint4* st = opqp(&SCR->SR[layer][c >> 4][j]);
  const uint32_t xa = opq(SM_X + 16 * o0), xb = opq(SM_X + 16 * (o0 ^ 1)), ua = opq(uchunk(0, j));
  uint4 s[2][2];
#pragma unroll
  for (int z = 0; z < 12; ++z) {
    uint4& v = z < 8 ? x[(z >> 2) & 1][(z >> 1) & 1][z & 1] : s[(z >> 1) & 1][z & 1];
    asm volatile("mov.b32 %0,0; mov.b32 %1,0; mov.b32 %2,0; mov.b32 %3,0;" : "=r"(v.x), "=r"(v.y), "=r"(v.z), "=r"(v.w));
  }
#pragma unroll 1
  for (uint32_t it = P.zero;; ++it) {
    if (it) {
      spin_guard(it);
      COUNT(3);
#pragma unroll
      for (int z = 0; z < 4; ++z) { uint4& v = s[z >> 1][z & 1]; ldr4_if(v, st + z * 128, bad8(v)); }
      const uint4* xp = &SCR->XG[layer][c * 1024 + o0];
#pragma unroll
      for (int z = 0; z < 8; ++z) {
        uint4& v = x[z >> 2][(z >> 1) & 1][z & 1];
        ldr4_if(v, (const uint4*)((uintptr_t)xp ^ (16 * (z & 1))) + (z >> 2) * 512 + (z & 2) * 64, bad8(v));
      }
    } else {
      mbar_wait(B_U, layer);
      PROF(layer ? 25 : 10);
#pragma unroll
      for (int z = 0; z < 4; ++z) s[z >> 1][z & 1] = ldr4(st + z * 128);
#pragma unroll
      for (int z = 0; z < 4; ++z) { uint4& v = s[z >> 1][z & 1]; ldr4_if(v, st + z * 128, bad8(v)); }
      PROF(layer ? 26 : 11);
      mbar_wait(B_E, layer);
#pragma unroll
      for (int z = 7; z >= 0; --z) x[z >> 2][(z >> 1) & 1][z & 1] = lds4((z & 1 ? xb : xa) + (z >> 2) * 8192 + (z & 2) * 1024);
      PROF(layer ? 27 : 14);
    }
    uint32_t m = ~0u;
#pragma unroll
    for (int z = 7; z >= 0; --z) {
      const int k = z >> 2, chl = z & 3;
#pragma unroll
      for (int tp = 0; tp < 4; ++tp) u[chl][tp] = hmul2(hsub2(xword(x[k][chl >> 1], chl & 1, tp), xword(s[k], 1, tp)), xword(s[k], 0, tp));
      sts4(ua + region(chl) + k * 2048, u[chl][0], u[chl][1], u[chl][2], u[chl][3]);
      const uint4& v = x[k][chl >> 1][chl & 1];
      m = min(m, min(v.x, v.z));
      if (z < 4) m = min(m, min(s[z >> 1][z & 1].x, s[z >> 1][z & 1].z));
    }
    if (!__any_sync(0xffffffffu, m == 0)) break;
  }
  PROF(4 + 12 * layer);
}

template <bool FULL> DEV void box_unit(uint32_t reg, int s, const uint2& a, const uint4& b, const uint32_t (&d)[4], uint32_t (&pv)[4]) {
  const uint32_t u[9] = {a.x, a.y, b.x, b.y, b.z, b.w, d[0], d[1], d[2]};
  uint32_t v[8], p[8];
#pragma unroll
  for (int j = 0; j < 8; ++j) { v[j] = prmt(u[j], u[j + 1], 0x5432); p[j] = hadd2(u[j], v[j]); }
  const uint32_t o = reg + s * 16;
  uint32_t x[4], y[4];
#pragma unroll
  for (int j = 0; j < 4; ++j) { x[j] = hadd2(hadd2(p[1 + j], p[2 + j]), u[3 + j]); y[j] = hadd2(v[3 + j], p[4 + j]); pv[j] = p[4 + j]; }
  sts4(o + R_X5, x[0], x[1], x[2], x[3]);
  sts4(o + R_X3, y[0], y[1], y[2], y[3]);
  if (FULL) {
#pragma unroll
    for (int j = 0; j < 4; ++j) { y[j] = hadd2(hadd2(v[j], v[3 + j]), x[j]); x[j] = hadd2(hadd2(u[j], u[4 + j]), y[j]); }
    const bool od = s & 1;
    sts4(o + R_BO, od ? y[0] : x[0], od ? y[1] : x[1], od ? y[2] : x[2], od ? y[3] : x[3]);
    sts4(o + R_BE + 16, od ? x[0] : y[0], od ? x[1] : y[1], od ? x[2] : y[2], od ? x[3] : y[3]);
  }
}
#define NBB(e) (320 - 32 * (e))
template <int C0, int C1> DEV void box_full(int j, uint32_t (&u)[4][4], uint32_t zero) {
  const uint32_t a2 = uchunk(8, j - 2), a1 = uchunk(0, j - 1);
  uint2 a[4]; uint4 b[4];
#define HALO(n) if (n < C1) { a[(n) & 3] = lds2(region(n) + a2); b[(n) & 3] = lds4(region(n) + a1); }
  HALO(C0) HALO(C0 + 1)
  split(zero);
#pragma unroll
  for (int chl = C0; chl < C1; ++chl) {
    const uint32_t d[4] = {u[chl][0], u[chl][1], u[chl][2], u[chl][3]};
    box_unit<true>(region(chl), j, a[chl], b[chl], d, u[chl]);
    fence_async_smem();
    bar_arrive(NB_B + chl, NBB(chl & 1));
    PROFC(28 + chl);
    if (chl == C0) { HALO(C0 + 2) }
  }
#undef HALO
}
DEV void box_help(int e, int n0, int dn, int lane, int layer) {
  bar_sync(NB_H, 224);
#pragma unroll 1
  for (int n = n0; n < 4; n += dn) {
    if (n == 2 && dn == 1) mbar_watch(B_RD, layer);
    const int chl = e + (n & 2), s = 128 + 32 * (n & 1) + lane;
    const uint32_t reg = region(chl);
    const uint4 d = lds4(uchunk(reg, s));
    const uint32_t u[4] = {d.x, d.y, d.z, d.w};
    uint32_t v[4];
    box_unit<false>(reg, s, lds2(uchunk(reg, s - 2) + 8), lds4(uchunk(reg, s - 1)), u, v);
    if (dn == 2 || (n & 1)) { fence_async_smem(); bar_arrive(NB_B + chl, NBB(e)); PROFC(28 + n); }
  }
}

DEV uint4 hadd8(const uint4& a, const uint4& b) { return make_uint4(hadd2(a.x, b.x), hadd2(a.y, b.y), hadd2(a.z, b.z), hadd2(a.w, b.w)); }
DEV void conv_out(int c, int j, int chl, uint4 (&x)[2][2][2], const uint32_t (&v)[4], uint4* XF, uint32_t zero) {
  const int rho = chl >> 1, e = chl & 1;
  const uint32_t ua = uchunk(region(chl), j), fa = region(chl) + R_X5 + j * 16, ha = region(chl) + R_X3 + (j & 1) * 1088 + (j >> 1) * 16;
  const int m8 = ((j & 4) + ((j >> 1) & 1) + 2 * (j & 1)) ^ ((2 * c + e) & 7);
  uint4* xo = XF + (((16 - 2 * (j & 8) + (j >> 4)) * 512 + 256 * rho + 2 * c + e) * 8 + m8);
  bar_sync(NB_Y + e + 7 * rho, 256);
  uint4 y[2], f[2], h[2];
#pragma unroll
  for (int k = 0; k < 2; ++k) {
    y[k] = lds4(ua + k * 2048);
    f[k] = lds4z(ua + k * 2048 + R_BO - R_U, k || j >= 36);
    h[k] = lds4z(fa + k * 2048 - 1024, k || j >= 64);
  }
  const uint32_t q = lds1(SM_TAP + chl * TAP_SZ + T_K);
  const uint4 r = lds4(ha);
  split(zero);
  if (chl == 3) mbar_arrive1(B_L + (r.x & zero));
  h[1] = hadd8(h[1], make_uint4(hfma2(q, v[0], r.x), hfma2(q, v[1], r.y), hfma2(q, v[2], r.z), hfma2(q, v[3], r.w)));
#pragma unroll
  for (int k = 0; k < 2; ++k) {
    const uint4 o = hadd8(hadd8(y[k], hadd8(f[k], h[k])), make_uint4(xword(x[k][rho], e, 0), xword(x[k][rho], e, 1), xword(x[k][rho], e, 2), xword(x[k][rho], e, 3)));
    const uint32_t keep = j & 1 ? 0x7632 : 0x5410, k0 = prmt(o.x, o.y, keep), k1 = prmt(o.z, o.w, keep);
    const uint32_t g0 = __shfl_xor_sync(0xffffffffu, prmt(o.x, o.y, keep ^ 0x2222), 1), g1 = __shfl_xor_sync(0xffffffffu, prmt(o.z, o.w, keep ^ 0x2222), 1);
    str4(xo + k * 32768, j & 1 ? g0 : k0, j & 1 ? g1 : k1, j & 1 ? k0 : g0, j & 1 ? k1 : g1);

  }
  if (e) { __syncwarp(); mbar_arrive1(B_RD + rho * 8); }
  PROFC(40 + chl);
}

DEV void conv_round(int e, int rho, int w, int lane) {
  const int g = lane >> 2, t = lane & 3, chl = 2 * rho + e;
  const uint32_t reg = region(chl), tp = SM_TAP + chl * TAP_SZ, dr = dlo(reg, 128);
  const uint32_t g0 = tp + ((g & 1) ? T_O : T_E) + 2 * (2 * t - g) - 16;
  const uint32_t ga = g0 - 32 * (w & 1) - 576 * (w >> 1), id = opq(0x3210u);
  float acc[32], f1[24], f2[16];
  uint32_t q[12][4];
  {
    uint32_t qn[18][4];
    qn[0][2] = lds1(ga + 64);
#pragma unroll
    for (int n = 0; n < 18; ++n) {
      const bool nz = n < 15 || w < 2 || (n == 15 && w == 2);
      qn[n][0] = n < 15 ? lds1(ga + 48 - 32 * n) : lds1z(ga + 48 - 32 * n, nz);
      qn[n][1] = n < 15 ? lds1(ga + 32 - 32 * n) : lds1z(ga + 32 - 32 * n, nz);
    }
#pragma unroll
    for (int n = 0; n < 18; ++n) { qn[n][3] = cpy(qn[n][0], id); if (n) qn[n][2] = cpy(qn[n - 1][1], id); }
#pragma unroll
    for (int n = 0; n < 8; ++n) {
      const int i = n & 3;
      const uint32_t a = g0 + 16 - 16 * w - 2 * (n < 4 ? X_5 : X_3) + 16 * i;
      uint32_t (&q1)[4] = q[(n & 4) + (i >> 1)], (&q2)[4] = q[(n & 4) + 2 + (i >> 1)];
      q1[2 * (i & 1)] = lds1z(a, i <= w); q1[2 * (i & 1) + 1] = lds1(a - 64);
      q2[2 * (i & 1)] = cpy(0, id); q2[2 * (i & 1) + 1] = lds1z(a - 128, i >= w);
    }
    const uint32_t gc = tp + T_C - 2 + 4 * (t - g - 8 * w);
#pragma unroll
    for (int kk = 0; kk < 4; ++kk) {
      q[8 + kk][0] = lds1z(gc + 32 * kk, w >= kk); q[8 + kk][2] = lds1z(gc + 32 * kk + 16, w >= kk);
      q[8 + kk][1] = lds1(gc + 32 * kk - 128); q[8 + kk][3] = lds1(gc + 32 * kk - 112);
    }
    PROFD(rho ? 43 : 47, qn[17][2] ^ q[11][3]);
    bar_sync_if(NB_U, NBARU, 1 - rho);
    mbar_arrive1_if(B_V, chl == 1 && w == 0);
    bar_sync_if(NB_T + 1 - e, 256, chl);
    const uint32_t db = dr + (R_U + 32) / 16;
    undef(acc);
    wg_fence();
#pragma unroll
    for (int n = 0; n < 18; ++n) {
      if (n) wg_rs64k<1>(acc, qn[n], db - 2 * n); else wg_rs64k<0>(acc, qn[0], db);
      if (n == 9) wg_commit();
    }
    wg_commit();
  }
  wg_wait<1>();
  PROFC(rho ? 12 : 2);
  bar_sync(NB_B + chl, NBB(e));
  const uint32_t d1 = dr + R_X5 / 16, d2 = dr + R_BO / 16;
  undef(f1); undef(f2);
  wg_fence();
#pragma unroll
  for (int n = 0; n < 4; ++n) { if (n) wg_rs32t<1>(f2, q[8 + n], d2 + 16 * n); else wg_rs32t<0>(f2, q[8], d2); }
  wg_commit();
#pragma unroll
  for (int n = 0; n < 8; ++n) {
    const uint32_t d = d1 + (n >> 2) * ((R_X3 - R_X5) / 16) + 16 * (n & 1) - 16 * (n & 2);
    if (n) wg_rs48t<1>(f1, q[n], d); else wg_rs48t<0>(f1, q[0], d);
  }
  wg_commit();
  wg_wait<1>();
  PROFC(rho ? 13 : 3);
  bar_arrive_if(NB_T + e, 256, chl - 3);
  bar_sync(NB_WG + e, 128);
  {
    const int p = (lane + 9 * (w >> 1)) & 31;
    const uint32_t ya = reg + ((w >> 1) ? R_BO : R_U) + p * 64 + (((2 * (w & 1)) ^ ((p >> 1) & 3)) * 16);
    const uint32_t up = p < lane ? 2048 : 0;
#pragma unroll
    for (int z = 0; z < 4; ++z) {
      const float* a = acc + 16 * (z >> 1) + 2 * (z & 1);
      stsm4t((ya + (up ^ ((z >> 1) * 2048))) ^ ((z & 1) * 16), pack2(a[0], a[1]), pack2(a[4], a[5]), pack2(a[8], a[9]), pack2(a[12], a[13]));
    }
  }
  wg_wait<0>();
  PROFC(rho ? 14 : 4);
  bar_sync(NB_WG + e, 128);
  {
    const uint32_t fa = reg + R_X5 + (8 * w + (lane & 7)) * 16 + (lane >> 3) * 512;
    uint32_t h[6];
#pragma unroll
    for (int p = 0; p < 6; ++p) h[p] = p ? pack2(f1[4 * p] + f1[4 * p - 2], f1[4 * p + 1] + f1[4 * p - 1]) : pack2(f1[0], f1[1]);
    stsm4(fa, h[0], h[1], h[2], h[3]);
    stsm2(fa + 2048, h[4], h[5]);
    stsm4(reg + R_X3 + (lane < 16 ? 1088 : 0) + (8 * w + (lane & 7) + 4 * (lane & 8)) * 16, pack2(f2[0], f2[1]), pack2(f2[2] + f2[4], f2[3] + f2[5]),
          pack2(f2[8], f2[9]), pack2(f2[10] + f2[12], f2[11] + f2[13]));
  }
  bar_arrive(NB_Y + e + 7 * rho, 256);
}
constexpr uint32_t FILL = 0xFFFFFFFFu;
template <int N> DEV void fixo(uint4 (&A)[N], const uint4* p) {
#pragma unroll 1
  for (int it = 0; it < SPIN_LIMIT; ++it) {
    uint32_t m = A[0].x;
#pragma unroll
    for (int k = 1; k < N; ++k) m = max(m, A[k].x);
    if (__all_sync(0xffffffffu, m != FILL)) break;
#pragma unroll
    for (int k = 0; k < N; ++k) ldr4_if(A[k], p + k * 32, A[k].x == FILL);
  }
}
DEV bool rows_nan(float a, float b) {
  return __any_sync(0xffffffffu, a != a || b != b);
}
template <int N> DEV void slow_step(float (&acc)[N], float a0, float a1, const uint16_t* wr, uint32_t zero) {
#pragma unroll
  for (int j = 0; j < N / 4; ++j) {
    const uint32_t v = __ldg((const uint32_t*)(wr + (j >> 3) * 512 + 8 * (j & 7)));
    acc[4 * j] += a0 * bflo(v); acc[4 * j + 1] += a0 * bfhi(v); acc[4 * j + 2] += a1 * bflo(v); acc[4 * j + 3] += a1 * bfhi(v);
    if ((j & 3) == 3) wr += __float_as_uint(acc[4 * j]) & zero;
  }
}
DEV int res_off(int w, int lane) { return ((lane & 7) + 8 * (lane >> 4)) * 8 + ((2 * (w & 2) + (w & 1) + ((lane >> 2) & 2)) ^ (lane & 7)); }
DEV void res_load(uint32_t (&res)[8][2], uint32_t sa, int w, int lane) {
  const uint32_t a = sa + res_off(w, opq(lane)) * 16;
#pragma unroll
  for (int j = 0; j < 8; j += 2) {
    uint32_t r[4];
    ldsm4t(r, a + j * 1024);
    res[j][0] = r[0]; res[j][1] = r[1]; res[j + 1][0] = r[2]; res[j + 1][1] = r[3];
  }
}

DEV void res_init(float (&ac)[32], const uint32_t (&res)[8][2]) {
#pragma unroll
  for (int j = 0; j < 16; ++j)
    asm volatile("shl.b32 %0,%2,16; and.b32 %1,%2,0xFFFF0000;" : "=&f"(ac[2 * j]), "=f"(ac[2 * j + 1]) : "r"(res[j >> 1][j & 1]));
}
DEV uint32_t after(uint32_t b, const uint32_t (&res)[8][2], uint32_t zero) {
  return b + ((res[0][0] ^ res[2][0] ^ res[4][0] ^ res[6][0]) & zero);
}

DEV void attn_phase(const Params& P, int c, int e, int w, int lane, int layer) {
  lane = opq(lane); c = opq(c);
  const int i = c >> 3, cg = c & 7, J = 16 * e + i, G = 8 * i + 4 - 4 * e + w;
  const int g = lane >> 2, t = lane & 3;
  float acc[96];
  uint32_t res[8][2];
  float2 cs[16];
  float4 st;
  const uint32_t csb = opq(SM_CS + 8 * t);
  {
    const uint32_t sa = SM_A + e * A_E, ba = B_A + 32 * e;
    const uint32_t da = dlo(sa, 8192), db = (SB >> 4) | (512 << 16);
    undef(acc);
#pragma unroll
    for (int j = 0; j < 8; ++j) asm volatile("" : "=r"(res[j][0]), "=r"(res[j][1]));
    mbar_wait(B_WF, layer);
    mbar_wait(ba, 0);
    mbar_wait(B_L, layer);
    bar_sync_if(NB_T, 256, e);
    PROF(24);
#pragma unroll
    for (int j = 0; j < 4; ++j) {
      if (j) mbar_wait(ba + 8 * j, 0);
      if (j == 1) PROFK(layer ? 39 : 15);
      wg_fence();
#pragma unroll
      for (int k = 0; k < 4; ++k) {
        if (j | k) wg_ss192<1>(acc, da + j * 512 + k * 128, db + wslot(j) * 512 + k * 128); else wg_ss192<0>(acc, da, db);
        if (j == 3 && k == 1) wg_commit();
      }
      wg_commit();
      if (j == 1 || j == 2) { wg_wait<1>(); mbar_arrive1_if(B_F + 8 * (j - 1), e); }
    }
    wg_wait<1>();
    bar_arrive(NB_T + e, 256);
    wg_wait<0>();
    if (cg < 4) res_load(res, sa + cg * 8192, w, lane);
    mbar_arrive1(after(B_AE + 8 * e, res, P.zero));
    PROF(25);
#pragma unroll 1
    for (uint32_t late = P.zero;; late = 1) {
      if (late) {
        const uint16_t* xr = (const uint16_t*)SCR->XF[layer] + opq(J) * 32768;
        COUNT(0);
        zero(acc);
#pragma unroll 1
        for (int k = 0; k < 512; ++k)
          slow_step(acc, ldnan(xr + k * 64 + ((2 * w) ^ (k & 7)) * 8 + g), ldnan(xr + k * 64 + ((2 * w + 1) ^ (k & 7)) * 8 + g),
                    P.wqkv + (k * 1536 + 64 * cg + 2 * t), P.zero);
        const uint32_t* q = (const uint32_t*)xr + ((64 * cg + g) * 32 + t);
        const int m8 = (2 * (w & 2) + (w & 1)) ^ g;
#pragma unroll 1
        for (int it = 0; it < SPIN_LIMIT; ++it) {
          uint32_t m = 0;
#pragma unroll
          for (int z = 0; z < 16; ++z) { const uint32_t x = ldr1(q + (z >> 1) * 256 + (m8 ^ (2 * (z & 1))) * 4); m = max(m, x); res[z >> 1][z & 1] = movm(x); }
          if (__all_sync(0xffffffffu, m != FILL)) break;
        }
#pragma unroll
        for (int z = 0; z < 16; ++z) cs[z] = lds2f(csb + 256 + z * 32);
      } else {
        mbar_wait(B_CS, 0);
#pragma unroll
        for (int z = 0; z < 16; ++z) cs[z] = lds2f(csb + 256 + z * 32);
        mbar_wait(B_W4, layer);
        mbar_wait(ba, 1);
        bar_sync(NB_T + 1 - e, 256);
        PROF(26);
#pragma unroll
        for (int j = 4; j < 8; ++j) {
          if (j > 4) mbar_wait(ba + 8 * (j - 4), 1);
          if (j >= 6) mbar_wait(B_W6 + 8 * (j - 6), layer);
          if (j > 4) PROF(31 + j);
          wg_fence();
#pragma unroll
          for (int k = 0; k < 4; ++k) {
            wg_ss192<1>(acc, da + (j & 3) * 512 + k * 128, db + wslot(j) * 512 + k * 128);
            if (j == 7 && k == 1) wg_commit();
          }
          wg_commit();
          if (j == 5) {
            if (cg >= 4) { mbar_wait(ba + 8 * (cg - 4), 1); res_load(res, sa + (cg - 4) * 8192, w, lane); }
            wg_wait<1>(); mbar_arrive1_if(B_F + 16, e); PROF(40);
          }

        }
      }
      uint32_t rs = hadd2(res[0][0], res[0][1]);
#pragma unroll
      for (int z = 2; z < 16; ++z) rs = hadd2(rs, res[z >> 1][z & 1]);
      const float rn = bflo(rs) + bfhi(rs);
      wg_wait<1>();
      bar_arrive_if(NB_T, 256, !(e | late));
      mbar_wait(B_ST + 8 * e, layer);
      st = lds4f(SM_STAT + ((4 * e + w) * 8 + g) * 16);
      PROF(34 + layer);
      wg_wait<0>();
      if (!rows_nan(acc[0] + rn, acc[2]) || late) break;
    }
  }
  mbar_arrive1(B_QE);
  PROFK(8 + 12 * layer);
  uint32_t Q[4][4], K[4][2][2], V[4][2][2];
  {
#pragma unroll
    for (int z = 0; z < 8; ++z) {
      const float* a = acc + 32 + 4 * z; const float* b = acc + 64 + 4 * z;
      K[z >> 1][1][z & 1] = pack2((a[2] - st.z * cs[z].x) * st.w, (a[3] - st.z * cs[z].y) * st.w);
      V[z >> 1][1][z & 1] = movm(pack2((b[2] - st.z * cs[8 + z].x) * st.w, (b[3] - st.z * cs[8 + z].y) * st.w));
    }
    const int hop = (G >> 1) & 3;
    const uint32_t kv = SM_KV + (2 * hop + (w & 1)) * 2048 + lane * 16;
    uint4* h = SCR->H[layer] + (c * 256 + (w & 1) * 128 + lane);
    if (hop == 3) {
#pragma unroll
      for (int z = 0; z < 4; ++z) str4(h + 2048 + z * 32, K[z][1][0], K[z][1][1], V[z][1][0], V[z][1][1]);
    } else {
      mbar_wait(B_F + 16, layer);
#pragma unroll
      for (int z = 0; z < 4; ++z) sts4(kv + z * 512, K[z][1][0], K[z][1][1], V[z][1][0], V[z][1][1]);
      bar_arrive(NB_B + hop, 128);
    }
    PROF(42);
    uint4 hv[4];
#pragma unroll
    for (int z = 0; z < 4; ++z) { hv[z] = make_uint4(0, 0, 0, 0); ldr4_if(hv[z], h + z * 32, G >= 2 && hop == 0); }
#pragma unroll
    for (int z = 0; z < 8; ++z) {
      const float* a = acc + 32 + 4 * z; const float* b = acc + 64 + 4 * z;
      K[z >> 1][0][z & 1] = pack2((a[0] - st.x * cs[z].x) * st.y, (a[1] - st.x * cs[z].y) * st.y);
      V[z >> 1][0][z & 1] = movm(pack2((b[0] - st.x * cs[8 + z].x) * st.y, (b[1] - st.x * cs[8 + z].y) * st.y));
    }
#pragma unroll
    for (int z = 0; z < 8; ++z) {
      const float2 cq = lds2f(csb + z * 32);
      const float* a = acc + 4 * z;
      Q[z >> 1][2 * (z & 1)] = pack2(a[0] - st.x * cq.x, a[1] - st.x * cq.y);
      Q[z >> 1][2 * (z & 1) + 1] = pack2(a[2] - st.z * cq.x, a[3] - st.z * cq.y);
    }
    PROF(27);
    const bool p0 = 2 * t > g, p1 = 2 * t + 1 > g, first = G < 2;
    float s[4][4], mx[4][2];
#pragma unroll
    for (int z = 0; z < 4; ++z) {
      float S[4];
      mma16z(s[z], Q[z][0], Q[z][1], Q[z][2], Q[z][3], K[z][0][0], K[z][0][1]);
      mma16z(S, Q[z][0], Q[z][1], Q[z][2], Q[z][3], K[z][1][0], K[z][1][1]);
      s[z][2] = p0 ? s[z][2] : S[2]; s[z][3] = p1 ? s[z][3] : S[3];
    }
    const float sc0 = st.y * (0.25f * 1.4426950408889634f), sc1 = st.w * (0.25f * 1.4426950408889634f);
    uint32_t pw[4][2];
#pragma unroll
    for (int r = 1; r >= 0; --r) {
      if (r == 0) {
        if (hop) {
          bar_sync(NB_B + hop - 1, 128);
#pragma unroll
          for (int z = 0; z < 4; ++z) hv[z] = lds4(kv - 4096 + z * 512);
        } else fixo(hv, h);
        PROFD(41, hv[3].x);
#pragma unroll
        for (int z = 0; z < 4; ++z) {
          float S[4];
          mma16z(S, Q[z][0], Q[z][1], Q[z][2], Q[z][3], hv[z].x, hv[z].y);
          if (first) S[0] = S[1] = __uint_as_float(0xFF800000u);
          s[z][0] = p0 ? S[0] : s[z][0]; s[z][1] = p1 ? S[1] : s[z][1];
        }
      }
#pragma unroll
      for (int z = 0; z < 4; ++z) mx[z][r] = fmaxf(s[z][2 * r], s[z][2 * r + 1]);
#pragma unroll
      for (int o = 1; o < 3; ++o)
#pragma unroll
        for (int z = 0; z < 4; ++z) mx[z][r] = fmaxf(mx[z][r], __shfl_xor_sync(0xffffffffu, mx[z][r], o));
#pragma unroll
      for (int z = 0; z < 4; ++z) pw[z][r] = pack2(ex2((s[z][2 * r] - mx[z][r]) * (r ? sc1 : sc0)), ex2((s[z][2 * r + 1] - mx[z][r]) * (r ? sc1 : sc0)));
    }
    mbar_wait(layer ? B_N : B_Z, 1);
    const uint32_t M = (p0 ? 0xFFFFu : 0u) | (p1 ? 0xFFFF0000u : 0u);
    uint4* O = SCR->O + ((J * 8 + cg) * 512 + (2 * (w & 2) + (w & 1)) * 64 + t * 8 + g);
#pragma unroll
    for (int h2 = 0; h2 < 2; ++h2) {
      uint32_t ow[2][4];
#pragma unroll
      for (int z = 0; z < 2; ++z) {
        const int n = 2 * h2 + z;
        const uint32_t w0 = pw[n][0], w1 = pw[n][1];
        float sm[4] = {0.f, 0.f, 0.f, 0.f}, Oa[2][4];
        mma8(sm, w0, w1, 0x3F803F80u);
        mma16z(Oa[0], w0 & ~M, w1 & M, 0u, w1 & ~M, V[n][0][0], V[n][1][0]); mma8(Oa[0], w0 & M, 0u, hv[n].z);
        mma16z(Oa[1], w0 & ~M, w1 & M, 0u, w1 & ~M, V[n][0][1], V[n][1][1]); mma8(Oa[1], w0 & M, 0u, hv[n].w);
        const float i0 = rcp(sm[0]), i1 = rcp(sm[2]);
#pragma unroll
        for (int d = 0; d < 2; ++d) { ow[0][2 * z + d] = pack2(Oa[d][0] * i0, Oa[d][1] * i0); ow[1][2 * z + d] = pack2(Oa[d][2] * i1, Oa[d][3] * i1); }
      }
#pragma unroll
      for (int hi = 0; hi < 2; ++hi) str4(O + hi * 128 + h2 * 32, ow[hi][0], ow[hi][1], ow[hi][2], ow[hi][3]);
    }
  }
  str1(SCR->OF[layer] + (J * 32 + cg * 4 + w), 1);
  mbar_arrive1(B_AT + 8 * e);
  PROFK(9 + 12 * layer);
  float ac[32];
  const uint32_t so = SM_O + e * O_E;
  uint2* xo = opqp(layer ? (uint2*)(P.out + ((16 * G + 2 * (lane >> 3)) * 512 + 64 * cg + 8 * (lane & 7)))
                         : (uint2*)SCR->XG[1] + ((32 * (cg & 3) + t) * 2048 + (cg >> 2) * 256 + xg_off(G, g)));
  const uint32_t stg = SM_X + (4 * e + w) * 2048;
  const uint32_t sw = opq(stg + (lane & 15) * 128 + (((lane >> 4) ^ (lane & 7)) * 16)), sr = opq(stg + (lane >> 3) * 128 + (((lane & 7) ^ (lane >> 3)) * 16));
  uint4* ps = opqp(&SCR->PS[(G * 8 + cg) * 8 + g]);
  {
    const uint32_t bo = B_O + 32 * e;
    const uint32_t dw = (SM_WO >> 4) | (512 << 16), da = dlo(so, 512);
    mbar_wait(B_WO, layer);
    res_init(ac, res);
    mbar_wait(B_AT + 8, layer);
#pragma unroll
    for (int j = 0; j < 4; ++j) {
      mbar_wait(bo + 8 * j, layer);
      if (j == 0) PROFK(32 + layer);
      wg_fence();
#pragma unroll
      for (int k = 8 * j; k < 8 * j + 8; ++k) {
        const uint32_t a = da + (k >> 2) * 512 + (k & 3) * 8, b = dw + (k & 3) * 1024 + (k >> 2) * 128;
        wg_ss64<1>(ac, a, b);
      }
      wg_commit();
    }
#pragma unroll 1
    for (uint32_t late = P.zero;; late = 1) {
      if (late) {
        const uint16_t* op = (const uint16_t*)(SCR->O + (J * 4096 + w * 128 + g));
        wg_wait<0>();
        COUNT(1);
        res_init(ac, res);
#pragma unroll 1
        for (int k = 0; k < 512; ++k) {
          const uint16_t* q = op + (k >> 6) * 4096 + (k & 56) * 8 + (k & 7);
          slow_step(ac, ldnan(q), ldnan(q + 512), P.wo + (((k & ~31) + 4 * (k & 6) + ((k >> 2) & 6) + (k & 1)) * 512 + 64 * cg + 2 * t), P.zero);
        }
      }
      wg_wait<0>();
      if (!rows_nan(ac[0], ac[2]) || late) break;
    }
  }
  PROFK(10 + 12 * layer);
#pragma unroll
  for (int j = 0; j < 16; ++j) res[j >> 1][j & 1] = pack2(ac[2 * j], ac[2 * j + 1]);
  if (layer == 0) {
    float s[2][4], q0[2][4], q1[2][4];
#pragma unroll
    for (int j = 0; j < 2; ++j) gram<true>(s[j], q0[j], q1[j], res[2 * j][0], res[2 * j][1], res[2 * j + 1][0], res[2 * j + 1][1]);
#pragma unroll
    for (int j = 0; j < 2; ++j) gram<false>(s[j], q0[j], q1[j], res[2 * j + 4][0], res[2 * j + 4][1], res[2 * j + 5][0], res[2 * j + 5][1]);
    const bool od = g & 1;
    str4_if(ps, nzmap(__float_as_uint(s[0][0] + s[1][0])), __float_as_uint(od ? q0[0][1] + q0[1][1] : q0[0][0] + q0[1][0]),
            __float_as_uint(s[0][2] + s[1][2]), __float_as_uint(od ? q1[0][3] + q1[1][3] : q1[0][2] + q1[1][2]), t == (g >> 1));
#pragma unroll
    for (int j = 0; j < 8; ++j) {
      str2(xo + j * 8192, nzmap(prmt(res[j][0], res[j][1], 0x5410)), prmt(res[j][0], res[j][1], 0x7632));
    }
    mbar_arrive1(B_ED + 8 * e);
  } else {
#pragma unroll
    for (int j = 0; j < 8; j += 2) stsm4(sw ^ (j * 16), res[j][0], res[j][1], res[j + 1][0], res[j + 1][1]);
    __syncwarp();
    uint4 v[4];
#pragma unroll
    for (int k = 0; k < 4; ++k) v[k] = lds4((sr ^ ((k & 1) * 64)) + k * 512);
#pragma unroll
    for (int k = 0; k < 4; ++k) stw4(xo + ((k & 1) * 8 + (k >> 1)) * 128, v[k].x, v[k].y, v[k].z, v[k].w);
  }
  PROFK(11 + 12 * layer);
}

DEV void col_sums(const Params& P, int c, int wa, int lane) {
  const int i = c >> 3, cg = c & 7;
  uint4 wv[8];
#pragma unroll
  for (int k = 0; k < 8; ++k) wv[k] = ldnc4(P.wqkv + ((32 * i + (lane >> 3)) * 1536 + wa * 512 + 64 * cg + 8 * (lane & 7)) + 4 * k * 1536);
  float cs[8];
  zero(cs);
#pragma unroll
  for (int k = 0; k < 8; ++k) {
    cs[0] += bflo(wv[k].x); cs[1] += bfhi(wv[k].x); cs[2] += bflo(wv[k].y); cs[3] += bfhi(wv[k].y);
    cs[4] += bflo(wv[k].z); cs[5] += bfhi(wv[k].z); cs[6] += bflo(wv[k].w); cs[7] += bfhi(wv[k].w);
  }
  const bool b4 = lane & 16, b3 = lane & 8;
#pragma unroll
  for (int k = 0; k < 4; ++k) cs[k] = (b4 ? cs[k + 4] : cs[k]) + __shfl_xor_sync(0xffffffffu, b4 ? cs[k] : cs[k + 4], 16);
#pragma unroll
  for (int k = 0; k < 2; ++k) cs[k] = (b3 ? cs[k + 2] : cs[k]) + __shfl_xor_sync(0xffffffffu, b3 ? cs[k] : cs[k + 2], 8);
  str2((uint2*)SCR->CS + (i * 768 + wa * 256 + 32 * cg + 4 * (lane & 7) + (lane >> 3)), nzmap(__float_as_uint(cs[0])), __float_as_uint(cs[1]));
}
DEV void col_gather(const Params& P, int c, int wa, int lane) {
  const uint2* p = (const uint2*)SCR->CS + (wa * 256 + 32 * (c & 7) + lane);
#pragma unroll 1
  for (int it = 0;; ++it) {
    float a = 0.f, b = 0.f;
    uint32_t m = ~0u;
#pragma unroll
    for (int k = 0; k < 16; ++k) { const uint2 q = ldr2(p + k * 768); m = min(m, q.x); a += __uint_as_float(q.x); b += __uint_as_float(q.y); }
    if (__all_sync(0xffffffffu, m != 0u)) { sts2f(SM_CS + wa * 256 + lane * 8, a, b); break; }
    spin_guard(it);
  }
  __syncwarp();
  mbar_arrive1(B_CS);
}

DEV void aux_prologue(const Params& P, int c, int wa, int lane) {
  const int g = lane >> 2, t = lane & 3, G = stat_group(c);
  {
    uint32_t w[16][2];
    const uint16_t* row = P.x0 + ((16 * G + 2 * g) * 512 + 128 * wa + 8 * t);
    bar_sync(NB_Y, 384);
#pragma unroll
    for (int z = 0; z < 8; ++z) {
      const uint4 v = ldw4(row + (z & 1) * 512 + (z >> 1) * 32);
      const int o = 4 * (z >> 1);
      w[o][z & 1] = v.x; w[o + 1][z & 1] = v.y; w[o + 2][z & 1] = v.z; w[o + 3][z & 1] = v.w;
    }
    PROF(34);
    PROFD(35, w[0][0]);
    PROFD(36, w[15][1]);
    uint2* xo = (uint2*)SCR->XG[0] + ((64 * (wa & 1) + 4 * t) * 2048 + (wa >> 1) * 256 + xg_off(G, g));
#pragma unroll
    for (int n = 0; n < 16; ++n) str2(xo + (16 * (n >> 2) + (n & 3)) * 2048, nzmap(prmt(w[n][0], w[n][1], 0x5410)), prmt(w[n][0], w[n][1], 0x7632));
    float s[2][4], q0[2][4], q1[2][4];
#pragma unroll
    for (int z = 0; z < 8; ++z) {
      const int o = 4 * (z >> 1), r = z & 1;
      if (z < 2) gram<true>(s[r], q0[r], q1[r], w[o][r], w[o + 1][r], w[o + 2][r], w[o + 3][r]);
      else gram<false>(s[r], q0[r], q1[r], w[o][r], w[o + 1][r], w[o + 2][r], w[o + 3][r]);
    }
    const bool od = g & 1;
    if (t == (g >> 1))
      sts4f(SM_STAT + (wa * 8 + g) * 16, s[0][0] + s[0][2], od ? q0[0][1] + q1[0][3] : q0[0][0] + q1[0][2],
            s[1][0] + s[1][2], od ? q0[1][1] + q1[1][3] : q0[1][0] + q1[1][2]);
    bar_arrive(NB_P0, 192);
  }
  PROF(2);
  if (lane == 0)
    asm volatile("cp.async.bulk.prefetch.L2.global [%0],4096;" :: "l"(wa < 3 ? P.wqkv + (3 * c + wa) * 2048 : P.wo + c * 2048) : "memory");
  bar_sync(NB_Y + 1, 256);
  mbar_wait(B_Z, 0);
}

DEV void stat_part(const Params& P, int c, int wa, int lane, int layer, int h, float (&v)[2]) {
  lane = opq(lane);
  const int e = wa >> 1;
  uint32_t x[4][4];
  mbar_wait(B_A + 16 * wa, h); mbar_wait(B_A + 16 * wa + 8, h);
  if (h == 0) mbar_wait(B_A + 32 * e + 24, 0);
#pragma unroll
  for (int k = 0; k < 4; ++k) ldsm4t(x[k], SM_A + e * A_E + (128 * (wa & 1) + lane) * 128 + (((c ^ lane) & 7) * 16) + k * 4096);
  float s[4] = {0.f, 0.f, 0.f, 0.f};
#pragma unroll
  for (int k = 0; k < 16; ++k) { const float a = bflo(x[k >> 2][k & 3]), b = bfhi(x[k >> 2][k & 3]); s[0] += a; s[1] += a * a; s[2] += b; s[3] += b * b; }
  s[0] += s[2]; s[1] += s[3];
  if (RARE(rows_nan(s[1], s[1]))) {
    const uint16_t* q = (const uint16_t*)(SCR->XF[layer] + ((32 * e + 2 * (c >> 3) + h) * 2048 + (wa & 1) * 1024)) + (lane >> 2);
    COUNT(2);
    s[0] = s[1] = 0.f;
#pragma unroll 1
    for (int k = 0; k < 32; ++k) {
      const int r = 2 * (lane & 3) + (k & 1);
      const float a = ldnan(q + ((k >> 1) * 8 + r) * 64 + ((c ^ r) & 7) * 8);
      s[0] += a; s[1] += a * a;
    }
  }
  v[0] += s[0]; v[1] += s[1];
  __syncwarp();
}
DEV void stat_finish(const Params& P, int c, int wa, int lane, int layer, float (&v)[2]) {
  lane = opq(lane);
  const bool b = lane & 1;
  const float s = (b ? v[1] : v[0]) + __shfl_xor_sync(0xffffffffu, b ? v[0] : v[1], 1);
  str1((uint32_t*)SCR->ST[layer] + ((128 * (wa >> 1) + c) * 64 + (wa & 1) * 32 + lane), nzmap(__float_as_uint(s)));
  const uint4* sp = SCR->ST[layer] + ((128 * (wa >> 1) + (c & ~7) + 4 * (wa & 1) + (lane >> 3)) * 16 + (lane & 7));
  uint4 x, y;
  for (int it = 0;; ++it) {
    x = ldr4(sp); y = ldr4(sp + 8);
    if (__all_sync(0xffffffffu, min(min(min(x.x, x.y), min(x.z, x.w)), min(min(y.x, y.y), min(y.z, y.w))) != 0u)) break;
    spin_guard(it);
  }
  const uint32_t q = ln_sums((__uint_as_float(x.x) + __uint_as_float(x.z)) + (__uint_as_float(y.x) + __uint_as_float(y.z)),
                             (__uint_as_float(x.y) + __uint_as_float(x.w)) + (__uint_as_float(y.y) + __uint_as_float(y.w)));
  sts2f(SM_STAT + (16 * wa + (lane >> 4) * 8 + (lane & 7)) * 16 + (lane & 8), bflo(q), rcp(bfhi(q)));
  __syncwarp();
  mbar_arrive1(B_ST + 4 * (wa & 2));
}

DEV void nan_source(uint32_t a, int lane) {
#pragma unroll
  for (int k = 0; k < 4; ++k) sts4(a + k * 512 + lane * 16, FILL, FILL, FILL, FILL);
  fence_async_smem();
  __syncwarp();
}
__global__ void __launch_bounds__(NTHR, 1)
fused_kernel(const __grid_constant__ Params P, const __grid_constant__ CUtensorMap mapW, const __grid_constant__ CUtensorMap mapWo,
             const __grid_constant__ CUtensorMap mapX) {
  extern __shared__ __align__(1024) uint8_t smem_raw[];
  const int warp = __shfl_sync(0xffffffffu, threadIdx.x >> 5, 0), lane = threadIdx.x & 31;
  uint32_t smid; asm volatile("mov.u32 %0,%%smid;" : "=r"(smid));
  const uint32_t* pw = (const uint32_t*)&P + threadIdx.y;
  const int role = P.role[(smid >> 1) + threadIdx.y] + (smid & 1) + (pw[0] & pw[12]);
  const int c = __shfl_sync(0xffffffffu, pw[1] ? role : blockIdx.x, 0);
  if (c >= 128) {
#pragma unroll 1
    for (int k = (c - 128) * NTHR + threadIdx.x; k < 131072; k += P.spare * NTHR) str4(SCR->XG[1] + k, 0, 0, 0, 0);
    __threadfence();
    __syncthreads();
    if (warp == 0) { poll(SCR->C + 1 + (lane & 3) * 32, 32); cnt_add1(SCR->C + 6); }
    __syncthreads();
#pragma unroll 1
    for (int k = (c - 128) * NTHR + threadIdx.x; k < 131072; k += P.spare * NTHR) str4(SCR->XG[0] + k, 0, 0, 0, 0);
    return;
  }
#define DONE() do {} while (0)
  const int cg = c & 7;
  if (warp < 8) {
    PROF(46);
    kgen(P, c, warp, lane);
    PROFK(1);
    bar_sync(0, 384);
#pragma unroll 1
    for (int layer = 0; layer < 2; ++layer) {
#pragma unroll 1
      for (int rho = 0; rho < 2; ++rho) {
        const int wz = warp + ((rho + layer) & P.zero);
        conv_round(wz >> 2, rho, wz & 3, lane_id());
        PROFK(6 + rho + 12 * layer);
      }
      const int z = layer & P.zero;
      attn_phase(P, c + z, (warp + z) >> 2, (warp + z) & 3, lane_id(), layer);
    }
    DONE();
  } else if (warp < 12) {
    asm volatile("setmaxnreg.dec.sync.aligned.u32 %0;" :: "n"(REG_AUX));
    aux_prologue(P, c, warp - 8, lane);
    PROF(1);
    const int c0 = c;
#pragma unroll 1
    for (int layer = 0;; ++layer) {
      const int c = c0 + (layer & P.zero), wa = warp - 8 + (layer & P.zero);
#define lane lane_id()
#define j (32 * wa + lane_id())
      uint4 x[2][2][2];
      uint32_t u[4][4];
      uprep(P, c, wa, lane, layer, x, u);
      fence_async_smem();
      bar_arrive(NB_U, NBARU);
      PROFK(5 + 12 * layer);
      bar_sync(NB_H, 224);
      box_full<0, 3>(j, u, P.zero);
      PROF(3 + 12 * layer);
      conv_out(c, j, 0, x, u[0], SCR->XF[layer], P.zero);
      PROF(32);
      conv_out(c, j, 1, x, u[1], SCR->XF[layer], P.zero);
      box_full<3, 4>(j, u, P.zero);
      PROF(6 + 12 * layer);
      if (layer == 0 && wa < 3) col_sums(P, c, wa, lane);
      conv_out(c, j, 2, x, u[2], SCR->XF[layer], P.zero);
      PROF(33);
      conv_out(c, j, 3, x, u[3], SCR->XF[layer], P.zero);
      PROFK(7 + 12 * layer);
      float v[2];
      zero(v);
#pragma unroll 1
      for (int h = 0; h < 2; ++h) {
        stat_part(P, c, wa, lane, layer, h, v);
        if (h) break;
        mbar_arrive1(B_AE + 4 * (wa & 2));
        if (layer == 0 && wa < 3) col_gather(P, c, wa, lane);
      }
      PROF(9 + 12 * layer);
      stat_finish(P, c, wa, lane, layer, v);
      PROF(8 + 12 * layer);
      if (layer) break;
      mbar_wait(B_ED, 0); mbar_wait(B_ED + 8, 0);
#undef lane
#undef j
    }
    DONE();
  } else {
    asm volatile("setmaxnreg.dec.sync.aligned.u32 %0;" :: "n"(REG_PROD));
    if (s2u(smem_raw) != SB) __trap();
#pragma unroll 1
    for (int n = warp - 12; n < 42; n += 4)
      asm volatile("{.reg .pred p; elect.sync _|p,0xffffffff; @p mbarrier.init.shared::cta.b64 [%0],%1;}"
                   :: "r"(SM_BAR + n * 8), "r"(n == 33 ? 4 : n > 14 ? 1 : (int)(0x322866444444444ull >> (4 * n)) & 15) : "memory");
    fence_async_smem();
    bar_sync(NB_AUX, 128);
    bar_arrive(0, 384); bar_arrive(NB_Y + 1, 256);
    PROF(1);
    if (warp == 12) {
      if (lane == 0) {
        asm volatile("prefetch.tensormap [%0];" :: "l"(&mapW) : "memory");
        asm volatile("prefetch.tensormap [%0];" :: "l"(&mapWo) : "memory");
        asm volatile("prefetch.tensormap [%0];" :: "l"(&mapX) : "memory");
      }
      nan_source(slot(12), lane);
#pragma unroll 1
      for (int k = 0; k < 8; ++k) tma2_store(&mapX, slot(12), 128 * c, 8 * k);
      bulk_wait();
      __threadfence();
      mbar_arrive1(B_Z);
      mbar_wait(B_E, 0);
#pragma unroll 1
      for (int k = 0; k < 4; ++k) bulk_store(SCR->H[k >> 1] + ((c + 8) * 256 + (k & 1) * 128), slot(12), 2048);
#pragma unroll 1
      for (int k = 0; k < 8; ++k) bulk_store(SCR->O + (c * 512 + (k >> 2) * 65536 + (k & 3) * 128), slot(12), 2048);
      bulk_wait();
      PROF(24);
#pragma unroll 1
      for (int layer = 0; layer < 2; ++layer) {
        mbar_wait(B_V, layer);
        if (layer == 1 && c < 4 && ((0x47 >> lane) & 1)) str1(SCR->C + c * 32 + lane, 0);
        mbar_expect1(B_WF, 4 * 24576);
#pragma unroll
        for (int k = 0; k < 4; ++k) tma3(slot(wslot(k)), &mapW, 64 * cg, 64 * k, 0, B_WF);
        if (layer == 0) { __threadfence(); mbar_arrive1(B_Z); }
        mbar_wait(B_WF, layer);
        mbar_expect1(B_W4, 2 * 24576);
#pragma unroll
        for (int k = 4; k < 6; ++k) tma3(slot(wslot(k)), &mapW, 64 * cg, 64 * k, 0, B_W4);
        bar_sync(NB_AUX, 64);
#pragma unroll 1
        for (int k = 0; k < 2; ++k) {
          mbar_expect1(B_W6 + 8 * k, 24576);
          mbar_wait(B_F + 8 * k, layer);
          tma3(slot(3 * k), &mapW, 64 * cg, 384 + 64 * k, 0, B_W6 + 8 * k);
        }
        mbar_expect1(B_WO, 65536);
        mbar_wait(B_AE + 8, layer);
        nan_source(slot(12), lane);
        uint4* fp = layer ? SCR->O + c * 512 : SCR->XF[1] + c * 512;
#pragma unroll 1
        for (int r = 7; r >= 0; --r) {
          __nanosleep(30);
          if (r >= 4) {
            bulk_store(fp + (r & 3) * 128, slot(12), 2048); bulk_store(fp + 65536 + (r & 3) * 128, slot(12), 2048);
          }
          if (r == 3) { bulk_wait(); __threadfence(); mbar_arrive1(B_N); PROF(9 + 12 * layer); }
          if (r == 1) mbar_wait(B_F + 16, layer);
          tma4(SM_WO + r * 8192, &mapWo, 64 * cg, 0, r >> 1, 32 * (r & 1), B_WO);
        }
        PROF(8 + 12 * layer);
      }
      DONE();
    } else if (warp == 13) {
      const int G = stat_group(c);
#pragma unroll 1
      for (int layer = 0; layer < 2; ++layer) {
        float z[4];
        uint2* so = opqp((uint2*)&SCR->SR[layer][lane >> 3][sr_off(G, lane)] + (lane & 1));
        if (layer == 0) {
          bar_sync(NB_P0, 192);
          const float4 a = lds4f(SM_STAT + lane * 16);
          z[0] = a.x; z[1] = a.y; z[2] = a.z; z[3] = a.w;
        } else {
          mbar_wait(B_ED + 2 * (c & 4), 0);
          uint4* ps = &SCR->PS[G * 64 + lane];
          uint4 a, b;
          for (int it = 0;; ++it) {
            a = ldr4(ps); b = ldr4(ps + 32);
            if (__all_sync(0xffffffffu, min(a.x, b.x) != 0u)) break;
            spin_guard(it);
          }
          z[0] = __uint_as_float(a.x) + __uint_as_float(b.x); z[1] = __uint_as_float(a.y) + __uint_as_float(b.y);
          z[2] = __uint_as_float(a.z) + __uint_as_float(b.z); z[3] = __uint_as_float(a.w) + __uint_as_float(b.w);
        }
#pragma unroll
        for (int o = 8; o < 32; o <<= 1)
#pragma unroll
          for (int k = 0; k < 4; ++k) z[k] += __shfl_xor_sync(0xffffffffu, z[k], o);
        const uint32_t w0 = ln_sums(z[0], z[1]), w1 = ln_sums(z[2], z[3]);
        const uint32_t r = nzmap(pack2(rcp(bfhi(w0)), rcp(bfhi(w1)))), m = prmt(w0, w1, 0x5410);
        str2(so, r, m); str2(so + 4 * 1024, r, m);
        PROF(4 + 12 * layer);
        box_help(0, 0, 2, lane, layer);
        PROF(6 + 12 * layer);
      }
      DONE();
    } else if (warp == 14) {
#pragma unroll 1
      for (int layer = 0; layer < 2; ++layer) {
        uint32_t* ca = opqp(SCR->C + (c >> 5) * 32 + 3 * layer);
        const uint32_t* cw = opqp(SCR->C + (lane & 3) * 32 + 3 * layer);
        const uint4* xg = opqp(SCR->XG[layer] + c * 1024);
        mbar_expect1(B_E, 16384);
        if (layer) { mbar_wait(B_N, 0); mbar_wait(B_ED, 0); mbar_wait(B_ED + 8, 0); } else bar_sync(NB_P0, 192);
        cnt_add1(ca);
        PROF(4 + 12 * layer);
#pragma unroll 1
        for (uint32_t it = 0, todo = 15; todo; ++it) {
          spin_guard(it);
          const uint32_t m = __ballot_sync(0xffffffffu, ldr1(cw) >= 32) & todo;
          todo ^= m;
          mbar_arrive1_if(B_U, todo == 0);
#pragma unroll
          for (int q = 0; q < 4; ++q)
            if ((m >> q) & 1) bulk(SM_X + 4096 * q, xg + 256 * q, 4096, B_E);
        }
        PROFK(5 + 12 * layer);
        box_help(0, 1, 2, lane, layer);
#pragma unroll 1
        for (int n = 0; n < 4; ++n) {
          const int e = n & 1;
          const uint4* src = opqp(SCR->XF[layer] + (32 * e + 2 * (c >> 3) + (n >> 1)) * 2048);
          const uint32_t dst = opq(SM_A + e * A_E), b = opq(B_A + 32 * e), f = opq(n == 1 ? B_L : (n & 2 ? B_AE : B_RD) + 8 * e);
          if (n == 2) poll(cw + 2, 32);
          if (n == 2) PROF(7 + 12 * layer);
          mbar_wait(f, layer);
          if (n == 0) cnt_add1(ca + 1);
          uint32_t ok = n ? 15 : 0;
#pragma unroll 1
          for (int q = 0, it = 0; q < 4; ++q) {
            mbar_expect1(b + 8 * q, 8192);
#pragma unroll 1
            for (; !((ok >> q) & 1); ++it) {
              spin_guard(it);
              ok = __ballot_sync(0xffffffffu, ldr1(cw + 1) >= 32);
            }
            bulk(dst + 8192 * q, src + 512 * q, 8192, b + 8 * q);
          }
          bar_arrive_if(NB_AUX, 64, n == 2);
          if (!e) PROFK(6 + n + 12 * layer);
        }
#pragma unroll 1
        for (int n = 0; n < 8; ++n) mbar_expect1(B_O + 8 * n, 16384);
        if (layer == 0) poll(SCR->C + 6, P.spare);
        mbar_wait(B_QE, layer);
#pragma unroll 1
        for (int e = 0; e < 2; ++e) {
          const int J = 16 * e + (c >> 3);
          const uint32_t* fl = opqp(SCR->OF[layer] + J * 32 + lane);
          const uint4* src[4];
          uint32_t dst[4], b[4];
#pragma unroll
          for (int n = 0; n < 4; ++n) { src[n] = opqp(SCR->O + (J * 4096 + n * 1024)); dst[n] = opq(SM_O + e * O_E + 16384 * n); b[n] = opq(B_O + 32 * e + 8 * n); }
          mbar_wait(B_AT + 8 * e, layer);
          if (!e) pause(260);
          poll(fl, 1);
#pragma unroll
          for (int n = 0; n < 4; ++n) bulk(dst[n], src[n], 16384, b[n]);
          PROFK(9 + e + 12 * layer);
        }
      }
      DONE();
    }
    if (warp == 15) {
      const int G = stat_group(c);
      str4(&SCR->ST[0][(lane >> 4) * 2048 + c * 16 + (lane & 15)], 0, 0, 0, 0); str4(&SCR->ST[1][(lane >> 4) * 2048 + c * 16 + (lane & 15)], 0, 0, 0, 0);
      if (lane < 4) str4(SCR->OF[lane >> 1] + ((lane & 1) * 512 + c * 4), 0, 0, 0, 0);
      str4(&SCR->PS[G * 64 + lane], 0, 0, 0, 0); str4(&SCR->PS[G * 64 + 32 + lane], 0, 0, 0, 0);
      str4(&SCR->SR[1][lane >> 2][sr_off(G, 2 * lane)], 0, 0, 0, 0);
      if (c < 4 && lane < 3) str1(SCR->C + c * 32 + 3 + lane, 0);
#pragma unroll
      for (int k = 0; k < 3; ++k) str2((uint2*)SCR->CS + ((c >> 3) * 768 + k * 256 + 32 * cg + lane), 0, 0);
      __threadfence();
#pragma unroll 1
      for (int layer = 0; layer < 2; ++layer) {
        PROF(4 + 12 * layer);
        mbar_watch(B_E, layer);
        box_help(1, 0, 1, lane, layer);
        if (layer) str4(&SCR->SR[0][lane >> 2][sr_off(G, 2 * lane)], 0, 0, 0, 0);
        uint32_t* ca = opqp(SCR->C + (c >> 5) * 32 + 3 * layer + 2);
        mbar_watch(B_Z, 1);
        mbar_watch(B_RD + 8, layer);
        cnt_add1(ca);
        if (P.spare == 0) {
#pragma unroll 1
          for (int k = 0; k < 32; ++k) str4(SCR->XG[layer] + (c * 1024 + k * 32 + lane), 0, 0, 0, 0);
        }
      }
      mbar_watch(B_O + 56, 1);
    }
  }
}

typedef CUresult (*EncodeFn)(CUtensorMap*, CUtensorMapDataType, cuuint32_t, void*, const cuuint64_t*, const cuuint64_t*,
                             const cuuint32_t*, const cuuint32_t*, CUtensorMapInterleave, CUtensorMapSwizzle,
                             CUtensorMapL2promotion, CUtensorMapFloatOOBfill);

static int place_roles(uint8_t* role) {
  int dev = 0, nsm = 0;
  cudaGetDevice(&dev);
  cudaDeviceGetAttribute(&nsm, cudaDevAttrMultiProcessorCount, dev);
  if (nsm <= 128 || nsm > 144 || (nsm & 1)) return 0;
  cudaFuncSetAttribute(fused_kernel, cudaFuncAttributeNonPortableClusterSizeAllowed, 1);
  int occ[9] = {0};
  for (int k = 2; k <= 8; ++k) {
    cudaLaunchConfig_t cfg = {};
    cudaLaunchAttribute at[1];
    at[0].id = cudaLaunchAttributeClusterDimension;
    at[0].val.clusterDim.x = 2 * k; at[0].val.clusterDim.y = 1; at[0].val.clusterDim.z = 1;
    cfg.gridDim = dim3(2 * k); cfg.blockDim = dim3(NTHR); cfg.dynamicSmemBytes = SM_TOTAL; cfg.attrs = at; cfg.numAttrs = 1;
    if (cudaOccupancyMaxActiveClusters(&occ[k], fused_kernel, &cfg) != cudaSuccess) { cudaGetLastError(); occ[k] = 0; }
  }
  int n[10];
  n[7] = occ[8]; n[6] = occ[7]; n[5] = occ[6] - 0; n[4] = occ[5];
  n[3] = occ[4] - n[7]; n[1] = occ[2] - n[3] - n[5] - n[7]; n[0] = n[2] = n[1];
  n[8] = occ[3] - n[2] - n[5];
  const int ntpc = nsm / 2;
  int sum = 0;
  bool ok = n[0] > 0 && n[0] <= 8;
  for (int r = 0; r < 9; ++r) { ok = ok && n[r] >= 0 && (r == 0 || n[r] <= n[r - 1]); sum += n[r]; }
  if (!ok || sum > ntpc) { for (int r = 0; r < 9; ++r) n[r] = r < 8 ? 8 : 0; sum = 64; }
  int tp[8][9], cnt[8] = {0}, pool[72], np = 0, id = 0;
  for (int r = 0; r < 9; ++r)
    for (int g = n[0] - n[r]; g < n[0]; ++g) tp[g][cnt[g]++] = id++;
  for (; id < ntpc; ++id) pool[np++] = id;
  int order[72], no = 0;
  for (int g = 0; g < n[0]; ++g) {
    const int full = cnt[g] / 4 * 4;
    for (int k = 0; k < cnt[g]; ++k) { if (k < full) order[no++] = tp[g][k]; else pool[np++] = tp[g][k]; }
  }
  for (int k = 0; k < np; ++k) order[no++] = pool[k];
  for (int k = 0; k < ntpc; ++k) role[order[k]] = 2 * k;
  return nsm;
}

extern "C" void kernel_launch(void* const* d_in, const int* in_sizes, int n_in, void* d_out, int out_size) {
  (void)in_sizes; (void)n_in; (void)out_size;
  static EncodeFn enc = nullptr;
  static uint8_t role[72];
  static int nsm = 0;
  static Scratch* scratch = nullptr;
  if (!enc) {
    void* fn = nullptr;
    cudaDriverEntryPointQueryResult qr;
    cudaGetDriverEntryPoint("cuTensorMapEncodeTiled", &fn, cudaEnableDefault, &qr);
    enc = (EncodeFn)fn;
    cudaFuncSetAttribute(fused_kernel, cudaFuncAttributeMaxDynamicSharedMemorySize, SM_TOTAL);
    nsm = place_roles(role);
    cudaGetSymbolAddress((void**)&scratch, g_S);
  }
  CUtensorMap mW, mWo, mX;
  {
    cuuint64_t dim[3] = {512, 512, 3}, str[2] = {3072, 1024};
    cuuint32_t box[3] = {64, 64, 3}, es[3] = {1, 1, 1};
    enc(&mW, CU_TENSOR_MAP_DATA_TYPE_BFLOAT16, 3, d_in[10], dim, str, box, es, CU_TENSOR_MAP_INTERLEAVE_NONE,
        CU_TENSOR_MAP_SWIZZLE_128B, CU_TENSOR_MAP_L2_PROMOTION_NONE, CU_TENSOR_MAP_FLOAT_OOB_FILL_NONE);
  }
  {
    cuuint64_t dim[4] = {512, 2, 4, 64}, str[3] = {1024, 2048, 8192};
    cuuint32_t box[4] = {64, 2, 1, 32}, es[4] = {1, 1, 1, 1};
    enc(&mWo, CU_TENSOR_MAP_DATA_TYPE_BFLOAT16, 4, d_in[11], dim, str, box, es, CU_TENSOR_MAP_INTERLEAVE_NONE,
        CU_TENSOR_MAP_SWIZZLE_128B, CU_TENSOR_MAP_L2_PROMOTION_NONE, CU_TENSOR_MAP_FLOAT_OOB_FILL_NONE);
  }
  {
    cuuint64_t dim[2] = {16384, 64}, str[1] = {32768};
    cuuint32_t box[2] = {128, 8}, es[2] = {1, 1};
    enc(&mX, CU_TENSOR_MAP_DATA_TYPE_BFLOAT16, 2, scratch->XF[0], dim, str, box, es, CU_TENSOR_MAP_INTERLEAVE_NONE,
        CU_TENSOR_MAP_SWIZZLE_NONE, CU_TENSOR_MAP_L2_PROMOTION_NONE, CU_TENSOR_MAP_FLOAT_OOB_FILL_NONE);
  }
  Params P;
  P.x0 = (const uint16_t*)d_in[0]; P.Are = (const uint16_t*)d_in[1]; P.Aim = (const uint16_t*)d_in[2];
  P.Bre = (const uint16_t*)d_in[3]; P.Bim = (const uint16_t*)d_in[4]; P.Cre = (const uint16_t*)d_in[5];
  P.Cim = (const uint16_t*)d_in[6]; P.logdt = (const uint16_t*)d_in[7]; P.dskip = (const uint16_t*)d_in[8];
  P.wqkv = (const uint16_t*)d_in[10]; P.wo = (const uint16_t*)d_in[11]; P.out = (uint16_t*)d_out;
  for (int k = 0; k < 72; ++k) P.role[k] = role[k];
  P.zero = 0;
  P.mid = (char*)scratch->C;
  P.spare = nsm > 0 ? nsm - 128 : 0;
  fused_kernel<<<nsm > 0 ? nsm : 128, NTHR, SM_TOTAL, cudaStreamPerThread>>>(P, mW, mWo, mX);
}
```

```cpp
#include <cuda_runtime.h>
#include <cuda_bf16.h>
#include <cuda.h>
#include <stdint.h>
#include <stddef.h>

#define DEV __device__ __forceinline__
#define RARE(x) __builtin_expect(!!(x), 0)

constexpr int NTHR = 512;
constexpr int REG_MAIN = 192, REG_AUX = 88, REG_PROD = 40;
constexpr int NBARU = 384;
constexpr int SPIN_LIMIT = 1 << 22;

constexpr uint32_t SB = 1024;
__host__ __device__ constexpr uint32_t slot(int n) { return SB + n * 8192; }
__host__ __device__ constexpr int wslot(int k) { return k < 2 ? 3 * k : k < 4 ? 3 * k + 6 : k < 6 ? 21 - 3 * k : 3 * k - 18; }
constexpr uint32_t SM_A = slot(22), A_E = 0u - 32768;
constexpr uint32_t SM_O = slot(18), O_E = 0u - 147456;
constexpr uint32_t SM_WO = slot(10), SM_X = slot(8), SM_KV = slot(9) - 4096;
constexpr uint32_t SM_TAP  = slot(26);
constexpr int TAP_SZ = 3440;
constexpr uint32_t SM_STAT = SM_TAP + 4 * TAP_SZ;
constexpr uint32_t SM_CS   = SM_STAT + 1024;
constexpr uint32_t SM_BAR  = SM_CS + 768;
constexpr int SM_TOTAL = SM_BAR + 352 - SB;
static_assert(SM_TOTAL <= 232448, "");
constexpr int R_SZ = 16384, R_U = 512, R_X5 = 5120, R_X3 = 8704, R_BO = 11776, R_BE = 13824;
constexpr int X_5 = 576, X_3 = 648, T_E = 2 * 720, T_O = 1600 + 2 * 721, T_C = 3390, T_K = 3424;
constexpr uint32_t B_RD = SM_BAR, B_ED = SM_BAR + 16, B_F = SM_BAR + 32, B_AT = SM_BAR + 56, B_L = SM_BAR + 264;
constexpr uint32_t B_AE = SM_BAR + 72, B_QE = SM_BAR + 88, B_ST = SM_BAR + 96, B_CS = SM_BAR + 112;
constexpr uint32_t B_WO = SM_BAR + 120, B_W6 = SM_BAR + 128, B_U = SM_BAR + 144, B_E = SM_BAR + 152, B_WF = SM_BAR + 160, B_W4 = SM_BAR + 168,
                   B_N = SM_BAR + 176, B_V = SM_BAR + 184, B_O = SM_BAR + 192, B_Z = SM_BAR + 256, B_A = SM_BAR + 272;
constexpr int NB_U = 1, NB_B = 2, NB_K = 8, NB_Y = 6, NB_WG = 8, NB_T = 10, NB_AUX = 12, NB_P0 = 13, NB_H = 15;

struct Scratch {
  uint4    XG[2][128 * 1024];
  uint4    O[32 * 8 * 512];
  uint32_t C[8 * 32];
  uint32_t OF[2][32 * 32];
  uint4    CS[16 * 1536 / 4];
  uint4    PS[128 * 64];
  uint4    ST[2][32 * 128];
  uint4    SR[2][8][512];
  uint4    XF[2][32 * 512 * 8];
  uint4    H[2][17 * 8 * 256];
};
__device__ __align__(1024) Scratch g_S;
#define SCR ((Scratch*)(P.mid - offsetof(Scratch, C)))
#define COUNT(k) do {} while (0)
#define PROFD(slot, v) do {} while (0)
#define PROF(slot) do {} while (0)
#define PROFK(slot) do {} while (0)

#define PROFC(slot) do {} while (0)

DEV uint32_t s2u(const void* p) { return (uint32_t)__cvta_generic_to_shared(p); }
template <class T> DEV T* opqp(T* x) { asm volatile("" : "+l"(x)); return x; }
template <class T> DEV T opq(T x) { asm volatile("" : "+r"(x)); return x; }
DEV int lane_id() { int l; asm volatile("mov.u32 %0,%%laneid;" : "=r"(l)); return l; }
DEV uint32_t pack2(float lo, float hi) { uint32_t d; asm("cvt.rn.bf16x2.f32 %0,%1,%2;" : "=r"(d) : "f"(hi), "f"(lo)); return d; }
DEV float bflo(uint32_t v) { return __uint_as_float(v << 16); }
DEV float bfhi(uint32_t v) { return __uint_as_float(v & 0xFFFF0000u); }
DEV float bfr(float x) { return bflo(pack2(x, 0.f)); }
DEV uint32_t hadd2(uint32_t a, uint32_t b) { uint32_t d; asm("add.rn.bf16x2 %0,%1,%2;" : "=r"(d) : "r"(a), "r"(b)); return d; }
DEV uint32_t hsub2(uint32_t a, uint32_t b) { uint32_t d; asm("sub.rn.bf16x2 %0,%1,%2;" : "=r"(d) : "r"(a), "r"(b)); return d; }
DEV uint32_t hmul2(uint32_t a, uint32_t b) { uint32_t d; asm("mul.rn.bf16x2 %0,%1,%2;" : "=r"(d) : "r"(a), "r"(b)); return d; }
DEV uint32_t hfma2(uint32_t a, uint32_t b, uint32_t c) { uint32_t d; asm("fma.rn.bf16x2 %0,%1,%2,%3;" : "=r"(d) : "r"(a), "r"(b), "r"(c)); return d; }
DEV uint32_t prmt(uint32_t a, uint32_t b, uint32_t s) { uint32_t d; asm("prmt.b32 %0,%1,%2,%3;" : "=r"(d) : "r"(a), "r"(b), "r"(s)); return d; }
DEV uint32_t nzmap(uint32_t v) { uint32_t d; asm("max.u32 %0,%1,1;" : "=r"(d) : "r"(v)); return d; }
DEV float rcp(float x) { float y; asm("rcp.approx.ftz.f32 %0,%1;" : "=f"(y) : "f"(x)); return y; }
DEV float sqrt_(float x) { float y; asm("sqrt.approx.ftz.f32 %0,%1;" : "=f"(y) : "f"(x)); return y; }
DEV float ex2(float x) { float y; asm("ex2.approx.ftz.f32 %0,%1;" : "=f"(y) : "f"(x)); return y; }

DEV uint4 ldr4(const void* p) { uint4 v; asm volatile("ld.relaxed.gpu.global.v4.u32 {%0,%1,%2,%3},[%4];" : "=r"(v.x), "=r"(v.y), "=r"(v.z), "=r"(v.w) : "l"(p) : "memory"); return v; }
DEV void ldr4_if(uint4& v, const void* p, bool c) {
  asm volatile("{.reg .pred q; setp.ne.u32 q,%5,0; @q ld.relaxed.gpu.global.v4.u32 {%0,%1,%2,%3},[%4];}"
    : "+r"(v.x), "+r"(v.y), "+r"(v.z), "+r"(v.w) : "l"(p), "r"((uint32_t)c) : "memory");
}
DEV uint2 ldr2(const void* p) { uint2 v; asm volatile("ld.relaxed.gpu.global.v2.u32 {%0,%1},[%2];" : "=r"(v.x), "=r"(v.y) : "l"(p) : "memory"); return v; }
DEV uint32_t ldr1(const void* p) { uint32_t v; asm volatile("ld.relaxed.gpu.global.u32 %0,[%1];" : "=r"(v) : "l"(p) : "memory"); return v; }
DEV float ldnan(const uint16_t* p) {
  uint32_t v = 0xFFFFu;
#pragma unroll 1
  for (int it = 0; it < SPIN_LIMIT && __any_sync(0xffffffffu, v == 0xFFFFu); ++it) asm volatile("ld.relaxed.gpu.global.u16 %0,[%1];" : "=r"(v) : "l"(p) : "memory");
  return __uint_as_float(v << 16);
}
DEV uint4 ldw4(const void* p) { uint4 v; asm volatile("ld.global.v4.u32 {%0,%1,%2,%3},[%4];" : "=r"(v.x), "=r"(v.y), "=r"(v.z), "=r"(v.w) : "l"(p) : "memory"); return v; }
DEV uint32_t ldw1(const void* p) { uint32_t v; asm volatile("ld.global.u32 %0,[%1];" : "=r"(v) : "l"(p) : "memory"); return v; }
DEV void str4(void* p, uint32_t a, uint32_t b, uint32_t c, uint32_t d) { asm volatile("st.relaxed.gpu.global.v4.u32 [%0],{%1,%2,%3,%4};" :: "l"(p), "r"(a), "r"(b), "r"(c), "r"(d) : "memory"); }
DEV void str2(void* p, uint32_t a, uint32_t b) { asm volatile("st.relaxed.gpu.global.v2.u32 [%0],{%1,%2};" :: "l"(p), "r"(a), "r"(b) : "memory"); }
DEV void str1(void* p, uint32_t a) { asm volatile("st.relaxed.gpu.global.u32 [%0],%1;" :: "l"(p), "r"(a) : "memory"); }
DEV void str4_if(void* p, uint32_t a, uint32_t b, uint32_t c, uint32_t d, bool q) {
  asm volatile("{.reg .pred q; setp.ne.u32 q,%5,0; @q st.relaxed.gpu.global.v4.u32 [%0],{%1,%2,%3,%4};}" :: "l"(p), "r"(a), "r"(b), "r"(c), "r"(d), "r"((uint32_t)q) : "memory");
}
DEV void stw4(void* p, uint32_t a, uint32_t b, uint32_t c, uint32_t d) { asm volatile("st.global.v4.u32 [%0],{%1,%2,%3,%4};" :: "l"(p), "r"(a), "r"(b), "r"(c), "r"(d) : "memory"); }
DEV uint4 ldnc4(const void* p) { uint4 v; asm volatile("ld.global.nc.v4.u32 {%0,%1,%2,%3},[%4];" : "=r"(v.x), "=r"(v.y), "=r"(v.z), "=r"(v.w) : "l"(p)); return v; }

DEV uint2 lds2(uint32_t a) { uint2 v; asm volatile("ld.volatile.shared.v2.u32 {%0,%1},[%2];" : "=r"(v.x), "=r"(v.y) : "r"(a)); return v; }
DEV void sts2(uint32_t a, uint32_t x, uint32_t y) { asm volatile("st.shared.v2.u32 [%0],{%1,%2};" :: "r"(a), "r"(x), "r"(y) : "memory"); }
DEV uint32_t lds1(uint32_t a) { uint32_t v; asm volatile("ld.volatile.shared.u32 %0,[%1];" : "=r"(v) : "r"(a)); return v; }
DEV uint32_t lds1z(uint32_t a, bool c) {
  uint32_t v; asm volatile("{.reg .pred q; setp.ne.u32 q,%2,0; mov.u32 %0,0; @q ld.volatile.shared.u32 %0,[%1];}" : "=r"(v) : "r"(a), "r"((uint32_t)c)); return v;
}
DEV uint4 lds4z(uint32_t a, bool c) {
  uint4 v = make_uint4(0, 0, 0, 0);
  asm volatile("{.reg .pred q; setp.ne.u32 q,%5,0; @q ld.volatile.shared.v4.u32 {%0,%1,%2,%3},[%4];}" : "+r"(v.x), "+r"(v.y), "+r"(v.z), "+r"(v.w) : "r"(a), "r"((uint32_t)c));
  return v;
}
DEV float2 lds2f(uint32_t a) { float2 v; asm volatile("ld.shared.v2.f32 {%0,%1},[%2];" : "=f"(v.x), "=f"(v.y) : "r"(a)); return v; }
DEV float4 lds4f(uint32_t a) { float4 v; asm volatile("ld.volatile.shared.v4.f32 {%0,%1,%2,%3},[%4];" : "=f"(v.x), "=f"(v.y), "=f"(v.z), "=f"(v.w) : "r"(a)); return v; }
DEV uint4 lds4(uint32_t a) { uint4 v; asm volatile("ld.volatile.shared.v4.u32 {%0,%1,%2,%3},[%4];" : "=r"(v.x), "=r"(v.y), "=r"(v.z), "=r"(v.w) : "r"(a)); return v; }
DEV void sts1(uint32_t a, uint32_t v) { asm volatile("st.shared.u32 [%0],%1;" :: "r"(a), "r"(v) : "memory"); }
DEV void sts16(uint32_t a, uint32_t v) { asm volatile("st.shared.u16 [%0],%1;" :: "r"(a), "r"(v) : "memory"); }
DEV void sts2f(uint32_t a, float x, float y) { asm volatile("st.shared.v2.f32 [%0],{%1,%2};" :: "r"(a), "f"(x), "f"(y) : "memory"); }
DEV void sts4f(uint32_t a, float x, float y, float z, float w) { asm volatile("st.shared.v4.f32 [%0],{%1,%2,%3,%4};" :: "r"(a), "f"(x), "f"(y), "f"(z), "f"(w) : "memory"); }
DEV void sts4(uint32_t a, uint32_t x, uint32_t y, uint32_t z, uint32_t w) { asm volatile("st.shared.v4.u32 [%0],{%1,%2,%3,%4};" :: "r"(a), "r"(x), "r"(y), "r"(z), "r"(w) : "memory"); }

DEV void ldsm4(uint32_t (&r)[4], uint32_t a) { asm volatile("ldmatrix.sync.aligned.m8n8.x4.shared.b16 {%0,%1,%2,%3},[%4];" : "=r"(r[0]), "=r"(r[1]), "=r"(r[2]), "=r"(r[3]) : "r"(a) : "memory"); }
DEV void ldsm4t(uint32_t (&r)[4], uint32_t a) { asm volatile("ldmatrix.sync.aligned.m8n8.x4.trans.shared.b16 {%0,%1,%2,%3},[%4];" : "=r"(r[0]), "=r"(r[1]), "=r"(r[2]), "=r"(r[3]) : "r"(a) : "memory"); }
DEV void stsm4(uint32_t a, uint32_t r0, uint32_t r1, uint32_t r2, uint32_t r3) { asm volatile("stmatrix.sync.aligned.m8n8.x4.shared.b16 [%0],{%1,%2,%3,%4};" :: "r"(a), "r"(r0), "r"(r1), "r"(r2), "r"(r3) : "memory"); }
DEV void stsm2(uint32_t a, uint32_t r0, uint32_t r1) { asm volatile("stmatrix.sync.aligned.m8n8.x2.shared.b16 [%0],{%1,%2};" :: "r"(a), "r"(r0), "r"(r1) : "memory"); }
DEV void stsm4t(uint32_t a, uint32_t r0, uint32_t r1, uint32_t r2, uint32_t r3) { asm volatile("stmatrix.sync.aligned.m8n8.x4.trans.shared.b16 [%0],{%1,%2,%3,%4};" :: "r"(a), "r"(r0), "r"(r1), "r"(r2), "r"(r3) : "memory"); }
DEV uint32_t movm(uint32_t a) { uint32_t d; asm volatile("movmatrix.sync.aligned.m8n8.trans.b16 %0,%1;" : "=r"(d) : "r"(a)); return d; }
DEV void mma16(float (&d)[4], uint32_t a0, uint32_t a1, uint32_t a2, uint32_t a3, uint32_t b0, uint32_t b1) {
  asm volatile("mma.sync.aligned.m16n8k16.row.col.f32.bf16.bf16.f32 {%0,%1,%2,%3},{%4,%5,%6,%7},{%8,%9},{%0,%1,%2,%3};"
    : "+f"(d[0]), "+f"(d[1]), "+f"(d[2]), "+f"(d[3]) : "r"(a0), "r"(a1), "r"(a2), "r"(a3), "r"(b0), "r"(b1));
}
DEV void mma16z(float (&d)[4], uint32_t a0, uint32_t a1, uint32_t a2, uint32_t a3, uint32_t b0, uint32_t b1) {
  asm volatile("mma.sync.aligned.m16n8k16.row.col.f32.bf16.bf16.f32 {%0,%1,%2,%3},{%4,%5,%6,%7},{%8,%9},{%10,%10,%10,%10};"
    : "=f"(d[0]), "=f"(d[1]), "=f"(d[2]), "=f"(d[3]) : "r"(a0), "r"(a1), "r"(a2), "r"(a3), "r"(b0), "r"(b1), "f"(0.f));
}
DEV void mma8(float (&d)[4], uint32_t a0, uint32_t a1, uint32_t b0) {
  asm volatile("mma.sync.aligned.m16n8k8.row.col.f32.bf16.bf16.f32 {%0,%1,%2,%3},{%4,%5},{%6},{%0,%1,%2,%3};"
    : "+f"(d[0]), "+f"(d[1]), "+f"(d[2]), "+f"(d[3]) : "r"(a0), "r"(a1), "r"(b0));
}

DEV void mma8z(float (&d)[4], uint32_t a0, uint32_t a1, uint32_t b0) {
  asm volatile("mma.sync.aligned.m16n8k8.row.col.f32.bf16.bf16.f32 {%0,%1,%2,%3},{%4,%5},{%6},{%7,%7,%7,%7};"
    : "=f"(d[0]), "=f"(d[1]), "=f"(d[2]), "=f"(d[3]) : "r"(a0), "r"(a1), "r"(b0), "f"(0.f));
}
DEV void bar_sync(int id, int n) { asm volatile("bar.sync %0,%1;" :: "r"(id), "r"(n) : "memory"); }
DEV void bar_sync_if(int id, int n, int c) { asm volatile("{.reg .pred q; setp.ne.s32 q,%2,0; @q bar.sync %0,%1;}" :: "r"(id), "r"(n), "r"(c) : "memory"); }
DEV void bar_arrive_if(int id, int n, int c) { asm volatile("{.reg .pred q; setp.ne.s32 q,%2,0; @q bar.arrive %0,%1;}" :: "r"(id), "r"(n), "r"(c) : "memory"); }
DEV void bar_arrive(int id, int n) { asm volatile("bar.arrive %0,%1;" :: "r"(id), "r"(n) : "memory"); }
DEV void fence_async_smem() { asm volatile("fence.proxy.async.shared::cta;" ::: "memory"); }
DEV void mbar_wait(uint32_t b, uint32_t ph) {
  asm volatile("{\n.reg .pred p;\nW: mbarrier.try_wait.parity.shared::cta.b64 p,[%0],%1;\n@!p bra W;\n}" :: "r"(b), "r"(ph) : "memory");
}
DEV void mbar_watch(uint32_t b, uint32_t ph) {
  asm volatile("{\n.reg .pred p,q;\n.reg .u32 n;\nmov.u32 n,0;\n"
               "W: mbarrier.try_wait.parity.shared::cta.b64 p,[%0],%1;\n@p bra D;\n"
               "add.u32 n,n,1;\nsetp.lt.u32 q,n,%2;\n@q bra W;\ntrap;\nD:\n}"
               :: "r"(b), "r"(ph), "n"(SPIN_LIMIT) : "memory");
}
DEV void spin_guard(int it) { asm volatile("{.reg .pred p; setp.gt.s32 p,%0,%1; @p trap;}" :: "r"(it), "n"(SPIN_LIMIT)); }
DEV void split(uint32_t zero) {
  asm volatile("{.reg .pred p; setp.ne.u32 p,%0,0; @p trap;}" :: "r"(zero) : "memory");
}
DEV void pause(int n) {
  uint32_t t0, t; asm volatile("mov.u32 %0,%%clock;" : "=r"(t0));
  do asm volatile("mov.u32 %0,%%clock;" : "=r"(t)); while (t - t0 < n);
}
DEV void poll(const uint32_t* k, uint32_t n) {
#pragma unroll 1
  for (int it = 0;; ++it) {
    spin_guard(it);
    if (__all_sync(0xffffffffu, ldr1(k) >= n)) break;
  }
}
DEV void mbar_arrive1(uint32_t b) { asm volatile("{.reg .pred p; elect.sync _|p,0xffffffff; @p mbarrier.arrive.shared::cta.b64 _,[%0];}" :: "r"(b) : "memory"); }
DEV void mbar_arrive1_if(uint32_t b, int c) {
  asm volatile("{.reg .pred p,q; setp.ne.s32 q,%1,0; elect.sync _|p,0xffffffff; and.pred p,p,q; @p mbarrier.arrive.shared::cta.b64 _,[%0];}" :: "r"(b), "r"(c) : "memory");
}
DEV void mbar_expect1(uint32_t b, int bytes) { asm volatile("{.reg .pred p; elect.sync _|p,0xffffffff; @p mbarrier.arrive.expect_tx.shared::cta.b64 _,[%0],%1;}" :: "r"(b), "r"(bytes) : "memory"); }
DEV void cnt_add1(uint32_t* q) { asm volatile("{.reg .pred p; elect.sync _|p,0xffffffff; @p red.relaxed.gpu.global.add.u32 [%0],1;}" :: "l"(q) : "memory"); }
DEV void tma4(uint32_t dst, const CUtensorMap* m, int c0, int c1, int c2, int c3, uint32_t bar) {
  asm volatile("{.reg .pred p; elect.sync _|p,0xffffffff;\n"
    "@p cp.async.bulk.tensor.4d.shared::cluster.global.mbarrier::complete_tx::bytes [%0],[%1,{%2,%3,%4,%5}],[%6];}"
    :: "r"(dst), "l"(m), "r"(c0), "r"(c1), "r"(c2), "r"(c3), "r"(bar) : "memory");
}
DEV void tma3(uint32_t dst, const CUtensorMap* m, int c0, int c1, int c2, uint32_t bar) {
  asm volatile("{.reg .pred p; elect.sync _|p,0xffffffff;\n"
    "@p cp.async.bulk.tensor.3d.shared::cluster.global.mbarrier::complete_tx::bytes [%0],[%1,{%2,%3,%4}],[%5];}"
    :: "r"(dst), "l"(m), "r"(c0), "r"(c1), "r"(c2), "r"(bar) : "memory");
}
DEV void bulk(uint32_t dst, const void* src, int bytes, uint32_t bar) {
  asm volatile("{.reg .pred p; elect.sync _|p,0xffffffff;\n@p cp.async.bulk.shared::cluster.global.mbarrier::complete_tx::bytes [%0],[%1],%2,[%3];}" :: "r"(dst), "l"(src), "r"(bytes), "r"(bar) : "memory");
}

DEV void bulk_store(void* dst, uint32_t src, int bytes) {
  asm volatile("{.reg .pred p; elect.sync _|p,0xffffffff;\n@p cp.async.bulk.global.shared::cta.bulk_group [%0],[%1],%2;}" :: "l"(dst), "r"(src), "r"(bytes) : "memory");
}
DEV void tma2_store(const CUtensorMap* m, uint32_t src, int c0, int c1) {
  asm volatile("{.reg .pred p; elect.sync _|p,0xffffffff;\n@p cp.async.bulk.tensor.2d.global.shared::cta.bulk_group [%0,{%2,%3}],[%1];}" :: "l"(m), "r"(src), "r"(c0), "r"(c1) : "memory");
}
DEV void bulk_wait() { asm volatile("cp.async.bulk.commit_group;\ncp.async.bulk.wait_group 0;\nfence.proxy.async.global;" ::: "memory"); }

DEV uint32_t dlo(uint32_t addr, uint32_t lbo) { return __shfl_sync(0xffffffffu, (addr >> 4) | ((lbo >> 4) << 16), 0); }
__host__ __device__ constexpr uint32_t dhi(uint32_t sbo, uint32_t swz) { return (sbo >> 4) | (swz << 30); }
DEV void wg_fence() { asm volatile("wgmma.fence.sync.aligned;" ::: "memory"); }
DEV void wg_commit() { asm volatile("wgmma.commit_group.sync.aligned;" ::: "memory"); }
template <int N> DEV void wg_wait() { asm volatile("wgmma.wait_group.sync.aligned %0;" :: "n"(N) : "memory"); }
template <int N> DEV void zero(float (&d)[N]) {
#pragma unroll
  for (int i = 0; i < N; ++i) d[i] = 0.f;
}
template <int N> DEV void zerov(float (&d)[N]) {
#pragma unroll
  for (int i = 0; i < N; ++i) asm volatile("mov.b32 %0,0;" : "=f"(d[i]));
}
template <int N> DEV void undef(float (&d)[N]) {
#pragma unroll
  for (int i = 0; i < N; ++i) asm volatile("" : "=f"(d[i]));
}
#define R4(d, o) "+f"(d[o]), "+f"(d[o + 1]), "+f"(d[o + 2]), "+f"(d[o + 3])
#define R8(d, o) R4(d, o), R4(d, o + 4)
#define R16(d, o) R8(d, o), R8(d, o + 8)
template <int ACC> DEV void wg_rs64k(float (&d)[32], const uint32_t (&a)[4], uint32_t db) {
  asm volatile("{.reg .pred p; .reg .b64 b; setp.ne.s32 p,%38,0; mov.b64 b,{%36,%37};\n"
    "wgmma.mma_async.sync.aligned.m64n64k16.f32.bf16.bf16 {%0,%1,%2,%3,%4,%5,%6,%7,%8,%9,%10,%11,%12,%13,%14,%15,%16,%17,%18,%19,%20,%21,%22,%23,%24,%25,%26,%27,%28,%29,%30,%31},{%32,%33,%34,%35},b,p,1,1,0;}"
    : R16(d, 0), R16(d, 16) : "r"(a[0]), "r"(a[1]), "r"(a[2]), "r"(a[3]), "r"(db), "n"(dhi(512, 2)), "n"(ACC));
}
template <int ACC> DEV void wg_rs48t(float (&d)[24], const uint32_t (&a)[4], uint32_t db) {
  asm volatile("{.reg .pred p; .reg .b64 b; setp.ne.s32 p,%30,0; mov.b64 b,{%28,%29};\n"
    "wgmma.mma_async.sync.aligned.m64n48k16.f32.bf16.bf16 {%0,%1,%2,%3,%4,%5,%6,%7,%8,%9,%10,%11,%12,%13,%14,%15,%16,%17,%18,%19,%20,%21,%22,%23},{%24,%25,%26,%27},b,p,1,1,1;}"
    : R16(d, 0), R8(d, 16) : "r"(a[0]), "r"(a[1]), "r"(a[2]), "r"(a[3]), "r"(db), "n"(dhi(512, 0)), "n"(ACC));
}
template <int ACC> DEV void wg_rs32t(float (&d)[16], const uint32_t (&a)[4], uint32_t db) {
  asm volatile("{.reg .pred p; .reg .b64 b; setp.ne.s32 p,%22,0; mov.b64 b,{%20,%21};\n"
    "wgmma.mma_async.sync.aligned.m64n32k16.f32.bf16.bf16 {%0,%1,%2,%3,%4,%5,%6,%7,%8,%9,%10,%11,%12,%13,%14,%15},{%16,%17,%18,%19},b,p,1,1,1;}"
    : R16(d, 0) : "r"(a[0]), "r"(a[1]), "r"(a[2]), "r"(a[3]), "r"(db), "n"(dhi(1024, 0)), "n"(ACC));
}
template <int ACC> DEV void wg_ss192(float (&d)[96], uint32_t da, uint32_t db) {
  asm volatile("{.reg .pred p; .reg .b64 a,b; setp.ne.s32 p,%100,0; mov.b64 a,{%96,%98}; mov.b64 b,{%97,%99};\n"
    "wgmma.mma_async.sync.aligned.m64n192k16.f32.bf16.bf16 {"
    "%0,%1,%2,%3,%4,%5,%6,%7,%8,%9,%10,%11,%12,%13,%14,%15,%16,%17,%18,%19,%20,%21,%22,%23,%24,%25,%26,%27,%28,%29,%30,%31,"
    "%32,%33,%34,%35,%36,%37,%38,%39,%40,%41,%42,%43,%44,%45,%46,%47,%48,%49,%50,%51,%52,%53,%54,%55,%56,%57,%58,%59,%60,%61,%62,%63,"
    "%64,%65,%66,%67,%68,%69,%70,%71,%72,%73,%74,%75,%76,%77,%78,%79,%80,%81,%82,%83,%84,%85,%86,%87,%88,%89,%90,%91,%92,%93,%94,%95},a,b,p,1,1,1,1;}"
    : R16(d, 0), R16(d, 16), R16(d, 32), R16(d, 48), R16(d, 64), R16(d, 80) : "r"(da), "r"(db), "n"(dhi(1024, 1)), "n"(dhi(1024, 1)), "n"(ACC));
}
template <int ACC> DEV void wg_ss64(float (&d)[32], uint32_t da, uint32_t db) {
  asm volatile("{.reg .pred p; .reg .b64 a,b; setp.ne.s32 p,%36,0; mov.b64 a,{%32,%34}; mov.b64 b,{%33,%35};\n"
    "wgmma.mma_async.sync.aligned.m64n64k16.f32.bf16.bf16 {"
    "%0,%1,%2,%3,%4,%5,%6,%7,%8,%9,%10,%11,%12,%13,%14,%15,%16,%17,%18,%19,%20,%21,%22,%23,%24,%25,%26,%27,%28,%29,%30,%31},a,b,p,1,1,0,1;}"
    : R16(d, 0), R16(d, 16) : "r"(da), "r"(db), "n"(dhi(1024, 0)), "n"(dhi(1024, 1)), "n"(ACC));
}

DEV uint32_t cpy(uint32_t v, uint32_t id) {
  uint32_t d; asm volatile("prmt.b32 %0,%1,%1,%2;" : "=r"(d) : "r"(v), "r"(id)); return d;
}
struct Params {
  uint32_t zero, spare;
  char* mid;
  const uint16_t *x0, *Are, *Aim, *Bre, *Bim, *Cre, *Cim, *logdt, *dskip, *wqkv, *wo;
  uint16_t* out;
  uint8_t role[72];
};

DEV uint32_t ln_word(float mean, float var) {
  float v = bfr(var);
  float s = sqrt_(bfr(v + 1e-5f));
  return pack2(mean, s);
}

DEV int stat_group(int c) { return c ^ 4; }
DEV int xg_off(int G, int g) { return (G >> 5) * 512 + (G & 31) * 8 + (g ^ (G & 2)); }
DEV int sr_off(int G, int g) { return (G >> 6) * 256 + (g & 2) * 64 + 2 * (G & 63) + ((g >> 2) & 1); }
DEV uint32_t region(int chl) { return SM_A + (chl >> 1) * A_E + (chl & 1) * R_SZ; }
template <bool FIRST> DEV void gram(float (&s)[4], float (&q0)[4], float (&q1)[4], uint32_t a0, uint32_t a1, uint32_t a2, uint32_t a3) {
  const uint32_t one = 0x3F803F80u;
  if (FIRST) { mma16z(s, a0, a1, a2, a3, one, one); mma8z(q0, a0, a1, a0); mma8z(q1, a0, a1, a1); }
  else { mma16(s, a0, a1, a2, a3, one, one); mma8(q0, a0, a1, a0); mma8(q1, a0, a1, a1); }
  mma8(q0, a2, a3, a2); mma8(q1, a2, a3, a3);
}
DEV uint32_t ln_sums(float s, float q) { const float m = s * (1.f / 512.f); return ln_word(m, fmaxf(q * (1.f / 512.f) - m * m, 0.f)); }
DEV void cmul(float& orr, float& oi, float ar, float ai, float br, float bi) {
  float r = ar * br - ai * bi, i = ar * bi + ai * br; orr = r; oi = i;
}
DEV void cexp_(float al, float bt, float s, float& er, float& ei) {
  float mag = ex2(al * s), ph = bt * s;
  ph -= rintf(ph);
  float ang = ph * 6.283185307179586f;
  er = mag * __cosf(ang); ei = mag * __sinf(ang);
}

DEV void kgen(const Params& P, int c, int wm, int lane) {
  const int chl = wm >> 1, mh = wm & 1, g = lane >> 2, t = lane & 3;
  const int ch = 256 * (chl >> 1) + 2 * c + (chl & 1);
  const int mo = ch * 64 + mh * 32 + lane;
  const uint32_t vAr = ldw1((const uint32_t*)P.Are + mo), vAi = ldw1((const uint32_t*)P.Aim + mo);
  const uint32_t vBr = ldw1((const uint32_t*)P.Bre + mo), vBi = ldw1((const uint32_t*)P.Bim + mo);
  const uint32_t vCr = ldw1((const uint32_t*)P.Cre + mo), vCi = ldw1((const uint32_t*)P.Cim + mo);
  const uint32_t vld = ldw1((const uint32_t*)P.logdt + (ch >> 1)), vds = ldw1((const uint32_t*)P.dskip + (ch >> 1));
  bar_arrive(NB_Y, 384);
  PROF(45);
  {
    const uint32_t tz = SM_TAP + chl * TAP_SZ + (mh * 32 + lane) * 16;
#pragma unroll
    for (int k = 0; k < 3; ++k) sts4(tz + k * 1024, 0, 0, 0, 0);
    static_assert(TAP_SZ > 3072 && TAP_SZ <= 4096, "");
    if (mh * 32 + lane < TAP_SZ / 16 - 192) sts4(tz + 3072, 0, 0, 0, 0);
  }
  const uint32_t tb = slot(wm), tw = opq(tb + lane * 4);
  const uint32_t aa = opq(tb + (lane & 15) * 144 + (lane >> 4) * 16), ba = opq(tb + (16 + (lane & 7)) * 144 + (lane >> 3) * 16);
  float acc[5][4], k2048 = 0.f;
#pragma unroll
  for (int i = 0; i < 5; ++i) zerov(acc[i]);
  sts1(tw, 0x3F80u);
  asm volatile("setmaxnreg.inc.sync.aligned.u32 %0;" :: "n"(REG_MAIN));
  PROF(44);
  const float dt = bfr(ex2((ch & 1 ? bfhi(vld) : bflo(vld)) * 1.4426950408889634f));
#pragma unroll 1
  for (int r = 0; r < 2; ++r) {
    const uint32_t sel = r ? 0x3244 : 0x1044;
    const float are = __uint_as_float(prmt(vAr, 0, sel)), aim = __uint_as_float(prmt(vAi, 0, sel)), bre = __uint_as_float(prmt(vBr, 0, sel));
    const float bim = __uint_as_float(prmt(vBi, 0, sel)), cre = __uint_as_float(prmt(vCr, 0, sel)), cim = __uint_as_float(prmt(vCi, 0, sel));
    const float al = dt * are * 1.4426950408889634f, bt = dt * aim * 0.15915494309189535f;
    float qr, qi; cmul(qr, qi, cre, cim, dt * bre, dt * bim);
    if (r == 0) PROFD(2, __float_as_uint(qr + al + bt));
    float er[3], ei[3], e8r, e8i, eLr, eLi;
    cexp_(al, bt, 1.f, er[0], ei[0]); cexp_(al, -bt, 8.f, e8r, e8i); cexp_(al, bt, 128.f, eLr, eLi);
    cmul(er[1], ei[1], er[0], ei[0], er[0], ei[0]); cmul(er[2], ei[2], er[1], ei[1], er[1], ei[1]);
    float yr = e8r, yi = e8i;
#pragma unroll
    for (int a = 0; a < 16; ++a) {
      if (a) sts1(tw + a * 144, pack2(yr, yi));
      if (a && a < 15) cmul(yr, yi, yr, yi, e8r, e8i);
      const int ls = a < 2 ? 0 : a < 4 ? 1 : a < 8 ? 2 : 3;
      const int row0 = 16 + (a < 2 ? 8 * a : a < 4 ? 16 + 4 * (a - 2) : a < 8 ? 24 + 2 * (a - 4) : 32 + (a - 8));
      float xr[8], xi[8];
      xr[0] = qr; xi[0] = qi;
#pragma unroll
      for (int k = 0; k < (8 >> ls); ++k) {
        const int hb = k >= 4 ? 2 : k >= 2 ? 1 : 0;
        if (k) cmul(xr[k], xi[k], xr[k - (1 << hb)], xi[k - (1 << hb)], er[(ls + hb) % 3], ei[(ls + hb) % 3]);
        sts1(tw + (row0 + k) * 144, pack2(xr[k], xi[k]));
      }
      cmul(qr, qi, qr, qi, eLr, eLi);
    }
    __syncwarp();
    if (r == 0) PROF(3);
#pragma unroll
    for (int kp = 0; kp < 2; ++kp) {
      uint32_t a0[4], a1[4];
      ldsm4(a0, aa + kp * 64); ldsm4(a1, aa + kp * 64 + 32);
#pragma unroll
      for (int tl = 0; tl < 5; ++tl) {
        uint32_t b[4];
        ldsm4(b, ba + 8 * tl * 144 + kp * 64);
        if (kp == 0) qr += __shfl_xor_sync(0xffffffffu, qr, 1 << tl);
        mma16(acc[tl], a0[0], a0[1], a0[2], a0[3], b[0], b[1]);
        mma16(acc[tl], a1[0], a1[1], a1[2], a1[3], b[2], b[3]);
      }
    }
    k2048 += qr;
    __syncwarp();
  }
  const uint32_t xa = tb + lane * 16, ob = xa ^ 8192, tp = SM_TAP + chl * TAP_SZ;
  if (mh == 0) {
    sts4f(xa, acc[2][0], acc[2][1], acc[2][2], acc[2][3]);
    sts4f(xa + 512, acc[3][0], acc[3][1], acc[3][2], acc[3][3]);
    sts1(tb + 1024, __float_as_uint(k2048));
  } else {
    sts4f(xa, acc[0][0], acc[0][1], acc[0][2], acc[0][3]);
    sts4f(xa + 512, acc[1][0], acc[1][1], acc[1][2], acc[1][3]);
    sts4f(xa + 1024, acc[4][0], acc[4][1], acc[4][2], acc[4][3]);
  }
  PROF(4);
  bar_sync(NB_K + chl, 64);
  float4 o[3];
#pragma unroll
  for (int k = 0; k < 3; ++k) o[k] = lds4f(ob + k * 512);
  if (mh == 0) {
    if (lane == 0) o[0].x += ch & 1 ? bfhi(vds) : bflo(vds);
    const uint32_t a = tp - 2 * (8 * g + 2 * t + 1);
#pragma unroll
    for (int z = 0; z < 4; ++z) {
      const float* k = acc[z >> 1] + 2 * (z & 1);
      const uint32_t v = z & 1 ? pack2(k[1] + o[z >> 1].w, k[0] + o[z >> 1].z) : pack2(k[1] + o[z >> 1].y, k[0] + o[z >> 1].x);
      sts1(a + T_O - 128 * z, v); sts16(a + T_E - 128 * z, v); sts16(a + T_E + 2 - 128 * z, v >> 16);
    }
    const uint32_t v0 = pack2(acc[4][0] + o[2].x, acc[4][1] + o[2].y), v1 = pack2(acc[4][2] + o[2].z, acc[4][3] + o[2].w);
    const uint32_t b = tp + T_C - 2 * (32 * t + g - 1);
    if (lane == 0) { sts16(tp + T_E - 2 * (X_5 + 63), v0); sts16(tp + T_O - 2 * (X_5 + 63), v0); sts1(tp + T_K, prmt(v0, v0, 0x1010)); }
    else sts16(b, v0);
    sts16(b - 32, v0 >> 16); sts16(b - 16, v1); sts16(b - 48, v1 >> 16);
  } else {
    const uint32_t a = tp - 2 * (256 + 128 * (t >> 1) + 4 * (t & 1) + 8 * g);
#pragma unroll
    for (int z = 0; z < 2; ++z) {
      const uint32_t v = z ? pack2(acc[2][3] + o[0].w, acc[2][2] + o[0].z) : pack2(acc[2][1] + o[0].y, acc[2][0] + o[0].x), d = prmt(v, v, 0x3232);
      sts1(a + T_E - 4 - 128 * z, v); sts16(a + T_O - 4 - 128 * z, v); sts1(a + T_O - 2 - 128 * z, d);
      if (z || lane) { sts1(a + T_E - 128 * z, d); sts16(a + T_O + 2 - 128 * z, d); } else sts16(a + T_E, d);
    }
    const uint32_t w0 = pack2(acc[3][0] + o[1].x, acc[3][1] + o[1].y), w1 = pack2(acc[3][2] + o[1].z, acc[3][3] + o[1].w);
    const uint32_t b = tp - 2 * (16 * t + g);
    if (lane == 0) {
      const uint32_t k = prmt(w0, w0, 0x1010);
      sts1(tp + T_E - 2 * 514, k); sts1(tp + T_E - 2 * 512, k);
      sts16(tp + T_O - 2 * 514, k); sts1(tp + T_O - 2 * 513, k); sts16(tp + T_O - 2 * 511, k);
      sts16(tp + T_C - 2 * 127, pack2(k2048 + o[2].x, 0.f));
    } else { sts16(b + T_E - 2 * (X_5 - 1), w0); sts16(b + T_O - 2 * (X_5 - 1), w0); }
    sts16(b + T_E - 2 * X_3, w0 >> 16); sts16(b + T_O - 2 * X_3, w0 >> 16);
    sts16(b + T_E - 2 * (X_5 + 7), w1); sts16(b + T_O - 2 * (X_5 + 7), w1);
    sts16(b + T_E - 2 * (X_3 + 8), w1 >> 16); sts16(b + T_O - 2 * (X_3 + 8), w1 >> 16);
  }
}

DEV bool bad8(const uint4& v) { return min(v.x, v.z) == 0u; }
DEV uint32_t uchunk(uint32_t reg, int x) { return reg + R_U + (x ^ ((x >> 3) & 3)) * 16; }
DEV uint32_t& xword(uint4 (&x)[2], int e, int tp) { uint4& v = x[tp >> 1]; return tp & 1 ? (e ? v.w : v.z) : (e ? v.y : v.x); }

DEV void uprep(const Params& P, int c, int wa, int lane, int layer, uint4 (&x)[2][2][2], uint32_t (&u)[4][4]) {
  const int j = 32 * wa + lane, o0 = 2 * (j + (j & 64)) + ((j >> 2) & 1);
  {
    const uint32_t za = region(wa) + lane * 16 - 512;
    sts4(za + R_U, 0, 0, 0, 0); sts4(za + R_X5, 0, 0, 0, 0); sts4(za + R_X3, 0, 0, 0, 0);
    sts4(region(wa) + R_BE, 0, 0, 0, 0);
  }
  const uint4* st = opqp(&SCR->SR[layer][c >> 4][j]);
  const uint32_t xa = opq(SM_X + 16 * o0), xb = opq(SM_X + 16 * (o0 ^ 1)), ua = opq(uchunk(0, j));
  uint4 s[2][2];
#pragma unroll
  for (int z = 0; z < 12; ++z) {
    uint4& v = z < 8 ? x[(z >> 2) & 1][(z >> 1) & 1][z & 1] : s[(z >> 1) & 1][z & 1];
    asm volatile("mov.b32 %0,0; mov.b32 %1,0; mov.b32 %2,0; mov.b32 %3,0;" : "=r"(v.x), "=r"(v.y), "=r"(v.z), "=r"(v.w));
  }
#pragma unroll 1
  for (uint32_t it = P.zero;; ++it) {
    if (it) {
      spin_guard(it);
      COUNT(3);
#pragma unroll
      for (int z = 0; z < 4; ++z) { uint4& v = s[z >> 1][z & 1]; ldr4_if(v, st + z * 128, bad8(v)); }
      const uint4* xp = &SCR->XG[layer][c * 1024 + o0];
#pragma unroll
      for (int z = 0; z < 8; ++z) {
        uint4& v = x[z >> 2][(z >> 1) & 1][z & 1];
        ldr4_if(v, (const uint4*)((uintptr_t)xp ^ (16 * (z & 1))) + (z >> 2) * 512 + (z & 2) * 64, bad8(v));
      }
    } else {
      mbar_wait(B_U, layer);
      PROF(layer ? 25 : 10);
#pragma unroll
      for (int z = 0; z < 4; ++z) s[z >> 1][z & 1] = ldr4(st + z * 128);
#pragma unroll
      for (int z = 0; z < 4; ++z) { uint4& v = s[z >> 1][z & 1]; ldr4_if(v, st + z * 128, bad8(v)); }
      PROF(layer ? 26 : 11);
      mbar_wait(B_E, layer);
#pragma unroll
      for (int z = 7; z >= 0; --z) x[z >> 2][(z >> 1) & 1][z & 1] = lds4((z & 1 ? xb : xa) + (z >> 2) * 8192 + (z & 2) * 1024);
      PROF(layer ? 27 : 14);
    }
    uint32_t m = ~0u;
#pragma unroll
    for (int z = 7; z >= 0; --z) {
      const int k = z >> 2, chl = z & 3;
#pragma unroll
      for (int tp = 0; tp < 4; ++tp) u[chl][tp] = hmul2(hsub2(xword(x[k][chl >> 1], chl & 1, tp), xword(s[k], 1, tp)), xword(s[k], 0, tp));
      sts4(ua + region(chl) + k * 2048, u[chl][0], u[chl][1], u[chl][2], u[chl][3]);
      const uint4& v = x[k][chl >> 1][chl & 1];
      m = min(m, min(v.x, v.z));
      if (z < 4) m = min(m, min(s[z >> 1][z & 1].x, s[z >> 1][z & 1].z));
    }
    if (!__any_sync(0xffffffffu, m == 0)) break;
  }
  PROF(4 + 12 * layer);
}

template <bool FULL> DEV void box_unit(uint32_t reg, int s, const uint2& a, const uint4& b, const uint32_t (&d)[4], uint32_t (&pv)[4]) {
  const uint32_t u[9] = {a.x, a.y, b.x, b.y, b.z, b.w, d[0], d[1], d[2]};
  uint32_t v[8], p[8];
#pragma unroll
  for (int j = 0; j < 8; ++j) { v[j] = prmt(u[j], u[j + 1], 0x5432); p[j] = hadd2(u[j], v[j]); }
  uint32_t x[4], y[4], z9[4], z7[4];
#pragma unroll
  for (int j = 0; j < 4; ++j) { x[j] = hadd2(hadd2(p[1 + j], p[2 + j]), u[3 + j]); y[j] = hadd2(v[3 + j], p[4 + j]); pv[j] = p[4 + j]; }
  const uint32_t o = reg + s * 16;
  if (FULL) {
#pragma unroll
    for (int j = 0; j < 4; ++j) { z7[j] = hadd2(hadd2(v[j], v[3 + j]), x[j]); z9[j] = hadd2(hadd2(u[j], u[4 + j]), z7[j]); }
  }
  sts4(o + R_X5, x[0], x[1], x[2], x[3]);
  sts4(o + R_X3, y[0], y[1], y[2], y[3]);
  if (FULL) {
    const bool od = s & 1;
    sts4(o + R_BO, od ? z7[0] : z9[0], od ? z7[1] : z9[1], od ? z7[2] : z9[2], od ? z7[3] : z9[3]);
    sts4(o + R_BE + 16, od ? z9[0] : z7[0], od ? z9[1] : z7[1], od ? z9[2] : z7[2], od ? z9[3] : z7[3]);
  }
}
#define NBB(e) (320 - 32 * (e))
template <int C0, int C1> DEV void box_full(int j, uint32_t (&u)[4][4], uint32_t zero) {
  const uint32_t a2 = uchunk(8, j - 2), a1 = uchunk(0, j - 1);
  uint2 a[4]; uint4 b[4];
#define HALO(n) if (n < C1) { a[(n) & 3] = lds2(region(n) + a2); b[(n) & 3] = lds4(region(n) + a1); }
  HALO(C0) HALO(C0 + 1)
  split(zero);
#pragma unroll
  for (int chl = C0; chl < C1; ++chl) {
    const uint32_t d[4] = {u[chl][0], u[chl][1], u[chl][2], u[chl][3]};
    box_unit<true>(region(chl), j, a[chl], b[chl], d, u[chl]);
    fence_async_smem();
    bar_arrive(NB_B + chl, NBB(chl & 1));
    PROFC(28 + chl);
    if (chl == C0) { HALO(C0 + 2) }
  }
#undef HALO
}
DEV void box_help(int e, int n0, int dn, int lane, int layer) {
  bar_sync(NB_H, 224);
#pragma unroll 1
  for (int n = n0; n < 4; n += dn) {
    if (n == 2 && dn == 1) mbar_watch(B_RD, layer);
    const int chl = e + (n & 2), s = 128 + 32 * (n & 1) + lane;
    const uint32_t reg = region(chl);
    const uint4 d = lds4(uchunk(reg, s));
    const uint32_t u[4] = {d.x, d.y, d.z, d.w};
    uint32_t v[4];
    box_unit<false>(reg, s, lds2(uchunk(reg, s - 2) + 8), lds4(uchunk(reg, s - 1)), u, v);
    if (dn == 2 || (n & 1)) { fence_async_smem(); bar_arrive(NB_B + chl, NBB(e)); PROFC(28 + n); }
  }
}

DEV uint4 hadd8(const uint4& a, const uint4& b) { return make_uint4(hadd2(a.x, b.x), hadd2(a.y, b.y), hadd2(a.z, b.z), hadd2(a.w, b.w)); }
DEV void conv_out(int c, int j, int chl, uint4 (&x)[2][2][2], const uint32_t (&v)[4], uint4* XF, uint32_t zero) {
  const int rho = chl >> 1, e = chl & 1;
  const uint32_t ua = uchunk(region(chl), j), fa = region(chl) + R_X5 + j * 16, ha = region(chl) + R_X3 + (j & 1) * 1088 + (j >> 1) * 16;
  const int m8 = ((j & 4) + ((j >> 1) & 1) + 2 * (j & 1)) ^ ((2 * c + e) & 7);
  uint4* xo = XF + (((16 - 2 * (j & 8) + (j >> 4)) * 512 + 256 * rho + 2 * c + e) * 8 + m8);
  bar_sync(NB_Y + e + 7 * rho, 256);
  uint4 y[2], f[2], h[2];
#pragma unroll
  for (int k = 0; k < 2; ++k) {
    y[k] = lds4(ua + k * 2048);
    f[k] = lds4z(ua + k * 2048 + R_BO - R_U, k || j >= 36);
    h[k] = lds4z(fa + k * 2048 - 1024, k || j >= 64);
  }
  const uint32_t q = lds1(SM_TAP + chl * TAP_SZ + T_K);
  const uint4 r = lds4(ha);
  if (chl == 3) mbar_arrive1(B_L + (r.x & zero));
  h[1] = hadd8(h[1], make_uint4(hfma2(q, v[0], r.x), hfma2(q, v[1], r.y), hfma2(q, v[2], r.z), hfma2(q, v[3], r.w)));
#pragma unroll
  for (int k = 0; k < 2; ++k) {
    const uint4 o = hadd8(hadd8(y[k], hadd8(f[k], h[k])), make_uint4(xword(x[k][rho], e, 0), xword(x[k][rho], e, 1), xword(x[k][rho], e, 2), xword(x[k][rho], e, 3)));
    const uint32_t keep = j & 1 ? 0x7632 : 0x5410, k0 = prmt(o.x, o.y, keep), k1 = prmt(o.z, o.w, keep);
    const uint32_t g0 = __shfl_xor_sync(0xffffffffu, prmt(o.x, o.y, keep ^ 0x2222), 1), g1 = __shfl_xor_sync(0xffffffffu, prmt(o.z, o.w, keep ^ 0x2222), 1);
    str4(xo + k * 32768, j & 1 ? g0 : k0, j & 1 ? g1 : k1, j & 1 ? k0 : g0, j & 1 ? k1 : g1);

  }
  if (e) { __syncwarp(); mbar_arrive1(B_RD + rho * 8); }
  PROFC(40 + chl);
}

DEV void conv_round(int e, int rho, int w, int lane, uint32_t zero) {
  const int g = lane >> 2, t = lane & 3, chl = 2 * rho + e;
  const uint32_t reg = region(chl), tp = SM_TAP + chl * TAP_SZ, dr = dlo(reg, 128);
  const uint32_t g0 = tp + ((g & 1) ? T_O : T_E) + 2 * (2 * t - g) - 16;
  const uint32_t ga = g0 - 32 * (w & 1) - 576 * (w >> 1), id = opq(0x3210u);
  float acc[32], f1[24], f2[16];
  uint32_t q[12][4];
  {
    uint32_t qn[18][4];
    qn[0][2] = lds1(ga + 64);
#pragma unroll
    for (int n = 0; n < 18; ++n) {
      const bool nz = n < 15 || w < 2 || (n == 15 && w == 2);
      qn[n][0] = n < 15 ? lds1(ga + 48 - 32 * n) : lds1z(ga + 48 - 32 * n, nz);
      qn[n][1] = n < 15 ? lds1(ga + 32 - 32 * n) : lds1z(ga + 32 - 32 * n, nz);
    }
#pragma unroll
    for (int n = 0; n < 18; ++n) { qn[n][3] = cpy(qn[n][0], id); if (n) qn[n][2] = cpy(qn[n - 1][1], id); }
#pragma unroll
    for (int n = 0; n < 8; ++n) {
      const int i = n & 3;
      const uint32_t a = g0 + 16 - 16 * w - 2 * (n < 4 ? X_5 : X_3) + 16 * i;
      uint32_t (&q1)[4] = q[(n & 4) + (i >> 1)], (&q2)[4] = q[(n & 4) + 2 + (i >> 1)];
      q1[2 * (i & 1)] = lds1z(a, i <= w); q1[2 * (i & 1) + 1] = lds1(a - 64);
      q2[2 * (i & 1)] = cpy(0, id); q2[2 * (i & 1) + 1] = lds1z(a - 128, i >= w);
    }
    const uint32_t gc = tp + T_C - 2 + 4 * (t - g - 8 * w);
#pragma unroll
    for (int kk = 0; kk < 4; ++kk) {
      q[8 + kk][0] = lds1z(gc + 32 * kk, w >= kk); q[8 + kk][2] = lds1z(gc + 32 * kk + 16, w >= kk);
      q[8 + kk][1] = lds1(gc + 32 * kk - 128); q[8 + kk][3] = lds1(gc + 32 * kk - 112);
    }
    PROFD(rho ? 43 : 47, qn[17][2] ^ q[11][3]);
    bar_sync_if(NB_U, NBARU, 1 - rho);
    mbar_arrive1_if(B_V, chl == 1 && w == 0);
    bar_sync_if(NB_T + 1 - e, 256, chl);
    const uint32_t db = dr + (R_U + 32) / 16;
    undef(acc);
    wg_fence();
#pragma unroll
    for (int n = 0; n < 18; ++n) {
      if (n) wg_rs64k<1>(acc, qn[n], db - 2 * n); else wg_rs64k<0>(acc, qn[0], db);
      if (n == 9) wg_commit();
    }
    wg_commit();
  }
  wg_wait<1>();
  PROFC(rho ? 12 : 2);
  bar_sync(NB_B + chl, NBB(e));
  const uint32_t d1 = dr + R_X5 / 16, d2 = dr + R_BO / 16;
  undef(f1); undef(f2);
  wg_fence();
#pragma unroll
  for (int n = 0; n < 4; ++n) { if (n) wg_rs32t<1>(f2, q[8 + n], d2 + 16 * n); else wg_rs32t<0>(f2, q[8], d2); }
  wg_commit();
#pragma unroll
  for (int n = 0; n < 8; ++n) {
    const uint32_t d = d1 + (n >> 2) * ((R_X3 - R_X5) / 16) + 16 * (n & 1) - 16 * (n & 2);
    if (n) wg_rs48t<1>(f1, q[n], d); else wg_rs48t<0>(f1, q[0], d);
  }
  wg_commit();
  { uint32_t ck; asm volatile("mov.u32 %0,%%clock;" : "=r"(ck) :: "memory"); lane += ck & zero; }
  const int p = (lane + 9 * (w >> 1)) & 31;
  const uint32_t yb = reg + ((w >> 1) ? R_BO : R_U) + p * 64 + (((2 * (w & 1)) ^ ((p >> 1) & 3)) * 16);
  const uint32_t y0 = opq(yb + (p < lane ? 2048 : 0)), y1 = opq(yb + (p < lane ? 0 : 2048));
  const uint32_t fa = opq(reg + R_X5 + (8 * w + (lane & 7)) * 16 + (lane >> 3) * 512);
  const uint32_t ha = opq(reg + R_X3 + (lane < 16 ? 1088 : 0) + (8 * w + (lane & 7) + 4 * (lane & 8)) * 16);
  wg_wait<1>();
  PROFC(rho ? 13 : 3);
  bar_arrive_if(NB_T + e, 256, chl - 3);
  bar_sync(NB_WG + e, 128);
#pragma unroll
  for (int z = 0; z < 4; ++z) {
    const float* a = acc + 16 * (z >> 1) + 2 * (z & 1);
    stsm4t((z >> 1 ? y1 : y0) ^ ((z & 1) * 16), pack2(a[0], a[1]), pack2(a[4], a[5]), pack2(a[8], a[9]), pack2(a[12], a[13]));
  }
  wg_wait<0>();
  PROFC(rho ? 14 : 4);
  bar_sync(NB_WG + e, 128);
  {
    uint32_t h[6];
#pragma unroll
    for (int p = 0; p < 6; ++p) h[p] = p ? pack2(f1[4 * p] + f1[4 * p - 2], f1[4 * p + 1] + f1[4 * p - 1]) : pack2(f1[0], f1[1]);
    stsm4(fa, h[0], h[1], h[2], h[3]);
    stsm2(fa + 2048, h[4], h[5]);
    stsm4(ha, pack2(f2[0], f2[1]), pack2(f2[2] + f2[4], f2[3] + f2[5]), pack2(f2[8], f2[9]), pack2(f2[10] + f2[12], f2[11] + f2[13]));
  }
  bar_arrive(NB_Y + e + 7 * rho, 256);
}
constexpr uint32_t FILL = 0xFFFFFFFFu;
template <int N> DEV void fixo(uint4 (&A)[N], const uint4* p) {
#pragma unroll 1
  for (int it = 0; it < SPIN_LIMIT; ++it) {
    uint32_t m = A[0].x;
#pragma unroll
    for (int k = 1; k < N; ++k) m = max(m, A[k].x);
    if (__all_sync(0xffffffffu, m != FILL)) break;
#pragma unroll
    for (int k = 0; k < N; ++k) ldr4_if(A[k], p + k * 32, A[k].x == FILL);
  }
}
DEV bool rows_nan(float a, float b) {
  return __any_sync(0xffffffffu, a != a || b != b);
}
DEV int res_off(int w, int lane) { return ((lane & 7) + 8 * (lane >> 4)) * 8 + ((2 * (w & 2) + (w & 1) + ((lane >> 2) & 2)) ^ (lane & 7)); }
DEV void res_load(uint32_t (&res)[8][2], uint32_t sa, int w, int lane) {
  const uint32_t a = sa + res_off(w, opq(lane)) * 16;
#pragma unroll
  for (int j = 0; j < 8; j += 2) {
    uint32_t r[4];
    ldsm4t(r, a + j * 1024);
    res[j][0] = r[0]; res[j][1] = r[1]; res[j + 1][0] = r[2]; res[j + 1][1] = r[3];
  }
}

DEV void res_init(float (&ac)[32], const uint32_t (&res)[8][2]) {
#pragma unroll
  for (int j = 0; j < 16; ++j)
    asm volatile("shl.b32 %0,%2,16; and.b32 %1,%2,0xFFFF0000;" : "=&f"(ac[2 * j]), "=f"(ac[2 * j + 1]) : "r"(res[j >> 1][j & 1]));
}
DEV uint32_t after(uint32_t b, const uint32_t (&res)[8][2], uint32_t zero) {
  return b + ((res[0][0] ^ res[2][0] ^ res[4][0] ^ res[6][0]) & zero);
}

DEV void attn_phase(const Params& P, int c, int e, int w, int lane, int layer) {
  lane = opq(lane); c = opq(c);
  const int i = c >> 3, cg = c & 7, J = 16 * e + i, G = 8 * i + 4 - 4 * e + w;
  const int g = lane >> 2, t = lane & 3;
  float acc[96];
  uint32_t res[8][2];
  float2 cs[16];
  float4 st;
  const uint32_t csb = opq(SM_CS + 8 * t);
  {
    const uint32_t sa = SM_A + e * A_E, ba = B_A + 32 * e;
    const uint32_t da = dlo(sa, 8192), db = (SB >> 4) | (512 << 16);
    undef(acc);
#pragma unroll
    for (int j = 0; j < 8; ++j) asm volatile("" : "=r"(res[j][0]), "=r"(res[j][1]));
    mbar_wait(B_WF, layer);
    mbar_wait(ba, 0);
    mbar_wait(B_L, layer);
    bar_sync_if(NB_T, 256, e);
    PROF(24);
#pragma unroll
    for (int j = 0; j < 4; ++j) {
      if (j) mbar_wait(ba + 8 * j, 0);
      if (j == 1) PROFK(layer ? 39 : 15);
      wg_fence();
#pragma unroll
      for (int k = 0; k < 4; ++k) {
        if (j | k) wg_ss192<1>(acc, da + j * 512 + k * 128, db + wslot(j) * 512 + k * 128); else wg_ss192<0>(acc, da, db);
        if (j == 3 && k == 1) wg_commit();
      }
      wg_commit();
      if (j == 2 && cg < 4) { mbar_wait(ba + 8 * cg, 0); res_load(res, sa + cg * 8192, w, lane); }
      if (j == 1 || j == 2) { wg_wait<1>(); mbar_arrive1_if(B_F + 8 * (j - 1), e); }
    }
    wg_wait<1>();
    bar_arrive(NB_T + e, 256);
    wg_wait<0>();
    mbar_arrive1(after(B_AE + 8 * e, res, P.zero));
    PROF(25);
#pragma unroll 1
    for (uint32_t late = P.zero;; late = 1) {
      if (late) {
        const int ln = lane_id() + (late & P.zero), g = ln >> 2, t = ln & 3;
        const uint32_t* xr = (const uint32_t*)SCR->XF[layer] + (J * 16384 + g * 32 + t);
        const uint32_t* wr = (const uint32_t*)P.wqkv + (g * 768 + 32 * cg + t);
        COUNT(0);
        zero(acc);
#pragma unroll 1
        for (int k = 0; k < 32; ++k) {
          uint32_t a[4];
#pragma unroll 1
          for (int it = 0; it < SPIN_LIMIT; ++it) {
#pragma unroll
            for (int z = 0; z < 4; ++z) a[z] = ldr1(xr + k * 512 + (z >> 1) * 256 + ((2 * w + (z & 1)) ^ g) * 4);
            if (__all_sync(0xffffffffu, max(max(a[0], a[1]), max(a[2], a[3])) != FILL)) break;
          }
#pragma unroll
          for (int z = 0; z < 4; ++z) a[z] = movm(a[z]);
#pragma unroll
          for (int j = 0; j < 24; ++j) {
            const uint32_t* q = wr + k * 12288 + (j >> 3) * 256 + 4 * (j & 7);
            mma16(*(float(*)[4])(acc + 4 * j), a[0], a[1], a[2], a[3], movm(ldw1(q)), movm(ldw1(q + 6144)));
          }
        }
        const uint32_t* q = xr + 64 * cg * 32;
        const int m8 = (2 * (w & 2) + (w & 1)) ^ g;
#pragma unroll 1
        for (int it = 0; it < SPIN_LIMIT; ++it) {
          uint32_t m = 0;
#pragma unroll
          for (int z = 0; z < 16; ++z) { const uint32_t x = ldr1(q + (z >> 1) * 256 + (m8 ^ (2 * (z & 1))) * 4); m = max(m, x); res[z >> 1][z & 1] = movm(x); }
          if (__all_sync(0xffffffffu, m != FILL)) break;
        }
#pragma unroll
        for (int z = 0; z < 16; ++z) cs[z] = lds2f(csb + 256 + z * 32);
      } else {
        mbar_wait(B_CS, 0);
#pragma unroll
        for (int z = 0; z < 16; ++z) cs[z] = lds2f(csb + 256 + z * 32);
        mbar_wait(B_W4, layer);
        mbar_wait(ba, 1);
        bar_sync(NB_T + 1 - e, 256);
        PROF(26);
#pragma unroll
        for (int j = 4; j < 8; ++j) {
          if (j > 4) mbar_wait(ba + 8 * (j - 4), 1);
          if (j >= 6) mbar_wait(B_W6 + 8 * (j - 6), layer);
          if (j > 4) PROF(31 + j);
          wg_fence();
#pragma unroll
          for (int k = 0; k < 4; ++k) {
            wg_ss192<1>(acc, da + (j & 3) * 512 + k * 128, db + wslot(j) * 512 + k * 128);
            if (j == 7 && k == 1) wg_commit();
          }
          wg_commit();
          if (j == 5) {
            if (cg >= 4) { mbar_wait(ba + 8 * (cg - 4), 1); res_load(res, sa + (cg - 4) * 8192, w, lane); }
            wg_wait<1>(); mbar_arrive1_if(B_F + 16, e); PROF(40);
          }

        }
      }
      uint32_t rs = hadd2(res[0][0], res[0][1]);
#pragma unroll
      for (int z = 2; z < 16; ++z) rs = hadd2(rs, res[z >> 1][z & 1]);
      const float rn = bflo(rs) + bfhi(rs);
      wg_wait<1>();
      bar_arrive_if(NB_T, 256, !(e | late));
      mbar_wait(B_ST + 8 * e, layer);
      st = lds4f(SM_STAT + ((4 * e + w) * 8 + g) * 16);
      PROF(34 + layer);
      wg_wait<0>();
      if (!rows_nan(acc[0] + rn, acc[2]) || late) break;
    }
  }
  mbar_arrive1(B_QE);
  PROFK(8 + 12 * layer);
  uint32_t Q[4][4], K[4][2][2], V[4][2][2];
  {
#pragma unroll
    for (int z = 0; z < 8; ++z) {
      const float* a = acc + 32 + 4 * z; const float* b = acc + 64 + 4 * z;
      K[z >> 1][1][z & 1] = pack2((a[2] - st.z * cs[z].x) * st.w, (a[3] - st.z * cs[z].y) * st.w);
      V[z >> 1][1][z & 1] = movm(pack2((b[2] - st.z * cs[8 + z].x) * st.w, (b[3] - st.z * cs[8 + z].y) * st.w));
    }
    const int hop = (G >> 1) & 3;
    const uint32_t kv = SM_KV + (2 * hop + (w & 1)) * 2048 + lane * 16;
    uint4* h = SCR->H[layer] + (c * 256 + (w & 1) * 128 + lane);
    if (hop == 3) {
#pragma unroll
      for (int z = 0; z < 4; ++z) str4(h + 2048 + z * 32, K[z][1][0], K[z][1][1], V[z][1][0], V[z][1][1]);
    } else {
      mbar_wait(B_F + 16, layer);
#pragma unroll
      for (int z = 0; z < 4; ++z) sts4(kv + z * 512, K[z][1][0], K[z][1][1], V[z][1][0], V[z][1][1]);
      bar_arrive(NB_B + hop, 128);
    }
    PROF(42);
    uint4 hv[4];
#pragma unroll
    for (int z = 0; z < 4; ++z) { hv[z] = make_uint4(0, 0, 0, 0); ldr4_if(hv[z], h + z * 32, G >= 2 && hop == 0); }
#pragma unroll
    for (int z = 0; z < 8; ++z) {
      const float* a = acc + 32 + 4 * z; const float* b = acc + 64 + 4 * z;
      K[z >> 1][0][z & 1] = pack2((a[0] - st.x * cs[z].x) * st.y, (a[1] - st.x * cs[z].y) * st.y);
      V[z >> 1][0][z & 1] = movm(pack2((b[0] - st.x * cs[8 + z].x) * st.y, (b[1] - st.x * cs[8 + z].y) * st.y));
    }
#pragma unroll
    for (int z = 0; z < 8; ++z) {
      const float2 cq = lds2f(csb + z * 32);
      const float* a = acc + 4 * z;
      Q[z >> 1][2 * (z & 1)] = pack2(a[0] - st.x * cq.x, a[1] - st.x * cq.y);
      Q[z >> 1][2 * (z & 1) + 1] = pack2(a[2] - st.z * cq.x, a[3] - st.z * cq.y);
    }
    PROF(27);
    const bool p0 = 2 * t > g, p1 = 2 * t + 1 > g, first = G < 2;
    float s[4][4], mx[4][2];
#pragma unroll
    for (int z = 0; z < 4; ++z) {
      float S[4];
      mma16z(s[z], Q[z][0], Q[z][1], Q[z][2], Q[z][3], K[z][0][0], K[z][0][1]);
      mma16z(S, Q[z][0], Q[z][1], Q[z][2], Q[z][3], K[z][1][0], K[z][1][1]);
      s[z][2] = p0 ? s[z][2] : S[2]; s[z][3] = p1 ? s[z][3] : S[3];
    }
    const float sc0 = st.y * (0.25f * 1.4426950408889634f), sc1 = st.w * (0.25f * 1.4426950408889634f);
    uint32_t pw[4][2];
#pragma unroll
    for (int r = 1; r >= 0; --r) {
      if (r == 0) {
        if (hop) {
          bar_sync(NB_B + hop - 1, 128);
#pragma unroll
          for (int z = 0; z < 4; ++z) hv[z] = lds4(kv - 4096 + z * 512);
        } else fixo(hv, h);
        PROFD(41, hv[3].x);
#pragma unroll
        for (int z = 0; z < 4; ++z) {
          float S[4];
          mma16z(S, Q[z][0], Q[z][1], Q[z][2], Q[z][3], hv[z].x, hv[z].y);
          if (first) S[0] = S[1] = __uint_as_float(0xFF800000u);
          s[z][0] = p0 ? S[0] : s[z][0]; s[z][1] = p1 ? S[1] : s[z][1];
        }
      }
#pragma unroll
      for (int z = 0; z < 4; ++z) mx[z][r] = fmaxf(s[z][2 * r], s[z][2 * r + 1]);
#pragma unroll
      for (int o = 1; o < 3; ++o)
#pragma unroll
        for (int z = 0; z < 4; ++z) mx[z][r] = fmaxf(mx[z][r], __shfl_xor_sync(0xffffffffu, mx[z][r], o));
#pragma unroll
      for (int z = 0; z < 4; ++z) pw[z][r] = pack2(ex2((s[z][2 * r] - mx[z][r]) * (r ? sc1 : sc0)), ex2((s[z][2 * r + 1] - mx[z][r]) * (r ? sc1 : sc0)));
    }
    mbar_wait(layer ? B_N : B_Z, 1);
    const uint32_t M = (p0 ? 0xFFFFu : 0u) | (p1 ? 0xFFFF0000u : 0u);
    uint4* O = SCR->O + ((J * 8 + cg) * 512 + (2 * (w & 2) + (w & 1)) * 64 + t * 8 + g);
#pragma unroll
    for (int h2 = 0; h2 < 2; ++h2) {
      uint32_t ow[2][4];
#pragma unroll
      for (int z = 0; z < 2; ++z) {
        const int n = 2 * h2 + z;
        const uint32_t w0 = pw[n][0], w1 = pw[n][1];
        float sm[4] = {0.f, 0.f, 0.f, 0.f}, Oa[2][4];
        mma8(sm, w0, w1, 0x3F803F80u);
        mma16z(Oa[0], w0 & ~M, w1 & M, 0u, w1 & ~M, V[n][0][0], V[n][1][0]); mma8(Oa[0], w0 & M, 0u, hv[n].z);
        mma16z(Oa[1], w0 & ~M, w1 & M, 0u, w1 & ~M, V[n][0][1], V[n][1][1]); mma8(Oa[1], w0 & M, 0u, hv[n].w);
        const float i0 = rcp(sm[0]), i1 = rcp(sm[2]);
#pragma unroll
        for (int d = 0; d < 2; ++d) { ow[0][2 * z + d] = pack2(Oa[d][0] * i0, Oa[d][1] * i0); ow[1][2 * z + d] = pack2(Oa[d][2] * i1, Oa[d][3] * i1); }
      }
#pragma unroll
      for (int hi = 0; hi < 2; ++hi) str4(O + hi * 128 + h2 * 32, ow[hi][0], ow[hi][1], ow[hi][2], ow[hi][3]);
    }
  }
  str1(SCR->OF[layer] + (J * 32 + cg * 4 + w), 1);
  mbar_arrive1(B_AT + 8 * e);
  PROFK(9 + 12 * layer);
  float ac[32];
  const uint32_t so = SM_O + e * O_E;
  uint2* xo = opqp(layer ? (uint2*)(P.out + ((16 * G + 2 * (lane >> 3)) * 512 + 64 * cg + 8 * (lane & 7)))
                         : (uint2*)SCR->XG[1] + ((32 * (cg & 3) + t) * 2048 + (cg >> 2) * 256 + xg_off(G, g)));
  const uint32_t stg = SM_X + (4 * e + w) * 2048;
  const uint32_t sw = opq(stg + (lane & 15) * 128 + (((lane >> 4) ^ (lane & 7)) * 16)), sr = opq(stg + (lane >> 3) * 128 + (((lane & 7) ^ (lane >> 3)) * 16));
  uint4* ps = opqp(&SCR->PS[(G * 8 + cg) * 8 + g]);
  {
    const uint32_t bo = B_O + 32 * e;
    const uint32_t dw = (SM_WO >> 4) | (512 << 16), da = dlo(so, 512);
    mbar_wait(B_WO, layer);
    res_init(ac, res);
    mbar_wait(B_AT + 8 + (((uint32_t)((uintptr_t)xo >> 16) ^ (uint32_t)((uintptr_t)ps >> 16) ^ sw ^ sr) & P.zero), layer);
#pragma unroll
    for (int j = 0; j < 4; ++j) {
      mbar_wait(bo + 8 * j, layer);
      if (j == 0) PROFK(32 + layer);
      wg_fence();
#pragma unroll
      for (int k = 8 * j; k < 8 * j + 8; ++k) {
        const uint32_t a = da + (k >> 2) * 512 + (k & 3) * 8, b = dw + (k & 3) * 1024 + (k >> 2) * 128;
        wg_ss64<1>(ac, a, b);
      }
      wg_commit();
    }
#pragma unroll 1
    for (uint32_t late = P.zero;; late = 1) {
      if (late) {
        const int ln = lane_id() + (late & P.zero);
        const uint32_t* op = (const uint32_t*)(SCR->O + (J * 4096 + w * 128)) + ln;
        wg_wait<0>();
        COUNT(1);
        res_init(ac, res);
#pragma unroll 1
        for (int k = 0; k < 32; ++k) {
          uint32_t a[4];
#pragma unroll 1
          for (int it = 0; it < SPIN_LIMIT; ++it) {
#pragma unroll
            for (int z = 0; z < 4; ++z) a[z] = ldr1(op + (k >> 2) * 2048 + (k & 3) * 32 + (z & 1) * 256 + (z >> 1) * 128);
            if (__all_sync(0xffffffffu, max(max(a[0], a[1]), max(a[2], a[3])) != FILL)) break;
          }
#pragma unroll
          for (int j = 0; j < 8; j += 2) {
            uint32_t b[4];
            ldsm4t(b, SM_WO + (k & 3) * 16384 + (k >> 2) * 2048 + (ln & 15) * 128 + (((j + (ln >> 4)) ^ (ln & 7)) * 16));
            mma16(*(float(*)[4])(ac + 4 * j), a[0], a[1], a[2], a[3], b[0], b[1]);
            mma16(*(float(*)[4])(ac + 4 * j + 4), a[0], a[1], a[2], a[3], b[2], b[3]);
          }
        }
      }
      wg_wait<0>();
      if (!rows_nan(ac[0], ac[2]) || late) break;
    }
  }
  PROFK(10 + 12 * layer);
#pragma unroll
  for (int j = 0; j < 16; ++j) res[j >> 1][j & 1] = pack2(ac[2 * j], ac[2 * j + 1]);
  if (layer == 0) {
    float s[2][4], q0[2][4], q1[2][4];
#pragma unroll
    for (int j = 0; j < 2; ++j) gram<true>(s[j], q0[j], q1[j], res[2 * j][0], res[2 * j][1], res[2 * j + 1][0], res[2 * j + 1][1]);
#pragma unroll
    for (int j = 0; j < 2; ++j) gram<false>(s[j], q0[j], q1[j], res[2 * j + 4][0], res[2 * j + 4][1], res[2 * j + 5][0], res[2 * j + 5][1]);
    const bool od = g & 1;
    str4_if(ps, nzmap(__float_as_uint(s[0][0] + s[1][0])), __float_as_uint(od ? q0[0][1] + q0[1][1] : q0[0][0] + q0[1][0]),
            __float_as_uint(s[0][2] + s[1][2]), __float_as_uint(od ? q1[0][3] + q1[1][3] : q1[0][2] + q1[1][2]), t == (g >> 1));
#pragma unroll
    for (int j = 0; j < 8; ++j) {
      str2(xo + j * 8192, nzmap(prmt(res[j][0], res[j][1], 0x5410)), prmt(res[j][0], res[j][1], 0x7632));
    }
    mbar_arrive1(B_ED + 8 * e);
  } else {
#pragma unroll
    for (int j = 0; j < 8; j += 2) stsm4(sw ^ (j * 16), res[j][0], res[j][1], res[j + 1][0], res[j + 1][1]);
    __syncwarp();
    uint4 v[4];
#pragma unroll
    for (int k = 0; k < 4; ++k) v[k] = lds4((sr ^ ((k & 1) * 64)) + k * 512);
#pragma unroll
    for (int k = 0; k < 4; ++k) stw4(xo + ((k & 1) * 8 + (k >> 1)) * 128, v[k].x, v[k].y, v[k].z, v[k].w);
  }
  PROFK(11 + 12 * layer);
}

DEV void col_sums(const Params& P, int c, int wa, int lane) {
  const int i = c >> 3, cg = c & 7;
  uint4 wv[8];
#pragma unroll
  for (int k = 0; k < 8; ++k) wv[k] = ldnc4(P.wqkv + ((32 * i + (lane >> 3)) * 1536 + wa * 512 + 64 * cg + 8 * (lane & 7)) + 4 * k * 1536);
  float cs[8];
  zero(cs);
#pragma unroll
  for (int k = 0; k < 8; ++k) {
    cs[0] += bflo(wv[k].x); cs[1] += bfhi(wv[k].x); cs[2] += bflo(wv[k].y); cs[3] += bfhi(wv[k].y);
    cs[4] += bflo(wv[k].z); cs[5] += bfhi(wv[k].z); cs[6] += bflo(wv[k].w); cs[7] += bfhi(wv[k].w);
  }
  const bool b4 = lane & 16, b3 = lane & 8;
#pragma unroll
  for (int k = 0; k < 4; ++k) cs[k] = (b4 ? cs[k + 4] : cs[k]) + __shfl_xor_sync(0xffffffffu, b4 ? cs[k] : cs[k + 4], 16);
#pragma unroll
  for (int k = 0; k < 2; ++k) cs[k] = (b3 ? cs[k + 2] : cs[k]) + __shfl_xor_sync(0xffffffffu, b3 ? cs[k] : cs[k + 2], 8);
  str2((uint2*)SCR->CS + (i * 768 + wa * 256 + 32 * cg + 4 * (lane & 7) + (lane >> 3)), nzmap(__float_as_uint(cs[0])), __float_as_uint(cs[1]));
}
DEV void col_gather(const Params& P, int c, int wa, int lane) {
  const uint2* p = (const uint2*)SCR->CS + (wa * 256 + 32 * (c & 7) + lane);
#pragma unroll 1
  for (int it = 0;; ++it) {
    float a = 0.f, b = 0.f;
    uint32_t m = ~0u;
#pragma unroll
    for (int k = 0; k < 16; ++k) { const uint2 q = ldr2(p + k * 768); m = min(m, q.x); a += __uint_as_float(q.x); b += __uint_as_float(q.y); }
    if (__all_sync(0xffffffffu, m != 0u)) { sts2f(SM_CS + wa * 256 + lane * 8, a, b); break; }
    spin_guard(it);
  }
  __syncwarp();
  mbar_arrive1(B_CS);
}

DEV void aux_prologue(const Params& P, int c, int wa, int lane) {
  const int g = lane >> 2, t = lane & 3, G = stat_group(c);
  {
    uint32_t w[16][2];
    const uint16_t* row = P.x0 + ((16 * G + 2 * g) * 512 + 128 * wa + 8 * t);
    bar_sync(NB_Y, 384);
#pragma unroll
    for (int z = 0; z < 8; ++z) {
      const uint4 v = ldw4(row + (z & 1) * 512 + (z >> 1) * 32);
      const int o = 4 * (z >> 1);
      w[o][z & 1] = v.x; w[o + 1][z & 1] = v.y; w[o + 2][z & 1] = v.z; w[o + 3][z & 1] = v.w;
    }
    PROF(34);
    PROFD(35, w[0][0]);
    PROFD(36, w[15][1]);
    uint2* xo = (uint2*)SCR->XG[0] + ((64 * (wa & 1) + 4 * t) * 2048 + (wa >> 1) * 256 + xg_off(G, g));
#pragma unroll
    for (int n = 0; n < 16; ++n) str2(xo + (16 * (n >> 2) + (n & 3)) * 2048, nzmap(prmt(w[n][0], w[n][1], 0x5410)), prmt(w[n][0], w[n][1], 0x7632));
    float s[2][4], q0[2][4], q1[2][4];
#pragma unroll
    for (int z = 0; z < 8; ++z) {
      const int o = 4 * (z >> 1), r = z & 1;
      if (z < 2) gram<true>(s[r], q0[r], q1[r], w[o][r], w[o + 1][r], w[o + 2][r], w[o + 3][r]);
      else gram<false>(s[r], q0[r], q1[r], w[o][r], w[o + 1][r], w[o + 2][r], w[o + 3][r]);
    }
    const bool od = g & 1;
    if (t == (g >> 1))
      sts4f(SM_STAT + (wa * 8 + g) * 16, s[0][0] + s[0][2], od ? q0[0][1] + q1[0][3] : q0[0][0] + q1[0][2],
            s[1][0] + s[1][2], od ? q0[1][1] + q1[1][3] : q0[1][0] + q1[1][2]);
    bar_arrive(NB_P0, 192);
  }
  PROF(2);
  if (lane == 0)
    asm volatile("cp.async.bulk.prefetch.L2.global [%0],4096;" :: "l"(wa < 3 ? P.wqkv + (3 * c + wa) * 2048 : P.wo + c * 2048) : "memory");
  bar_sync(NB_Y + 1, 256);
  mbar_wait(B_Z, 0);
}

DEV void stat_part(const Params& P, int c, int wa, int lane, int layer, int h, float (&v)[2]) {
  lane = opq(lane);
  const int e = wa >> 1;
  uint32_t x[4][4];
  mbar_wait(B_A + 16 * wa, h); mbar_wait(B_A + 16 * wa + 8, h);
  if (h == 0) mbar_wait(B_A + 32 * e + 24, 0);
#pragma unroll
  for (int k = 0; k < 4; ++k) ldsm4t(x[k], SM_A + e * A_E + (128 * (wa & 1) + lane) * 128 + (((c ^ lane) & 7) * 16) + k * 4096);
  float s[4] = {0.f, 0.f, 0.f, 0.f};
#pragma unroll
  for (int k = 0; k < 16; ++k) { const float a = bflo(x[k >> 2][k & 3]), b = bfhi(x[k >> 2][k & 3]); s[0] += a; s[1] += a * a; s[2] += b; s[3] += b * b; }
  s[0] += s[2]; s[1] += s[3];
  if (RARE(rows_nan(s[1], s[1]))) {
    const uint16_t* q = (const uint16_t*)(SCR->XF[layer] + ((32 * e + 2 * (c >> 3) + h) * 2048 + (wa & 1) * 1024)) + (lane >> 2);
    COUNT(2);
    s[0] = s[1] = 0.f;
#pragma unroll 1
    for (int k = 0; k < 32; ++k) {
      const int r = 2 * (lane & 3) + (k & 1);
      const float a = ldnan(q + ((k >> 1) * 8 + r) * 64 + ((c ^ r) & 7) * 8);
      s[0] += a; s[1] += a * a;
    }
  }
  v[0] += s[0]; v[1] += s[1];
  __syncwarp();
}
DEV void stat_finish(const Params& P, int c, int wa, int lane, int layer, float (&v)[2]) {
  lane = opq(lane);
  const bool b = lane & 1;
  const float s = (b ? v[1] : v[0]) + __shfl_xor_sync(0xffffffffu, b ? v[0] : v[1], 1);
  str1((uint32_t*)SCR->ST[layer] + ((128 * (wa >> 1) + c) * 64 + (wa & 1) * 32 + lane), nzmap(__float_as_uint(s)));
  const uint4* sp = SCR->ST[layer] + ((128 * (wa >> 1) + (c & ~7) + 4 * (wa & 1) + (lane >> 3)) * 16 + (lane & 7));
  uint4 x, y;
  for (int it = 0;; ++it) {
    x = ldr4(sp); y = ldr4(sp + 8);
    if (__all_sync(0xffffffffu, min(min(min(x.x, x.y), min(x.z, x.w)), min(min(y.x, y.y), min(y.z, y.w))) != 0u)) break;
    spin_guard(it);
  }
  const uint32_t q = ln_sums((__uint_as_float(x.x) + __uint_as_float(x.z)) + (__uint_as_float(y.x) + __uint_as_float(y.z)),
                             (__uint_as_float(x.y) + __uint_as_float(x.w)) + (__uint_as_float(y.y) + __uint_as_float(y.w)));
  sts2f(SM_STAT + (16 * wa + (lane >> 4) * 8 + (lane & 7)) * 16 + (lane & 8), bflo(q), rcp(bfhi(q)));
  __syncwarp();
  mbar_arrive1(B_ST + 4 * (wa & 2));
}

DEV void nan_source(uint32_t a, int lane) {
#pragma unroll
  for (int k = 0; k < 4; ++k) sts4(a + k * 512 + lane * 16, FILL, FILL, FILL, FILL);
  fence_async_smem();
  __syncwarp();
}
__global__ void __launch_bounds__(NTHR, 1)
fused_kernel(const __grid_constant__ Params P, const __grid_constant__ CUtensorMap mapW, const __grid_constant__ CUtensorMap mapWo,
             const __grid_constant__ CUtensorMap mapX) {
  extern __shared__ __align__(1024) uint8_t smem_raw[];
  const int warp = __shfl_sync(0xffffffffu, threadIdx.x >> 5, 0), lane = threadIdx.x & 31;
  uint32_t smid; asm volatile("mov.u32 %0,%%smid;" : "=r"(smid));
  const uint32_t* pw = (const uint32_t*)&P + threadIdx.y;
  const int role = P.role[(smid >> 1) + threadIdx.y] + (smid & 1) + (pw[0] & pw[12]);
  const int c = __shfl_sync(0xffffffffu, pw[1] ? role : blockIdx.x, 0);
  if (c >= 128) {
#pragma unroll 1
    for (int k = (c - 128) * NTHR + threadIdx.x; k < 131072; k += P.spare * NTHR) str4(SCR->XG[1] + k, 0, 0, 0, 0);
    __threadfence();
    __syncthreads();
    if (warp == 0) { poll(SCR->C + 1 + (lane & 3) * 32, 32); cnt_add1(SCR->C + 6); }
    __syncthreads();
#pragma unroll 1
    for (int k = (c - 128) * NTHR + threadIdx.x; k < 131072; k += P.spare * NTHR) str4(SCR->XG[0] + k, 0, 0, 0, 0);
    return;
  }
#define DONE() do {} while (0)
  const int cg = c & 7;
  if (warp < 8) {
    PROF(46);
    kgen(P, c, warp, lane);
    PROFK(1);
    bar_sync(0, 384);
#pragma unroll 1
    for (int layer = 0; layer < 2; ++layer) {
#pragma unroll 1
      for (int rho = 0; rho < 2; ++rho) {
        const int wz = warp + ((rho + layer) & P.zero);
        conv_round(wz >> 2, rho, wz & 3, lane_id(), P.zero);
        PROFK(6 + rho + 12 * layer);
      }
      const int z = layer & P.zero;
      attn_phase(P, c + z, (warp + z) >> 2, (warp + z) & 3, lane_id(), layer);
    }
    DONE();
  } else if (warp < 12) {
    asm volatile("setmaxnreg.dec.sync.aligned.u32 %0;" :: "n"(REG_AUX));
    aux_prologue(P, c, warp - 8, lane);
    PROF(1);
    const int c0 = c;
#pragma unroll 1
    for (int layer = 0;; ++layer) {
      const int c = c0 + (layer & P.zero), wa = warp - 8 + (layer & P.zero);
#define lane lane_id()
#define j (32 * wa + lane_id())
      uint4 x[2][2][2];
      uint32_t u[4][4];
      uprep(P, c, wa, lane, layer, x, u);
      fence_async_smem();
      bar_arrive(NB_U, NBARU);
      PROFK(5 + 12 * layer);
      bar_sync(NB_H, 224);
      box_full<0, 3>(j, u, P.zero);
      PROF(3 + 12 * layer);
      conv_out(c, j, 0, x, u[0], SCR->XF[layer], P.zero);
      PROF(32);
      conv_out(c, j, 1, x, u[1], SCR->XF[layer], P.zero);
      box_full<3, 4>(j, u, P.zero);
      PROF(6 + 12 * layer);
      if (layer == 0 && wa < 3) col_sums(P, c, wa, lane);
      conv_out(c, j, 2, x, u[2], SCR->XF[layer], P.zero);
      PROF(33);
      conv_out(c, j, 3, x, u[3], SCR->XF[layer], P.zero);
      PROFK(7 + 12 * layer);
      float v[2];
      zero(v);
#pragma unroll 1
      for (int h = 0; h < 2; ++h) {
        stat_part(P, c, wa, lane, layer, h, v);
        if (h) break;
        mbar_arrive1(B_AE + 4 * (wa & 2));
        if (layer == 0 && wa < 3) col_gather(P, c, wa, lane);
      }
      PROF(9 + 12 * layer);
      stat_finish(P, c, wa, lane, layer, v);
      PROF(8 + 12 * layer);
      if (layer) break;
      mbar_wait(B_ED, 0); mbar_wait(B_ED + 8, 0);
#undef lane
#undef j
    }
    DONE();
  } else {
    asm volatile("setmaxnreg.dec.sync.aligned.u32 %0;" :: "n"(REG_PROD));
    if (s2u(smem_raw) != SB) __trap();
#pragma unroll 1
    for (int n = warp - 12; n < 42; n += 4)
      asm volatile("{.reg .pred p; elect.sync _|p,0xffffffff; @p mbarrier.init.shared::cta.b64 [%0],%1;}"
                   :: "r"(SM_BAR + n * 8), "r"(n == 33 ? 4 : n > 14 ? 1 : (int)(0x322866444444444ull >> (4 * n)) & 15) : "memory");
    fence_async_smem();
    bar_sync(NB_AUX, 128);
    bar_arrive(0, 384); bar_arrive(NB_Y + 1, 256);
    PROF(1);
    if (warp == 12) {
      if (lane == 0) {
        asm volatile("prefetch.tensormap [%0];" :: "l"(&mapW) : "memory");
        asm volatile("prefetch.tensormap [%0];" :: "l"(&mapWo) : "memory");
        asm volatile("prefetch.tensormap [%0];" :: "l"(&mapX) : "memory");
      }
      nan_source(slot(12), lane);
#pragma unroll 1
      for (int k = 0; k < 8; ++k) tma2_store(&mapX, slot(12), 128 * c, 8 * k);
      bulk_wait();
      __threadfence();
      mbar_arrive1(B_Z);
      mbar_wait(B_E, 0);
#pragma unroll 1
      for (int k = 0; k < 4; ++k) bulk_store(SCR->H[k >> 1] + ((c + 8) * 256 + (k & 1) * 128), slot(12), 2048);
#pragma unroll 1
      for (int k = 0; k < 8; ++k) bulk_store(SCR->O + (c * 512 + (k >> 2) * 65536 + (k & 3) * 128), slot(12), 2048);
      bulk_wait();
      PROF(24);
#pragma unroll 1
      for (int layer = 0; layer < 2; ++layer) {
        mbar_wait(B_V, layer);
        if (layer == 1 && c < 4 && ((0x47 >> lane) & 1)) str1(SCR->C + c * 32 + lane, 0);
        mbar_expect1(B_WF, 4 * 24576);
#pragma unroll
        for (int k = 0; k < 4; ++k) tma3(slot(wslot(k)), &mapW, 64 * cg, 64 * k, 0, B_WF);
        if (layer == 0) { __threadfence(); mbar_arrive1(B_Z); }
        mbar_wait(B_WF, layer);
        mbar_expect1(B_W4, 2 * 24576);
#pragma unroll
        for (int k = 4; k < 6; ++k) tma3(slot(wslot(k)), &mapW, 64 * cg, 64 * k, 0, B_W4);
        bar_sync(NB_AUX, 64);
#pragma unroll 1
        for (int k = 0; k < 2; ++k) {
          mbar_expect1(B_W6 + 8 * k, 24576);
          mbar_wait(B_F + 8 * k, layer);
          tma3(slot(3 * k), &mapW, 64 * cg, 384 + 64 * k, 0, B_W6 + 8 * k);
        }
        mbar_expect1(B_WO, 65536);
        mbar_wait(B_AE + 8, layer);
        nan_source(slot(12), lane);
        uint4* fp = layer ? SCR->O + c * 512 : SCR->XF[1] + c * 512;
#pragma unroll 1
        for (int r = 7; r >= 0; --r) {
          __nanosleep(30);
          if (r >= 4) {
            bulk_store(fp + (r & 3) * 128, slot(12), 2048); bulk_store(fp + 65536 + (r & 3) * 128, slot(12), 2048);
          }
          if (r == 3) { bulk_wait(); __threadfence(); mbar_arrive1(B_N); PROF(9 + 12 * layer); }
          if (r == 1) mbar_wait(B_F + 16, layer);
          tma4(SM_WO + r * 8192, &mapWo, 64 * cg, 0, r >> 1, 32 * (r & 1), B_WO);
        }
        PROF(8 + 12 * layer);
      }
      DONE();
    } else if (warp == 13) {
      const int G = stat_group(c);
#pragma unroll 1
      for (int layer = 0; layer < 2; ++layer) {
        float z[4];
        uint2* so = opqp((uint2*)&SCR->SR[layer][lane >> 3][sr_off(G, lane)] + (lane & 1));
        if (layer == 0) {
          bar_sync(NB_P0, 192);
          const float4 a = lds4f(SM_STAT + lane * 16);
          z[0] = a.x; z[1] = a.y; z[2] = a.z; z[3] = a.w;
        } else {
          mbar_wait(B_ED + 2 * (c & 4), 0);
          uint4* ps = &SCR->PS[G * 64 + lane];
          uint4 a, b;
          for (int it = 0;; ++it) {
            a = ldr4(ps); b = ldr4(ps + 32);
            if (__all_sync(0xffffffffu, min(a.x, b.x) != 0u)) break;
            spin_guard(it);
          }
          z[0] = __uint_as_float(a.x) + __uint_as_float(b.x); z[1] = __uint_as_float(a.y) + __uint_as_float(b.y);
          z[2] = __uint_as_float(a.z) + __uint_as_float(b.z); z[3] = __uint_as_float(a.w) + __uint_as_float(b.w);
        }
#pragma unroll
        for (int o = 8; o < 32; o <<= 1)
#pragma unroll
          for (int k = 0; k < 4; ++k) z[k] += __shfl_xor_sync(0xffffffffu, z[k], o);
        const uint32_t w0 = ln_sums(z[0], z[1]), w1 = ln_sums(z[2], z[3]);
        const uint32_t r = nzmap(pack2(rcp(bfhi(w0)), rcp(bfhi(w1)))), m = prmt(w0, w1, 0x5410);
        str2(so, r, m); str2(so + 4 * 1024, r, m);
        PROF(4 + 12 * layer);
        box_help(0, 0, 2, lane, layer);
        PROF(6 + 12 * layer);
      }
      DONE();
    } else if (warp == 14) {
#pragma unroll 1
      for (int layer = 0; layer < 2; ++layer) {
        uint32_t* ca = opqp(SCR->C + (c >> 5) * 32 + 3 * layer);
        const uint32_t* cw = opqp(SCR->C + (lane & 3) * 32 + 3 * layer);
        const uint4* xg = opqp(SCR->XG[layer] + c * 1024);
        mbar_expect1(B_E, 16384);
        if (layer) { mbar_wait(B_N, 0); mbar_wait(B_ED, 0); mbar_wait(B_ED + 8, 0); } else bar_sync(NB_P0, 192);
        cnt_add1(ca);
        PROF(4 + 12 * layer);
#pragma unroll 1
        for (uint32_t it = 0, todo = 15; todo; ++it) {
          spin_guard(it);
          const uint32_t m = __ballot_sync(0xffffffffu, ldr1(cw) >= 32) & todo;
          todo ^= m;
          mbar_arrive1_if(B_U, todo == 0);
#pragma unroll
          for (int q = 0; q < 4; ++q)
            if ((m >> q) & 1) bulk(SM_X + 4096 * q, xg + 256 * q, 4096, B_E);
        }
        PROFK(5 + 12 * layer);
        box_help(0, 1, 2, lane, layer);
#pragma unroll 1
        for (int n = 0; n < 4; ++n) {
          const int e = n & 1;
          const uint4* src = opqp(SCR->XF[layer] + (32 * e + 2 * (c >> 3) + (n >> 1)) * 2048);
          const uint32_t dst = opq(SM_A + e * A_E), b = opq(B_A + 32 * e), f = opq(n == 1 ? B_L : (n & 2 ? B_AE : B_RD) + 8 * e);
          if (n == 2) poll(cw + 2, 32);
          if (n == 2) PROF(7 + 12 * layer);
          mbar_wait(f, layer);
          if (n == 0) cnt_add1(ca + 1);
          uint32_t ok = n ? 15 : 0;
#pragma unroll 1
          for (int q = 0, it = 0; q < 4; ++q) {
            mbar_expect1(b + 8 * q, 8192);
#pragma unroll 1
            for (; !((ok >> q) & 1); ++it) {
              spin_guard(it);
              ok = __ballot_sync(0xffffffffu, ldr1(cw + 1) >= 32);
            }
            bulk(dst + 8192 * q, src + 512 * q, 8192, b + 8 * q);
          }
          bar_arrive_if(NB_AUX, 64, n == 2);
          if (!e) PROFK(6 + n + 12 * layer);
        }
#pragma unroll 1
        for (int n = 0; n < 8; ++n) mbar_expect1(B_O + 8 * n, 16384);
        if (layer == 0) poll(SCR->C + 6, P.spare);
        mbar_wait(B_QE, layer);
#pragma unroll 1
        for (int e = 0; e < 2; ++e) {
          const int J = 16 * e + (c >> 3);
          const uint32_t* fl = opqp(SCR->OF[layer] + J * 32 + lane);
          const uint4* src[4];
          uint32_t dst[4], b[4];
#pragma unroll
          for (int n = 0; n < 4; ++n) { src[n] = opqp(SCR->O + (J * 4096 + n * 1024)); dst[n] = opq(SM_O + e * O_E + 16384 * n); b[n] = opq(B_O + 32 * e + 8 * n); }
          mbar_wait(B_AT + 8 * e, layer);
          if (!e) pause(260);
          poll(fl, 1);
#pragma unroll
          for (int n = 0; n < 4; ++n) bulk(dst[n], src[n], 16384, b[n]);
          PROFK(9 + e + 12 * layer);
        }
      }
      DONE();
    }
    if (warp == 15) {
      const int G = stat_group(c);
      str4(&SCR->ST[0][(lane >> 4) * 2048 + c * 16 + (lane & 15)], 0, 0, 0, 0); str4(&SCR->ST[1][(lane >> 4) * 2048 + c * 16 + (lane & 15)], 0, 0, 0, 0);
      if (lane < 4) str4(SCR->OF[lane >> 1] + ((lane & 1) * 512 + c * 4), 0, 0, 0, 0);
      str4(&SCR->PS[G * 64 + lane], 0, 0, 0, 0); str4(&SCR->PS[G * 64 + 32 + lane], 0, 0, 0, 0);
      str4(&SCR->SR[1][lane >> 2][sr_off(G, 2 * lane)], 0, 0, 0, 0);
      if (c < 4 && lane < 3) str1(SCR->C + c * 32 + 3 + lane, 0);
#pragma unroll
      for (int k = 0; k < 3; ++k) str2((uint2*)SCR->CS + ((c >> 3) * 768 + k * 256 + 32 * cg + lane), 0, 0);
      __threadfence();
#pragma unroll 1
      for (int layer = 0; layer < 2; ++layer) {
        PROF(4 + 12 * layer);
        mbar_watch(B_E, layer);
        box_help(1, 0, 1, lane, layer);
        if (layer) str4(&SCR->SR[0][lane >> 2][sr_off(G, 2 * lane)], 0, 0, 0, 0);
        uint32_t* ca = opqp(SCR->C + (c >> 5) * 32 + 3 * layer + 2);
        mbar_watch(B_Z, 1);
        mbar_watch(B_RD + 8, layer);
        cnt_add1(ca);
        if (P.spare == 0) {
#pragma unroll 1
          for (int k = 0; k < 32; ++k) str4(SCR->XG[layer] + (c * 1024 + k * 32 + lane), 0, 0, 0, 0);
        }
      }
      mbar_watch(B_O + 56, 1);
    }
  }
}

typedef CUresult (*EncodeFn)(CUtensorMap*, CUtensorMapDataType, cuuint32_t, void*, const cuuint64_t*, const cuuint64_t*,
                             const cuuint32_t*, const cuuint32_t*, CUtensorMapInterleave, CUtensorMapSwizzle,
                             CUtensorMapL2promotion, CUtensorMapFloatOOBfill);

static int place_roles(uint8_t* role) {
  int dev = 0, nsm = 0;
  cudaGetDevice(&dev);
  cudaDeviceGetAttribute(&nsm, cudaDevAttrMultiProcessorCount, dev);
  if (nsm <= 128 || nsm > 144 || (nsm & 1)) return 0;
  cudaFuncSetAttribute(fused_kernel, cudaFuncAttributeNonPortableClusterSizeAllowed, 1);
  int occ[9] = {0};
  for (int k = 2; k <= 8; ++k) {
    cudaLaunchConfig_t cfg = {};
    cudaLaunchAttribute at[1];
    at[0].id = cudaLaunchAttributeClusterDimension;
    at[0].val.clusterDim.x = 2 * k; at[0].val.clusterDim.y = 1; at[0].val.clusterDim.z = 1;
    cfg.gridDim = dim3(2 * k); cfg.blockDim = dim3(NTHR); cfg.dynamicSmemBytes = SM_TOTAL; cfg.attrs = at; cfg.numAttrs = 1;
    if (cudaOccupancyMaxActiveClusters(&occ[k], fused_kernel, &cfg) != cudaSuccess) { cudaGetLastError(); occ[k] = 0; }
  }
  int n[10];
  n[7] = occ[8]; n[6] = occ[7]; n[5] = occ[6] - 0; n[4] = occ[5];
  n[3] = occ[4] - n[7]; n[1] = occ[2] - n[3] - n[5] - n[7]; n[0] = n[2] = n[1];
  n[8] = occ[3] - n[2] - n[5];
  const int ntpc = nsm / 2;
  int sum = 0;
  bool ok = n[0] > 0 && n[0] <= 8;
  for (int r = 0; r < 9; ++r) { ok = ok && n[r] >= 0 && (r == 0 || n[r] <= n[r - 1]); sum += n[r]; }
  if (!ok || sum > ntpc) { for (int r = 0; r < 9; ++r) n[r] = r < 8 ? 8 : 0; sum = 64; }
  int tp[8][9], cnt[8] = {0}, pool[72], np = 0, id = 0;
  for (int r = 0; r < 9; ++r)
    for (int g = n[0] - n[r]; g < n[0]; ++g) tp[g][cnt[g]++] = id++;
  for (; id < ntpc; ++id) pool[np++] = id;
  int order[72], no = 0;
  for (int g = 0; g < n[0]; ++g) {
    const int full = cnt[g] / 4 * 4;
    for (int k = 0; k < cnt[g]; ++k) { if (k < full) order[no++] = tp[g][k]; else pool[np++] = tp[g][k]; }
  }
  for (int k = 0; k < np; ++k) order[no++] = pool[k];
  for (int k = 0; k < ntpc; ++k) role[order[k]] = 2 * k;
  return nsm;
}

extern "C" void kernel_launch(void* const* d_in, const int* in_sizes, int n_in, void* d_out, int out_size) {
  (void)in_sizes; (void)n_in; (void)out_size;
  static EncodeFn enc = nullptr;
  static uint8_t role[72];
  static int nsm = 0;
  static Scratch* scratch = nullptr;
  if (!enc) {
    void* fn = nullptr;
    cudaDriverEntryPointQueryResult qr;
    cudaGetDriverEntryPoint("cuTensorMapEncodeTiled", &fn, cudaEnableDefault, &qr);
    enc = (EncodeFn)fn;
    cudaFuncSetAttribute(fused_kernel, cudaFuncAttributeMaxDynamicSharedMemorySize, SM_TOTAL);
    nsm = place_roles(role);
    cudaGetSymbolAddress((void**)&scratch, g_S);
  }
  CUtensorMap mW, mWo, mX;
  {
    cuuint64_t dim[3] = {512, 512, 3}, str[2] = {3072, 1024};
    cuuint32_t box[3] = {64, 64, 3}, es[3] = {1, 1, 1};
    enc(&mW, CU_TENSOR_MAP_DATA_TYPE_BFLOAT16, 3, d_in[10], dim, str, box, es, CU_TENSOR_MAP_INTERLEAVE_NONE,
        CU_TENSOR_MAP_SWIZZLE_128B, CU_TENSOR_MAP_L2_PROMOTION_NONE, CU_TENSOR_MAP_FLOAT_OOB_FILL_NONE);
  }
  {
    cuuint64_t dim[4] = {512, 2, 4, 64}, str[3] = {1024, 2048, 8192};
    cuuint32_t box[4] = {64, 2, 1, 32}, es[4] = {1, 1, 1, 1};
    enc(&mWo, CU_TENSOR_MAP_DATA_TYPE_BFLOAT16, 4, d_in[11], dim, str, box, es, CU_TENSOR_MAP_INTERLEAVE_NONE,
        CU_TENSOR_MAP_SWIZZLE_128B, CU_TENSOR_MAP_L2_PROMOTION_NONE, CU_TENSOR_MAP_FLOAT_OOB_FILL_NONE);
  }
  {
    cuuint64_t dim[2] = {16384, 64}, str[1] = {32768};
    cuuint32_t box[2] = {128, 8}, es[2] = {1, 1};
    enc(&mX, CU_TENSOR_MAP_DATA_TYPE_BFLOAT16, 2, scratch->XF[0], dim, str, box, es, CU_TENSOR_MAP_INTERLEAVE_NONE,
        CU_TENSOR_MAP_SWIZZLE_NONE, CU_TENSOR_MAP_L2_PROMOTION_NONE, CU_TENSOR_MAP_FLOAT_OOB_FILL_NONE);
  }
  Params P;
  P.x0 = (const uint16_t*)d_in[0]; P.Are = (const uint16_t*)d_in[1]; P.Aim = (const uint16_t*)d_in[2];
  P.Bre = (const uint16_t*)d_in[3]; P.Bim = (const uint16_t*)d_in[4]; P.Cre = (const uint16_t*)d_in[5];
  P.Cim = (const uint16_t*)d_in[6]; P.logdt = (const uint16_t*)d_in[7]; P.dskip = (const uint16_t*)d_in[8];
  P.wqkv = (const uint16_t*)d_in[10]; P.wo = (const uint16_t*)d_in[11]; P.out = (uint16_t*)d_out;
  for (int k = 0; k < 72; ++k) P.role[k] = role[k];
  P.zero = 0;
  P.mid = (char*)scratch->C;
  P.spare = nsm > 0 ? nsm - 128 : 0;
  fused_kernel<<<nsm > 0 ? nsm : 128, NTHR, SM_TOTAL, cudaStreamPerThread>>>(P, mW, mWo, mX);
}
```

```cpp
#include <cuda_runtime.h>
#include <cuda_bf16.h>
#include <cuda.h>
#include <stdint.h>
#include <stddef.h>

#define DEV __device__ __forceinline__
#define RARE(x) __builtin_expect(!!(x), 0)

constexpr int NTHR = 512;
constexpr int REG_MAIN = 192, REG_AUX = 88, REG_PROD = 40;
constexpr int NBARU = 384;
constexpr int SPIN_LIMIT = 1 << 22;

constexpr uint32_t SB = 1024;
__host__ __device__ constexpr uint32_t slot(int n) { return SB + n * 8192; }
__host__ __device__ constexpr int wslot(int k) { return k < 2 ? 3 * k : k < 4 ? 3 * k + 6 : k < 6 ? 21 - 3 * k : 3 * k - 18; }
constexpr uint32_t SM_A = slot(22), A_E = 0u - 32768;
constexpr uint32_t SM_O = slot(18), O_E = 0u - 147456;
constexpr uint32_t SM_WO = slot(10), SM_X = slot(8), SM_KV = slot(9) - 4096;
constexpr uint32_t SM_TAP  = slot(26);
constexpr int TAP_SZ = 3440;
constexpr uint32_t SM_STAT = SM_TAP + 4 * TAP_SZ;
constexpr uint32_t SM_CS   = SM_STAT + 1024;
constexpr uint32_t SM_BAR  = SM_CS + 768;
constexpr int SM_TOTAL = SM_BAR + 352 - SB;
static_assert(SM_TOTAL <= 232448, "");
constexpr int R_SZ = 16384, R_U = 512, R_X5 = 5120, R_X3 = 8704, R_BO = 11776, R_BE = 13824;
constexpr int X_5 = 576, X_3 = 648, T_E = 2 * 720, T_O = 1600 + 2 * 721, T_C = 3390, T_K = 3424;
constexpr uint32_t B_RD = SM_BAR, B_ED = SM_BAR + 16, B_F = SM_BAR + 32, B_AT = SM_BAR + 56, B_L = SM_BAR + 264;
constexpr uint32_t B_AE = SM_BAR + 72, B_QE = SM_BAR + 88, B_ST = SM_BAR + 96, B_CS = SM_BAR + 112;
constexpr uint32_t B_WO = SM_BAR + 120, B_W6 = SM_BAR + 128, B_U = SM_BAR + 144, B_E = SM_BAR + 152, B_WF = SM_BAR + 160, B_W4 = SM_BAR + 168,
                   B_N = SM_BAR + 176, B_V = SM_BAR + 184, B_O = SM_BAR + 192, B_Z = SM_BAR + 256, B_A = SM_BAR + 272;
constexpr int NB_U = 1, NB_B = 2, NB_K = 8, NB_Y = 6, NB_WG = 8, NB_T = 10, NB_AUX = 12, NB_P0 = 13, NB_H = 15;

struct Scratch {
  uint4    XG[2][128 * 1024];
  uint4    O[32 * 8 * 512];
  uint32_t C[8 * 32];
  uint32_t OF[2][32 * 32];
  uint4    CS[16 * 1536 / 4];
  uint4    PS[128 * 64];
  uint4    ST[2][32 * 128];
  uint4    SR[2][8][512];
  uint4    XF[2][32 * 512 * 8];
  uint4    H[2][17 * 8 * 256];
};
__device__ __align__(1024) Scratch g_S;
#define SCR ((Scratch*)(P.mid - offsetof(Scratch, C)))
#define COUNT(k) do {} while (0)
#define PROFD(slot, v) do {} while (0)
#define PROF(slot) do {} while (0)
#define PROFK(slot) do {} while (0)

#define PROFC(slot) do {} while (0)

DEV uint32_t s2u(const void* p) { return (uint32_t)__cvta_generic_to_shared(p); }
template <class T> DEV T* opqp(T* x) { asm volatile("" : "+l"(x)); return x; }
template <class T> DEV T opq(T x) { asm volatile("" : "+r"(x)); return x; }
DEV int lane_id() { int l; asm volatile("mov.u32 %0,%%laneid;" : "=r"(l)); return l; }
DEV uint32_t pack2(float lo, float hi) { uint32_t d; asm("cvt.rn.bf16x2.f32 %0,%1,%2;" : "=r"(d) : "f"(hi), "f"(lo)); return d; }
DEV float bflo(uint32_t v) { return __uint_as_float(v << 16); }
DEV float bfhi(uint32_t v) { return __uint_as_float(v & 0xFFFF0000u); }
DEV float bfr(float x) { return bflo(pack2(x, 0.f)); }
DEV uint32_t hadd2(uint32_t a, uint32_t b) { uint32_t d; asm("add.rn.bf16x2 %0,%1,%2;" : "=r"(d) : "r"(a), "r"(b)); return d; }
DEV uint32_t hsub2(uint32_t a, uint32_t b) { uint32_t d; asm("sub.rn.bf16x2 %0,%1,%2;" : "=r"(d) : "r"(a), "r"(b)); return d; }
DEV uint32_t hmul2(uint32_t a, uint32_t b) { uint32_t d; asm("mul.rn.bf16x2 %0,%1,%2;" : "=r"(d) : "r"(a), "r"(b)); return d; }
DEV uint32_t hfma2(uint32_t a, uint32_t b, uint32_t c) { uint32_t d; asm("fma.rn.bf16x2 %0,%1,%2,%3;" : "=r"(d) : "r"(a), "r"(b), "r"(c)); return d; }
DEV uint32_t prmt(uint32_t a, uint32_t b, uint32_t s) { uint32_t d; asm("prmt.b32 %0,%1,%2,%3;" : "=r"(d) : "r"(a), "r"(b), "r"(s)); return d; }
DEV uint32_t nzmap(uint32_t v) { uint32_t d; asm("max.u32 %0,%1,1;" : "=r"(d) : "r"(v)); return d; }
DEV float rcp(float x) { float y; asm("rcp.approx.ftz.f32 %0,%1;" : "=f"(y) : "f"(x)); return y; }
DEV float sqrt_(float x) { float y; asm("sqrt.approx.ftz.f32 %0,%1;" : "=f"(y) : "f"(x)); return y; }
DEV float ex2(float x) { float y; asm("ex2.approx.ftz.f32 %0,%1;" : "=f"(y) : "f"(x)); return y; }

DEV uint4 ldr4(const void* p) { uint4 v; asm volatile("ld.relaxed.gpu.global.v4.u32 {%0,%1,%2,%3},[%4];" : "=r"(v.x), "=r"(v.y), "=r"(v.z), "=r"(v.w) : "l"(p) : "memory"); return v; }
DEV void ldr4_if(uint4& v, const void* p, bool c) {
  asm volatile("{.reg .pred q; setp.ne.u32 q,%5,0; @q ld.relaxed.gpu.global.v4.u32 {%0,%1,%2,%3},[%4];}"
    : "+r"(v.x), "+r"(v.y), "+r"(v.z), "+r"(v.w) : "l"(p), "r"((uint32_t)c) : "memory");
}
DEV uint2 ldr2(const void* p) { uint2 v; asm volatile("ld.relaxed.gpu.global.v2.u32 {%0,%1},[%2];" : "=r"(v.x), "=r"(v.y) : "l"(p) : "memory"); return v; }
DEV uint32_t ldr1(const void* p) { uint32_t v; asm volatile("ld.relaxed.gpu.global.u32 %0,[%1];" : "=r"(v) : "l"(p) : "memory"); return v; }
DEV float ldnan(const uint16_t* p) {
  uint32_t v = 0xFFFFu;
#pragma unroll 1
  for (int it = 0; it < SPIN_LIMIT && __any_sync(0xffffffffu, v == 0xFFFFu); ++it) asm volatile("ld.relaxed.gpu.global.u16 %0,[%1];" : "=r"(v) : "l"(p) : "memory");
  return __uint_as_float(v << 16);
}
DEV uint4 ldw4(const void* p) { uint4 v; asm volatile("ld.global.v4.u32 {%0,%1,%2,%3},[%4];" : "=r"(v.x), "=r"(v.y), "=r"(v.z), "=r"(v.w) : "l"(p) : "memory"); return v; }
DEV uint32_t ldw1(const void* p) { uint32_t v; asm volatile("ld.global.u32 %0,[%1];" : "=r"(v) : "l"(p) : "memory"); return v; }
DEV void str4(void* p, uint32_t a, uint32_t b, uint32_t c, uint32_t d) { asm volatile("st.relaxed.gpu.global.v4.u32 [%0],{%1,%2,%3,%4};" :: "l"(p), "r"(a), "r"(b), "r"(c), "r"(d) : "memory"); }
DEV void str2(void* p, uint32_t a, uint32_t b) { asm volatile("st.relaxed.gpu.global.v2.u32 [%0],{%1,%2};" :: "l"(p), "r"(a), "r"(b) : "memory"); }
DEV void str1(void* p, uint32_t a) { asm volatile("st.relaxed.gpu.global.u32 [%0],%1;" :: "l"(p), "r"(a) : "memory"); }
DEV void str4_if(void* p, uint32_t a, uint32_t b, uint32_t c, uint32_t d, bool q) {
  asm volatile("{.reg .pred q; setp.ne.u32 q,%5,0; @q st.relaxed.gpu.global.v4.u32 [%0],{%1,%2,%3,%4};}" :: "l"(p), "r"(a), "r"(b), "r"(c), "r"(d), "r"((uint32_t)q) : "memory");
}
DEV void stw4(void* p, uint32_t a, uint32_t b, uint32_t c, uint32_t d) { asm volatile("st.global.v4.u32 [%0],{%1,%2,%3,%4};" :: "l"(p), "r"(a), "r"(b), "r"(c), "r"(d) : "memory"); }
DEV uint4 ldnc4(const void* p) { uint4 v; asm volatile("ld.global.nc.v4.u32 {%0,%1,%2,%3},[%4];" : "=r"(v.x), "=r"(v.y), "=r"(v.z), "=r"(v.w) : "l"(p)); return v; }

DEV uint2 lds2(uint32_t a) { uint2 v; asm volatile("ld.volatile.shared.v2.u32 {%0,%1},[%2];" : "=r"(v.x), "=r"(v.y) : "r"(a)); return v; }
DEV void sts2(uint32_t a, uint32_t x, uint32_t y) { asm volatile("st.shared.v2.u32 [%0],{%1,%2};" :: "r"(a), "r"(x), "r"(y) : "memory"); }
DEV uint32_t lds1(uint32_t a) { uint32_t v; asm volatile("ld.volatile.shared.u32 %0,[%1];" : "=r"(v) : "r"(a)); return v; }
DEV uint32_t lds1z(uint32_t a, bool c) {
  uint32_t v; asm volatile("{.reg .pred q; setp.ne.u32 q,%2,0; mov.u32 %0,0; @q ld.volatile.shared.u32 %0,[%1];}" : "=r"(v) : "r"(a), "r"((uint32_t)c)); return v;
}
DEV uint4 lds4z(uint32_t a, bool c) {
  uint4 v = make_uint4(0, 0, 0, 0);
  asm volatile("{.reg .pred q; setp.ne.u32 q,%5,0; @q ld.volatile.shared.v4.u32 {%0,%1,%2,%3},[%4];}" : "+r"(v.x), "+r"(v.y), "+r"(v.z), "+r"(v.w) : "r"(a), "r"((uint32_t)c));
  return v;
}
DEV float2 lds2f(uint32_t a) { float2 v; asm volatile("ld.shared.v2.f32 {%0,%1},[%2];" : "=f"(v.x), "=f"(v.y) : "r"(a)); return v; }
DEV float4 lds4f(uint32_t a) { float4 v; asm volatile("ld.volatile.shared.v4.f32 {%0,%1,%2,%3},[%4];" : "=f"(v.x), "=f"(v.y), "=f"(v.z), "=f"(v.w) : "r"(a)); return v; }
DEV uint4 lds4(uint32_t a) { uint4 v; asm volatile("ld.volatile.shared.v4.u32 {%0,%1,%2,%3},[%4];" : "=r"(v.x), "=r"(v.y), "=r"(v.z), "=r"(v.w) : "r"(a)); return v; }
DEV void sts1(uint32_t a, uint32_t v) { asm volatile("st.shared.u32 [%0],%1;" :: "r"(a), "r"(v) : "memory"); }
DEV void sts16(uint32_t a, uint32_t v) { asm volatile("st.shared.u16 [%0],%1;" :: "r"(a), "r"(v) : "memory"); }
DEV void sts2f(uint32_t a, float x, float y) { asm volatile("st.shared.v2.f32 [%0],{%1,%2};" :: "r"(a), "f"(x), "f"(y) : "memory"); }
DEV void sts4f(uint32_t a, float x, float y, float z, float w) { asm volatile("st.shared.v4.f32 [%0],{%1,%2,%3,%4};" :: "r"(a), "f"(x), "f"(y), "f"(z), "f"(w) : "memory"); }
DEV void sts4(uint32_t a, uint32_t x, uint32_t y, uint32_t z, uint32_t w) { asm volatile("st.shared.v4.u32 [%0],{%1,%2,%3,%4};" :: "r"(a), "r"(x), "r"(y), "r"(z), "r"(w) : "memory"); }

DEV void ldsm4(uint32_t (&r)[4], uint32_t a) { asm volatile("ldmatrix.sync.aligned.m8n8.x4.shared.b16 {%0,%1,%2,%3},[%4];" : "=r"(r[0]), "=r"(r[1]), "=r"(r[2]), "=r"(r[3]) : "r"(a) : "memory"); }
DEV void ldsm4t(uint32_t (&r)[4], uint32_t a) { asm volatile("ldmatrix.sync.aligned.m8n8.x4.trans.shared.b16 {%0,%1,%2,%3},[%4];" : "=r"(r[0]), "=r"(r[1]), "=r"(r[2]), "=r"(r[3]) : "r"(a) : "memory"); }
DEV void stsm4(uint32_t a, uint32_t r0, uint32_t r1, uint32_t r2, uint32_t r3) { asm volatile("stmatrix.sync.aligned.m8n8.x4.shared.b16 [%0],{%1,%2,%3,%4};" :: "r"(a), "r"(r0), "r"(r1), "r"(r2), "r"(r3) : "memory"); }
DEV void stsm2(uint32_t a, uint32_t r0, uint32_t r1) { asm volatile("stmatrix.sync.aligned.m8n8.x2.shared.b16 [%0],{%1,%2};" :: "r"(a), "r"(r0), "r"(r1) : "memory"); }
DEV void stsm4t(uint32_t a, uint32_t r0, uint32_t r1, uint32_t r2, uint32_t r3) { asm volatile("stmatrix.sync.aligned.m8n8.x4.trans.shared.b16 [%0],{%1,%2,%3,%4};" :: "r"(a), "r"(r0), "r"(r1), "r"(r2), "r"(r3) : "memory"); }
DEV uint32_t movm(uint32_t a) { uint32_t d; asm volatile("movmatrix.sync.aligned.m8n8.trans.b16 %0,%1;" : "=r"(d) : "r"(a)); return d; }
DEV void mma16(float (&d)[4], uint32_t a0, uint32_t a1, uint32_t a2, uint32_t a3, uint32_t b0, uint32_t b1) {
  asm volatile("mma.sync.aligned.m16n8k16.row.col.f32.bf16.bf16.f32 {%0,%1,%2,%3},{%4,%5,%6,%7},{%8,%9},{%0,%1,%2,%3};"
    : "+f"(d[0]), "+f"(d[1]), "+f"(d[2]), "+f"(d[3]) : "r"(a0), "r"(a1), "r"(a2), "r"(a3), "r"(b0), "r"(b1));
}
DEV void mma16z(float (&d)[4], uint32_t a0, uint32_t a1, uint32_t a2, uint32_t a3, uint32_t b0, uint32_t b1) {
  asm volatile("mma.sync.aligned.m16n8k16.row.col.f32.bf16.bf16.f32 {%0,%1,%2,%3},{%4,%5,%6,%7},{%8,%9},{%10,%10,%10,%10};"
    : "=f"(d[0]), "=f"(d[1]), "=f"(d[2]), "=f"(d[3]) : "r"(a0), "r"(a1), "r"(a2), "r"(a3), "r"(b0), "r"(b1), "f"(0.f));
}
DEV void mma8(float (&d)[4], uint32_t a0, uint32_t a1, uint32_t b0) {
  asm volatile("mma.sync.aligned.m16n8k8.row.col.f32.bf16.bf16.f32 {%0,%1,%2,%3},{%4,%5},{%6},{%0,%1,%2,%3};"
    : "+f"(d[0]), "+f"(d[1]), "+f"(d[2]), "+f"(d[3]) : "r"(a0), "r"(a1), "r"(b0));
}

DEV void mma8z(float (&d)[4], uint32_t a0, uint32_t a1, uint32_t b0) {
  asm volatile("mma.sync.aligned.m16n8k8.row.col.f32.bf16.bf16.f32 {%0,%1,%2,%3},{%4,%5},{%6},{%7,%7,%7,%7};"
    : "=f"(d[0]), "=f"(d[1]), "=f"(d[2]), "=f"(d[3]) : "r"(a0), "r"(a1), "r"(b0), "f"(0.f));
}
DEV void bar_sync(int id, int n) { asm volatile("bar.sync %0,%1;" :: "r"(id), "r"(n) : "memory"); }
DEV void bar_sync_if(int id, int n, int c) { asm volatile("{.reg .pred q; setp.ne.s32 q,%2,0; @q bar.sync %0,%1;}" :: "r"(id), "r"(n), "r"(c) : "memory"); }
DEV void bar_arrive_if(int id, int n, int c) { asm volatile("{.reg .pred q; setp.ne.s32 q,%2,0; @q bar.arrive %0,%1;}" :: "r"(id), "r"(n), "r"(c) : "memory"); }
DEV void bar_arrive(int id, int n) { asm volatile("bar.arrive %0,%1;" :: "r"(id), "r"(n) : "memory"); }
DEV void fence_async_smem() { asm volatile("fence.proxy.async.shared::cta;" ::: "memory"); }
DEV void mbar_wait(uint32_t b, uint32_t ph) {
  asm volatile("{\n.reg .pred p;\nW: mbarrier.try_wait.parity.shared::cta.b64 p,[%0],%1;\n@!p bra W;\n}" :: "r"(b), "r"(ph) : "memory");
}
DEV void mbar_watch(uint32_t b, uint32_t ph) {
  asm volatile("{\n.reg .pred p,q;\n.reg .u32 n;\nmov.u32 n,0;\n"
               "W: mbarrier.try_wait.parity.shared::cta.b64 p,[%0],%1;\n@p bra D;\n"
               "add.u32 n,n,1;\nsetp.lt.u32 q,n,%2;\n@q bra W;\ntrap;\nD:\n}"
               :: "r"(b), "r"(ph), "n"(SPIN_LIMIT) : "memory");
}
DEV void spin_guard(int it) { asm volatile("{.reg .pred p; setp.gt.s32 p,%0,%1; @p trap;}" :: "r"(it), "n"(SPIN_LIMIT)); }
DEV void split(uint32_t zero) {
  asm volatile("{.reg .pred p; setp.ne.u32 p,%0,0; @p trap;}" :: "r"(zero) : "memory");
}
DEV void pause(int n) {
  uint32_t t0, t; asm volatile("mov.u32 %0,%%clock;" : "=r"(t0));
  do asm volatile("mov.u32 %0,%%clock;" : "=r"(t)); while (t - t0 < n);
}
DEV void poll(const uint32_t* k, uint32_t n) {
#pragma unroll 1
  for (int it = 0;; ++it) {
    spin_guard(it);
    if (__all_sync(0xffffffffu, ldr1(k) >= n)) break;
  }
}
DEV void mbar_arrive1(uint32_t b) { asm volatile("{.reg .pred p; elect.sync _|p,0xffffffff; @p mbarrier.arrive.shared::cta.b64 _,[%0];}" :: "r"(b) : "memory"); }
DEV void mbar_arrive1_if(uint32_t b, int c) {
  asm volatile("{.reg .pred p,q; setp.ne.s32 q,%1,0; elect.sync _|p,0xffffffff; and.pred p,p,q; @p mbarrier.arrive.shared::cta.b64 _,[%0];}" :: "r"(b), "r"(c) : "memory");
}
DEV void mbar_expect1(uint32_t b, int bytes) { asm volatile("{.reg .pred p; elect.sync _|p,0xffffffff; @p mbarrier.arrive.expect_tx.shared::cta.b64 _,[%0],%1;}" :: "r"(b), "r"(bytes) : "memory"); }
DEV void cnt_add1(uint32_t* q) { asm volatile("{.reg .pred p; elect.sync _|p,0xffffffff; @p red.relaxed.gpu.global.add.u32 [%0],1;}" :: "l"(q) : "memory"); }
DEV void tma4(uint32_t dst, const CUtensorMap* m, int c0, int c1, int c2, int c3, uint32_t bar) {
  asm volatile("{.reg .pred p; elect.sync _|p,0xffffffff;\n"
    "@p cp.async.bulk.tensor.4d.shared::cluster.global.mbarrier::complete_tx::bytes [%0],[%1,{%2,%3,%4,%5}],[%6];}"
    :: "r"(dst), "l"(m), "r"(c0), "r"(c1), "r"(c2), "r"(c3), "r"(bar) : "memory");
}
DEV void tma3(uint32_t dst, const CUtensorMap* m, int c0, int c1, int c2, uint32_t bar) {
  asm volatile("{.reg .pred p; elect.sync _|p,0xffffffff;\n"
    "@p cp.async.bulk.tensor.3d.shared::cluster.global.mbarrier::complete_tx::bytes [%0],[%1,{%2,%3,%4}],[%5];}"
    :: "r"(dst), "l"(m), "r"(c0), "r"(c1), "r"(c2), "r"(bar) : "memory");
}
DEV void bulk(uint32_t dst, const void* src, int bytes, uint32_t bar) {
  asm volatile("{.reg .pred p; elect.sync _|p,0xffffffff;\n@p cp.async.bulk.shared::cluster.global.mbarrier::complete_tx::bytes [%0],[%1],%2,[%3];}" :: "r"(dst), "l"(src), "r"(bytes), "r"(bar) : "memory");
}

DEV void bulk_store(void* dst, uint32_t src, int bytes) {
  asm volatile("{.reg .pred p; elect.sync _|p,0xffffffff;\n@p cp.async.bulk.global.shared::cta.bulk_group [%0],[%1],%2;}" :: "l"(dst), "r"(src), "r"(bytes) : "memory");
}
DEV void tma2_store(const CUtensorMap* m, uint32_t src, int c0, int c1) {
  asm volatile("{.reg .pred p; elect.sync _|p,0xffffffff;\n@p cp.async.bulk.tensor.2d.global.shared::cta.bulk_group [%0,{%2,%3}],[%1];}" :: "l"(m), "r"(src), "r"(c0), "r"(c1) : "memory");
}
DEV void bulk_wait() { asm volatile("cp.async.bulk.commit_group;\ncp.async.bulk.wait_group 0;\nfence.proxy.async.global;" ::: "memory"); }

DEV uint32_t dlo(uint32_t addr, uint32_t lbo) { return __shfl_sync(0xffffffffu, (addr >> 4) | ((lbo >> 4) << 16), 0); }
__host__ __device__ constexpr uint32_t dhi(uint32_t sbo, uint32_t swz) { return (sbo >> 4) | (swz << 30); }
DEV void wg_fence() { asm volatile("wgmma.fence.sync.aligned;" ::: "memory"); }
DEV void wg_commit() { asm volatile("wgmma.commit_group.sync.aligned;" ::: "memory"); }
template <int N> DEV void wg_wait() { asm volatile("wgmma.wait_group.sync.aligned %0;" :: "n"(N) : "memory"); }
template <int N> DEV void zero(float (&d)[N]) {
#pragma unroll
  for (int i = 0; i < N; ++i) d[i] = 0.f;
}
template <int N> DEV void zerov(float (&d)[N]) {
#pragma unroll
  for (int i = 0; i < N; ++i) asm volatile("mov.b32 %0,0;" : "=f"(d[i]));
}
template <int N> DEV void undef(float (&d)[N]) {
#pragma unroll
  for (int i = 0; i < N; ++i) asm volatile("" : "=f"(d[i]));
}
#define R4(d, o) "+f"(d[o]), "+f"(d[o + 1]), "+f"(d[o + 2]), "+f"(d[o + 3])
#define R8(d, o) R4(d, o), R4(d, o + 4)
#define R16(d, o) R8(d, o), R8(d, o + 8)
template <int ACC> DEV void wg_rs64k(float (&d)[32], const uint32_t (&a)[4], uint32_t db) {
  asm volatile("{.reg .pred p; .reg .b64 b; setp.ne.s32 p,%38,0; mov.b64 b,{%36,%37};\n"
    "wgmma.mma_async.sync.aligned.m64n64k16.f32.bf16.bf16 {%0,%1,%2,%3,%4,%5,%6,%7,%8,%9,%10,%11,%12,%13,%14,%15,%16,%17,%18,%19,%20,%21,%22,%23,%24,%25,%26,%27,%28,%29,%30,%31},{%32,%33,%34,%35},b,p,1,1,0;}"
    : R16(d, 0), R16(d, 16) : "r"(a[0]), "r"(a[1]), "r"(a[2]), "r"(a[3]), "r"(db), "n"(dhi(512, 2)), "n"(ACC));
}
template <int ACC> DEV void wg_rs48t(float (&d)[24], const uint32_t (&a)[4], uint32_t db) {
  asm volatile("{.reg .pred p; .reg .b64 b; setp.ne.s32 p,%30,0; mov.b64 b,{%28,%29};\n"
    "wgmma.mma_async.sync.aligned.m64n48k16.f32.bf16.bf16 {%0,%1,%2,%3,%4,%5,%6,%7,%8,%9,%10,%11,%12,%13,%14,%15,%16,%17,%18,%19,%20,%21,%22,%23},{%24,%25,%26,%27},b,p,1,1,1;}"
    : R16(d, 0), R8(d, 16) : "r"(a[0]), "r"(a[1]), "r"(a[2]), "r"(a[3]), "r"(db), "n"(dhi(512, 0)), "n"(ACC));
}
template <int ACC> DEV void wg_rs32t(float (&d)[16], const uint32_t (&a)[4], uint32_t db) {
  asm volatile("{.reg .pred p; .reg .b64 b; setp.ne.s32 p,%22,0; mov.b64 b,{%20,%21};\n"
    "wgmma.mma_async.sync.aligned.m64n32k16.f32.bf16.bf16 {%0,%1,%2,%3,%4,%5,%6,%7,%8,%9,%10,%11,%12,%13,%14,%15},{%16,%17,%18,%19},b,p,1,1,1;}"
    : R16(d, 0) : "r"(a[0]), "r"(a[1]), "r"(a[2]), "r"(a[3]), "r"(db), "n"(dhi(1024, 0)), "n"(ACC));
}
template <int ACC> DEV void wg_ss192(float (&d)[96], uint32_t da, uint32_t db) {
  asm volatile("{.reg .pred p; .reg .b64 a,b; setp.ne.s32 p,%100,0; mov.b64 a,{%96,%98}; mov.b64 b,{%97,%99};\n"
    "wgmma.mma_async.sync.aligned.m64n192k16.f32.bf16.bf16 {"
    "%0,%1,%2,%3,%4,%5,%6,%7,%8,%9,%10,%11,%12,%13,%14,%15,%16,%17,%18,%19,%20,%21,%22,%23,%24,%25,%26,%27,%28,%29,%30,%31,"
    "%32,%33,%34,%35,%36,%37,%38,%39,%40,%41,%42,%43,%44,%45,%46,%47,%48,%49,%50,%51,%52,%53,%54,%55,%56,%57,%58,%59,%60,%61,%62,%63,"
    "%64,%65,%66,%67,%68,%69,%70,%71,%72,%73,%74,%75,%76,%77,%78,%79,%80,%81,%82,%83,%84,%85,%86,%87,%88,%89,%90,%91,%92,%93,%94,%95},a,b,p,1,1,1,1;}"
    : R16(d, 0), R16(d, 16), R16(d, 32), R16(d, 48), R16(d, 64), R16(d, 80) : "r"(da), "r"(db), "n"(dhi(1024, 1)), "n"(dhi(1024, 1)), "n"(ACC));
}
template <int ACC> DEV void wg_ss64(float (&d)[32], uint32_t da, uint32_t db) {
  asm volatile("{.reg .pred p; .reg .b64 a,b; setp.ne.s32 p,%36,0; mov.b64 a,{%32,%34}; mov.b64 b,{%33,%35};\n"
    "wgmma.mma_async.sync.aligned.m64n64k16.f32.bf16.bf16 {"
    "%0,%1,%2,%3,%4,%5,%6,%7,%8,%9,%10,%11,%12,%13,%14,%15,%16,%17,%18,%19,%20,%21,%22,%23,%24,%25,%26,%27,%28,%29,%30,%31},a,b,p,1,1,0,1;}"
    : R16(d, 0), R16(d, 16) : "r"(da), "r"(db), "n"(dhi(1024, 0)), "n"(dhi(1024, 1)), "n"(ACC));
}

DEV uint32_t cpy(uint32_t v, uint32_t id) {
  uint32_t d; asm volatile("prmt.b32 %0,%1,%1,%2;" : "=r"(d) : "r"(v), "r"(id)); return d;
}
struct Params {
  uint32_t zero, spare;
  char* mid;
  const uint16_t *x0, *Are, *Aim, *Bre, *Bim, *Cre, *Cim, *logdt, *dskip, *wqkv, *wo;
  uint16_t* out;
  uint8_t role[72];
};

DEV uint32_t ln_word(float mean, float var) {
  float v = bfr(var);
  float s = sqrt_(bfr(v + 1e-5f));
  return pack2(mean, s);
}

DEV int stat_group(int c) { return c ^ 4; }
DEV int xg_off(int G, int g) { return (G >> 5) * 512 + (G & 31) * 8 + (g ^ (G & 2)); }
DEV int sr_off(int G, int g) { return (G >> 6) * 256 + (g & 2) * 64 + 2 * (G & 63) + ((g >> 2) & 1); }
DEV uint32_t region(int chl) { return SM_A + (chl >> 1) * A_E + (chl & 1) * R_SZ; }
template <bool FIRST> DEV void gram(float (&s)[4], float (&q0)[4], float (&q1)[4], uint32_t a0, uint32_t a1, uint32_t a2, uint32_t a3) {
  const uint32_t one = 0x3F803F80u;
  if (FIRST) { mma16z(s, a0, a1, a2, a3, one, one); mma8z(q0, a0, a1, a0); mma8z(q1, a0, a1, a1); }
  else { mma16(s, a0, a1, a2, a3, one, one); mma8(q0, a0, a1, a0); mma8(q1, a0, a1, a1); }
  mma8(q0, a2, a3, a2); mma8(q1, a2, a3, a3);
}
DEV uint32_t ln_sums(float s, float q) { const float m = s * (1.f / 512.f); return ln_word(m, fmaxf(q * (1.f / 512.f) - m * m, 0.f)); }
DEV void cmul(float& orr, float& oi, float ar, float ai, float br, float bi) {
  float r = ar * br - ai * bi, i = ar * bi + ai * br; orr = r; oi = i;
}
DEV void cexp_(float al, float bt, float s, float& er, float& ei) {
  float mag = ex2(al * s), ph = bt * s;
  ph -= rintf(ph);
  float ang = ph * 6.283185307179586f;
  er = mag * __cosf(ang); ei = mag * __sinf(ang);
}

DEV void kgen(const Params& P, int c, int wm, int lane) {
  const int chl = wm >> 1, mh = wm & 1, g = lane >> 2, t = lane & 3;
  const int ch = 256 * (chl >> 1) + 2 * c + (chl & 1);
  const int mo = ch * 64 + mh * 32 + lane;
  const uint32_t vAr = ldw1((const uint32_t*)P.Are + mo), vAi = ldw1((const uint32_t*)P.Aim + mo);
  const uint32_t vBr = ldw1((const uint32_t*)P.Bre + mo), vBi = ldw1((const uint32_t*)P.Bim + mo);
  const uint32_t vCr = ldw1((const uint32_t*)P.Cre + mo), vCi = ldw1((const uint32_t*)P.Cim + mo);
  const uint32_t vld = ldw1((const uint32_t*)P.logdt + (ch >> 1)), vds = ldw1((const uint32_t*)P.dskip + (ch >> 1));
  bar_arrive(NB_Y, 384);
  PROF(45);
  {
    const uint32_t tz = SM_TAP + chl * TAP_SZ + (mh * 32 + lane) * 16;
#pragma unroll
    for (int k = 0; k < 3; ++k) sts4(tz + k * 1024, 0, 0, 0, 0);
    static_assert(TAP_SZ > 3072 && TAP_SZ <= 4096, "");
    if (mh * 32 + lane < TAP_SZ / 16 - 192) sts4(tz + 3072, 0, 0, 0, 0);
  }
  const uint32_t tb = slot(wm), tw = opq(tb + lane * 4);
  const uint32_t aa = opq(tb + (lane & 15) * 144 + (lane >> 4) * 16), ba = opq(tb + (16 + (lane & 7)) * 144 + (lane >> 3) * 16);
  float acc[5][4], k2048 = 0.f;
#pragma unroll
  for (int i = 0; i < 5; ++i) zerov(acc[i]);
  sts1(tw, 0x3F80u);
  asm volatile("setmaxnreg.inc.sync.aligned.u32 %0;" :: "n"(REG_MAIN));
  PROF(44);
  const float dt = bfr(ex2((ch & 1 ? bfhi(vld) : bflo(vld)) * 1.4426950408889634f));
#pragma unroll 1
  for (int r = 0; r < 2; ++r) {
    const uint32_t sel = r ? 0x3244 : 0x1044;
    const float are = __uint_as_float(prmt(vAr, 0, sel)), aim = __uint_as_float(prmt(vAi, 0, sel)), bre = __uint_as_float(prmt(vBr, 0, sel));
    const float bim = __uint_as_float(prmt(vBi, 0, sel)), cre = __uint_as_float(prmt(vCr, 0, sel)), cim = __uint_as_float(prmt(vCi, 0, sel));
    const float al = dt * are * 1.4426950408889634f, bt = dt * aim * 0.15915494309189535f;
    float qr, qi; cmul(qr, qi, cre, cim, dt * bre, dt * bim);
    if (r == 0) PROFD(2, __float_as_uint(qr + al + bt));
    float er[3], ei[3], e8r, e8i, eLr, eLi;
    cexp_(al, bt, 1.f, er[0], ei[0]); cexp_(al, -bt, 8.f, e8r, e8i); cexp_(al, bt, 128.f, eLr, eLi);
    cmul(er[1], ei[1], er[0], ei[0], er[0], ei[0]); cmul(er[2], ei[2], er[1], ei[1], er[1], ei[1]);
    float yr = e8r, yi = e8i;
#pragma unroll
    for (int a = 0; a < 16; ++a) {
      if (a) sts1(tw + a * 144, pack2(yr, yi));
      if (a && a < 15) cmul(yr, yi, yr, yi, e8r, e8i);
      const int ls = a < 2 ? 0 : a < 4 ? 1 : a < 8 ? 2 : 3;
      const int row0 = 16 + (a < 2 ? 8 * a : a < 4 ? 16 + 4 * (a - 2) : a < 8 ? 24 + 2 * (a - 4) : 32 + (a - 8));
      float xr[8], xi[8];
      xr[0] = qr; xi[0] = qi;
#pragma unroll
      for (int k = 0; k < (8 >> ls); ++k) {
        const int hb = k >= 4 ? 2 : k >= 2 ? 1 : 0;
        if (k) cmul(xr[k], xi[k], xr[k - (1 << hb)], xi[k - (1 << hb)], er[(ls + hb) % 3], ei[(ls + hb) % 3]);
        sts1(tw + (row0 + k) * 144, pack2(xr[k], xi[k]));
      }
      cmul(qr, qi, qr, qi, eLr, eLi);
    }
    __syncwarp();
    if (r == 0) PROF(3);
#pragma unroll
    for (int kp = 0; kp < 2; ++kp) {
      uint32_t a0[4], a1[4];
      ldsm4(a0, aa + kp * 64); ldsm4(a1, aa + kp * 64 + 32);
#pragma unroll
      for (int tl = 0; tl < 5; ++tl) {
        uint32_t b[4];
        ldsm4(b, ba + 8 * tl * 144 + kp * 64);
        if (kp == 0) qr += __shfl_xor_sync(0xffffffffu, qr, 1 << tl);
        mma16(acc[tl], a0[0], a0[1], a0[2], a0[3], b[0], b[1]);
        mma16(acc[tl], a1[0], a1[1], a1[2], a1[3], b[2], b[3]);
      }
    }
    k2048 += qr;
    __syncwarp();
  }
  const uint32_t xa = tb + lane * 16, ob = xa ^ 8192, tp = SM_TAP + chl * TAP_SZ;
  if (mh == 0) {
    sts4f(xa, acc[2][0], acc[2][1], acc[2][2], acc[2][3]);
    sts4f(xa + 512, acc[3][0], acc[3][1], acc[3][2], acc[3][3]);
    sts1(tb + 1024, __float_as_uint(k2048));
  } else {
    sts4f(xa, acc[0][0], acc[0][1], acc[0][2], acc[0][3]);
    sts4f(xa + 512, acc[1][0], acc[1][1], acc[1][2], acc[1][3]);
    sts4f(xa + 1024, acc[4][0], acc[4][1], acc[4][2], acc[4][3]);
  }
  PROF(4);
  bar_sync(NB_K + chl, 64);
  float4 o[3];
#pragma unroll
  for (int k = 0; k < 3; ++k) o[k] = lds4f(ob + k * 512);
  if (mh == 0) {
    if (lane == 0) o[0].x += ch & 1 ? bfhi(vds) : bflo(vds);
    const uint32_t a = tp - 2 * (8 * g + 2 * t + 1);
#pragma unroll
    for (int z = 0; z < 4; ++z) {
      const float* k = acc[z >> 1] + 2 * (z & 1);
      const uint32_t v = z & 1 ? pack2(k[1] + o[z >> 1].w, k[0] + o[z >> 1].z) : pack2(k[1] + o[z >> 1].y, k[0] + o[z >> 1].x);
      sts1(a + T_O - 128 * z, v); sts16(a + T_E - 128 * z, v); sts16(a + T_E + 2 - 128 * z, v >> 16);
    }
    const uint32_t v0 = pack2(acc[4][0] + o[2].x, acc[4][1] + o[2].y), v1 = pack2(acc[4][2] + o[2].z, acc[4][3] + o[2].w);
    const uint32_t b = tp + T_C - 2 * (32 * t + g - 1);
    if (lane == 0) { sts16(tp + T_E - 2 * (X_5 + 63), v0); sts16(tp + T_O - 2 * (X_5 + 63), v0); sts1(tp + T_K, prmt(v0, v0, 0x1010)); }
    else sts16(b, v0);
    sts16(b - 32, v0 >> 16); sts16(b - 16, v1); sts16(b - 48, v1 >> 16);
  } else {
    const uint32_t a = tp - 2 * (256 + 128 * (t >> 1) + 4 * (t & 1) + 8 * g);
#pragma unroll
    for (int z = 0; z < 2; ++z) {
      const uint32_t v = z ? pack2(acc[2][3] + o[0].w, acc[2][2] + o[0].z) : pack2(acc[2][1] + o[0].y, acc[2][0] + o[0].x), d = prmt(v, v, 0x3232);
      sts1(a + T_E - 4 - 128 * z, v); sts16(a + T_O - 4 - 128 * z, v); sts1(a + T_O - 2 - 128 * z, d);
      if (z || lane) { sts1(a + T_E - 128 * z, d); sts16(a + T_O + 2 - 128 * z, d); } else sts16(a + T_E, d);
    }
    const uint32_t w0 = pack2(acc[3][0] + o[1].x, acc[3][1] + o[1].y), w1 = pack2(acc[3][2] + o[1].z, acc[3][3] + o[1].w);
    const uint32_t b = tp - 2 * (16 * t + g);
    if (lane == 0) {
      const uint32_t k = prmt(w0, w0, 0x1010);
      sts1(tp + T_E - 2 * 514, k); sts1(tp + T_E - 2 * 512, k);
      sts16(tp + T_O - 2 * 514, k); sts1(tp + T_O - 2 * 513, k); sts16(tp + T_O - 2 * 511, k);
      sts16(tp + T_C - 2 * 127, pack2(k2048 + o[2].x, 0.f));
    } else { sts16(b + T_E - 2 * (X_5 - 1), w0); sts16(b + T_O - 2 * (X_5 - 1), w0); }
    sts16(b + T_E - 2 * X_3, w0 >> 16); sts16(b + T_O - 2 * X_3, w0 >> 16);
    sts16(b + T_E - 2 * (X_5 + 7), w1); sts16(b + T_O - 2 * (X_5 + 7), w1);
    sts16(b + T_E - 2 * (X_3 + 8), w1 >> 16); sts16(b + T_O - 2 * (X_3 + 8), w1 >> 16);
  }
}

DEV bool bad8(const uint4& v) { return min(v.x, v.z) == 0u; }
DEV uint32_t uchunk(uint32_t reg, int x) { return reg + R_U + (x ^ ((x >> 3) & 3)) * 16; }
DEV uint32_t& xword(uint4 (&x)[2], int e, int tp) { uint4& v = x[tp >> 1]; return tp & 1 ? (e ? v.w : v.z) : (e ? v.y : v.x); }

DEV void uprep(const Params& P, int c, int wa, int lane, int layer, uint4 (&x)[2][2][2], uint32_t (&u)[4][4]) {
  const int j = 32 * wa + lane, o0 = 2 * (j + (j & 64)) + ((j >> 2) & 1);
  {
    const uint32_t za = region(wa) + lane * 16 - 512;
    sts4(za + R_U, 0, 0, 0, 0); sts4(za + R_X5, 0, 0, 0, 0); sts4(za + R_X3, 0, 0, 0, 0);
    sts4(region(wa) + R_BE, 0, 0, 0, 0);
  }
  const uint4* st = opqp(&SCR->SR[layer][c >> 4][j]);
  const uint32_t xa = opq(SM_X + 16 * o0), xb = opq(SM_X + 16 * (o0 ^ 1)), ua = opq(uchunk(0, j));
  uint4 s[2][2];
#pragma unroll
  for (int z = 0; z < 12; ++z) {
    uint4& v = z < 8 ? x[(z >> 2) & 1][(z >> 1) & 1][z & 1] : s[(z >> 1) & 1][z & 1];
    asm volatile("mov.b32 %0,0; mov.b32 %1,0; mov.b32 %2,0; mov.b32 %3,0;" : "=r"(v.x), "=r"(v.y), "=r"(v.z), "=r"(v.w));
  }
#pragma unroll 1
  for (uint32_t it = P.zero;; ++it) {
    if (it) {
      spin_guard(it);
      COUNT(3);
#pragma unroll
      for (int z = 0; z < 4; ++z) { uint4& v = s[z >> 1][z & 1]; ldr4_if(v, st + z * 128, bad8(v)); }
      const uint4* xp = &SCR->XG[layer][c * 1024 + o0];
#pragma unroll
      for (int z = 0; z < 8; ++z) {
        uint4& v = x[z >> 2][(z >> 1) & 1][z & 1];
        ldr4_if(v, (const uint4*)((uintptr_t)xp ^ (16 * (z & 1))) + (z >> 2) * 512 + (z & 2) * 64, bad8(v));
      }
    } else {
      mbar_wait(B_U, layer);
      PROF(layer ? 25 : 10);
#pragma unroll
      for (int z = 0; z < 4; ++z) s[z >> 1][z & 1] = ldr4(st + z * 128);
#pragma unroll
      for (int z = 0; z < 4; ++z) { uint4& v = s[z >> 1][z & 1]; ldr4_if(v, st + z * 128, bad8(v)); }
      PROF(layer ? 26 : 11);
      mbar_wait(B_E, layer);
#pragma unroll
      for (int z = 7; z >= 0; --z) x[z >> 2][(z >> 1) & 1][z & 1] = lds4((z & 1 ? xb : xa) + (z >> 2) * 8192 + (z & 2) * 1024);
      PROF(layer ? 27 : 14);
    }
    uint32_t m = ~0u;
#pragma unroll
    for (int z = 7; z >= 0; --z) {
      const int k = z >> 2, chl = z & 3;
#pragma unroll
      for (int tp = 0; tp < 4; ++tp) u[chl][tp] = hmul2(hsub2(xword(x[k][chl >> 1], chl & 1, tp), xword(s[k], 1, tp)), xword(s[k], 0, tp));
      sts4(ua + region(chl) + k * 2048, u[chl][0], u[chl][1], u[chl][2], u[chl][3]);
      const uint4& v = x[k][chl >> 1][chl & 1];
      m = min(m, min(v.x, v.z));
      if (z < 4) m = min(m, min(s[z >> 1][z & 1].x, s[z >> 1][z & 1].z));
    }
    if (!__any_sync(0xffffffffu, m == 0)) break;
  }
  PROF(4 + 12 * layer);
}

template <bool FULL> DEV void box_unit(uint32_t reg, int s, const uint2& a, const uint4& b, const uint32_t (&d)[4], uint32_t (&pv)[4]) {
  const uint32_t u[9] = {a.x, a.y, b.x, b.y, b.z, b.w, d[0], d[1], d[2]};
  uint32_t v[8], p[8];
#pragma unroll
  for (int j = 0; j < 8; ++j) { v[j] = prmt(u[j], u[j + 1], 0x5432); p[j] = hadd2(u[j], v[j]); }
  uint32_t x[4], y[4], z9[4], z7[4];
#pragma unroll
  for (int j = 0; j < 4; ++j) { x[j] = hadd2(hadd2(p[1 + j], p[2 + j]), u[3 + j]); y[j] = hadd2(v[3 + j], p[4 + j]); pv[j] = p[4 + j]; }
  const uint32_t o = reg + s * 16;
  if (FULL) {
#pragma unroll
    for (int j = 0; j < 4; ++j) { z7[j] = hadd2(hadd2(v[j], v[3 + j]), x[j]); z9[j] = hadd2(hadd2(u[j], u[4 + j]), z7[j]); }
  }
  sts4(o + R_X5, x[0], x[1], x[2], x[3]);
  sts4(o + R_X3, y[0], y[1], y[2], y[3]);
  if (FULL) {
    const bool od = s & 1;
    sts4(o + R_BO, od ? z7[0] : z9[0], od ? z7[1] : z9[1], od ? z7[2] : z9[2], od ? z7[3] : z9[3]);
    sts4(o + R_BE + 16, od ? z9[0] : z7[0], od ? z9[1] : z7[1], od ? z9[2] : z7[2], od ? z9[3] : z7[3]);
  }
}
#define NBB(e) (320 - 32 * (e))
template <int C0, int C1> DEV void box_full(int j, uint32_t (&u)[4][4], uint32_t zero) {
  const uint32_t a2 = uchunk(8, j - 2), a1 = uchunk(0, j - 1);
  uint2 a[4]; uint4 b[4];
#define HALO(n) if (n < C1) { a[(n) & 3] = lds2(region(n) + a2); b[(n) & 3] = lds4(region(n) + a1); }
  HALO(C0) HALO(C0 + 1)
  split(zero);
#pragma unroll
  for (int chl = C0; chl < C1; ++chl) {
    const uint32_t d[4] = {u[chl][0], u[chl][1], u[chl][2], u[chl][3]};
    box_unit<true>(region(chl), j, a[chl], b[chl], d, u[chl]);
    fence_async_smem();
    bar_arrive(NB_B + chl, NBB(chl & 1));
    PROFC(28 + chl);
    if (chl == C0) { HALO(C0 + 2) }
  }
#undef HALO
}
DEV void box_help(int e, int n0, int dn, int lane, int layer) {
  bar_sync(NB_H, 224);
#pragma unroll 1
  for (int n = n0; n < 4; n += dn) {
    if (n == 2 && dn == 1) mbar_watch(B_RD, layer);
    const int chl = e + (n & 2), s = 128 + 32 * (n & 1) + lane;
    const uint32_t reg = region(chl);
    const uint4 d = lds4(uchunk(reg, s));
    const uint32_t u[4] = {d.x, d.y, d.z, d.w};
    uint32_t v[4];
    box_unit<false>(reg, s, lds2(uchunk(reg, s - 2) + 8), lds4(uchunk(reg, s - 1)), u, v);
    if (dn == 2 || (n & 1)) { fence_async_smem(); bar_arrive(NB_B + chl, NBB(e)); PROFC(28 + n); }
  }
}

DEV uint4 hadd8(const uint4& a, const uint4& b) { return make_uint4(hadd2(a.x, b.x), hadd2(a.y, b.y), hadd2(a.z, b.z), hadd2(a.w, b.w)); }
DEV void conv_out(int c, int j, int chl, uint4 (&x)[2][2][2], const uint32_t (&v)[4], uint4* XF, uint32_t zero) {
  const int rho = chl >> 1, e = chl & 1;
  const uint32_t ua = uchunk(region(chl), j), fa = region(chl) + R_X5 + j * 16, ha = region(chl) + R_X3 + (j & 1) * 1088 + (j >> 1) * 16;
  const int m8 = ((j & 4) + ((j >> 1) & 1) + 2 * (j & 1)) ^ ((2 * c + e) & 7);
  uint4* xo = XF + (((16 - 2 * (j & 8) + (j >> 4)) * 512 + 256 * rho + 2 * c + e) * 8 + m8);
  bar_sync(NB_Y + e + 7 * rho, 256);
  uint4 y[2], f[2], h[2];
#pragma unroll
  for (int k = 0; k < 2; ++k) {
    y[k] = lds4(ua + k * 2048);
    f[k] = lds4z(ua + k * 2048 + R_BO - R_U, k || j >= 36);
    h[k] = lds4z(fa + k * 2048 - 1024, k || j >= 64);
  }
  const uint32_t q = lds1(SM_TAP + chl * TAP_SZ + T_K);
  const uint4 r = lds4(ha);
  if (chl == 3) mbar_arrive1(B_L + (r.x & zero));
  h[1] = hadd8(h[1], make_uint4(hfma2(q, v[0], r.x), hfma2(q, v[1], r.y), hfma2(q, v[2], r.z), hfma2(q, v[3], r.w)));
#pragma unroll
  for (int k = 0; k < 2; ++k) {
    const uint4 o = hadd8(hadd8(y[k], hadd8(f[k], h[k])), make_uint4(xword(x[k][rho], e, 0), xword(x[k][rho], e, 1), xword(x[k][rho], e, 2), xword(x[k][rho], e, 3)));
    const uint32_t keep = j & 1 ? 0x7632 : 0x5410, k0 = prmt(o.x, o.y, keep), k1 = prmt(o.z, o.w, keep);
    const uint32_t g0 = __shfl_xor_sync(0xffffffffu, prmt(o.x, o.y, keep ^ 0x2222), 1), g1 = __shfl_xor_sync(0xffffffffu, prmt(o.z, o.w, keep ^ 0x2222), 1);
    str4(xo + k * 32768, j & 1 ? g0 : k0, j & 1 ? g1 : k1, j & 1 ? k0 : g0, j & 1 ? k1 : g1);

  }
  if (e) { __syncwarp(); mbar_arrive1(B_RD + rho * 8); }
  PROFC(40 + chl);
}

DEV void conv_round(int e, int rho, int w, int lane, uint32_t zero) {
  const int g = lane >> 2, t = lane & 3, chl = 2 * rho + e;
  const uint32_t reg = region(chl), tp = SM_TAP + chl * TAP_SZ, dr = dlo(reg, 128);
  const uint32_t g0 = tp + ((g & 1) ? T_O : T_E) + 2 * (2 * t - g) - 16;
  const uint32_t ga = g0 - 32 * (w & 1) - 576 * (w >> 1), id = opq(0x3210u);
  float acc[32], f1[24], f2[16];
  uint32_t q[12][4];
  {
    uint32_t qn[18][4];
    qn[0][2] = lds1(ga + 64);
#pragma unroll
    for (int n = 0; n < 18; ++n) {
      const bool nz = n < 15 || w < 2 || (n == 15 && w == 2);
      qn[n][0] = n < 15 ? lds1(ga + 48 - 32 * n) : lds1z(ga + 48 - 32 * n, nz);
      qn[n][1] = n < 15 ? lds1(ga + 32 - 32 * n) : lds1z(ga + 32 - 32 * n, nz);
    }
#pragma unroll
    for (int n = 0; n < 18; ++n) { qn[n][3] = cpy(qn[n][0], id); if (n) qn[n][2] = cpy(qn[n - 1][1], id); }
#pragma unroll
    for (int n = 0; n < 8; ++n) {
      const int i = n & 3;
      const uint32_t a = g0 + 16 - 16 * w - 2 * (n < 4 ? X_5 : X_3) + 16 * i;
      uint32_t (&q1)[4] = q[(n & 4) + (i >> 1)], (&q2)[4] = q[(n & 4) + 2 + (i >> 1)];
      q1[2 * (i & 1)] = lds1z(a, i <= w); q1[2 * (i & 1) + 1] = lds1(a - 64);
      q2[2 * (i & 1)] = cpy(0, id); q2[2 * (i & 1) + 1] = lds1z(a - 128, i >= w);
    }
    const uint32_t gc = tp + T_C - 2 + 4 * (t - g - 8 * w);
#pragma unroll
    for (int kk = 0; kk < 4; ++kk) {
      q[8 + kk][0] = lds1z(gc + 32 * kk, w >= kk); q[8 + kk][2] = lds1z(gc + 32 * kk + 16, w >= kk);
      q[8 + kk][1] = lds1(gc + 32 * kk - 128); q[8 + kk][3] = lds1(gc + 32 * kk - 112);
    }
    PROFD(rho ? 43 : 47, qn[17][2] ^ q[11][3]);
    bar_sync_if(NB_U, NBARU, 1 - rho);
    mbar_arrive1_if(B_V, chl == 1 && w == 0);
    bar_sync_if(NB_T + 1 - e, 256, chl);
    const uint32_t db = dr + (R_U + 32) / 16;
    undef(acc);
    wg_fence();
#pragma unroll
    for (int n = 0; n < 18; ++n) {
      if (n) wg_rs64k<1>(acc, qn[n], db - 2 * n); else wg_rs64k<0>(acc, qn[0], db);
      if (n == 9) wg_commit();
    }
    wg_commit();
  }
  wg_wait<1>();
  PROFC(rho ? 12 : 2);
  bar_sync(NB_B + chl, NBB(e));
  const uint32_t d1 = dr + R_X5 / 16, d2 = dr + R_BO / 16;
  undef(f1); undef(f2);
  wg_fence();
#pragma unroll
  for (int n = 0; n < 4; ++n) { if (n) wg_rs32t<1>(f2, q[8 + n], d2 + 16 * n); else wg_rs32t<0>(f2, q[8], d2); }
  wg_commit();
#pragma unroll
  for (int n = 0; n < 8; ++n) {
    const uint32_t d = d1 + (n >> 2) * ((R_X3 - R_X5) / 16) + 16 * (n & 1) - 16 * (n & 2);
    if (n) wg_rs48t<1>(f1, q[n], d); else wg_rs48t<0>(f1, q[0], d);
  }
  wg_commit();
  { uint32_t ck; asm volatile("mov.u32 %0,%%clock;" : "=r"(ck) :: "memory"); lane += ck & zero; }
  const int p = (lane + 9 * (w >> 1)) & 31;
  const uint32_t yb = reg + ((w >> 1) ? R_BO : R_U) + p * 64 + (((2 * (w & 1)) ^ ((p >> 1) & 3)) * 16);
  const uint32_t y0 = opq(yb + (p < lane ? 2048 : 0)), y1 = opq(yb + (p < lane ? 0 : 2048));
  const uint32_t fa = opq(reg + R_X5 + (8 * w + (lane & 7)) * 16 + (lane >> 3) * 512);
  const uint32_t ha = opq(reg + R_X3 + (lane < 16 ? 1088 : 0) + (8 * w + (lane & 7) + 4 * (lane & 8)) * 16);
  wg_wait<1>();
  PROFC(rho ? 13 : 3);
  bar_arrive_if(NB_T + e, 256, chl - 3);
  bar_sync(NB_WG + e, 128);
#pragma unroll
  for (int z = 0; z < 4; ++z) {
    const float* a = acc + 16 * (z >> 1) + 2 * (z & 1);
    stsm4t((z >> 1 ? y1 : y0) ^ ((z & 1) * 16), pack2(a[0], a[1]), pack2(a[4], a[5]), pack2(a[8], a[9]), pack2(a[12], a[13]));
  }
  wg_wait<0>();
  PROFC(rho ? 14 : 4);
  bar_sync(NB_WG + e, 128);
  {
    uint32_t h[6];
#pragma unroll
    for (int p = 0; p < 6; ++p) h[p] = p ? pack2(f1[4 * p] + f1[4 * p - 2], f1[4 * p + 1] + f1[4 * p - 1]) : pack2(f1[0], f1[1]);
    stsm4(fa, h[0], h[1], h[2], h[3]);
    stsm2(fa + 2048, h[4], h[5]);
    stsm4(ha, pack2(f2[0], f2[1]), pack2(f2[2] + f2[4], f2[3] + f2[5]), pack2(f2[8], f2[9]), pack2(f2[10] + f2[12], f2[11] + f2[13]));
  }
  bar_arrive(NB_Y + e + 7 * rho, 256);
}
constexpr uint32_t FILL = 0xFFFFFFFFu;
template <int N> DEV void fixo(uint4 (&A)[N], const uint4* p) {
#pragma unroll 1
  for (int it = 0; it < SPIN_LIMIT; ++it) {
    uint32_t m = A[0].x;
#pragma unroll
    for (int k = 1; k < N; ++k) m = max(m, A[k].x);
    if (__all_sync(0xffffffffu, m != FILL)) break;
#pragma unroll
    for (int k = 0; k < N; ++k) ldr4_if(A[k], p + k * 32, A[k].x == FILL);
  }
}
DEV bool rows_nan(float a, float b) {
  return __any_sync(0xffffffffu, a != a || b != b);
}
DEV int res_off(int w, int lane) { return ((lane & 7) + 8 * (lane >> 4)) * 8 + ((2 * (w & 2) + (w & 1) + ((lane >> 2) & 2)) ^ (lane & 7)); }
DEV void res_load(uint32_t (&res)[8][2], uint32_t sa, int w, int lane) {
  const uint32_t a = sa + res_off(w, opq(lane)) * 16;
#pragma unroll
  for (int j = 0; j < 8; j += 2) {
    uint32_t r[4];
    ldsm4t(r, a + j * 1024);
    res[j][0] = r[0]; res[j][1] = r[1]; res[j + 1][0] = r[2]; res[j + 1][1] = r[3];
  }
}

DEV void res_init(float (&ac)[32], const uint32_t (&res)[8][2]) {
#pragma unroll
  for (int j = 0; j < 16; ++j)
    asm volatile("shl.b32 %0,%2,16; and.b32 %1,%2,0xFFFF0000;" : "=&f"(ac[2 * j]), "=f"(ac[2 * j + 1]) : "r"(res[j >> 1][j & 1]));
}
DEV uint32_t after(uint32_t b, const uint32_t (&res)[8][2], uint32_t zero) {
  return b + ((res[0][0] ^ res[2][0] ^ res[4][0] ^ res[6][0]) & zero);
}

DEV void attn_phase(const Params& P, int c, int e, int w, int lane, int layer) {
  lane = opq(lane); c = opq(c);
  const int i = c >> 3, cg = c & 7, J = 16 * e + i, G = 8 * i + 4 - 4 * e + w;
  const int g = lane >> 2, t = lane & 3;
  float acc[96];
  uint32_t res[8][2];
  float2 cs[16];
  float4 st;
  const uint32_t csb = opq(SM_CS + 8 * t);
  {
    const uint32_t sa = SM_A + e * A_E, ba = B_A + 32 * e;
    const uint32_t da = dlo(sa, 8192), db = (SB >> 4) | (512 << 16);
    undef(acc);
#pragma unroll
    for (int j = 0; j < 8; ++j) asm volatile("" : "=r"(res[j][0]), "=r"(res[j][1]));
    mbar_wait(B_WF, layer);
    mbar_wait(ba, 0);
    mbar_wait(B_L, layer);
    bar_sync_if(NB_T, 256, e);
    PROF(24);
#pragma unroll
    for (int j = 0; j < 4; ++j) {
      if (j) mbar_wait(ba + 8 * j, 0);
      if (j == 1) PROFK(layer ? 39 : 15);
      wg_fence();
#pragma unroll
      for (int k = 0; k < 4; ++k) {
        if (j | k) wg_ss192<1>(acc, da + j * 512 + k * 128, db + wslot(j) * 512 + k * 128); else wg_ss192<0>(acc, da, db);
        if (j == 3 && k == 1) wg_commit();
      }
      wg_commit();
      if (j == 1 && cg < 4) { mbar_wait(ba + 8 * cg, 0); res_load(res, sa + cg * 8192, w, lane); }
      if (j == 2) { wg_wait<2>(); mbar_arrive1_if(B_F, e); }
      if (j == 3) { wg_wait<3>(); mbar_arrive1_if(B_F + 8, e); }
    }
    wg_wait<1>();
    bar_arrive(NB_T + e, 256);
    wg_wait<0>();
    mbar_arrive1(after(B_AE + 8 * e, res, P.zero));
    PROF(25);
#pragma unroll 1
    for (uint32_t late = P.zero;; late = 1) {
      if (late) {
        const int ln = lane_id() + (late & P.zero), g = ln >> 2, t = ln & 3;
        const uint32_t* xr = (const uint32_t*)SCR->XF[layer] + (J * 16384 + g * 32 + t);
        const uint32_t* wr = (const uint32_t*)P.wqkv + (g * 768 + 32 * cg + t);
        COUNT(0);
        zero(acc);
#pragma unroll 1
        for (int k = 0; k < 32; ++k) {
          uint32_t a[4];
#pragma unroll 1
          for (int it = 0; it < SPIN_LIMIT; ++it) {
#pragma unroll
            for (int z = 0; z < 4; ++z) a[z] = ldr1(xr + k * 512 + (z >> 1) * 256 + ((2 * w + (z & 1)) ^ g) * 4);
            if (__all_sync(0xffffffffu, max(max(a[0], a[1]), max(a[2], a[3])) != FILL)) break;
          }
#pragma unroll
          for (int z = 0; z < 4; ++z) a[z] = movm(a[z]);
#pragma unroll
          for (int j = 0; j < 24; ++j) {
            const uint32_t* q = wr + k * 12288 + (j >> 3) * 256 + 4 * (j & 7);
            mma16(*(float(*)[4])(acc + 4 * j), a[0], a[1], a[2], a[3], movm(ldw1(q)), movm(ldw1(q + 6144)));
          }
        }
        const uint32_t* q = xr + 64 * cg * 32;
        const int m8 = (2 * (w & 2) + (w & 1)) ^ g;
#pragma unroll 1
        for (int it = 0; it < SPIN_LIMIT; ++it) {
          uint32_t m = 0;
#pragma unroll
          for (int z = 0; z < 16; ++z) { const uint32_t x = ldr1(q + (z >> 1) * 256 + (m8 ^ (2 * (z & 1))) * 4); m = max(m, x); res[z >> 1][z & 1] = movm(x); }
          if (__all_sync(0xffffffffu, m != FILL)) break;
        }
#pragma unroll
        for (int z = 0; z < 16; ++z) cs[z] = lds2f(csb + 256 + z * 32);
      } else {
        mbar_wait(B_CS, 0);
#pragma unroll
        for (int z = 0; z < 16; ++z) cs[z] = lds2f(csb + 256 + z * 32);
        mbar_wait(B_W4, layer);
        mbar_wait(ba, 1);
        bar_sync(NB_T + 1 - e, 256);
        PROF(26);
#pragma unroll
        for (int j = 4; j < 8; ++j) {
          if (j > 4) mbar_wait(ba + 8 * (j - 4), 1);
          if (j >= 6) mbar_wait(B_W6 + 8 * (j - 6), layer);
          if (j > 4) PROF(31 + j);
          wg_fence();
#pragma unroll
          for (int k = 0; k < 4; ++k) {
            wg_ss192<1>(acc, da + (j & 3) * 512 + k * 128, db + wslot(j) * 512 + k * 128);
            if (j == 7 && k == 0) wg_commit();
          }
          wg_commit();
          if (j == 5 && cg >= 4) { mbar_wait(ba + 8 * (cg - 4), 1); res_load(res, sa + (cg - 4) * 8192, w, lane); }
          if (j == 6) { wg_wait<2>(); mbar_arrive1_if(B_F + 16, e); PROF(40); }

        }
      }
      uint32_t rs = hadd2(res[0][0], res[0][1]);
#pragma unroll
      for (int z = 2; z < 16; ++z) rs = hadd2(rs, res[z >> 1][z & 1]);
      const float rn = bflo(rs) + bfhi(rs);
      wg_wait<1>();
      bar_arrive_if(NB_T, 256, !(e | late));
      mbar_wait(B_ST + 8 * e, layer);
      st = lds4f(SM_STAT + ((4 * e + w) * 8 + g) * 16);
      PROF(34 + layer);
      wg_wait<0>();
      if (!rows_nan(acc[0] + rn, acc[2]) || late) break;
    }
  }
  mbar_arrive1(B_QE);
  PROFK(8 + 12 * layer);
  uint32_t Q[4][4], K[4][2][2], V[4][2][2];
  {
#pragma unroll
    for (int z = 0; z < 8; ++z) {
      const float* a = acc + 32 + 4 * z; const float* b = acc + 64 + 4 * z;
      K[z >> 1][1][z & 1] = pack2((a[2] - st.z * cs[z].x) * st.w, (a[3] - st.z * cs[z].y) * st.w);
      V[z >> 1][1][z & 1] = movm(pack2((b[2] - st.z * cs[8 + z].x) * st.w, (b[3] - st.z * cs[8 + z].y) * st.w));
    }
    const int hop = (G >> 1) & 3;
    const uint32_t kv = SM_KV + (2 * hop + (w & 1)) * 2048 + lane * 16;
    uint4* h = SCR->H[layer] + (c * 256 + (w & 1) * 128 + lane);
    if (hop == 3) {
#pragma unroll
      for (int z = 0; z < 4; ++z) str4(h + 2048 + z * 32, K[z][1][0], K[z][1][1], V[z][1][0], V[z][1][1]);
    } else {
      mbar_wait(B_F + 16, layer);
#pragma unroll
      for (int z = 0; z < 4; ++z) sts4(kv + z * 512, K[z][1][0], K[z][1][1], V[z][1][0], V[z][1][1]);
      bar_arrive(NB_B + hop, 128);
    }
    PROF(42);
    uint4 hv[4];
#pragma unroll
    for (int z = 0; z < 4; ++z) { hv[z] = make_uint4(0, 0, 0, 0); ldr4_if(hv[z], h + z * 32, G >= 2 && hop == 0); }
#pragma unroll
    for (int z = 0; z < 8; ++z) {
      const float* a = acc + 32 + 4 * z; const float* b = acc + 64 + 4 * z;
      K[z >> 1][0][z & 1] = pack2((a[0] - st.x * cs[z].x) * st.y, (a[1] - st.x * cs[z].y) * st.y);
      V[z >> 1][0][z & 1] = movm(pack2((b[0] - st.x * cs[8 + z].x) * st.y, (b[1] - st.x * cs[8 + z].y) * st.y));
    }
#pragma unroll
    for (int z = 0; z < 8; ++z) {
      const float2 cq = lds2f(csb + z * 32);
      const float* a = acc + 4 * z;
      Q[z >> 1][2 * (z & 1)] = pack2(a[0] - st.x * cq.x, a[1] - st.x * cq.y);
      Q[z >> 1][2 * (z & 1) + 1] = pack2(a[2] - st.z * cq.x, a[3] - st.z * cq.y);
    }
    PROF(27);
    const bool p0 = 2 * t > g, p1 = 2 * t + 1 > g, first = G < 2;
    float s[4][4], mx[4][2];
#pragma unroll
    for (int z = 0; z < 4; ++z) {
      float S[4];
      mma16z(s[z], Q[z][0], Q[z][1], Q[z][2], Q[z][3], K[z][0][0], K[z][0][1]);
      mma16z(S, Q[z][0], Q[z][1], Q[z][2], Q[z][3], K[z][1][0], K[z][1][1]);
      s[z][2] = p0 ? s[z][2] : S[2]; s[z][3] = p1 ? s[z][3] : S[3];
    }
    const float sc0 = st.y * (0.25f * 1.4426950408889634f), sc1 = st.w * (0.25f * 1.4426950408889634f);
    uint32_t pw[4][2];
#pragma unroll
    for (int r = 1; r >= 0; --r) {
      if (r == 0) {
        if (hop) {
          bar_sync(NB_B + hop - 1, 128);
#pragma unroll
          for (int z = 0; z < 4; ++z) hv[z] = lds4(kv - 4096 + z * 512);
        } else fixo(hv, h);
        PROFD(41, hv[3].x);
#pragma unroll
        for (int z = 0; z < 4; ++z) {
          float S[4];
          mma16z(S, Q[z][0], Q[z][1], Q[z][2], Q[z][3], hv[z].x, hv[z].y);
          if (first) S[0] = S[1] = __uint_as_float(0xFF800000u);
          s[z][0] = p0 ? S[0] : s[z][0]; s[z][1] = p1 ? S[1] : s[z][1];
        }
      }
#pragma unroll
      for (int z = 0; z < 4; ++z) mx[z][r] = fmaxf(s[z][2 * r], s[z][2 * r + 1]);
#pragma unroll
      for (int o = 1; o < 3; ++o)
#pragma unroll
        for (int z = 0; z < 4; ++z) mx[z][r] = fmaxf(mx[z][r], __shfl_xor_sync(0xffffffffu, mx[z][r], o));
#pragma unroll
      for (int z = 0; z < 4; ++z) pw[z][r] = pack2(ex2((s[z][2 * r] - mx[z][r]) * (r ? sc1 : sc0)), ex2((s[z][2 * r + 1] - mx[z][r]) * (r ? sc1 : sc0)));
    }
    mbar_wait(layer ? B_N : B_Z, 1);
    const uint32_t M = (p0 ? 0xFFFFu : 0u) | (p1 ? 0xFFFF0000u : 0u);
    uint4* O = SCR->O + ((J * 8 + cg) * 512 + (2 * (w & 2) + (w & 1)) * 64 + t * 8 + g);
#pragma unroll
    for (int h2 = 0; h2 < 2; ++h2) {
      uint32_t ow[2][4];
#pragma unroll
      for (int z = 0; z < 2; ++z) {
        const int n = 2 * h2 + z;
        const uint32_t w0 = pw[n][0], w1 = pw[n][1];
        float sm[4] = {0.f, 0.f, 0.f, 0.f}, Oa[2][4];
        mma8(sm, w0, w1, 0x3F803F80u);
        mma16z(Oa[0], w0 & ~M, w1 & M, 0u, w1 & ~M, V[n][0][0], V[n][1][0]); mma8(Oa[0], w0 & M, 0u, hv[n].z);
        mma16z(Oa[1], w0 & ~M, w1 & M, 0u, w1 & ~M, V[n][0][1], V[n][1][1]); mma8(Oa[1], w0 & M, 0u, hv[n].w);
        const float i0 = rcp(sm[0]), i1 = rcp(sm[2]);
#pragma unroll
        for (int d = 0; d < 2; ++d) { ow[0][2 * z + d] = pack2(Oa[d][0] * i0, Oa[d][1] * i0); ow[1][2 * z + d] = pack2(Oa[d][2] * i1, Oa[d][3] * i1); }
      }
#pragma unroll
      for (int hi = 0; hi < 2; ++hi) str4(O + hi * 128 + h2 * 32, ow[hi][0], ow[hi][1], ow[hi][2], ow[hi][3]);
    }
  }
  str1(SCR->OF[layer] + (J * 32 + cg * 4 + w), 1);
  mbar_arrive1(B_AT + 8 * e);
  PROFK(9 + 12 * layer);
  float ac[32];
  const uint32_t so = SM_O + e * O_E;
  uint2* xo = opqp(layer ? (uint2*)(P.out + ((16 * G + 2 * (lane >> 3)) * 512 + 64 * cg + 8 * (lane & 7)))
                         : (uint2*)SCR->XG[1] + ((32 * (cg & 3) + t) * 2048 + (cg >> 2) * 256 + xg_off(G, g)));
  const uint32_t stg = SM_X + (4 * e + w) * 2048;
  const uint32_t sw = opq(stg + (lane & 15) * 128 + (((lane >> 4) ^ (lane & 7)) * 16)), sr = opq(stg + (lane >> 3) * 128 + (((lane & 7) ^ (lane >> 3)) * 16));
  uint4* ps = opqp(&SCR->PS[(G * 8 + cg) * 8 + g]);
  {
    const uint32_t bo = B_O + 32 * e;
    const uint32_t dw = (SM_WO >> 4) | (512 << 16), da = dlo(so, 512);
    mbar_wait(B_WO, layer);
    res_init(ac, res);
    mbar_wait(B_AT + 8 + (((uint32_t)((uintptr_t)xo >> 16) ^ (uint32_t)((uintptr_t)ps >> 16) ^ sw ^ sr) & P.zero), layer);
#pragma unroll
    for (int j = 0; j < 4; ++j) {
      mbar_wait(bo + 8 * j, layer);
      if (j == 0) PROFK(32 + layer);
      wg_fence();
#pragma unroll
      for (int k = 8 * j; k < 8 * j + 8; ++k) {
        const uint32_t a = da + (k >> 2) * 512 + (k & 3) * 8, b = dw + (k & 3) * 1024 + (k >> 2) * 128;
        wg_ss64<1>(ac, a, b);
      }
      wg_commit();
    }
#pragma unroll 1
    for (uint32_t late = P.zero;; late = 1) {
      if (late) {
        const int ln = lane_id() + (late & P.zero);
        const uint32_t* op = (const uint32_t*)(SCR->O + (J * 4096 + w * 128)) + ln;
        wg_wait<0>();
        COUNT(1);
        res_init(ac, res);
#pragma unroll 1
        for (int k = 0; k < 32; ++k) {
          uint32_t a[4];
#pragma unroll 1
          for (int it = 0; it < SPIN_LIMIT; ++it) {
#pragma unroll
            for (int z = 0; z < 4; ++z) a[z] = ldr1(op + (k >> 2) * 2048 + (k & 3) * 32 + (z & 1) * 256 + (z >> 1) * 128);
            if (__all_sync(0xffffffffu, max(max(a[0], a[1]), max(a[2], a[3])) != FILL)) break;
          }
#pragma unroll
          for (int j = 0; j < 8; j += 2) {
            uint32_t b[4];
            ldsm4t(b, SM_WO + (k & 3) * 16384 + (k >> 2) * 2048 + (ln & 15) * 128 + (((j + (ln >> 4)) ^ (ln & 7)) * 16));
            mma16(*(float(*)[4])(ac + 4 * j), a[0], a[1], a[2], a[3], b[0], b[1]);
            mma16(*(float(*)[4])(ac + 4 * j + 4), a[0], a[1], a[2], a[3], b[2], b[3]);
          }
        }
      }
      wg_wait<0>();
      if (!rows_nan(ac[0], ac[2]) || late) break;
    }
  }
  PROFK(10 + 12 * layer);
#pragma unroll
  for (int j = 0; j < 16; ++j) res[j >> 1][j & 1] = pack2(ac[2 * j], ac[2 * j + 1]);
  if (layer == 0) {
    float s[2][4], q0[2][4], q1[2][4];
#pragma unroll
    for (int j = 0; j < 2; ++j) gram<true>(s[j], q0[j], q1[j], res[2 * j][0], res[2 * j][1], res[2 * j + 1][0], res[2 * j + 1][1]);
#pragma unroll
    for (int j = 0; j < 2; ++j) gram<false>(s[j], q0[j], q1[j], res[2 * j + 4][0], res[2 * j + 4][1], res[2 * j + 5][0], res[2 * j + 5][1]);
    const bool od = g & 1;
    str4_if(ps, nzmap(__float_as_uint(s[0][0] + s[1][0])), __float_as_uint(od ? q0[0][1] + q0[1][1] : q0[0][0] + q0[1][0]),
            __float_as_uint(s[0][2] + s[1][2]), __float_as_uint(od ? q1[0][3] + q1[1][3] : q1[0][2] + q1[1][2]), t == (g >> 1));
#pragma unroll
    for (int j = 0; j < 8; ++j) {
      str2(xo + j * 8192, nzmap(prmt(res[j][0], res[j][1], 0x5410)), prmt(res[j][0], res[j][1], 0x7632));
    }
    mbar_arrive1(B_ED + 8 * e);
  } else {
#pragma unroll
    for (int j = 0; j < 8; j += 2) stsm4(sw ^ (j * 16), res[j][0], res[j][1], res[j + 1][0], res[j + 1][1]);
    __syncwarp();
    uint4 v[4];
#pragma unroll
    for (int k = 0; k < 4; ++k) v[k] = lds4((sr ^ ((k & 1) * 64)) + k * 512);
#pragma unroll
    for (int k = 0; k < 4; ++k) stw4(xo + ((k & 1) * 8 + (k >> 1)) * 128, v[k].x, v[k].y, v[k].z, v[k].w);
  }
  PROFK(11 + 12 * layer);
}

DEV void col_sums(const Params& P, int c, int wa, int lane) {
  const int i = c >> 3, cg = c & 7;
  uint4 wv[8];
#pragma unroll
  for (int k = 0; k < 8; ++k) wv[k] = ldnc4(P.wqkv + ((32 * i + (lane >> 3)) * 1536 + wa * 512 + 64 * cg + 8 * (lane & 7)) + 4 * k * 1536);
  float cs[8];
  zero(cs);
#pragma unroll
  for (int k = 0; k < 8; ++k) {
    cs[0] += bflo(wv[k].x); cs[1] += bfhi(wv[k].x); cs[2] += bflo(wv[k].y); cs[3] += bfhi(wv[k].y);
    cs[4] += bflo(wv[k].z); cs[5] += bfhi(wv[k].z); cs[6] += bflo(wv[k].w); cs[7] += bfhi(wv[k].w);
  }
  const bool b4 = lane & 16, b3 = lane & 8;
#pragma unroll
  for (int k = 0; k < 4; ++k) cs[k] = (b4 ? cs[k + 4] : cs[k]) + __shfl_xor_sync(0xffffffffu, b4 ? cs[k] : cs[k + 4], 16);
#pragma unroll
  for (int k = 0; k < 2; ++k) cs[k] = (b3 ? cs[k + 2] : cs[k]) + __shfl_xor_sync(0xffffffffu, b3 ? cs[k] : cs[k + 2], 8);
  str2((uint2*)SCR->CS + (i * 768 + wa * 256 + 32 * cg + 4 * (lane & 7) + (lane >> 3)), nzmap(__float_as_uint(cs[0])), __float_as_uint(cs[1]));
}
DEV void col_gather(const Params& P, int c, int wa, int lane) {
  const uint2* p = (const uint2*)SCR->CS + (wa * 256 + 32 * (c & 7) + lane);
#pragma unroll 1
  for (int it = 0;; ++it) {
    float a = 0.f, b = 0.f;
    uint32_t m = ~0u;
#pragma unroll
    for (int k = 0; k < 16; ++k) { const uint2 q = ldr2(p + k * 768); m = min(m, q.x); a += __uint_as_float(q.x); b += __uint_as_float(q.y); }
    if (__all_sync(0xffffffffu, m != 0u)) { sts2f(SM_CS + wa * 256 + lane * 8, a, b); break; }
    spin_guard(it);
  }
  __syncwarp();
  mbar_arrive1(B_CS);
}

DEV void aux_prologue(const Params& P, int c, int wa, int lane) {
  const int g = lane >> 2, t = lane & 3, G = stat_group(c);
  {
    uint32_t w[16][2];
    const uint16_t* row = P.x0 + ((16 * G + 2 * g) * 512 + 128 * wa + 8 * t);
    bar_sync(NB_Y, 384);
#pragma unroll
    for (int z = 0; z < 8; ++z) {
      const uint4 v = ldw4(row + (z & 1) * 512 + (z >> 1) * 32);
      const int o = 4 * (z >> 1);
      w[o][z & 1] = v.x; w[o + 1][z & 1] = v.y; w[o + 2][z & 1] = v.z; w[o + 3][z & 1] = v.w;
    }
    PROF(34);
    PROFD(35, w[0][0]);
    PROFD(36, w[15][1]);
    uint2* xo = (uint2*)SCR->XG[0] + ((64 * (wa & 1) + 4 * t) * 2048 + (wa >> 1) * 256 + xg_off(G, g));
#pragma unroll
    for (int n = 0; n < 16; ++n) str2(xo + (16 * (n >> 2) + (n & 3)) * 2048, nzmap(prmt(w[n][0], w[n][1], 0x5410)), prmt(w[n][0], w[n][1], 0x7632));
    float s[2][4], q0[2][4], q1[2][4];
#pragma unroll
    for (int z = 0; z < 8; ++z) {
      const int o = 4 * (z >> 1), r = z & 1;
      if (z < 2) gram<true>(s[r], q0[r], q1[r], w[o][r], w[o + 1][r], w[o + 2][r], w[o + 3][r]);
      else gram<false>(s[r], q0[r], q1[r], w[o][r], w[o + 1][r], w[o + 2][r], w[o + 3][r]);
    }
    const bool od = g & 1;
    if (t == (g >> 1))
      sts4f(SM_STAT + (wa * 8 + g) * 16, s[0][0] + s[0][2], od ? q0[0][1] + q1[0][3] : q0[0][0] + q1[0][2],
            s[1][0] + s[1][2], od ? q0[1][1] + q1[1][3] : q0[1][0] + q1[1][2]);
    bar_arrive(NB_P0, 192);
  }
  PROF(2);
  if (lane == 0)
    asm volatile("cp.async.bulk.prefetch.L2.global [%0],4096;" :: "l"(wa < 3 ? P.wqkv + (3 * c + wa) * 2048 : P.wo + c * 2048) : "memory");
  bar_sync(NB_Y + 1, 256);
  mbar_wait(B_Z, 0);
}

DEV void stat_part(const Params& P, int c, int wa, int lane, int layer, int h, float (&v)[2]) {
  lane = opq(lane);
  const int e = wa >> 1;
  uint32_t x[4][4];
  mbar_wait(B_A + 16 * wa, h); mbar_wait(B_A + 16 * wa + 8, h);
  if (h == 0) mbar_wait(B_A + 32 * e + 24, 0);
#pragma unroll
  for (int k = 0; k < 4; ++k) ldsm4t(x[k], SM_A + e * A_E + (128 * (wa & 1) + lane) * 128 + (((c ^ lane) & 7) * 16) + k * 4096);
  float s[4] = {0.f, 0.f, 0.f, 0.f};
#pragma unroll
  for (int k = 0; k < 16; ++k) { const float a = bflo(x[k >> 2][k & 3]), b = bfhi(x[k >> 2][k & 3]); s[0] += a; s[1] += a * a; s[2] += b; s[3] += b * b; }
  s[0] += s[2]; s[1] += s[3];
  if (RARE(rows_nan(s[1], s[1]))) {
    const uint16_t* q = (const uint16_t*)(SCR->XF[layer] + ((32 * e + 2 * (c >> 3) + h) * 2048 + (wa & 1) * 1024)) + (lane >> 2);
    COUNT(2);
    s[0] = s[1] = 0.f;
#pragma unroll 1
    for (int k = 0; k < 32; ++k) {
      const int r = 2 * (lane & 3) + (k & 1);
      const float a = ldnan(q + ((k >> 1) * 8 + r) * 64 + ((c ^ r) & 7) * 8);
      s[0] += a; s[1] += a * a;
    }
  }
  v[0] += s[0]; v[1] += s[1];
  __syncwarp();
}
DEV void stat_finish(const Params& P, int c, int wa, int lane, int layer, float (&v)[2]) {
  lane = opq(lane);
  const bool b = lane & 1;
  const float s = (b ? v[1] : v[0]) + __shfl_xor_sync(0xffffffffu, b ? v[0] : v[1], 1);
  str1((uint32_t*)SCR->ST[layer] + ((128 * (wa >> 1) + c) * 64 + (wa & 1) * 32 + lane), nzmap(__float_as_uint(s)));
  const uint4* sp = SCR->ST[layer] + ((128 * (wa >> 1) + (c & ~7) + 4 * (wa & 1) + (lane >> 3)) * 16 + (lane & 7));
  uint4 x, y;
  for (int it = 0;; ++it) {
    x = ldr4(sp); y = ldr4(sp + 8);
    if (__all_sync(0xffffffffu, min(min(min(x.x, x.y), min(x.z, x.w)), min(min(y.x, y.y), min(y.z, y.w))) != 0u)) break;
    spin_guard(it);
  }
  const uint32_t q = ln_sums((__uint_as_float(x.x) + __uint_as_float(x.z)) + (__uint_as_float(y.x) + __uint_as_float(y.z)),
                             (__uint_as_float(x.y) + __uint_as_float(x.w)) + (__uint_as_float(y.y) + __uint_as_float(y.w)));
  sts2f(SM_STAT + (16 * wa + (lane >> 4) * 8 + (lane & 7)) * 16 + (lane & 8), bflo(q), rcp(bfhi(q)));
  __syncwarp();
  mbar_arrive1(B_ST + 4 * (wa & 2));
}

DEV void nan_source(uint32_t a, int lane) {
#pragma unroll
  for (int k = 0; k < 4; ++k) sts4(a + k * 512 + lane * 16, FILL, FILL, FILL, FILL);
  fence_async_smem();
  __syncwarp();
}
__global__ void __launch_bounds__(NTHR, 1)
fused_kernel(const __grid_constant__ Params P, const __grid_constant__ CUtensorMap mapW, const __grid_constant__ CUtensorMap mapWo,
             const __grid_constant__ CUtensorMap mapX) {
  extern __shared__ __align__(1024) uint8_t smem_raw[];
  const int warp = __shfl_sync(0xffffffffu, threadIdx.x >> 5, 0), lane = threadIdx.x & 31;
  uint32_t smid; asm volatile("mov.u32 %0,%%smid;" : "=r"(smid));
  const uint32_t* pw = (const uint32_t*)&P + threadIdx.y;
  const int role = P.role[(smid >> 1) + threadIdx.y] + (smid & 1) + (pw[0] & pw[12]);
  const int c = __shfl_sync(0xffffffffu, pw[1] ? role : blockIdx.x, 0);
  if (c >= 128) {
#pragma unroll 1
    for (int k = (c - 128) * NTHR + threadIdx.x; k < 131072; k += P.spare * NTHR) str4(SCR->XG[1] + k, 0, 0, 0, 0);
    __threadfence();
    __syncthreads();
    if (warp == 0) { poll(SCR->C + 1 + (lane & 3) * 32, 32); cnt_add1(SCR->C + 6); }
    __syncthreads();
#pragma unroll 1
    for (int k = (c - 128) * NTHR + threadIdx.x; k < 131072; k += P.spare * NTHR) str4(SCR->XG[0] + k, 0, 0, 0, 0);
    return;
  }
#define DONE() do {} while (0)
  const int cg = c & 7;
  if (warp < 8) {
    PROF(46);
    kgen(P, c, warp, lane);
    PROFK(1);
    bar_sync(0, 384);
#pragma unroll 1
    for (int layer = 0; layer < 2; ++layer) {
#pragma unroll 1
      for (int rho = 0; rho < 2; ++rho) {
        const int wz = warp + ((rho + layer) & P.zero);
        conv_round(wz >> 2, rho, wz & 3, lane_id(), P.zero);
        PROFK(6 + rho + 12 * layer);
      }
      const int z = layer & P.zero;
      attn_phase(P, c + z, (warp + z) >> 2, (warp + z) & 3, lane_id(), layer);
    }
    DONE();
  } else if (warp < 12) {
    asm volatile("setmaxnreg.dec.sync.aligned.u32 %0;" :: "n"(REG_AUX));
    aux_prologue(P, c, warp - 8, lane);
    PROF(1);
    const int c0 = c;
#pragma unroll 1
    for (int layer = 0;; ++layer) {
      const int c = c0 + (layer & P.zero), wa = warp - 8 + (layer & P.zero);
#define lane lane_id()
#define j (32 * wa + lane_id())
      uint4 x[2][2][2];
      uint32_t u[4][4];
      uprep(P, c, wa, lane, layer, x, u);
      fence_async_smem();
      bar_arrive(NB_U, NBARU);
      PROFK(5 + 12 * layer);
      bar_sync(NB_H, 224);
      box_full<0, 3>(j, u, P.zero);
      PROF(3 + 12 * layer);
      conv_out(c, j, 0, x, u[0], SCR->XF[layer], P.zero);
      PROF(32);
      conv_out(c, j, 1, x, u[1], SCR->XF[layer], P.zero);
      box_full<3, 4>(j, u, P.zero);
      PROF(6 + 12 * layer);
      if (layer == 0 && wa < 3) col_sums(P, c, wa, lane);
      conv_out(c, j, 2, x, u[2], SCR->XF[layer], P.zero);
      PROF(33);
      conv_out(c, j, 3, x, u[3], SCR->XF[layer], P.zero);
      PROFK(7 + 12 * layer);
      float v[2];
      zero(v);
#pragma unroll 1
      for (int h = 0; h < 2; ++h) {
        stat_part(P, c, wa, lane, layer, h, v);
        if (h) break;
        mbar_arrive1(B_AE + 4 * (wa & 2));
        if (layer == 0 && wa < 3) col_gather(P, c, wa, lane);
      }
      PROF(9 + 12 * layer);
      stat_finish(P, c, wa, lane, layer, v);
      PROF(8 + 12 * layer);
      if (layer) break;
      mbar_wait(B_ED, 0); mbar_wait(B_ED + 8, 0);
#undef lane
#undef j
    }
    DONE();
  } else {
    asm volatile("setmaxnreg.dec.sync.aligned.u32 %0;" :: "n"(REG_PROD));
    if (s2u(smem_raw) != SB) __trap();
#pragma unroll 1
    for (int n = warp - 12; n < 42; n += 4)
      asm volatile("{.reg .pred p; elect.sync _|p,0xffffffff; @p mbarrier.init.shared::cta.b64 [%0],%1;}"
                   :: "r"(SM_BAR + n * 8), "r"(n == 33 ? 4 : n > 14 ? 1 : (int)(0x322866444444444ull >> (4 * n)) & 15) : "memory");
    fence_async_smem();
    bar_sync(NB_AUX, 128);
    bar_arrive(0, 384); bar_arrive(NB_Y + 1, 256);
    PROF(1);
    if (warp == 12) {
      if (lane == 0) {
        asm volatile("prefetch.tensormap [%0];" :: "l"(&mapW) : "memory");
        asm volatile("prefetch.tensormap [%0];" :: "l"(&mapWo) : "memory");
        asm volatile("prefetch.tensormap [%0];" :: "l"(&mapX) : "memory");
      }
      nan_source(slot(12), lane);
#pragma unroll 1
      for (int k = 0; k < 8; ++k) tma2_store(&mapX, slot(12), 128 * c, 8 * k);
      bulk_wait();
      __threadfence();
      mbar_arrive1(B_Z);
      mbar_wait(B_E, 0);
#pragma unroll 1
      for (int k = 0; k < 4; ++k) bulk_store(SCR->H[k >> 1] + ((c + 8) * 256 + (k & 1) * 128), slot(12), 2048);
#pragma unroll 1
      for (int k = 0; k < 8; ++k) bulk_store(SCR->O + (c * 512 + (k >> 2) * 65536 + (k & 3) * 128), slot(12), 2048);
      bulk_wait();
      PROF(24);
#pragma unroll 1
      for (int layer = 0; layer < 2; ++layer) {
        mbar_wait(B_V, layer);
        if (layer == 1 && c < 4 && ((0x47 >> lane) & 1)) str1(SCR->C + c * 32 + lane, 0);
        mbar_expect1(B_WF, 4 * 24576);
#pragma unroll
        for (int k = 0; k < 4; ++k) tma3(slot(wslot(k)), &mapW, 64 * cg, 64 * k, 0, B_WF);
        if (layer == 0) { __threadfence(); mbar_arrive1(B_Z); }
        mbar_wait(B_WF, layer);
        mbar_expect1(B_W4, 2 * 24576);
#pragma unroll
        for (int k = 4; k < 6; ++k) tma3(slot(wslot(k)), &mapW, 64 * cg, 64 * k, 0, B_W4);
        bar_sync(NB_AUX, 64);
#pragma unroll 1
        for (int k = 0; k < 2; ++k) {
          mbar_expect1(B_W6 + 8 * k, 24576);
          mbar_wait(B_F + 8 * k, layer);
          tma3(slot(3 * k), &mapW, 64 * cg, 384 + 64 * k, 0, B_W6 + 8 * k);
        }
        mbar_expect1(B_WO, 65536);
        mbar_wait(B_AE + 8, layer);
        nan_source(slot(12), lane);
        uint4* fp = layer ? SCR->O + c * 512 : SCR->XF[1] + c * 512;
#pragma unroll 1
        for (int r = 7; r >= 0; --r) {
          __nanosleep(30);
          if (r >= 4) {
            bulk_store(fp + (r & 3) * 128, slot(12), 2048); bulk_store(fp + 65536 + (r & 3) * 128, slot(12), 2048);
          }
          if (r == 3) { bulk_wait(); __threadfence(); mbar_arrive1(B_N); PROF(9 + 12 * layer); }
          if (r == 1) mbar_wait(B_F + 16, layer);
          tma4(SM_WO + r * 8192, &mapWo, 64 * cg, 0, r >> 1, 32 * (r & 1), B_WO);
        }
        PROF(8 + 12 * layer);
      }
      DONE();
    } else if (warp == 13) {
      const int G = stat_group(c);
#pragma unroll 1
      for (int layer = 0; layer < 2; ++layer) {
        float z[4];
        uint2* so = opqp((uint2*)&SCR->SR[layer][lane >> 3][sr_off(G, lane)] + (lane & 1));
        if (layer == 0) {
          bar_sync(NB_P0, 192);
          const float4 a = lds4f(SM_STAT + lane * 16);
          z[0] = a.x; z[1] = a.y; z[2] = a.z; z[3] = a.w;
        } else {
          mbar_wait(B_ED + 2 * (c & 4), 0);
          uint4* ps = &SCR->PS[G * 64 + lane];
          uint4 a, b;
          for (int it = 0;; ++it) {
            a = ldr4(ps); b = ldr4(ps + 32);
            if (__all_sync(0xffffffffu, min(a.x, b.x) != 0u)) break;
            spin_guard(it);
          }
          z[0] = __uint_as_float(a.x) + __uint_as_float(b.x); z[1] = __uint_as_float(a.y) + __uint_as_float(b.y);
          z[2] = __uint_as_float(a.z) + __uint_as_float(b.z); z[3] = __uint_as_float(a.w) + __uint_as_float(b.w);
        }
#pragma unroll
        for (int o = 8; o < 32; o <<= 1)
#pragma unroll
          for (int k = 0; k < 4; ++k) z[k] += __shfl_xor_sync(0xffffffffu, z[k], o);
        const uint32_t w0 = ln_sums(z[0], z[1]), w1 = ln_sums(z[2], z[3]);
        const uint32_t r = nzmap(pack2(rcp(bfhi(w0)), rcp(bfhi(w1)))), m = prmt(w0, w1, 0x5410);
        str2(so, r, m); str2(so + 4 * 1024, r, m);
        PROF(4 + 12 * layer);
        box_help(0, 0, 2, lane, layer);
        PROF(6 + 12 * layer);
      }
      DONE();
    } else if (warp == 14) {
#pragma unroll 1
      for (int layer = 0; layer < 2; ++layer) {
        uint32_t* ca = opqp(SCR->C + (c >> 5) * 32 + 3 * layer);
        const uint32_t* cw = opqp(SCR->C + (lane & 3) * 32 + 3 * layer);
        const uint4* xg = opqp(SCR->XG[layer] + c * 1024);
        mbar_expect1(B_E, 16384);
        if (layer) { mbar_wait(B_N, 0); mbar_wait(B_ED, 0); mbar_wait(B_ED + 8, 0); } else bar_sync(NB_P0, 192);
        cnt_add1(ca);
        PROF(4 + 12 * layer);
#pragma unroll 1
        for (uint32_t it = 0, todo = 15; todo; ++it) {
          spin_guard(it);
          const uint32_t m = __ballot_sync(0xffffffffu, ldr1(cw) >= 32) & todo;
          todo ^= m;
          mbar_arrive1_if(B_U, todo == 0);
#pragma unroll
          for (int q = 0; q < 4; ++q)
            if ((m >> q) & 1) bulk(SM_X + 4096 * q, xg + 256 * q, 4096, B_E);
        }
        PROFK(5 + 12 * layer);
        box_help(0, 1, 2, lane, layer);
#pragma unroll 1
        for (int n = 0; n < 4; ++n) {
          const int e = n & 1;
          const uint4* src = opqp(SCR->XF[layer] + (32 * e + 2 * (c >> 3) + (n >> 1)) * 2048);
          const uint32_t dst = opq(SM_A + e * A_E), b = opq(B_A + 32 * e), f = opq(n == 1 ? B_L : (n & 2 ? B_AE : B_RD) + 8 * e);
          if (n == 2) poll(cw + 2, 32);
          if (n == 2) PROF(7 + 12 * layer);
          mbar_wait(f, layer);
          if (n == 0) cnt_add1(ca + 1);
          uint32_t ok = n ? 15 : 0;
#pragma unroll 1
          for (int q = 0, it = 0; q < 4; ++q) {
            mbar_expect1(b + 8 * q, 8192);
#pragma unroll 1
            for (; !((ok >> q) & 1); ++it) {
              spin_guard(it);
              ok = __ballot_sync(0xffffffffu, ldr1(cw + 1) >= 32);
            }
            bulk(dst + 8192 * q, src + 512 * q, 8192, b + 8 * q);
          }
          bar_arrive_if(NB_AUX, 64, n == 2);
          if (!e) PROFK(6 + n + 12 * layer);
        }
#pragma unroll 1
        for (int n = 0; n < 8; ++n) mbar_expect1(B_O + 8 * n, 16384);
        if (layer == 0) poll(SCR->C + 6, P.spare);
        mbar_wait(B_QE, layer);
#pragma unroll 1
        for (int e = 0; e < 2; ++e) {
          const int J = 16 * e + (c >> 3);
          const uint32_t* fl = opqp(SCR->OF[layer] + J * 32 + lane);
          const uint4* src[4];
          uint32_t dst[4], b[4];
#pragma unroll
          for (int n = 0; n < 4; ++n) { src[n] = opqp(SCR->O + (J * 4096 + n * 1024)); dst[n] = opq(SM_O + e * O_E + 16384 * n); b[n] = opq(B_O + 32 * e + 8 * n); }
          mbar_wait(B_AT + 8 * e, layer);
          if (!e) pause(260);
          poll(fl, 1);
#pragma unroll
          for (int n = 0; n < 4; ++n) bulk(dst[n], src[n], 16384, b[n]);
          PROFK(9 + e + 12 * layer);
        }
      }
      DONE();
    }
    if (warp == 15) {
      const int G = stat_group(c);
      str4(&SCR->ST[0][(lane >> 4) * 2048 + c * 16 + (lane & 15)], 0, 0, 0, 0); str4(&SCR->ST[1][(lane >> 4) * 2048 + c * 16 + (lane & 15)], 0, 0, 0, 0);
      if (lane < 4) str4(SCR->OF[lane >> 1] + ((lane & 1) * 512 + c * 4), 0, 0, 0, 0);
      str4(&SCR->PS[G * 64 + lane], 0, 0, 0, 0); str4(&SCR->PS[G * 64 + 32 + lane], 0, 0, 0, 0);
      str4(&SCR->SR[1][lane >> 2][sr_off(G, 2 * lane)], 0, 0, 0, 0);
      if (c < 4 && lane < 3) str1(SCR->C + c * 32 + 3 + lane, 0);
#pragma unroll
      for (int k = 0; k < 3; ++k) str2((uint2*)SCR->CS + ((c >> 3) * 768 + k * 256 + 32 * cg + lane), 0, 0);
      __threadfence();
#pragma unroll 1
      for (int layer = 0; layer < 2; ++layer) {
        PROF(4 + 12 * layer);
        mbar_watch(B_E, layer);
        box_help(1, 0, 1, lane, layer);
        if (layer) str4(&SCR->SR[0][lane >> 2][sr_off(G, 2 * lane)], 0, 0, 0, 0);
        uint32_t* ca = opqp(SCR->C + (c >> 5) * 32 + 3 * layer + 2);
        mbar_watch(B_Z, 1);
        mbar_watch(B_RD + 8, layer);
        cnt_add1(ca);
        if (P.spare == 0) {
#pragma unroll 1
          for (int k = 0; k < 32; ++k) str4(SCR->XG[layer] + (c * 1024 + k * 32 + lane), 0, 0, 0, 0);
        }
      }
      mbar_watch(B_O + 56, 1);
    }
  }
}

typedef CUresult (*EncodeFn)(CUtensorMap*, CUtensorMapDataType, cuuint32_t, void*, const cuuint64_t*, const cuuint64_t*,
                             const cuuint32_t*, const cuuint32_t*, CUtensorMapInterleave, CUtensorMapSwizzle,
                             CUtensorMapL2promotion, CUtensorMapFloatOOBfill);

static int place_roles(uint8_t* role) {
  int dev = 0, nsm = 0;
  cudaGetDevice(&dev);
  cudaDeviceGetAttribute(&nsm, cudaDevAttrMultiProcessorCount, dev);
  if (nsm <= 128 || nsm > 144 || (nsm & 1)) return 0;
  cudaFuncSetAttribute(fused_kernel, cudaFuncAttributeNonPortableClusterSizeAllowed, 1);
  int occ[9] = {0};
  for (int k = 2; k <= 8; ++k) {
    cudaLaunchConfig_t cfg = {};
    cudaLaunchAttribute at[1];
    at[0].id = cudaLaunchAttributeClusterDimension;
    at[0].val.clusterDim.x = 2 * k; at[0].val.clusterDim.y = 1; at[0].val.clusterDim.z = 1;
    cfg.gridDim = dim3(2 * k); cfg.blockDim = dim3(NTHR); cfg.dynamicSmemBytes = SM_TOTAL; cfg.attrs = at; cfg.numAttrs = 1;
    if (cudaOccupancyMaxActiveClusters(&occ[k], fused_kernel, &cfg) != cudaSuccess) { cudaGetLastError(); occ[k] = 0; }
  }
  int n[10];
  n[7] = occ[8]; n[6] = occ[7]; n[5] = occ[6] - 0; n[4] = occ[5];
  n[3] = occ[4] - n[7]; n[1] = occ[2] - n[3] - n[5] - n[7]; n[0] = n[2] = n[1];
  n[8] = occ[3] - n[2] - n[5];
  const int ntpc = nsm / 2;
  int sum = 0;
  bool ok = n[0] > 0 && n[0] <= 8;
  for (int r = 0; r < 9; ++r) { ok = ok && n[r] >= 0 && (r == 0 || n[r] <= n[r - 1]); sum += n[r]; }
  if (!ok || sum > ntpc) { for (int r = 0; r < 9; ++r) n[r] = r < 8 ? 8 : 0; sum = 64; }
  int tp[8][9], cnt[8] = {0}, pool[72], np = 0, id = 0;
  for (int r = 0; r < 9; ++r)
    for (int g = n[0] - n[r]; g < n[0]; ++g) tp[g][cnt[g]++] = id++;
  for (; id < ntpc; ++id) pool[np++] = id;
  int order[72], no = 0;
  for (int g = 0; g < n[0]; ++g) {
    const int full = cnt[g] / 4 * 4;
    for (int k = 0; k < cnt[g]; ++k) { if (k < full) order[no++] = tp[g][k]; else pool[np++] = tp[g][k]; }
  }
  for (int k = 0; k < np; ++k) order[no++] = pool[k];
  for (int k = 0; k < ntpc; ++k) role[order[k]] = 2 * k;
  return nsm;
}

extern "C" void kernel_launch(void* const* d_in, const int* in_sizes, int n_in, void* d_out, int out_size) {
  (void)in_sizes; (void)n_in; (void)out_size;
  static EncodeFn enc = nullptr;
  static uint8_t role[72];
  static int nsm = 0;
  static Scratch* scratch = nullptr;
  if (!enc) {
    void* fn = nullptr;
    cudaDriverEntryPointQueryResult qr;
    cudaGetDriverEntryPoint("cuTensorMapEncodeTiled", &fn, cudaEnableDefault, &qr);
    enc = (EncodeFn)fn;
    cudaFuncSetAttribute(fused_kernel, cudaFuncAttributeMaxDynamicSharedMemorySize, SM_TOTAL);
    nsm = place_roles(role);
    cudaGetSymbolAddress((void**)&scratch, g_S);
  }
  CUtensorMap mW, mWo, mX;
  {
    cuuint64_t dim[3] = {512, 512, 3}, str[2] = {3072, 1024};
    cuuint32_t box[3] = {64, 64, 3}, es[3] = {1, 1, 1};
    enc(&mW, CU_TENSOR_MAP_DATA_TYPE_BFLOAT16, 3, d_in[10], dim, str, box, es, CU_TENSOR_MAP_INTERLEAVE_NONE,
        CU_TENSOR_MAP_SWIZZLE_128B, CU_TENSOR_MAP_L2_PROMOTION_NONE, CU_TENSOR_MAP_FLOAT_OOB_FILL_NONE);
  }
  {
    cuuint64_t dim[4] = {512, 2, 4, 64}, str[3] = {1024, 2048, 8192};
    cuuint32_t box[4] = {64, 2, 1, 32}, es[4] = {1, 1, 1, 1};
    enc(&mWo, CU_TENSOR_MAP_DATA_TYPE_BFLOAT16, 4, d_in[11], dim, str, box, es, CU_TENSOR_MAP_INTERLEAVE_NONE,
        CU_TENSOR_MAP_SWIZZLE_128B, CU_TENSOR_MAP_L2_PROMOTION_NONE, CU_TENSOR_MAP_FLOAT_OOB_FILL_NONE);
  }
  {
    cuuint64_t dim[2] = {16384, 64}, str[1] = {32768};
    cuuint32_t box[2] = {128, 8}, es[2] = {1, 1};
    enc(&mX, CU_TENSOR_MAP_DATA_TYPE_BFLOAT16, 2, scratch->XF[0], dim, str, box, es, CU_TENSOR_MAP_INTERLEAVE_NONE,
        CU_TENSOR_MAP_SWIZZLE_NONE, CU_TENSOR_MAP_L2_PROMOTION_NONE, CU_TENSOR_MAP_FLOAT_OOB_FILL_NONE);
  }
  Params P;
  P.x0 = (const uint16_t*)d_in[0]; P.Are = (const uint16_t*)d_in[1]; P.Aim = (const uint16_t*)d_in[2];
  P.Bre = (const uint16_t*)d_in[3]; P.Bim = (const uint16_t*)d_in[4]; P.Cre = (const uint16_t*)d_in[5];
  P.Cim = (const uint16_t*)d_in[6]; P.logdt = (const uint16_t*)d_in[7]; P.dskip = (const uint16_t*)d_in[8];
  P.wqkv = (const uint16_t*)d_in[10]; P.wo = (const uint16_t*)d_in[11]; P.out = (uint16_t*)d_out;
  for (int k = 0; k < 72; ++k) P.role[k] = role[k];
  P.zero = 0;
  P.mid = (char*)scratch->C;
  P.spare = nsm > 0 ? nsm - 128 : 0;
  fused_kernel<<<nsm > 0 ? nsm : 128, NTHR, SM_TOTAL, cudaStreamPerThread>>>(P, mW, mWo, mX);
}
```
